```python
import torch

def _softmax(x, axis=-1):
    return torch.softmax(x, dim=axis)

def _gelu(x):
    return torch.nn.functional.gelu(x, approximate='tanh')

def _silu(x):
    return torch.nn.functional.silu(x)

def _sigmoid(x):
    return torch.sigmoid(x)

def _layernorm(x, axis=-1, eps=1e-05):
    m = x.mean(dim=axis, keepdim=True)
    v = x.var(dim=axis, keepdim=True, unbiased=False)
    return (x - m) / torch.sqrt(v + eps)

def _scatter_add(tgt, idx, src, axis=0):
    return tgt.clone().index_add_(axis, idx, src)

def _segment_sum(src, seg, n):
    out = torch.zeros((n,) + src.shape[1:], dtype=src.dtype)
    return out.index_add_(0, seg, src)

def _pad(x, pw):
    flat = tuple((v for pair in reversed(pw) for v in pair))
    return torch.nn.functional.pad(x, flat)
kernel_name = 'parallel_sum__spectral_fnet__mixer_gmlp__prompt'

def setup_inputs():

    _w = lambda a: (lambda t: t.to(torch.bfloat16) if t.is_floating_point() else t)(torch.as_tensor(a))

    def _A_setup():
        B, S, D = (1, 2048, 640)
        ns = torch.arange(S)[:, None] * torch.arange(S)[None, :]
        nd = torch.arange(D)[:, None] * torch.arange(D)[None, :]
        Ws_re = torch.cos(-2.0 * torch.pi * ns / S).to(float)
        Ws_im = torch.sin(-2.0 * torch.pi * ns / S).to(float)
        Wd_re = torch.cos(-2.0 * torch.pi * nd / D).to(float)
        Wd_im = torch.sin(-2.0 * torch.pi * nd / D).to(float)
        return {'x': _w((lambda *s: torch.randn(*s, dtype=torch.bfloat16) * 0.05)(B, S, D)), 'dft_seq_re': _w(Ws_re), 'dft_seq_im': _w(Ws_im), 'dft_hid_re': _w(Wd_re), 'dft_hid_im': _w(Wd_im)}
    _A_in = _A_setup()

    def _B_setup():
        B, S, D, F = (1, 2048, 640, 1536)
        Fh = F // 2
        return {'x': _w((lambda *s: torch.randn(*s, dtype=torch.bfloat16) * 0.05)(B, S, D)), 'w_in': _w((lambda *s: torch.randn(*s, dtype=torch.bfloat16) * 0.8)(D, 2 * Fh)), 'w_sp': _w(0.01 * (lambda *s: torch.randn(*s, dtype=torch.bfloat16) * 0.8)(S, S)), 'b_sp': _w(1.0 + 0.01 * (lambda *s: torch.randn(*s, dtype=torch.bfloat16) * 0.8)(S)), 'w_out': _w((lambda *s: torch.randn(*s, dtype=torch.bfloat16) * 0.8)(Fh, D))}
    _B_in = _B_setup()
    return {'A_x': _A_in['x'], 'A_dft_seq_re': _A_in['dft_seq_re'], 'A_dft_seq_im': _A_in['dft_seq_im'], 'A_dft_hid_re': _A_in['dft_hid_re'], 'A_dft_hid_im': _A_in['dft_hid_im'], 'B_x': _B_in['x'], 'B_w_in': _B_in['w_in'], 'B_w_sp': _B_in['w_sp'], 'B_b_sp': _B_in['b_sp'], 'B_w_out': _B_in['w_out']}

def reference(A_x, A_dft_seq_re, A_dft_seq_im, A_dft_hid_re, A_dft_hid_im, B_x, B_w_in, B_w_sp, B_b_sp, B_w_out):

    def _A_ref(x, dft_seq_re, dft_seq_im, dft_hid_re, dft_hid_im):
        a = torch.einsum('bsd,ed->bse', x, dft_hid_re)
        b = torch.einsum('bsd,ed->bse', x, dft_hid_im)
        y = torch.einsum('ts,bse->bte', dft_seq_re, a) - torch.einsum('ts,bse->bte', dft_seq_im, b)
        return y

    def _B_ref(x, w_in, w_sp, b_sp, w_out):
        B, S, D = x.shape
        F = w_in.shape[-1]
        Fh = F // 2
        z = _gelu(torch.einsum('bsd,df->bsf', x, w_in))
        z1 = z[..., :Fh].clone()
        z2 = _layernorm(z[..., Fh:], axis=-1)
        g = torch.einsum('ts,bsf->btf', w_sp, z2) + b_sp[None, :, None]
        return torch.einsum('bsf,fd->bsd', z1 * g, w_out)
    x = A_x
    xn = _layernorm(x, axis=-1)
    return x + _A_ref(xn, A_dft_seq_re, A_dft_seq_im, A_dft_hid_re, A_dft_hid_im) + _B_ref(xn, B_w_in, B_w_sp, B_b_sp, B_w_out)
```

```cpp
#include <cuda_runtime.h>
#include <cuda_bf16.h>
#include <cuda.h>
#include <stdint.h>

namespace {

typedef __nv_bfloat16 bf16;

constexpr int SEQ = 2048, DM = 640, FF = 1536, FH = 768;
constexpr int NX = 5;
constexpr int STAGES = 4;
constexpr int A_BYTES = 16384;
constexpr int STAGE_BYTES = 40960;
constexpr int BUF_OFF = STAGES * STAGE_BYTES;
constexpr int BUF_BYTES = 49152;
constexpr int MISC_OFF = BUF_OFF + BUF_BYTES;
constexpr int ROWSTAT_OFF = MISC_OFF;
constexpr int COLSUM_OFF = ROWSTAT_OFF + 1024;
constexpr int RED_OFF = COLSUM_OFF + 1536;
constexpr int BAR_OFF = RED_OFF + 256;
constexpr int EPOCH_OFF = BAR_OFF + 64;
constexpr int SMEM_BYTES = EPOCH_OFF + 64;
constexpr int KB_A = 20 + 32 + NX + 12;
constexpr int KB_B = 20 + 64 - NX;
constexpr float LN_EPS = 1e-5f;
constexpr int DEADLINE_OFF = EPOCH_OFF + 8;

constexpr int BAR_ORD1 = 1, BAR_ORD2 = 2, BAR_WG1 = 3, BAR_WG2 = 4, BAR_STATS = 5, BAR_BUF = 6, BAR_Z1 = 7;

struct Maps {
  CUtensorMap x, wsre, wsim, wsp, h, h3, win3, z23, wdre, wdim, ab, wout, out;
};

__device__ __align__(1024) bf16 g_abT[2 * DM * SEQ];
__device__ __align__(1024) bf16 g_z2[SEQ * FH];
__device__ __align__(1024) bf16 g_h[SEQ * FH];
__device__ __align__(16) uint4 g_xstat[SEQ];
__device__ __align__(16) uint2 g_csum[2 * DM + FF];
__device__ __align__(16) uint4 g_zstat[16 * 4 * 128];
__device__ __align__(16) uint4 g_part[128 * 27 * 128];
__device__ unsigned g_flags[4 * 64];
__device__ unsigned g_done;

extern __shared__ __align__(1024) uint8_t smem[];

__device__ __forceinline__ unsigned long long gtime() { unsigned long long t; asm volatile("mov.u64 %0, %%globaltimer;" : "=l"(t)); return t; }
__device__ __forceinline__ bool timed_out() { return gtime() > *reinterpret_cast<volatile unsigned long long*>(smem + DEADLINE_OFF); }
__device__ __forceinline__ uint32_t smem_u32(const void* p) { return (uint32_t)__cvta_generic_to_shared(p); }
__device__ __forceinline__ void mbar_init(uint32_t bar, uint32_t cnt) { asm volatile("mbarrier.init.shared::cta.b64 [%0], %1;" :: "r"(bar), "r"(cnt)); }
__device__ __forceinline__ void mbar_expect_tx(uint32_t bar, uint32_t bytes) { asm volatile("mbarrier.arrive.expect_tx.shared::cta.b64 _, [%0], %1;" :: "r"(bar), "r"(bytes) : "memory"); }
__device__ __forceinline__ void mbar_arrive_cluster(uint32_t bar, uint32_t cta) {
  asm volatile("{\n.reg .b32 ra;\nmapa.shared::cluster.u32 ra, %0, %1;\nmbarrier.arrive.shared::cluster.b64 _, [ra];\n}" :: "r"(bar), "r"(cta) : "memory");
}
__device__ __forceinline__ bool mbar_try(uint32_t bar, uint32_t parity) {
  uint32_t ok;
  asm volatile("{\n.reg .pred p;\nmbarrier.try_wait.parity.shared::cta.b64 p, [%1], %2;\nselp.u32 %0, 1, 0, p;\n}" : "=r"(ok) : "r"(bar), "r"(parity) : "memory");
  return ok != 0;
}
__device__ __forceinline__ void mbar_wait(uint32_t bar, uint32_t parity) {
  unsigned n = 0;
  while (!mbar_try(bar, parity)) { if ((++n & 4095u) == 0 && timed_out()) break; }
}
__device__ __forceinline__ void tma_load_2d(uint32_t dst, const CUtensorMap* map, uint32_t bar, int c0, int c1) {
  asm volatile("cp.async.bulk.tensor.2d.shared::cluster.global.mbarrier::complete_tx::bytes [%0], [%1, {%3, %4}], [%2];"
    :: "r"(dst), "l"((uint64_t)map), "r"(bar), "r"(c0), "r"(c1) : "memory");
}
__device__ __forceinline__ void tma_load_3d(uint32_t dst, const CUtensorMap* map, uint32_t bar, int c0, int c1, int c2) {
  asm volatile("cp.async.bulk.tensor.3d.shared::cluster.global.mbarrier::complete_tx::bytes [%0], [%1, {%3, %4, %5}], [%2];"
    :: "r"(dst), "l"((uint64_t)map), "r"(bar), "r"(c0), "r"(c1), "r"(c2) : "memory");
}
__device__ __forceinline__ void tma_load_2d_mc(uint32_t dst, const CUtensorMap* map, uint32_t bar, int c0, int c1, uint16_t mask) {
  asm volatile("cp.async.bulk.tensor.2d.shared::cluster.global.mbarrier::complete_tx::bytes.multicast::cluster [%0], [%1, {%3, %4}], [%2], %5;"
    :: "r"(dst), "l"((uint64_t)map), "r"(bar), "r"(c0), "r"(c1), "h"(mask) : "memory");
}
__device__ __forceinline__ void tma_store_2d(const CUtensorMap* map, uint32_t src, int c0, int c1) {
  asm volatile("cp.async.bulk.tensor.2d.global.shared::cta.bulk_group [%0, {%2, %3}], [%1];"
    :: "l"((uint64_t)map), "r"(src), "r"(c0), "r"(c1) : "memory");
}
__device__ __forceinline__ void tma_store_3d(const CUtensorMap* map, uint32_t src, int c0, int c1, int c2) {
  asm volatile("cp.async.bulk.tensor.3d.global.shared::cta.bulk_group [%0, {%2, %3, %4}], [%1];"
    :: "l"((uint64_t)map), "r"(src), "r"(c0), "r"(c1), "r"(c2) : "memory");
}
__device__ __forceinline__ void bulk_commit() { asm volatile("cp.async.bulk.commit_group;" ::: "memory"); }
__device__ __forceinline__ void bulk_wait_all() { asm volatile("cp.async.bulk.wait_group 0;" ::: "memory"); }
__device__ __forceinline__ void bulk_wait_read() { asm volatile("cp.async.bulk.wait_group.read 0;" ::: "memory"); }
__device__ __forceinline__ void fence_async_smem() { asm volatile("fence.proxy.async.shared::cta;" ::: "memory"); }
__device__ __forceinline__ void fence_async_global() { asm volatile("fence.proxy.async.global;" ::: "memory"); }
__device__ __forceinline__ void wgmma_fence() { asm volatile("wgmma.fence.sync.aligned;" ::: "memory"); }
__device__ __forceinline__ void wgmma_commit() { asm volatile("wgmma.commit_group.sync.aligned;" ::: "memory"); }
template<int N> __device__ __forceinline__ void wgmma_wait() { asm volatile("wgmma.wait_group.sync.aligned %0;" :: "n"(N) : "memory"); }
template<int ID> __device__ __forceinline__ void bar_sync(int n) { asm volatile("bar.sync %0, %1;" :: "n"(ID), "r"(n) : "memory"); }
template<int ID> __device__ __forceinline__ void bar_arrive(int n) { asm volatile("bar.arrive %0, %1;" :: "n"(ID), "r"(n) : "memory"); }
__device__ __forceinline__ uint64_t make_desc(uint32_t addr, uint32_t lbo, uint32_t sbo) {
  return (uint64_t)((addr & 0x3FFFF) >> 4) | ((uint64_t)(lbo >> 4) << 16) | ((uint64_t)(sbo >> 4) << 32) | (1ull << 62);
}
__device__ __forceinline__ uint4 ld_vol4(const uint4* p) {
  uint4 v; asm volatile("ld.volatile.global.v4.u32 {%0,%1,%2,%3}, [%4];" : "=r"(v.x), "=r"(v.y), "=r"(v.z), "=r"(v.w) : "l"(p) : "memory"); return v;
}
__device__ __forceinline__ uint2 ld_vol2(const uint2* p) {
  uint2 v; asm volatile("ld.volatile.global.v2.u32 {%0,%1}, [%2];" : "=r"(v.x), "=r"(v.y) : "l"(p) : "memory"); return v;
}
__device__ __forceinline__ void st_vol4(uint4* p, uint32_t a, uint32_t b, uint32_t c, uint32_t d) {
  asm volatile("st.volatile.global.v4.u32 [%0], {%1,%2,%3,%4};" :: "l"(p), "r"(a), "r"(b), "r"(c), "r"(d) : "memory");
}
__device__ __forceinline__ void st_vol2(uint2* p, uint32_t a, uint32_t b) {
  asm volatile("st.volatile.global.v2.u32 [%0], {%1,%2};" :: "l"(p), "r"(a), "r"(b) : "memory");
}
__device__ __forceinline__ unsigned ld_acquire(const unsigned* p) {
  unsigned v; asm volatile("ld.acquire.gpu.global.u32 %0, [%1];" : "=r"(v) : "l"(p) : "memory"); return v;
}
__device__ __forceinline__ void st_release(unsigned* p, unsigned v) {
  asm volatile("st.release.gpu.global.u32 [%0], %1;" :: "l"(p), "r"(v) : "memory");
}
__device__ __forceinline__ uint32_t pack_bf16(float lo, float hi) {
  uint32_t r; asm("cvt.rn.bf16x2.f32 %0, %1, %2;" : "=r"(r) : "f"(hi), "f"(lo)); return r;
}
__device__ __forceinline__ float bf_lo(uint32_t v) { return __uint_as_float(v << 16); }
__device__ __forceinline__ float bf_hi(uint32_t v) { return __uint_as_float(v & 0xFFFF0000u); }
__device__ __forceinline__ void stsm4(uint32_t addr, uint32_t a, uint32_t b, uint32_t c, uint32_t d) {
  asm volatile("stmatrix.sync.aligned.m8n8.x4.shared.b16 [%0], {%1,%2,%3,%4};" :: "r"(addr), "r"(a), "r"(b), "r"(c), "r"(d) : "memory");
}
__device__ __forceinline__ void stsm4_t(uint32_t addr, uint32_t a, uint32_t b, uint32_t c, uint32_t d) {
  asm volatile("stmatrix.sync.aligned.m8n8.x4.trans.shared.b16 [%0], {%1,%2,%3,%4};" :: "r"(addr), "r"(a), "r"(b), "r"(c), "r"(d) : "memory");
}
__device__ __forceinline__ void ldsm4(uint32_t addr, uint32_t& a, uint32_t& b, uint32_t& c, uint32_t& d) {
  asm volatile("ldmatrix.sync.aligned.m8n8.x4.shared.b16 {%0,%1,%2,%3}, [%4];" : "=r"(a), "=r"(b), "=r"(c), "=r"(d) : "r"(addr) : "memory");
}
__device__ __forceinline__ float gelu_tanh(float v) {
  float u = v * fmaf(0.0356774081f, v * v, 0.7978845608f);
  float t; asm("tanh.approx.f32 %0, %1;" : "=f"(t) : "f"(u));
  float hv = 0.5f * v;
  return fmaf(hv, t, hv);
}
__device__ __forceinline__ float warp_sum(float v) {
  #pragma unroll
  for (int o = 16; o > 0; o >>= 1) v += __shfl_xor_sync(0xffffffffu, v, o);
  return v;
}
__device__ __forceinline__ float quad_sum(float v) {
  v += __shfl_xor_sync(0xffffffffu, v, 1);
  v += __shfl_xor_sync(0xffffffffu, v, 2);
  return v;
}

template<int TB>
__device__ __forceinline__ void wgmma_n192(float (&d)[96], uint64_t da, uint64_t db, int scale_d) {
  asm volatile("{\n.reg .pred p;\nsetp.ne.b32 p, %98, 0;\n"
   "wgmma.mma_async.sync.aligned.m64n192k16.f32.bf16.bf16 {%0,%1,%2,%3,%4,%5,%6,%7,%8,%9,%10,%11,%12,%13,%14,%15,%16,%17,%18,%19,%20,%21,%22,%23,%24,%25,%26,%27,%28,%29,%30,%31,%32,%33,%34,%35,%36,%37,%38,%39,%40,%41,%42,%43,%44,%45,%46,%47,%48,%49,%50,%51,%52,%53,%54,%55,%56,%57,%58,%59,%60,%61,%62,%63,%64,%65,%66,%67,%68,%69,%70,%71,%72,%73,%74,%75,%76,%77,%78,%79,%80,%81,%82,%83,%84,%85,%86,%87,%88,%89,%90,%91,%92,%93,%94,%95}, %96, %97, p, 1, 1, 0, %99;\n}"
   : "+f"(d[0]),"+f"(d[1]),"+f"(d[2]),"+f"(d[3]),"+f"(d[4]),"+f"(d[5]),"+f"(d[6]),"+f"(d[7]),"+f"(d[8]),"+f"(d[9]),"+f"(d[10]),"+f"(d[11]),"+f"(d[12]),"+f"(d[13]),"+f"(d[14]),"+f"(d[15]),"+f"(d[16]),"+f"(d[17]),"+f"(d[18]),"+f"(d[19]),"+f"(d[20]),"+f"(d[21]),"+f"(d[22]),"+f"(d[23]),"+f"(d[24]),"+f"(d[25]),"+f"(d[26]),"+f"(d[27]),"+f"(d[28]),"+f"(d[29]),"+f"(d[30]),"+f"(d[31]),"+f"(d[32]),"+f"(d[33]),"+f"(d[34]),"+f"(d[35]),"+f"(d[36]),"+f"(d[37]),"+f"(d[38]),"+f"(d[39]),"+f"(d[40]),"+f"(d[41]),"+f"(d[42]),"+f"(d[43]),"+f"(d[44]),"+f"(d[45]),"+f"(d[46]),"+f"(d[47]),"+f"(d[48]),"+f"(d[49]),"+f"(d[50]),"+f"(d[51]),"+f"(d[52]),"+f"(d[53]),"+f"(d[54]),"+f"(d[55]),"+f"(d[56]),"+f"(d[57]),"+f"(d[58]),"+f"(d[59]),"+f"(d[60]),"+f"(d[61]),"+f"(d[62]),"+f"(d[63]),"+f"(d[64]),"+f"(d[65]),"+f"(d[66]),"+f"(d[67]),"+f"(d[68]),"+f"(d[69]),"+f"(d[70]),"+f"(d[71]),"+f"(d[72]),"+f"(d[73]),"+f"(d[74]),"+f"(d[75]),"+f"(d[76]),"+f"(d[77]),"+f"(d[78]),"+f"(d[79]),"+f"(d[80]),"+f"(d[81]),"+f"(d[82]),"+f"(d[83]),"+f"(d[84]),"+f"(d[85]),"+f"(d[86]),"+f"(d[87]),"+f"(d[88]),"+f"(d[89]),"+f"(d[90]),"+f"(d[91]),"+f"(d[92]),"+f"(d[93]),"+f"(d[94]),"+f"(d[95])
   : "l"(da), "l"(db), "r"(scale_d), "n"(TB));
}
template<int TB>
__device__ __forceinline__ void wgmma_n160(float (&d)[80], uint64_t da, uint64_t db, int scale_d) {
  asm volatile("{\n.reg .pred p;\nsetp.ne.b32 p, %82, 0;\n"
   "wgmma.mma_async.sync.aligned.m64n160k16.f32.bf16.bf16 {%0,%1,%2,%3,%4,%5,%6,%7,%8,%9,%10,%11,%12,%13,%14,%15,%16,%17,%18,%19,%20,%21,%22,%23,%24,%25,%26,%27,%28,%29,%30,%31,%32,%33,%34,%35,%36,%37,%38,%39,%40,%41,%42,%43,%44,%45,%46,%47,%48,%49,%50,%51,%52,%53,%54,%55,%56,%57,%58,%59,%60,%61,%62,%63,%64,%65,%66,%67,%68,%69,%70,%71,%72,%73,%74,%75,%76,%77,%78,%79}, %80, %81, p, 1, 1, 0, %83;\n}"
   : "+f"(d[0]),"+f"(d[1]),"+f"(d[2]),"+f"(d[3]),"+f"(d[4]),"+f"(d[5]),"+f"(d[6]),"+f"(d[7]),"+f"(d[8]),"+f"(d[9]),"+f"(d[10]),"+f"(d[11]),"+f"(d[12]),"+f"(d[13]),"+f"(d[14]),"+f"(d[15]),"+f"(d[16]),"+f"(d[17]),"+f"(d[18]),"+f"(d[19]),"+f"(d[20]),"+f"(d[21]),"+f"(d[22]),"+f"(d[23]),"+f"(d[24]),"+f"(d[25]),"+f"(d[26]),"+f"(d[27]),"+f"(d[28]),"+f"(d[29]),"+f"(d[30]),"+f"(d[31]),"+f"(d[32]),"+f"(d[33]),"+f"(d[34]),"+f"(d[35]),"+f"(d[36]),"+f"(d[37]),"+f"(d[38]),"+f"(d[39]),"+f"(d[40]),"+f"(d[41]),"+f"(d[42]),"+f"(d[43]),"+f"(d[44]),"+f"(d[45]),"+f"(d[46]),"+f"(d[47]),"+f"(d[48]),"+f"(d[49]),"+f"(d[50]),"+f"(d[51]),"+f"(d[52]),"+f"(d[53]),"+f"(d[54]),"+f"(d[55]),"+f"(d[56]),"+f"(d[57]),"+f"(d[58]),"+f"(d[59]),"+f"(d[60]),"+f"(d[61]),"+f"(d[62]),"+f"(d[63]),"+f"(d[64]),"+f"(d[65]),"+f"(d[66]),"+f"(d[67]),"+f"(d[68]),"+f"(d[69]),"+f"(d[70]),"+f"(d[71]),"+f"(d[72]),"+f"(d[73]),"+f"(d[74]),"+f"(d[75]),"+f"(d[76]),"+f"(d[77]),"+f"(d[78]),"+f"(d[79])
   : "l"(da), "l"(db), "r"(scale_d), "n"(TB));
}


template<int N, int TB>
__device__ __forceinline__ void wgmma_n(float (&d)[N / 2], uint64_t da, uint64_t db, int scale_d) {
  if constexpr (N == 192) wgmma_n192<TB>(d, da, db, scale_d); else wgmma_n160<TB>(d, da, db, scale_d);
}

template<int R>
__device__ __forceinline__ void pin(float (&acc)[2][R]) {
  #pragma unroll
  for (int mi = 0; mi < 2; mi++)
    #pragma unroll
    for (int i = 0; i < R; i++) asm volatile("" : "+f"(acc[mi][i]) :: "memory");
}

template<int N, int TB>
__device__ __forceinline__ void mma_kblock(float (&acc)[2][N / 2], uint32_t sa, int accum) {
  const uint32_t sb = sa + A_BYTES;
  #pragma unroll
  for (int k = 0; k < 4; k++) {
    const uint64_t db = TB ? make_desc(sb + k * 2048, 8192, 1024) : make_desc(sb + k * 32, 16, 1024);
    #pragma unroll
    for (int mi = 0; mi < 2; mi++)
      wgmma_n<N, TB>(acc[mi], make_desc(sa + mi * 8192 + k * 32, 16, 1024), db, accum | k);
  }
}

template<int N, int TB, bool CONT, bool DRAIN, int ORD_BAR>
__device__ __forceinline__ void mainloop(float (&acc)[2][N / 2], uint32_t sbase, int g0, int nk, int total, int accum0) {
  const uint32_t full0 = sbase + BAR_OFF, empty0 = full0 + 8 * STAGES;
  const int lane = threadIdx.x & 31;
  const bool rel = ((threadIdx.x & 127) < 2);
  if (!CONT) pin(acc);
  #pragma unroll 1
  for (int i = 0; i < nk; i++) {
    const int g = g0 + i;
    const int s = g & (STAGES - 1);
    mbar_wait(full0 + 8 * s, (g / STAGES) & 1);
    wgmma_fence();
    mma_kblock<N, TB>(acc, sbase + s * STAGE_BYTES, accum0 | i);
    wgmma_commit();
    if (ORD_BAR != 0 && i == nk - 1) bar_arrive<ORD_BAR>(256);
    wgmma_wait<1>();
    if (rel && (CONT || i > 0) && g - 1 + STAGES < total) mbar_arrive_cluster(empty0 + 8 * ((g - 1) & (STAGES - 1)), lane);
  }
  if (DRAIN) {
    wgmma_wait<0>();
    pin(acc);
    const int g = g0 + nk - 1;
    if (rel && g + STAGES < total) mbar_arrive_cluster(empty0 + 8 * (g & (STAGES - 1)), lane);
  }
}

__device__ __forceinline__ void wait_flags(const unsigned* flags, int stride, int n, unsigned epoch) {
  const int lane = threadIdx.x & 31;
  unsigned it = 0;
  while (true) {
    bool ok = lane >= n || ld_acquire(flags + lane * stride) == epoch;
    if (__all_sync(0xffffffffu, ok)) break;
    if ((++it & 4095u) == 0 && timed_out()) break;
  }
  fence_async_global();
}

__device__ __forceinline__ void publish(unsigned* flag, unsigned epoch) {
  bulk_commit();
  bulk_wait_all();
  fence_async_global();
  __threadfence();
  st_release(flag, epoch);
}

__device__ __forceinline__ void stats_prologue(const bf16* __restrict__ x, const bf16* __restrict__ wdre,
    const bf16* __restrict__ wdim, const bf16* __restrict__ win, int rb, int cs0, int cs1, int ncol, unsigned epoch) {
  const int t = threadIdx.x & 127, w = t >> 5, l = t & 31, cta = blockIdx.x;
  uint2 xv[4][5], wv[3][5];
  uint4 cv[5][2];
  #pragma unroll
  for (int i = 0; i < 4; i++) {
    const uint2* p = reinterpret_cast<const uint2*>(x + (size_t)(cta * 16 + w * 4 + i) * DM);
    #pragma unroll
    for (int j = 0; j < 5; j++) xv[i][j] = __ldg(p + l + 32 * j);
  }
  if (cta < 96) {
    #pragma unroll
    for (int i = 0; i < 5; i++) {
      const uint4* p = reinterpret_cast<const uint4*>(win + (size_t)(t + 128 * i) * FF + cta * 16);
      cv[i][0] = __ldg(p); cv[i][1] = __ldg(p + 1);
    }
  }
  #pragma unroll
  for (int i = 0; i < 3; i++) {
    int r = cta * 10 + min(w + 4 * i, 9);
    const uint2* p = reinterpret_cast<const uint2*>(r < DM ? wdre + (size_t)r * DM : wdim + (size_t)(r - DM) * DM);
    #pragma unroll
    for (int j = 0; j < 5; j++) wv[i][j] = __ldg(p + l + 32 * j);
  }
  #pragma unroll
  for (int i = 0; i < 4; i++) {
    float s = 0.f;
    #pragma unroll
    for (int j = 0; j < 5; j++) s += (bf_lo(xv[i][j].x) + bf_hi(xv[i][j].x)) + (bf_lo(xv[i][j].y) + bf_hi(xv[i][j].y));
    const float mean = warp_sum(s) * (1.f / DM);
    float q = 0.f;
    #pragma unroll
    for (int j = 0; j < 5; j++) {
      float d0 = bf_lo(xv[i][j].x) - mean, d1 = bf_hi(xv[i][j].x) - mean, d2 = bf_lo(xv[i][j].y) - mean, d3 = bf_hi(xv[i][j].y) - mean;
      q += d0 * d0 + d1 * d1 + d2 * d2 + d3 * d3;
    }
    const float rstd = 1.f / sqrtf(warp_sum(q) * (1.f / DM) + LN_EPS);
    if (l == 0) st_vol4(&g_xstat[cta * 16 + w * 4 + i], __float_as_uint(rstd), __float_as_uint(-mean * rstd), epoch, 0u);
  }
  #pragma unroll
  for (int i = 0; i < 3; i++) {
    float s = 0.f;
    #pragma unroll
    for (int j = 0; j < 5; j++) s += (bf_lo(wv[i][j].x) + bf_hi(wv[i][j].x)) + (bf_lo(wv[i][j].y) + bf_hi(wv[i][j].y));
    s = warp_sum(s);
    if (l == 0 && w + 4 * i < 10) st_vol2(&g_csum[cta * 10 + w + 4 * i], __float_as_uint(s), epoch);
  }
  if (cta < 96) {
    float v[16];
    #pragma unroll
    for (int c = 0; c < 16; c++) v[c] = 0.f;
    #pragma unroll
    for (int i = 0; i < 5; i++) {
      const uint32_t u[8] = {cv[i][0].x, cv[i][0].y, cv[i][0].z, cv[i][0].w, cv[i][1].x, cv[i][1].y, cv[i][1].z, cv[i][1].w};
      #pragma unroll
      for (int c = 0; c < 8; c++) { v[2 * c] += bf_lo(u[c]); v[2 * c + 1] += bf_hi(u[c]); }
    }
    #pragma unroll
    for (int o = 16, n = 8; n >= 1; o >>= 1, n >>= 1) {
      const bool up = (l & o) != 0;
      #pragma unroll
      for (int c = 0; c < n; c++) {
        const float keep = up ? v[c + n] : v[c], send = up ? v[c] : v[c + n];
        v[c] = keep + __shfl_xor_sync(0xffffffffu, send, o);
      }
    }
    v[0] += __shfl_xor_sync(0xffffffffu, v[0], 1);
    float* red = reinterpret_cast<float*>(smem + RED_OFF);
    if ((l & 1) == 0) red[w * 16 + (l >> 1)] = v[0];
    bar_sync<BAR_WG2>(128);
    if (t < 16) st_vol2(&g_csum[2 * DM + cta * 16 + t], __float_as_uint((red[t] + red[16 + t]) + (red[32 + t] + red[48 + t])), epoch);
  }
  {
    unsigned it = 0;
    uint4 v;
    while ((v = ld_vol4(&g_xstat[rb * 128 + t])).z != epoch) { if ((++it & 4095u) == 0 && timed_out()) break; }
    reinterpret_cast<float2*>(smem + ROWSTAT_OFF)[t] = make_float2(__uint_as_float(v.x), __uint_as_float(v.y));
    float* cs = reinterpret_cast<float*>(smem + COLSUM_OFF);
    #pragma unroll
    for (int i = 0; i < 4; i++) {
      const int c = t + (i & 1) * 128;
      if (c < ncol) {
        uint2 u;
        while ((u = ld_vol2(&g_csum[(i >> 1 ? cs1 : cs0) + c])).y != epoch) { if ((++it & 4095u) == 0 && timed_out()) break; }
        cs[(i >> 1) * 192 + c] = __uint_as_float(u.x);
      }
    }
  }
}

template<int N>
__device__ __forceinline__ void fold_ln(float (&acc)[2][N / 2], int item, float sign) {
  const int t = threadIdx.x & 127, w = t >> 5, l = t & 31;
  const float2* rs = reinterpret_cast<const float2*>(smem + ROWSTAT_OFF);
  const float2* cs = reinterpret_cast<const float2*>(smem + COLSUM_OFF + item * 768);
  float2 st[2][2];
  #pragma unroll
  for (int mi = 0; mi < 2; mi++)
    #pragma unroll
    for (int hf = 0; hf < 2; hf++) {
      st[mi][hf] = rs[mi * 64 + w * 16 + hf * 8 + (l >> 2)];
      st[mi][hf].x *= sign; st[mi][hf].y *= sign;
    }
  #pragma unroll
  for (int j = 0; j < N / 8; j++) {
    const float2 c = cs[j * 4 + (l & 3)];
    #pragma unroll
    for (int mi = 0; mi < 2; mi++) {
      acc[mi][4 * j + 0] = fmaf(acc[mi][4 * j + 0], st[mi][0].x, st[mi][0].y * c.x);
      acc[mi][4 * j + 1] = fmaf(acc[mi][4 * j + 1], st[mi][0].x, st[mi][0].y * c.y);
      acc[mi][4 * j + 2] = fmaf(acc[mi][4 * j + 2], st[mi][1].x, st[mi][1].y * c.x);
      acc[mi][4 * j + 3] = fmaf(acc[mi][4 * j + 3], st[mi][1].x, st[mi][1].y * c.y);
    }
  }
}

__device__ __forceinline__ uint32_t stage_addr_rm(uint32_t buf, int mi, int jj) {
  const int t = threadIdx.x & 127, w = t >> 5, l = t & 31;
  const int row = w * 16 + ((l >> 3) & 1) * 8 + (l & 7);
  const int chunk = (jj & 3) * 2 + (l >> 4);
  return buf + mi * 24576 + (jj >> 2) * 8192 + row * 128 + ((chunk ^ (l & 7)) << 4);
}

__device__ __forceinline__ void stage_transposed(float (&acc)[2][80], uint32_t buf) {
  const int t = threadIdx.x & 127, w = t >> 5, l = t & 31;
  #pragma unroll
  for (int mi = 0; mi < 2; mi++)
    #pragma unroll
    for (int jj = 0; jj < 10; jj++) {
      const float* a = &acc[mi][8 * jj];
      const int e = jj * 16 + (l >> 4) * 8 + (l & 7);
      const int sc = w * 2 + ((l >> 3) & 1);
      stsm4_t(buf + mi * 20480 + e * 128 + ((sc ^ (l & 7)) << 4),
              pack_bf16(a[0], a[1]), pack_bf16(a[2], a[3]), pack_bf16(a[4], a[5]), pack_bf16(a[6], a[7]));
    }
  fence_async_smem();
}

template<int KEEP>
__device__ __forceinline__ void init_residual(float (&acc)[2][80], const bf16* __restrict__ x, int rb, int ct) {
  const int t = threadIdx.x & 127, w = t >> 5, l = t & 31;
  const bf16* p = x + (size_t)(rb * 128 + KEEP * 64 + w * 16 + (l >> 2)) * DM + ct * 160 + (l & 3) * 2;
  #pragma unroll
  for (int j = 0; j < 20; j++) {
    const uint32_t v0 = __ldg(reinterpret_cast<const uint32_t*>(p + j * 8));
    const uint32_t v1 = __ldg(reinterpret_cast<const uint32_t*>(p + 8 * DM + j * 8));
    acc[KEEP][4 * j + 0] = bf_lo(v0); acc[KEEP][4 * j + 1] = bf_hi(v0);
    acc[KEEP][4 * j + 2] = bf_lo(v1); acc[KEEP][4 * j + 3] = bf_hi(v1);
    acc[1 - KEEP][4 * j + 0] = 0.f; acc[1 - KEEP][4 * j + 1] = 0.f; acc[1 - KEEP][4 * j + 2] = 0.f; acc[1 - KEEP][4 * j + 3] = 0.f;
  }
}

template<int KEEP>
__device__ __forceinline__ void final_epilogue(float (&acc)[2][80], uint32_t sbase, const Maps& maps, int rb, int ct, unsigned epoch) {
  const int t = threadIdx.x & 127, w = t >> 5, l = t & 31;
  uint4* dst = g_part + (size_t)blockIdx.x * 27 * 128 + t;
  const uint4* src = g_part + (size_t)(blockIdx.x ^ 2) * 27 * 128 + t;
  #pragma unroll
  for (int i = 0; i < 27; i++)
    st_vol4(dst + i * 128, __float_as_uint(acc[1 - KEEP][3 * i]), __float_as_uint(acc[1 - KEEP][3 * i + 1]),
            __float_as_uint(i < 26 ? acc[1 - KEEP][3 * i + 2] : 0.f), epoch);
  unsigned it = 0;
  #pragma unroll
  for (int gq = 0; gq < 3; gq++) {
    uint4 v[9];
    while (true) {
      bool ok = true;
      #pragma unroll
      for (int i = 0; i < 9; i++) v[i] = ld_vol4(src + (gq * 9 + i) * 128);
      #pragma unroll
      for (int i = 0; i < 9; i++) ok = ok && (v[i].w == epoch);
      if (ok) break;
      if ((++it & 4095u) == 0 && timed_out()) break;
    }
    #pragma unroll
    for (int i = 0; i < 9; i++) {
      const int e = (gq * 9 + i) * 3;
      acc[KEEP][e] += __uint_as_float(v[i].x);
      acc[KEEP][e + 1] += __uint_as_float(v[i].y);
      if (e + 2 < 80) acc[KEEP][e + 2] += __uint_as_float(v[i].z);
    }
  }
  const uint32_t slab = sbase + BUF_OFF + w * (16 * 320);
  const uint32_t addr = slab + (((l >> 3) & 1) * 8 + (l & 7)) * 320 + (l >> 4) * 16;
  #pragma unroll
  for (int jj = 0; jj < 10; jj++) {
    const float* a = &acc[KEEP][8 * jj];
    stsm4(addr + jj * 32, pack_bf16(a[0], a[1]), pack_bf16(a[2], a[3]), pack_bf16(a[4], a[5]), pack_bf16(a[6], a[7]));
  }
  fence_async_smem();
  __syncwarp();
  if (l == 0) {
    tma_store_2d(&maps.out, slab, ct * 160, rb * 128 + KEEP * 64 + w * 16);
    bulk_commit();
    bulk_wait_read();
  }
}

__global__ void __cluster_dims__(2, 1, 1) __launch_bounds__(384, 1)
fused_kernel(const __grid_constant__ Maps maps, const bf16* __restrict__ x, const bf16* __restrict__ wdre,
             const bf16* __restrict__ wdim, const bf16* __restrict__ win, const bf16* __restrict__ bsp) {
  const uint32_t sbase = smem_u32(smem);
  const uint32_t full0 = sbase + BAR_OFF, empty0 = full0 + 8 * STAGES;
  const int tid = threadIdx.x, wg = tid >> 7;
  const int rank = blockIdx.x & 1, grp = (blockIdx.x >> 1) & 1, q = blockIdx.x >> 2;
  const int rb = q >> 1, ct = (q & 1) * 2 + rank;
  unsigned* flag_a = g_flags, *flag_b = g_flags + 64, *flag_z = g_flags + 128, *flag_h = g_flags + 192;

  if (tid == 0) {
    for (int s = 0; s < STAGES; s++) { mbar_init(full0 + 8 * s, 2); mbar_init(empty0 + 8 * s, 2); }
    asm volatile("fence.mbarrier_init.release.cluster;" ::: "memory");
  }
  if (tid == 32) {
    *reinterpret_cast<unsigned long long*>(smem + DEADLINE_OFF) = gtime() + 200000000ull;
    *reinterpret_cast<unsigned*>(smem + EPOCH_OFF) = (*reinterpret_cast<volatile unsigned*>(&g_done) >> 7) + 1u;
  }
  __syncthreads();
  asm volatile("barrier.cluster.arrive.release.aligned;\nbarrier.cluster.wait.acquire.aligned;" ::: "memory");
  const unsigned epoch = *reinterpret_cast<unsigned*>(smem + EPOCH_OFF);

  if (wg == 0) {
    asm volatile("setmaxnreg.dec.sync.aligned.u32 40;");
    const int warp = tid >> 5, lane = tid & 31;
    int g = 0;
    auto acquire = [&](uint32_t bytes) -> uint32_t {
      const int s = g & (STAGES - 1);
      mbar_wait(empty0 + 8 * s, ((g / STAGES) & 1) ^ 1);
      mbar_expect_tx(full0 + 8 * s, bytes);
      g++;
      return s;
    };
    if (warp == 0) {
      const int row = rb * 128 + rank * 64;
      auto loadA = [&](const CUtensorMap* m, int kb0, int n) {
        if (lane == 0)
          for (int i = 0; i < n; i++) {
            const uint32_t s = acquire(A_BYTES);
            tma_load_2d_mc(sbase + s * STAGE_BYTES + rank * 8192, m, full0 + 8 * s, (kb0 + i) * 64, row, 3);
          }
        __syncwarp();
      };
      loadA(&maps.x, 0, 10);
      loadA(&maps.x, 0, 10);
      if (grp == 0) {
        loadA(&maps.wsp, 0, 32);
        loadA(&maps.wsim, 32 - NX, NX);
        wait_flags(flag_h + rb * 4, 1, 4, epoch);
        loadA(&maps.h, 0, 12);
      } else {
        loadA(&maps.wsre, 0, 32);
        loadA(&maps.wsim, 0, 32 - NX);
      }
    } else if (warp == 1) {
      auto loadB3 = [&](const CUtensorMap* m, int chunk, int n) {
        if (lane == 0)
          for (int i = 0; i < n; i++) {
            const uint32_t s = acquire(24576);
            tma_load_3d(sbase + s * STAGE_BYTES + A_BYTES, m, full0 + 8 * s, 0, i * 64, chunk);
          }
        __syncwarp();
      };
      auto loadBK = [&](const CUtensorMap* m, int row, int kb0, int n) {
        if (lane == 0)
          for (int i = 0; i < n; i++) {
            const uint32_t s = acquire(20480);
            tma_load_2d(sbase + s * STAGE_BYTES + A_BYTES, m, full0 + 8 * s, (kb0 + i) * 64, row);
          }
        __syncwarp();
      };
      if (grp == 0) {
        loadB3(&maps.win3, 12 + 3 * ct, 10);
        loadB3(&maps.win3, 3 * ct, 10);
        wait_flags(flag_z + ct, 4, 16, epoch);
        loadB3(&maps.z23, 3 * ct, 32);
        wait_flags(flag_b + ct, 4, 16, epoch);
        loadBK(&maps.ab, DM + ct * 160, 32 - NX, NX);
        if (lane == 0)
          for (int i = 0; i < 12; i++) {
            const uint32_t s = acquire(24576);
            #pragma unroll
            for (int j = 0; j < 3; j++)
              tma_load_2d(sbase + s * STAGE_BYTES + A_BYTES + j * 8192, &maps.wout, full0 + 8 * s, ct * 160 + j * 64, i * 64);
          }
      } else {
        loadBK(&maps.wdre, ct * 160, 0, 10);
        loadBK(&maps.wdim, ct * 160, 0, 10);
        wait_flags(flag_a + ct, 4, 16, epoch);
        loadBK(&maps.ab, ct * 160, 0, 32);
        wait_flags(flag_b + ct, 4, 16, epoch);
        loadBK(&maps.ab, DM + ct * 160, 0, 32 - NX);
      }
    }
  } else {
    asm volatile("setmaxnreg.inc.sync.aligned.u32 232;");
    const int t = tid & 127, w = t >> 5, l = t & 31;
    const uint32_t buf = sbase + BUF_OFF;
    if (grp == 0) {
      if (wg == 1) {
        float acc[2][96];
        mainloop<192, 1, false, true, BAR_ORD1>(acc, sbase, 0, 10, KB_A, 0);
        bar_sync<BAR_STATS>(256);
        fold_ln<192>(acc, 0, 1.f);
        float mean[4], m2[4];
        #pragma unroll
        for (int mi = 0; mi < 2; mi++) {
          float s0 = 0.f, s1 = 0.f;
          #pragma unroll
          for (int j = 0; j < 24; j++) {
            #pragma unroll
            for (int e = 0; e < 4; e++) acc[mi][4 * j + e] = gelu_tanh(acc[mi][4 * j + e]);
            s0 += acc[mi][4 * j] + acc[mi][4 * j + 1];
            s1 += acc[mi][4 * j + 2] + acc[mi][4 * j + 3];
          }
          const float mu0 = quad_sum(s0) * (1.f / 192), mu1 = quad_sum(s1) * (1.f / 192);
          float q0 = 0.f, q1 = 0.f;
          #pragma unroll
          for (int j = 0; j < 24; j++) {
            const float d0 = acc[mi][4 * j] - mu0, d1 = acc[mi][4 * j + 1] - mu0, d2 = acc[mi][4 * j + 2] - mu1, d3 = acc[mi][4 * j + 3] - mu1;
            q0 += d0 * d0 + d1 * d1; q1 += d2 * d2 + d3 * d3;
          }
          mean[mi * 2] = mu0; mean[mi * 2 + 1] = mu1;
          m2[mi * 2] = quad_sum(q0); m2[mi * 2 + 1] = quad_sum(q1);
        }
        {
          const int qd = l & 3;
          const float pm = qd == 0 ? mean[0] : qd == 1 ? mean[1] : qd == 2 ? mean[2] : mean[3];
          const float pq = qd == 0 ? m2[0] : qd == 1 ? m2[1] : qd == 2 ? m2[2] : m2[3];
          const int rbase = w * 16 + (l >> 2);
          st_vol4(&g_zstat[(rb * 4 + ct) * 128 + rbase + (qd >> 1) * 64 + (qd & 1) * 8], __float_as_uint(pm), __float_as_uint(pq), epoch, 0u);
          if (qd != ct) {
            const uint4* src = &g_zstat[(rb * 4 + qd) * 128 + rbase];
            unsigned it = 0;
            while (true) {
              uint4 v[4];
              #pragma unroll
              for (int r = 0; r < 4; r++) v[r] = ld_vol4(src + (r >> 1) * 64 + (r & 1) * 8);
              bool ok = true;
              #pragma unroll
              for (int r = 0; r < 4; r++) { ok = ok && v[r].z == epoch; mean[r] = __uint_as_float(v[r].x); m2[r] = __uint_as_float(v[r].y); }
              if (ok) break;
              if ((++it & 4095u) == 0 && timed_out()) break;
            }
          }
          __syncwarp();
          #pragma unroll
          for (int r = 0; r < 4; r++) {
            const float mu = quad_sum(mean[r]) * 0.25f;
            const float d = mean[r] - mu;
            const float var = quad_sum(fmaf(192.f * d, d, m2[r])) * (1.f / FH);
            const float rstd = 1.f / sqrtf(var + LN_EPS);
            mean[r] = -mu * rstd; m2[r] = rstd;
          }
        }
        #pragma unroll
        for (int mi = 0; mi < 2; mi++)
          #pragma unroll
          for (int jj = 0; jj < 12; jj++) {
            const float* a = &acc[mi][8 * jj];
            const float r0 = m2[mi * 2], o0 = mean[mi * 2], r1 = m2[mi * 2 + 1], o1 = mean[mi * 2 + 1];
            stsm4(stage_addr_rm(buf, mi, jj),
                  pack_bf16(fmaf(a[0], r0, o0), fmaf(a[1], r0, o0)), pack_bf16(fmaf(a[2], r1, o1), fmaf(a[3], r1, o1)),
                  pack_bf16(fmaf(a[4], r0, o0), fmaf(a[5], r0, o0)), pack_bf16(fmaf(a[6], r1, o1), fmaf(a[7], r1, o1)));
          }
        fence_async_smem();
        bar_sync<BAR_WG1>(128);
        if (t == 0) {
          tma_store_3d(&maps.z23, buf, 0, rb * 128, 3 * ct);
          tma_store_3d(&maps.z23, buf + 24576, 0, rb * 128 + 64, 3 * ct);
          publish(flag_z + rb * 4 + ct, epoch);
        }
        __syncwarp();
        bar_arrive<BAR_BUF>(256);
        bar_sync<BAR_ORD2>(256);
        mainloop<192, 1, false, true, BAR_ORD1>(acc, sbase, 20, 32, KB_A, 0);
        bar_sync<BAR_Z1>(256);
        #pragma unroll
        for (int mi = 0; mi < 2; mi++) {
          const int row = rb * 128 + mi * 64 + w * 16 + (l >> 2);
          const float b0 = __bfloat162float(bsp[row]), b1 = __bfloat162float(bsp[row + 8]);
          #pragma unroll
          for (int jj = 0; jj < 12; jj++) {
            const float* a = &acc[mi][8 * jj];
            const uint32_t ad = stage_addr_rm(buf, mi, jj);
            uint32_t z0, z1, z2, z3;
            ldsm4(ad, z0, z1, z2, z3);
            stsm4(ad, pack_bf16(bf_lo(z0) * (a[0] + b0), bf_hi(z0) * (a[1] + b0)), pack_bf16(bf_lo(z1) * (a[2] + b1), bf_hi(z1) * (a[3] + b1)),
                      pack_bf16(bf_lo(z2) * (a[4] + b0), bf_hi(z2) * (a[5] + b0)), pack_bf16(bf_lo(z3) * (a[6] + b1), bf_hi(z3) * (a[7] + b1)));
          }
        }
        fence_async_smem();
        bar_sync<BAR_WG1>(128);
        if (t == 0) {
          tma_store_3d(&maps.h3, buf, 0, rb * 128, 3 * ct);
          tma_store_3d(&maps.h3, buf + 24576, 0, rb * 128 + 64, 3 * ct);
          publish(flag_h + rb * 4 + ct, epoch);
        }
        __syncwarp();
        bar_arrive<BAR_BUF>(256);
      } else {
        stats_prologue(x, wdre, wdim, win, rb, 2 * DM + FH + ct * 192, 2 * DM + ct * 192, 192, epoch);
        bar_arrive<BAR_STATS>(256);
        {
          float acc[2][96];
          bar_sync<BAR_ORD1>(256);
          mainloop<192, 1, false, true, BAR_ORD2>(acc, sbase, 10, 10, KB_A, 0);
          fold_ln<192>(acc, 1, 1.f);
          bar_sync<BAR_BUF>(256);
          #pragma unroll
          for (int mi = 0; mi < 2; mi++)
            #pragma unroll
            for (int jj = 0; jj < 12; jj++) {
              const float* a = &acc[mi][8 * jj];
              stsm4(stage_addr_rm(buf, mi, jj), pack_bf16(gelu_tanh(a[0]), gelu_tanh(a[1])), pack_bf16(gelu_tanh(a[2]), gelu_tanh(a[3])),
                    pack_bf16(gelu_tanh(a[4]), gelu_tanh(a[5])), pack_bf16(gelu_tanh(a[6]), gelu_tanh(a[7])));
            }
          bar_arrive<BAR_Z1>(256);
        }
        {
          float acc[2][80];
          init_residual<0>(acc, x, rb, ct);
          bar_sync<BAR_ORD1>(256);
          mainloop<160, 0, false, false, 0>(acc, sbase, 52, NX, KB_A, 1);
          mainloop<160, 1, true, true, 0>(acc, sbase, 52 + NX, 12, KB_A, 1);
          bar_sync<BAR_BUF>(256);
          final_epilogue<0>(acc, sbase, maps, rb, ct, epoch);
        }
      }
    } else {
      float acc[2][80];
      if (wg == 1) {
        mainloop<160, 0, false, true, BAR_ORD1>(acc, sbase, 0, 10, KB_B, 0);
        bar_sync<BAR_STATS>(256);
        fold_ln<160>(acc, 0, 1.f);
        stage_transposed(acc, buf);
        bar_sync<BAR_WG1>(128);
        if (t == 0) {
          tma_store_2d(&maps.ab, buf, rb * 128, ct * 160);
          tma_store_2d(&maps.ab, buf + 20480, rb * 128 + 64, ct * 160);
          publish(flag_a + rb * 4 + ct, epoch);
        }
        __syncwarp();
        bar_arrive<BAR_BUF>(256);
        init_residual<1>(acc, x, rb, ct);
        bar_sync<BAR_ORD2>(256);
        mainloop<160, 0, false, true, 0>(acc, sbase, 20, 64 - NX, KB_B, 1);
        bar_sync<BAR_Z1>(256);
        final_epilogue<1>(acc, sbase, maps, rb, ct, epoch);
      } else {
        stats_prologue(x, wdre, wdim, win, rb, ct * 160, DM + ct * 160, 160, epoch);
        bar_arrive<BAR_STATS>(256);
        bar_sync<BAR_ORD1>(256);
        mainloop<160, 0, false, true, BAR_ORD2>(acc, sbase, 10, 10, KB_B, 0);
        fold_ln<160>(acc, 1, -1.f);
        bar_sync<BAR_BUF>(256);
        stage_transposed(acc, buf);
        bar_sync<BAR_WG2>(128);
        if (t == 0) {
          tma_store_2d(&maps.ab, buf, rb * 128, DM + ct * 160);
          tma_store_2d(&maps.ab, buf + 20480, rb * 128 + 64, DM + ct * 160);
          publish(flag_b + rb * 4 + ct, epoch);
        }
        __syncwarp();
        bar_arrive<BAR_Z1>(256);
      }
    }
    if (t == 0 && wg == (grp == 0 ? 2 : 1)) atomicAdd(&g_done, 1u);
  }
}

typedef CUresult (*EncodeFn)(CUtensorMap*, CUtensorMapDataType, cuuint32_t, void*, const cuuint64_t*, const cuuint64_t*,
                             const cuuint32_t*, const cuuint32_t*, CUtensorMapInterleave, CUtensorMapSwizzle,
                             CUtensorMapL2promotion, CUtensorMapFloatOOBfill);

void make2d(EncodeFn enc, CUtensorMap* m, const void* p, uint64_t cols, uint64_t rows, uint32_t bc, uint32_t br, bool swz = true) {
  cuuint64_t gd[2] = {cols, rows}, gs[1] = {cols * 2};
  cuuint32_t bd[2] = {bc, br}, es[2] = {1, 1};
  enc(m, CU_TENSOR_MAP_DATA_TYPE_BFLOAT16, 2, const_cast<void*>(p), gd, gs, bd, es, CU_TENSOR_MAP_INTERLEAVE_NONE,
      swz ? CU_TENSOR_MAP_SWIZZLE_128B : CU_TENSOR_MAP_SWIZZLE_NONE, CU_TENSOR_MAP_L2_PROMOTION_L2_256B, CU_TENSOR_MAP_FLOAT_OOB_FILL_NONE);
}
void make3d(EncodeFn enc, CUtensorMap* m, const void* p, uint64_t cols, uint64_t rows) {
  cuuint64_t gd[3] = {64, rows, cols / 64}, gs[2] = {cols * 2, 128};
  cuuint32_t bd[3] = {64, 64, 3}, es[3] = {1, 1, 1};
  enc(m, CU_TENSOR_MAP_DATA_TYPE_BFLOAT16, 3, const_cast<void*>(p), gd, gs, bd, es, CU_TENSOR_MAP_INTERLEAVE_NONE,
      CU_TENSOR_MAP_SWIZZLE_128B, CU_TENSOR_MAP_L2_PROMOTION_L2_256B, CU_TENSOR_MAP_FLOAT_OOB_FILL_NONE);
}

}

extern "C" void kernel_launch(void* const* d_in, const int* in_sizes, int n_in, void* d_out, int out_size) {
  const bf16* x = (const bf16*)d_in[0];
  const bf16* wsre = (const bf16*)d_in[1];
  const bf16* wsim = (const bf16*)d_in[2];
  const bf16* wdre = (const bf16*)d_in[3];
  const bf16* wdim = (const bf16*)d_in[4];
  const bf16* win = (const bf16*)d_in[6];
  const bf16* wsp = (const bf16*)d_in[7];
  const bf16* bsp = (const bf16*)d_in[8];
  const bf16* wout = (const bf16*)d_in[9];

  void* fn = nullptr;
  cudaDriverEntryPointQueryResult qr;
  cudaGetDriverEntryPoint("cuTensorMapEncodeTiled", &fn, cudaEnableDefault, &qr);
  EncodeFn enc = (EncodeFn)fn;
  void *abT, *z2, *h;
  cudaGetSymbolAddress(&abT, g_abT);
  cudaGetSymbolAddress(&z2, g_z2);
  cudaGetSymbolAddress(&h, g_h);

  Maps maps;
  make2d(enc, &maps.x, x, DM, SEQ, 64, 64);
  make2d(enc, &maps.wsre, wsre, SEQ, SEQ, 64, 64);
  make2d(enc, &maps.wsim, wsim, SEQ, SEQ, 64, 64);
  make2d(enc, &maps.wsp, wsp, SEQ, SEQ, 64, 64);
  make2d(enc, &maps.h, h, FH, SEQ, 64, 64);
  make3d(enc, &maps.h3, h, FH, SEQ);
  make3d(enc, &maps.win3, win, FF, DM);
  make3d(enc, &maps.z23, z2, FH, SEQ);
  make2d(enc, &maps.wdre, wdre, DM, DM, 64, 160);
  make2d(enc, &maps.wdim, wdim, DM, DM, 64, 160);
  make2d(enc, &maps.ab, abT, SEQ, 2 * DM, 64, 160);
  make2d(enc, &maps.wout, wout, DM, FH, 64, 64);
  make2d(enc, &maps.out, d_out, DM, SEQ, 160, 16, false);

  cudaFuncSetAttribute(fused_kernel, cudaFuncAttributeMaxDynamicSharedMemorySize, SMEM_BYTES);
  fused_kernel<<<128, 384, SMEM_BYTES>>>(maps, x, wdre, wdim, win, bsp);
}
```

```cpp
#include <cuda_runtime.h>
#include <cuda_bf16.h>
#include <cuda.h>
#include <stdint.h>

namespace {

typedef __nv_bfloat16 bf16;

constexpr int SEQ = 2048, DM = 640, FF = 1536, FH = 768;
constexpr int NX = 5;
constexpr int STAGES = 4;
constexpr int A_BYTES = 16384;
constexpr int STAGE_BYTES = 40960;
constexpr int BUF_OFF = STAGES * STAGE_BYTES;
constexpr int BUF_BYTES = 49152;
constexpr int MISC_OFF = BUF_OFF + BUF_BYTES;
constexpr int ROWSTAT_OFF = MISC_OFF;
constexpr int COLSUM_OFF = ROWSTAT_OFF + 1024;
constexpr int RED_OFF = COLSUM_OFF + 1536;
constexpr int BAR_OFF = RED_OFF + 256;
constexpr int EPOCH_OFF = BAR_OFF + 128;
constexpr int SMEM_BYTES = EPOCH_OFF + 64;
constexpr int KB_A = 20 + 32 + NX + 12;
constexpr int KB_B = 20 + 64 - NX;
constexpr float LN_EPS = 1e-5f;
constexpr int DEADLINE_OFF = EPOCH_OFF + 8;

constexpr int BAR_ORD1 = 1, BAR_ORD2 = 2, BAR_WG1 = 3, BAR_WG2 = 4, BAR_STATS = 5, BAR_BUF = 6, BAR_Z1 = 7;

enum { M_X, M_WSRE, M_WSIM, M_WSP, M_H, M_H3, M_WIN3, M_Z23, M_WDRE, M_WDIM, M_AB, M_WOUT, M_OUT, M_COUNT };
struct Maps { CUtensorMap m[M_COUNT]; };

__device__ __align__(1024) bf16 g_abT[2 * DM * SEQ];
__device__ __align__(1024) bf16 g_z2[SEQ * FH];
__device__ __align__(1024) bf16 g_h[SEQ * FH];
__device__ __align__(16) uint4 g_xstat[SEQ];
__device__ __align__(16) uint2 g_csum[2 * DM + FF];
__device__ __align__(16) uint4 g_zstat[16 * 4 * 128];
__device__ __align__(16) uint4 g_part[128 * 27 * 128];
__device__ unsigned g_flags[4 * 64];
__device__ unsigned g_done;
#define TS(role, ev)

extern __shared__ __align__(1024) uint8_t smem[];

__device__ __forceinline__ unsigned long long gtime() { unsigned long long t; asm volatile("mov.u64 %0, %%globaltimer;" : "=l"(t)); return t; }
__device__ __forceinline__ bool timed_out() { return gtime() > *reinterpret_cast<volatile unsigned long long*>(smem + DEADLINE_OFF); }
__device__ __forceinline__ uint32_t smem_u32(const void* p) { return (uint32_t)__cvta_generic_to_shared(p); }
__device__ __forceinline__ void mbar_init(uint32_t bar, uint32_t cnt) { asm volatile("mbarrier.init.shared::cta.b64 [%0], %1;" :: "r"(bar), "r"(cnt)); }
__device__ __forceinline__ void mbar_expect_tx(uint32_t bar, uint32_t bytes) { asm volatile("mbarrier.arrive.expect_tx.shared::cta.b64 _, [%0], %1;" :: "r"(bar), "r"(bytes) : "memory"); }
__device__ __forceinline__ void mbar_arrive(uint32_t bar) { asm volatile("mbarrier.arrive.shared::cta.b64 _, [%0];" :: "r"(bar) : "memory"); }
__device__ __forceinline__ void mbar_arrive_cluster(uint32_t bar, uint32_t cta) {
  asm volatile("{\n.reg .b32 ra;\nmapa.shared::cluster.u32 ra, %0, %1;\nmbarrier.arrive.shared::cluster.b64 _, [ra];\n}" :: "r"(bar), "r"(cta) : "memory");
}
__device__ __forceinline__ bool mbar_try(uint32_t bar, uint32_t parity) {
  uint32_t ok;
  asm volatile("{\n.reg .pred p;\nmbarrier.try_wait.parity.shared::cta.b64 p, [%1], %2;\nselp.u32 %0, 1, 0, p;\n}" : "=r"(ok) : "r"(bar), "r"(parity) : "memory");
  return ok != 0;
}
__device__ __forceinline__ void mbar_wait(uint32_t bar, uint32_t parity) {
  unsigned n = 0;
  while (!mbar_try(bar, parity)) { if ((++n & 4095u) == 0 && timed_out()) break; }
}
__device__ __forceinline__ void tma_load_2d(uint32_t dst, const CUtensorMap* map, uint32_t bar, int c0, int c1) {
  asm volatile("cp.async.bulk.tensor.2d.shared::cluster.global.mbarrier::complete_tx::bytes [%0], [%1, {%3, %4}], [%2];"
    :: "r"(dst), "l"((uint64_t)map), "r"(bar), "r"(c0), "r"(c1) : "memory");
}
__device__ __forceinline__ void tma_load_3d(uint32_t dst, const CUtensorMap* map, uint32_t bar, int c0, int c1, int c2) {
  asm volatile("cp.async.bulk.tensor.3d.shared::cluster.global.mbarrier::complete_tx::bytes [%0], [%1, {%3, %4, %5}], [%2];"
    :: "r"(dst), "l"((uint64_t)map), "r"(bar), "r"(c0), "r"(c1), "r"(c2) : "memory");
}
__device__ __forceinline__ void tma_load_2d_mc(uint32_t dst, const CUtensorMap* map, uint32_t bar, int c0, int c1, uint16_t mask) {
  asm volatile("cp.async.bulk.tensor.2d.shared::cluster.global.mbarrier::complete_tx::bytes.multicast::cluster [%0], [%1, {%3, %4}], [%2], %5;"
    :: "r"(dst), "l"((uint64_t)map), "r"(bar), "r"(c0), "r"(c1), "h"(mask) : "memory");
}
__device__ __forceinline__ void tma_store_2d(const CUtensorMap* map, uint32_t src, int c0, int c1) {
  asm volatile("cp.async.bulk.tensor.2d.global.shared::cta.bulk_group [%0, {%2, %3}], [%1];"
    :: "l"((uint64_t)map), "r"(src), "r"(c0), "r"(c1) : "memory");
}
__device__ __forceinline__ void tma_store_3d(const CUtensorMap* map, uint32_t src, int c0, int c1, int c2) {
  asm volatile("cp.async.bulk.tensor.3d.global.shared::cta.bulk_group [%0, {%2, %3, %4}], [%1];"
    :: "l"((uint64_t)map), "r"(src), "r"(c0), "r"(c1), "r"(c2) : "memory");
}
__device__ __forceinline__ void tma_prefetch_2d(const CUtensorMap* map, int c0, int c1) {
  asm volatile("cp.async.bulk.prefetch.tensor.2d.L2.global.tile [%0, {%1, %2}];" :: "l"((uint64_t)map), "r"(c0), "r"(c1) : "memory");
}
__device__ __forceinline__ void tma_prefetch_3d(const CUtensorMap* map, int c0, int c1, int c2) {
  asm volatile("cp.async.bulk.prefetch.tensor.3d.L2.global.tile [%0, {%1, %2, %3}];" :: "l"((uint64_t)map), "r"(c0), "r"(c1), "r"(c2) : "memory");
}
__device__ __forceinline__ void bulk_commit() { asm volatile("cp.async.bulk.commit_group;" ::: "memory"); }
__device__ __forceinline__ void bulk_wait_all() { asm volatile("cp.async.bulk.wait_group 0;" ::: "memory"); }
__device__ __forceinline__ void bulk_wait_read() { asm volatile("cp.async.bulk.wait_group.read 0;" ::: "memory"); }
__device__ __forceinline__ void fence_async_smem() { asm volatile("fence.proxy.async.shared::cta;" ::: "memory"); }
__device__ __forceinline__ void fence_async_global() { asm volatile("fence.proxy.async.global;" ::: "memory"); }
__device__ __forceinline__ void wgmma_fence() { asm volatile("wgmma.fence.sync.aligned;" ::: "memory"); }
__device__ __forceinline__ void wgmma_commit() { asm volatile("wgmma.commit_group.sync.aligned;" ::: "memory"); }
template<int N> __device__ __forceinline__ void wgmma_wait() { asm volatile("wgmma.wait_group.sync.aligned %0;" :: "n"(N) : "memory"); }
template<int ID> __device__ __forceinline__ void bar_sync(int n) { asm volatile("bar.sync %0, %1;" :: "n"(ID), "r"(n) : "memory"); }
template<int ID> __device__ __forceinline__ void bar_arrive(int n) { asm volatile("bar.arrive %0, %1;" :: "n"(ID), "r"(n) : "memory"); }
__device__ __forceinline__ uint64_t make_desc(uint32_t addr, uint32_t lbo, uint32_t sbo) {
  return (uint64_t)((addr & 0x3FFFF) >> 4) | ((uint64_t)(lbo >> 4) << 16) | ((uint64_t)(sbo >> 4) << 32) | (1ull << 62);
}
__device__ __forceinline__ uint4 ld_vol4(const uint4* p) {
  uint4 v; asm volatile("ld.volatile.global.v4.u32 {%0,%1,%2,%3}, [%4];" : "=r"(v.x), "=r"(v.y), "=r"(v.z), "=r"(v.w) : "l"(p) : "memory"); return v;
}
__device__ __forceinline__ uint2 ld_vol2(const uint2* p) {
  uint2 v; asm volatile("ld.volatile.global.v2.u32 {%0,%1}, [%2];" : "=r"(v.x), "=r"(v.y) : "l"(p) : "memory"); return v;
}
__device__ __forceinline__ void st_vol4(uint4* p, uint32_t a, uint32_t b, uint32_t c, uint32_t d) {
  asm volatile("st.volatile.global.v4.u32 [%0], {%1,%2,%3,%4};" :: "l"(p), "r"(a), "r"(b), "r"(c), "r"(d) : "memory");
}
__device__ __forceinline__ void st_vol2(uint2* p, uint32_t a, uint32_t b) {
  asm volatile("st.volatile.global.v2.u32 [%0], {%1,%2};" :: "l"(p), "r"(a), "r"(b) : "memory");
}
__device__ __forceinline__ unsigned ld_acquire(const unsigned* p) {
  unsigned v; asm volatile("ld.acquire.gpu.global.u32 %0, [%1];" : "=r"(v) : "l"(p) : "memory"); return v;
}
__device__ __forceinline__ void st_release(unsigned* p, unsigned v) {
  asm volatile("st.release.gpu.global.u32 [%0], %1;" :: "l"(p), "r"(v) : "memory");
}
__device__ __forceinline__ uint32_t pack_bf16(float lo, float hi) {
  uint32_t r; asm("cvt.rn.bf16x2.f32 %0, %1, %2;" : "=r"(r) : "f"(hi), "f"(lo)); return r;
}
__device__ __forceinline__ float bf_lo(uint32_t v) { return __uint_as_float(v << 16); }
__device__ __forceinline__ float bf_hi(uint32_t v) { return __uint_as_float(v & 0xFFFF0000u); }
__device__ __forceinline__ void stsm4(uint32_t addr, uint32_t a, uint32_t b, uint32_t c, uint32_t d) {
  asm volatile("stmatrix.sync.aligned.m8n8.x4.shared.b16 [%0], {%1,%2,%3,%4};" :: "r"(addr), "r"(a), "r"(b), "r"(c), "r"(d) : "memory");
}
__device__ __forceinline__ void stsm4_t(uint32_t addr, uint32_t a, uint32_t b, uint32_t c, uint32_t d) {
  asm volatile("stmatrix.sync.aligned.m8n8.x4.trans.shared.b16 [%0], {%1,%2,%3,%4};" :: "r"(addr), "r"(a), "r"(b), "r"(c), "r"(d) : "memory");
}
__device__ __forceinline__ void ldsm4(uint32_t addr, uint32_t& a, uint32_t& b, uint32_t& c, uint32_t& d) {
  asm volatile("ldmatrix.sync.aligned.m8n8.x4.shared.b16 {%0,%1,%2,%3}, [%4];" : "=r"(a), "=r"(b), "=r"(c), "=r"(d) : "r"(addr) : "memory");
}
__device__ __forceinline__ uint4 lds128(uint32_t a) {
  uint4 v; asm volatile("ld.shared.v4.u32 {%0,%1,%2,%3}, [%4];" : "=r"(v.x), "=r"(v.y), "=r"(v.z), "=r"(v.w) : "r"(a) : "memory"); return v;
}
__device__ __forceinline__ void sts128(uint32_t a, uint32_t x, uint32_t y, uint32_t z, uint32_t w) {
  asm volatile("st.shared.v4.u32 [%0], {%1,%2,%3,%4};" :: "r"(a), "r"(x), "r"(y), "r"(z), "r"(w) : "memory");
}
__device__ __forceinline__ uint32_t hmul2_bf16(uint32_t a, uint32_t b) {
  uint32_t r; asm("mul.rn.bf16x2 %0, %1, %2;" : "=r"(r) : "r"(a), "r"(b)); return r;
}
__device__ __forceinline__ float gelu_tanh(float v) {
  float u = v * fmaf(0.0356774081f, v * v, 0.7978845608f);
  float t; asm("tanh.approx.f32 %0, %1;" : "=f"(t) : "f"(u));
  float hv = 0.5f * v;
  return fmaf(hv, t, hv);
}
__device__ __forceinline__ float warp_sum(float v) {
  #pragma unroll
  for (int o = 16; o > 0; o >>= 1) v += __shfl_xor_sync(0xffffffffu, v, o);
  return v;
}
__device__ __forceinline__ float quad_sum(float v) {
  v += __shfl_xor_sync(0xffffffffu, v, 1);
  v += __shfl_xor_sync(0xffffffffu, v, 2);
  return v;
}

template<int TB>
__device__ __forceinline__ void wgmma_n192(float (&d)[96], uint64_t da, uint64_t db, int scale_d) {
  asm volatile("{\n.reg .pred p;\nsetp.ne.b32 p, %98, 0;\n"
   "wgmma.mma_async.sync.aligned.m64n192k16.f32.bf16.bf16 {%0,%1,%2,%3,%4,%5,%6,%7,%8,%9,%10,%11,%12,%13,%14,%15,%16,%17,%18,%19,%20,%21,%22,%23,%24,%25,%26,%27,%28,%29,%30,%31,%32,%33,%34,%35,%36,%37,%38,%39,%40,%41,%42,%43,%44,%45,%46,%47,%48,%49,%50,%51,%52,%53,%54,%55,%56,%57,%58,%59,%60,%61,%62,%63,%64,%65,%66,%67,%68,%69,%70,%71,%72,%73,%74,%75,%76,%77,%78,%79,%80,%81,%82,%83,%84,%85,%86,%87,%88,%89,%90,%91,%92,%93,%94,%95}, %96, %97, p, 1, 1, 0, %99;\n}"
   : "+f"(d[0]),"+f"(d[1]),"+f"(d[2]),"+f"(d[3]),"+f"(d[4]),"+f"(d[5]),"+f"(d[6]),"+f"(d[7]),"+f"(d[8]),"+f"(d[9]),"+f"(d[10]),"+f"(d[11]),"+f"(d[12]),"+f"(d[13]),"+f"(d[14]),"+f"(d[15]),"+f"(d[16]),"+f"(d[17]),"+f"(d[18]),"+f"(d[19]),"+f"(d[20]),"+f"(d[21]),"+f"(d[22]),"+f"(d[23]),"+f"(d[24]),"+f"(d[25]),"+f"(d[26]),"+f"(d[27]),"+f"(d[28]),"+f"(d[29]),"+f"(d[30]),"+f"(d[31]),"+f"(d[32]),"+f"(d[33]),"+f"(d[34]),"+f"(d[35]),"+f"(d[36]),"+f"(d[37]),"+f"(d[38]),"+f"(d[39]),"+f"(d[40]),"+f"(d[41]),"+f"(d[42]),"+f"(d[43]),"+f"(d[44]),"+f"(d[45]),"+f"(d[46]),"+f"(d[47]),"+f"(d[48]),"+f"(d[49]),"+f"(d[50]),"+f"(d[51]),"+f"(d[52]),"+f"(d[53]),"+f"(d[54]),"+f"(d[55]),"+f"(d[56]),"+f"(d[57]),"+f"(d[58]),"+f"(d[59]),"+f"(d[60]),"+f"(d[61]),"+f"(d[62]),"+f"(d[63]),"+f"(d[64]),"+f"(d[65]),"+f"(d[66]),"+f"(d[67]),"+f"(d[68]),"+f"(d[69]),"+f"(d[70]),"+f"(d[71]),"+f"(d[72]),"+f"(d[73]),"+f"(d[74]),"+f"(d[75]),"+f"(d[76]),"+f"(d[77]),"+f"(d[78]),"+f"(d[79]),"+f"(d[80]),"+f"(d[81]),"+f"(d[82]),"+f"(d[83]),"+f"(d[84]),"+f"(d[85]),"+f"(d[86]),"+f"(d[87]),"+f"(d[88]),"+f"(d[89]),"+f"(d[90]),"+f"(d[91]),"+f"(d[92]),"+f"(d[93]),"+f"(d[94]),"+f"(d[95])
   : "l"(da), "l"(db), "r"(scale_d), "n"(TB));
}
template<int TB>
__device__ __forceinline__ void wgmma_n160(float (&d)[80], uint64_t da, uint64_t db, int scale_d) {
  asm volatile("{\n.reg .pred p;\nsetp.ne.b32 p, %82, 0;\n"
   "wgmma.mma_async.sync.aligned.m64n160k16.f32.bf16.bf16 {%0,%1,%2,%3,%4,%5,%6,%7,%8,%9,%10,%11,%12,%13,%14,%15,%16,%17,%18,%19,%20,%21,%22,%23,%24,%25,%26,%27,%28,%29,%30,%31,%32,%33,%34,%35,%36,%37,%38,%39,%40,%41,%42,%43,%44,%45,%46,%47,%48,%49,%50,%51,%52,%53,%54,%55,%56,%57,%58,%59,%60,%61,%62,%63,%64,%65,%66,%67,%68,%69,%70,%71,%72,%73,%74,%75,%76,%77,%78,%79}, %80, %81, p, 1, 1, 0, %83;\n}"
   : "+f"(d[0]),"+f"(d[1]),"+f"(d[2]),"+f"(d[3]),"+f"(d[4]),"+f"(d[5]),"+f"(d[6]),"+f"(d[7]),"+f"(d[8]),"+f"(d[9]),"+f"(d[10]),"+f"(d[11]),"+f"(d[12]),"+f"(d[13]),"+f"(d[14]),"+f"(d[15]),"+f"(d[16]),"+f"(d[17]),"+f"(d[18]),"+f"(d[19]),"+f"(d[20]),"+f"(d[21]),"+f"(d[22]),"+f"(d[23]),"+f"(d[24]),"+f"(d[25]),"+f"(d[26]),"+f"(d[27]),"+f"(d[28]),"+f"(d[29]),"+f"(d[30]),"+f"(d[31]),"+f"(d[32]),"+f"(d[33]),"+f"(d[34]),"+f"(d[35]),"+f"(d[36]),"+f"(d[37]),"+f"(d[38]),"+f"(d[39]),"+f"(d[40]),"+f"(d[41]),"+f"(d[42]),"+f"(d[43]),"+f"(d[44]),"+f"(d[45]),"+f"(d[46]),"+f"(d[47]),"+f"(d[48]),"+f"(d[49]),"+f"(d[50]),"+f"(d[51]),"+f"(d[52]),"+f"(d[53]),"+f"(d[54]),"+f"(d[55]),"+f"(d[56]),"+f"(d[57]),"+f"(d[58]),"+f"(d[59]),"+f"(d[60]),"+f"(d[61]),"+f"(d[62]),"+f"(d[63]),"+f"(d[64]),"+f"(d[65]),"+f"(d[66]),"+f"(d[67]),"+f"(d[68]),"+f"(d[69]),"+f"(d[70]),"+f"(d[71]),"+f"(d[72]),"+f"(d[73]),"+f"(d[74]),"+f"(d[75]),"+f"(d[76]),"+f"(d[77]),"+f"(d[78]),"+f"(d[79])
   : "l"(da), "l"(db), "r"(scale_d), "n"(TB));
}

template<int N, int TB>
__device__ __forceinline__ void wgmma_n(float (&d)[N / 2], uint64_t da, uint64_t db, int scale_d) {
  if constexpr (N == 192) wgmma_n192<TB>(d, da, db, scale_d); else wgmma_n160<TB>(d, da, db, scale_d);
}

template<int R>
__device__ __forceinline__ void pin(float (&acc)[2][R]) {
  #pragma unroll
  for (int mi = 0; mi < 2; mi++)
    #pragma unroll
    for (int i = 0; i < R; i++) asm volatile("" : "+f"(acc[mi][i]) :: "memory");
}

template<int N, int TB, bool CONT>
__device__ __forceinline__ void mainloop(float (&acc)[2][N / 2], uint32_t sbase, int g0, int nk, int total, int accum0,
                                         int ord_bar, bool drain, int mswap) {
  const uint32_t full0 = sbase + BAR_OFF, empty0 = full0 + 8 * STAGES;
  const int lane = threadIdx.x & 31;
  const bool rel = ((threadIdx.x & 127) < 2);
  const uint64_t da0 = make_desc(sbase + mswap * 8192, 16, 1024), da1 = make_desc(sbase + (mswap ^ 1) * 8192, 16, 1024);
  const uint64_t db0 = TB ? make_desc(sbase + A_BYTES, 8192, 1024) : make_desc(sbase + A_BYTES, 16, 1024);
  if (!CONT) pin(acc);
  #pragma unroll 1
  for (int i = 0; i < nk; i++) {
    const int g = g0 + i;
    const int s = g & (STAGES - 1);
    const uint64_t so = (uint64_t)(s * (STAGE_BYTES >> 4));
    mbar_wait(full0 + 8 * s, (g / STAGES) & 1);
    wgmma_fence();
    #pragma unroll
    for (int k = 0; k < 4; k++) {
      const uint64_t db = db0 + so + (TB ? k * 128 : k * 2);
      wgmma_n<N, TB>(acc[0], da0 + so + k * 2, db, accum0 | i | k);
      wgmma_n<N, TB>(acc[1], da1 + so + k * 2, db, accum0 | i | k);
    }
    wgmma_commit();
    if (ord_bar != 0 && i == nk - 1) asm volatile("bar.arrive %0, 256;" :: "r"(ord_bar) : "memory");
    wgmma_wait<1>();
    if (rel && (CONT || i > 0) && g - 1 + STAGES < total) mbar_arrive_cluster(empty0 + 8 * ((g - 1) & (STAGES - 1)), lane);
  }
  if (drain) {
    wgmma_wait<0>();
    const int g = g0 + nk - 1;
    if (rel && g + STAGES < total) mbar_arrive_cluster(empty0 + 8 * (g & (STAGES - 1)), lane);
  }
}

__device__ __forceinline__ void publish(unsigned* flag, unsigned epoch) {
  bulk_commit();
  bulk_wait_all();
  st_release(flag, epoch);
}

__device__ __forceinline__ float sum4(uint2 v) { return (bf_lo(v.x) + bf_hi(v.x)) + (bf_lo(v.y) + bf_hi(v.y)); }

__device__ __forceinline__ void stats_prologue(const bf16* __restrict__ x, const bf16* __restrict__ wdre,
    const bf16* __restrict__ wdim, const bf16* __restrict__ win, int rb, int cs0, int cs1, int ncol, unsigned epoch) {
  const int t = threadIdx.x & 127, w = t >> 5, l = t & 31, cta = blockIdx.x;
  uint4 rv[2][10];
  uint4 cv[5][2];
  int ridx[2];
  #pragma unroll
  for (int p = 0; p < 2; p++) {
    const int r = min(p * 16 + w * 4 + (l >> 3), 25);
    ridx[p] = r;
    const int wr = cta * 10 + r - 16;
    const bf16* src = p == 0 ? x + (size_t)(cta * 16 + r) * DM : (wr < DM ? wdre + (size_t)wr * DM : wdim + (size_t)(wr - DM) * DM);
    #pragma unroll
    for (int j = 0; j < 10; j++) rv[p][j] = __ldg(reinterpret_cast<const uint4*>(src) + (l & 7) + 8 * j);
  }
  const int cc = min(cta, 95);
  #pragma unroll
  for (int i = 0; i < 5; i++) {
    const uint4* p = reinterpret_cast<const uint4*>(win + (size_t)(t + 128 * i) * FF + cc * 16);
    cv[i][0] = __ldg(p); cv[i][1] = __ldg(p + 1);
  }
  float sm[2];
  #pragma unroll
  for (int p = 0; p < 2; p++) {
    float s = 0.f;
    #pragma unroll
    for (int j = 0; j < 10; j++) s += sum4(make_uint2(rv[p][j].x, rv[p][j].y)) + sum4(make_uint2(rv[p][j].z, rv[p][j].w));
    s += __shfl_xor_sync(0xffffffffu, s, 1); s += __shfl_xor_sync(0xffffffffu, s, 2); s += __shfl_xor_sync(0xffffffffu, s, 4);
    sm[p] = s;
  }
  {
    const float mean = sm[0] * (1.f / DM);
    float q = 0.f;
    #pragma unroll
    for (int j = 0; j < 10; j++) {
      const uint32_t u[4] = {rv[0][j].x, rv[0][j].y, rv[0][j].z, rv[0][j].w};
      #pragma unroll
      for (int c = 0; c < 4; c++) { const float d0 = bf_lo(u[c]) - mean, d1 = bf_hi(u[c]) - mean; q = fmaf(d0, d0, q); q = fmaf(d1, d1, q); }
    }
    q += __shfl_xor_sync(0xffffffffu, q, 1); q += __shfl_xor_sync(0xffffffffu, q, 2); q += __shfl_xor_sync(0xffffffffu, q, 4);
    const float rstd = rsqrtf(fmaf(q, 1.f / DM, LN_EPS));
    if ((l & 7) == 0) {
      st_vol4(&g_xstat[cta * 16 + ridx[0]], __float_as_uint(rstd), __float_as_uint(-mean * rstd), epoch, 0u);
      st_vol2(&g_csum[cta * 10 + ridx[1] - 16], __float_as_uint(sm[1]), epoch);
    }
  }
  {
    float v[16];
    #pragma unroll
    for (int c = 0; c < 16; c++) v[c] = 0.f;
    #pragma unroll
    for (int i = 0; i < 5; i++) {
      const uint32_t u[8] = {cv[i][0].x, cv[i][0].y, cv[i][0].z, cv[i][0].w, cv[i][1].x, cv[i][1].y, cv[i][1].z, cv[i][1].w};
      #pragma unroll
      for (int c = 0; c < 8; c++) { v[2 * c] += bf_lo(u[c]); v[2 * c + 1] += bf_hi(u[c]); }
    }
    #pragma unroll
    for (int o = 16, n = 8; n >= 1; o >>= 1, n >>= 1) {
      const bool up = (l & o) != 0;
      #pragma unroll
      for (int c = 0; c < n; c++) {
        const float keep = up ? v[c + n] : v[c], send = up ? v[c] : v[c + n];
        v[c] = keep + __shfl_xor_sync(0xffffffffu, send, o);
      }
    }
    v[0] += __shfl_xor_sync(0xffffffffu, v[0], 1);
    float* red = reinterpret_cast<float*>(smem + RED_OFF);
    if ((l & 1) == 0) red[w * 16 + (l >> 1)] = v[0];
    bar_sync<BAR_WG2>(128);
    if (t < 16) st_vol2(&g_csum[2 * DM + cc * 16 + t], __float_as_uint((red[t] + red[16 + t]) + (red[32 + t] + red[48 + t])), epoch);
  }
  {
    unsigned it = 0;
    const int c1 = min(t + 128, ncol - 1);
    while (true) {
      const uint4 v = ld_vol4(&g_xstat[rb * 128 + t]);
      const uint2 u0 = ld_vol2(&g_csum[cs0 + t]), u1 = ld_vol2(&g_csum[cs0 + c1]), u2 = ld_vol2(&g_csum[cs1 + t]), u3 = ld_vol2(&g_csum[cs1 + c1]);
      reinterpret_cast<float2*>(smem + ROWSTAT_OFF)[t] = make_float2(__uint_as_float(v.x), __uint_as_float(v.y));
      uint32_t* cs = reinterpret_cast<uint32_t*>(smem + COLSUM_OFF);
      cs[t] = u0.x; cs[c1] = u1.x; cs[192 + t] = u2.x; cs[192 + c1] = u3.x;
      if (v.z == epoch && u0.y == epoch && u1.y == epoch && u2.y == epoch && u3.y == epoch) break;
      if ((++it & 4095u) == 0 && timed_out()) break;
    }
  }
}

__device__ __forceinline__ void fold_pack(const float* a, float2 s0, float2 s1, float2 c0, float2 c1, uint32_t (&r)[4]) {
  r[0] = pack_bf16(fmaf(a[0], s0.x, s0.y * c0.x), fmaf(a[1], s0.x, s0.y * c0.y));
  r[1] = pack_bf16(fmaf(a[2], s1.x, s1.y * c0.x), fmaf(a[3], s1.x, s1.y * c0.y));
  r[2] = pack_bf16(fmaf(a[4], s0.x, s0.y * c1.x), fmaf(a[5], s0.x, s0.y * c1.y));
  r[3] = pack_bf16(fmaf(a[6], s1.x, s1.y * c1.x), fmaf(a[7], s1.x, s1.y * c1.y));
}

__global__ void __cluster_dims__(2, 1, 1) __launch_bounds__(384, 1)
fused_kernel(const __grid_constant__ Maps maps, const bf16* __restrict__ x, const bf16* __restrict__ wdre,
             const bf16* __restrict__ wdim, const bf16* __restrict__ win, const bf16* __restrict__ bsp) {
  const uint32_t sbase = smem_u32(smem);
  const uint32_t full0 = sbase + BAR_OFF, empty0 = full0 + 8 * STAGES, dep0 = empty0 + 8 * STAGES;
  const int tid = threadIdx.x, wg = tid >> 7;
  const int rank = blockIdx.x & 1, grp = (blockIdx.x >> 1) & 1, q = blockIdx.x >> 2;
  const int rb = q >> 1, ct = (q & 1) * 2 + rank;
  const int total = grp == 0 ? KB_A : KB_B;

  if (tid == 0) {
    TS(0, 0);
    for (int s = 0; s < STAGES; s++) { mbar_init(full0 + 8 * s, 2); mbar_init(empty0 + 8 * s, 2); mbar_init(dep0 + 8 * s, 1); }
    *reinterpret_cast<unsigned long long*>(smem + DEADLINE_OFF) = gtime() + 200000000ull;
    asm volatile("fence.mbarrier_init.release.cluster;" ::: "memory");
  }
  __syncthreads();
  asm volatile("barrier.cluster.arrive.release.aligned;" ::: "memory");

  if (wg == 0) {
    asm volatile("setmaxnreg.dec.sync.aligned.u32 40;");
    const int warp = tid >> 5, lane = tid & 31;
    if (warp == 0) {
      const int row = rb * 128;
      if (lane == 0) {
        TS(0, 1);
        for (int g = 0; g < STAGES; g++) {
          mbar_expect_tx(full0 + 8 * g, A_BYTES);
          tma_load_2d(sbase + g * STAGE_BYTES, &maps.m[M_X], full0 + 8 * g, g * 64, row);
          tma_load_2d(sbase + g * STAGE_BYTES + 8192, &maps.m[M_X], full0 + 8 * g, g * 64, row + 64);
        }
      }
      __syncwarp();
      asm volatile("barrier.cluster.wait.acquire.aligned;" ::: "memory");
      if (lane == 0) {
        #pragma unroll 1
        for (int g = STAGES; g < total; g++) {
          int mi, kb;
          if (g < 20) { mi = M_X; kb = g < 10 ? g : g - 10; }
          else if (g < 52) { mi = grp == 0 ? M_WSP : M_WSRE; kb = g - 20; }
          else if (grp == 1) { mi = M_WSIM; kb = g - 52; }
          else if (g < 52 + NX) { mi = M_WSIM; kb = g - 52 + 32 - NX; }
          else { mi = M_H; kb = g - 52 - NX; if (kb == 0) { TS(0, 3); mbar_wait(dep0 + 16, 0); fence_async_global(); TS(0, 4); } }
          const int s = g & (STAGES - 1);
          mbar_wait(empty0 + 8 * s, ((g / STAGES) & 1) ^ 1);
          mbar_expect_tx(full0 + 8 * s, A_BYTES);
          tma_load_2d_mc(sbase + s * STAGE_BYTES + rank * 8192, &maps.m[mi], full0 + 8 * s, kb * 64, row + rank * 64, 3);
        }
        TS(0, 5);
      }
    } else if (warp == 1) {
      if (lane == 0) {
        #pragma unroll 1
        for (int g = 0; g < total; g++) {
          int kind, mi, kb, c;
          if (grp == 0) {
            if (g < 20) { kind = 0; mi = M_WIN3; kb = g < 10 ? g : g - 10; c = 3 * ct + (g < 10 ? 12 : 0); }
            else if (g < 52) { kind = 0; mi = M_Z23; kb = g - 20; c = 3 * ct; }
            else if (g < 52 + NX) { kind = 1; mi = M_AB; kb = g - 52 + 32 - NX; c = DM + ct * 160; }
            else { kind = 2; mi = M_WOUT; kb = g - 52 - NX; c = ct * 160; }
          } else {
            kind = 1;
            if (g < 20) { mi = g < 10 ? M_WDRE : M_WDIM; kb = g < 10 ? g : g - 10; c = ct * 160; }
            else { mi = M_AB; kb = g < 52 ? g - 20 : g - 52; c = ct * 160 + (g < 52 ? 0 : DM); }
          }
          if (g == 20 || g == 52) { TS(1, g == 20 ? 0 : 2); mbar_wait(dep0 + (g == 20 ? 0 : 8), 0); fence_async_global(); TS(1, g == 20 ? 1 : 3); }
          const int s = g & (STAGES - 1);
          const uint32_t dst = sbase + s * STAGE_BYTES + A_BYTES, fb = full0 + 8 * s;
          mbar_wait(empty0 + 8 * s, ((g / STAGES) & 1) ^ 1);
          mbar_expect_tx(fb, kind == 1 ? 20480 : 24576);
          if (kind == 0) tma_load_3d(dst, &maps.m[mi], fb, 0, kb * 64, c);
          else if (kind == 1) tma_load_2d(dst, &maps.m[mi], fb, kb * 64, c);
          else {
            #pragma unroll 1
            for (int j = 0; j < 3; j++) tma_load_2d(dst + j * 8192, &maps.m[mi], fb, c + j * 64, kb * 64);
          }
        }
      }
      __syncwarp();
      asm volatile("barrier.cluster.wait.acquire.aligned;" ::: "memory");
    } else if (warp == 2) {
      asm volatile("barrier.cluster.wait.acquire.aligned;" ::: "memory");
      const unsigned epoch = (*reinterpret_cast<volatile unsigned*>(&g_done) >> 7) + 1u;
      #pragma unroll 1
      for (int d = 0; d < 3 - grp; d++) {
        const unsigned* f = d == 2 ? g_flags + 192 + rb * 4 + (lane & 3) : g_flags + (d == 1 ? 64 : grp == 0 ? 128 : 0) + (lane & 15) * 4 + ct;
        unsigned it = 0;
        while (!__all_sync(0xffffffffu, ld_acquire(f) == epoch)) { if ((++it & 4095u) == 0 && timed_out()) break; }
        fence_async_global();
        __syncwarp();
        if (lane == 0) mbar_arrive(dep0 + 8 * d);
      }
    } else {
      if (lane < 6) tma_prefetch_2d(&maps.m[M_X], (4 + lane) * 64, rb * 128 + rank * 64);
      else if (lane < 22) {
        const int g = lane - 2, kb = g < 10 ? g : g - 10;
        if (grp == 0) tma_prefetch_3d(&maps.m[M_WIN3], 0, kb * 64, 3 * ct + (g < 10 ? 12 : 0));
        else tma_prefetch_2d(&maps.m[g < 10 ? M_WDRE : M_WDIM], kb * 64, ct * 160);
      }
      __syncwarp();
      asm volatile("barrier.cluster.wait.acquire.aligned;" ::: "memory");
    }
  } else {
    asm volatile("setmaxnreg.inc.sync.aligned.u32 232;");
    const int t = tid & 127, w = t >> 5, l = t & 31;
    const uint32_t buf = sbase + BUF_OFF;
    const unsigned epoch = (*reinterpret_cast<volatile unsigned*>(&g_done) >> 7) + 1u;
    asm volatile("barrier.cluster.wait.acquire.aligned;" ::: "memory");
    const int item = wg - 1;
    const int my_ord = wg == 1 ? BAR_ORD1 : BAR_ORD2;
    if (wg == 2) {
      stats_prologue(x, wdre, wdim, win, rb, grp == 0 ? 2 * DM + FH + ct * 192 : ct * 160,
                     grp == 0 ? 2 * DM + ct * 192 : DM + ct * 160, grp == 0 ? 192 : 160, epoch);
      TS(3, 0);
      bar_arrive<BAR_STATS>(256);
      bar_sync<BAR_ORD1>(256);
      TS(3, 1);
    }
    const float2* rs = reinterpret_cast<const float2*>(smem + ROWSTAT_OFF) + w * 16 + (l >> 2);
    const float2* cs = reinterpret_cast<const float2*>(smem + COLSUM_OFF + item * 768) + (l & 3);
    if (grp == 0) {
      float acc[2][96];
      const uint32_t st_base = buf + (w * 16 + ((l >> 3) & 1) * 8 + (l & 7)) * 128;
      const uint32_t st_x = ((l >> 4) ^ (l & 7)) << 4;
      #pragma unroll 1
      for (int it = 0; it < 2 - item; it++) {
        mainloop<192, 1, false>(acc, sbase, it == 0 ? item * 10 : 20, it == 0 ? 10 : 32, KB_A, 0, my_ord, true, 0);
        pin(acc);
        TS(wg + 1, it == 0 ? 2 : 7);
        if (it == 0) {
          if (wg == 1) bar_sync<BAR_STATS>(256); else bar_sync<BAR_BUF>(256);
          #pragma unroll
          for (int mi = 0; mi < 2; mi++) {
            const float2 s0 = rs[mi * 64], s1 = rs[mi * 64 + 8];
            #pragma unroll
            for (int jj = 0; jj < 12; jj++) {
              uint32_t r[4];
              fold_pack(&acc[mi][8 * jj], s0, s1, cs[jj * 8], cs[jj * 8 + 4], r);
              stsm4(st_base + mi * 24576 + (jj >> 2) * 8192 + (st_x ^ ((jj & 3) << 5)), r[0], r[1], r[2], r[3]);
            }
          }
          __syncwarp();
          TS(wg + 1, 3);
          const int row = (l >> 4) * 64 + w * 16 + (l & 15);
          const uint32_t rbase = buf + (l >> 4) * 24576 + (w * 16 + (l & 15)) * 128;
          float sum = 0.f, sq = 0.f;
          #pragma unroll 2
          for (int c = 0; c < 24; c++) {
            const uint32_t ad = rbase + (c >> 3) * 8192 + (((c ^ l) & 7) << 4);
            const uint4 v = lds128(ad);
            const uint32_t u[4] = {v.x, v.y, v.z, v.w};
            uint32_t o[4];
            #pragma unroll
            for (int e = 0; e < 4; e++) {
              o[e] = pack_bf16(gelu_tanh(bf_lo(u[e])), gelu_tanh(bf_hi(u[e])));
              const float g0 = bf_lo(o[e]), g1 = bf_hi(o[e]);
              sum += g0 + g1; sq = fmaf(g0, g0, sq); sq = fmaf(g1, g1, sq);
            }
            sts128(ad, o[0], o[1], o[2], o[3]);
          }
          TS(wg + 1, 4);
          if (wg == 2) { bar_arrive<BAR_Z1>(256); break; }
          {
            const float mu = sum * (1.f / 192), m2 = fmaxf(sq - sum * mu, 0.f);
            st_vol4(&g_zstat[(rb * 4 + ct) * 128 + row], __float_as_uint(mu), __float_as_uint(m2), epoch, 0u);
            uint4 v[3];
            unsigned n = 0;
            while (true) {
              #pragma unroll
              for (int j = 0; j < 3; j++) v[j] = ld_vol4(&g_zstat[(rb * 4 + ((ct + 1 + j) & 3)) * 128 + row]);
              if (v[0].z == epoch && v[1].z == epoch && v[2].z == epoch) break;
              if ((++n & 4095u) == 0 && timed_out()) break;
            }
            const float m0 = __uint_as_float(v[0].x), m1 = __uint_as_float(v[1].x), m3 = __uint_as_float(v[2].x);
            const float mean = 0.25f * ((mu + m0) + (m1 + m3));
            const float d = (mu - mean) * (mu - mean) + (m0 - mean) * (m0 - mean) + (m1 - mean) * (m1 - mean) + (m3 - mean) * (m3 - mean);
            const float var = (fmaf(192.f, d, m2) + __uint_as_float(v[0].y) + __uint_as_float(v[1].y) + __uint_as_float(v[2].y)) * (1.f / FH);
            const float rstd = rsqrtf(var + LN_EPS), off = -mean * rstd;
            TS(2, 5);
            #pragma unroll 2
            for (int c = 0; c < 24; c++) {
              const uint32_t ad = rbase + (c >> 3) * 8192 + (((c ^ l) & 7) << 4);
              const uint4 z = lds128(ad);
              sts128(ad, pack_bf16(fmaf(bf_lo(z.x), rstd, off), fmaf(bf_hi(z.x), rstd, off)), pack_bf16(fmaf(bf_lo(z.y), rstd, off), fmaf(bf_hi(z.y), rstd, off)),
                         pack_bf16(fmaf(bf_lo(z.z), rstd, off), fmaf(bf_hi(z.z), rstd, off)), pack_bf16(fmaf(bf_lo(z.w), rstd, off), fmaf(bf_hi(z.w), rstd, off)));
            }
          }
        } else {
          bar_sync<BAR_Z1>(256);
          #pragma unroll
          for (int mi = 0; mi < 2; mi++) {
            const int row = rb * 128 + mi * 64 + w * 16 + (l >> 2);
            const float b0 = __bfloat162float(bsp[row]), b1 = __bfloat162float(bsp[row + 8]);
            #pragma unroll
            for (int jj = 0; jj < 12; jj++) {
              const float* a = &acc[mi][8 * jj];
              const uint32_t ad = st_base + mi * 24576 + (jj >> 2) * 8192 + (st_x ^ ((jj & 3) << 5));
              uint32_t z0, z1, z2, z3;
              ldsm4(ad, z0, z1, z2, z3);
              stsm4(ad, hmul2_bf16(z0, pack_bf16(a[0] + b0, a[1] + b0)), hmul2_bf16(z1, pack_bf16(a[2] + b1, a[3] + b1)),
                        hmul2_bf16(z2, pack_bf16(a[4] + b0, a[5] + b0)), hmul2_bf16(z3, pack_bf16(a[6] + b1, a[7] + b1)));
            }
          }
        }
        fence_async_smem();
        bar_sync<BAR_WG1>(128);
        TS(2, it == 0 ? 6 : 8);
        if (t == 0) {
          const CUtensorMap* m = &maps.m[it == 0 ? M_Z23 : M_H3];
          tma_store_3d(m, buf, 0, rb * 128, 3 * ct);
          tma_store_3d(m, buf + 24576, 0, rb * 128 + 64, 3 * ct);
          publish(g_flags + (it == 0 ? 128 : 192) + rb * 4 + ct, epoch);
        }
        __syncwarp();
        TS(2, it == 0 ? 10 : 9);
        bar_arrive<BAR_BUF>(256);
        if (it == 0) bar_sync<BAR_ORD2>(256);
      }
    }
    if (grp == 1 || wg == 2) {
      float acc[2][80];
      #pragma unroll 1
      for (int it = 1 - grp; it < 2; it++) {
        if (it == 1) {
          const bf16* p = x + (size_t)(rb * 128 + grp * 64 + w * 16 + (l >> 2)) * DM + ct * 160 + (l & 3) * 2;
          #pragma unroll
          for (int j = 0; j < 20; j++) {
            const uint32_t v0 = __ldg(reinterpret_cast<const uint32_t*>(p + j * 8));
            const uint32_t v1 = __ldg(reinterpret_cast<const uint32_t*>(p + 8 * DM + j * 8));
            acc[0][4 * j + 0] = bf_lo(v0); acc[0][4 * j + 1] = bf_hi(v0); acc[0][4 * j + 2] = bf_lo(v1); acc[0][4 * j + 3] = bf_hi(v1);
            acc[1][4 * j + 0] = 0.f; acc[1][4 * j + 1] = 0.f; acc[1][4 * j + 2] = 0.f; acc[1][4 * j + 3] = 0.f;
          }
          if (grp == 0) bar_sync<BAR_ORD1>(256); else bar_sync<BAR_ORD2>(256);
          TS(wg + 1, 11);
        }
        mainloop<160, 0, false>(acc, sbase, it == 0 ? item * 10 : grp == 0 ? 52 : 20, it == 0 ? 10 : grp == 0 ? NX : 64 - NX, total, it,
                                it == 0 ? my_ord : 0, grp == 1, it & grp);
        if (it == 1) break;
        pin(acc);
        TS(wg + 1, 2);
        if (wg == 1) bar_sync<BAR_STATS>(256); else bar_sync<BAR_BUF>(256);
        const float sign = wg == 1 ? 1.f : -1.f;
        const uint32_t tb = buf + ((l >> 4) * 8 + (l & 7)) * 128 + (((w * 2 + ((l >> 3) & 1)) ^ (l & 7)) << 4);
        #pragma unroll
        for (int mi = 0; mi < 2; mi++) {
          float2 s0 = rs[mi * 64], s1 = rs[mi * 64 + 8];
          s0.x *= sign; s0.y *= sign; s1.x *= sign; s1.y *= sign;
          #pragma unroll
          for (int jj = 0; jj < 10; jj++) {
            uint32_t r[4];
            fold_pack(&acc[mi][8 * jj], s0, s1, cs[jj * 8], cs[jj * 8 + 4], r);
            stsm4_t(tb + mi * 20480 + jj * 2048, r[0], r[1], r[2], r[3]);
          }
        }
        fence_async_smem();
        if (wg == 1) bar_sync<BAR_WG1>(128); else bar_sync<BAR_WG2>(128);
        TS(wg + 1, 6);
        if (t == 0) {
          tma_store_2d(&maps.m[M_AB], buf, rb * 128, item * DM + ct * 160);
          tma_store_2d(&maps.m[M_AB], buf + 20480, rb * 128 + 64, item * DM + ct * 160);
          publish(g_flags + item * 64 + rb * 4 + ct, epoch);
        }
        __syncwarp();
        TS(wg + 1, 10);
        if (wg == 2) { bar_arrive<BAR_Z1>(256); return; }
        bar_arrive<BAR_BUF>(256);
      }
      if (grp == 0) mainloop<160, 1, true>(acc, sbase, 52 + NX, 12, KB_A, 1, 0, true, 0);
      pin(acc);
      TS(wg + 1, 12);
      uint4* dst = g_part + (size_t)blockIdx.x * 27 * 128 + t;
      const uint4* src = g_part + (size_t)(blockIdx.x ^ 2) * 27 * 128 + t;
      #pragma unroll
      for (int i = 0; i < 27; i++)
        st_vol4(dst + i * 128, __float_as_uint(acc[1][3 * i]), __float_as_uint(acc[1][3 * i + 1]),
                __float_as_uint(i < 26 ? acc[1][3 * i + 2] : 0.f), epoch);
      if (grp == 0) bar_sync<BAR_BUF>(256); else bar_sync<BAR_Z1>(256);
      TS(wg + 1, 13);
      {
        uint4 v[27];
        unsigned n = 0;
        while (true) {
          bool ok = true;
          #pragma unroll
          for (int i = 0; i < 27; i++) v[i] = ld_vol4(src + i * 128);
          #pragma unroll
          for (int i = 0; i < 27; i++) ok = ok && (v[i].w == epoch);
          if (ok) break;
          if ((++n & 4095u) == 0 && timed_out()) break;
        }
        #pragma unroll
        for (int i = 0; i < 27; i++) {
          acc[0][3 * i] += __uint_as_float(v[i].x);
          acc[0][3 * i + 1] += __uint_as_float(v[i].y);
          if (i < 26) acc[0][3 * i + 2] += __uint_as_float(v[i].z);
        }
      }
      TS(wg + 1, 14);
      const uint32_t slab = buf + w * (16 * 320);
      const uint32_t addr = slab + (((l >> 3) & 1) * 8 + (l & 7)) * 320 + (l >> 4) * 16;
      #pragma unroll
      for (int jj = 0; jj < 10; jj++) {
        const float* a = &acc[0][8 * jj];
        stsm4(addr + jj * 32, pack_bf16(a[0], a[1]), pack_bf16(a[2], a[3]), pack_bf16(a[4], a[5]), pack_bf16(a[6], a[7]));
      }
      fence_async_smem();
      __syncwarp();
      if (l == 0) {
        tma_store_2d(&maps.m[M_OUT], slab, ct * 160, rb * 128 + grp * 64 + w * 16);
        bulk_commit();
        bulk_wait_read();
        if (w == 0) atomicAdd(&g_done, 1u);
      }
      TS(wg + 1, 15);
    }
  }
}

typedef CUresult (*EncodeFn)(CUtensorMap*, CUtensorMapDataType, cuuint32_t, void*, const cuuint64_t*, const cuuint64_t*,
                             const cuuint32_t*, const cuuint32_t*, CUtensorMapInterleave, CUtensorMapSwizzle,
                             CUtensorMapL2promotion, CUtensorMapFloatOOBfill);

void make2d(EncodeFn enc, CUtensorMap* m, const void* p, uint64_t cols, uint64_t rows, uint32_t bc, uint32_t br, bool swz = true) {
  cuuint64_t gd[2] = {cols, rows}, gs[1] = {cols * 2};
  cuuint32_t bd[2] = {bc, br}, es[2] = {1, 1};
  enc(m, CU_TENSOR_MAP_DATA_TYPE_BFLOAT16, 2, const_cast<void*>(p), gd, gs, bd, es, CU_TENSOR_MAP_INTERLEAVE_NONE,
      swz ? CU_TENSOR_MAP_SWIZZLE_128B : CU_TENSOR_MAP_SWIZZLE_NONE, CU_TENSOR_MAP_L2_PROMOTION_L2_256B, CU_TENSOR_MAP_FLOAT_OOB_FILL_NONE);
}
void make3d(EncodeFn enc, CUtensorMap* m, const void* p, uint64_t cols, uint64_t rows) {
  cuuint64_t gd[3] = {64, rows, cols / 64}, gs[2] = {cols * 2, 128};
  cuuint32_t bd[3] = {64, 64, 3}, es[3] = {1, 1, 1};
  enc(m, CU_TENSOR_MAP_DATA_TYPE_BFLOAT16, 3, const_cast<void*>(p), gd, gs, bd, es, CU_TENSOR_MAP_INTERLEAVE_NONE,
      CU_TENSOR_MAP_SWIZZLE_128B, CU_TENSOR_MAP_L2_PROMOTION_L2_256B, CU_TENSOR_MAP_FLOAT_OOB_FILL_NONE);
}

}

extern "C" void kernel_launch(void* const* d_in, const int* in_sizes, int n_in, void* d_out, int out_size) {
  const bf16* x = (const bf16*)d_in[0];
  const bf16* wsre = (const bf16*)d_in[1];
  const bf16* wsim = (const bf16*)d_in[2];
  const bf16* wdre = (const bf16*)d_in[3];
  const bf16* wdim = (const bf16*)d_in[4];
  const bf16* win = (const bf16*)d_in[6];
  const bf16* wsp = (const bf16*)d_in[7];
  const bf16* bsp = (const bf16*)d_in[8];
  const bf16* wout = (const bf16*)d_in[9];

  void* fn = nullptr;
  cudaDriverEntryPointQueryResult qr;
  cudaGetDriverEntryPoint("cuTensorMapEncodeTiled", &fn, cudaEnableDefault, &qr);
  EncodeFn enc = (EncodeFn)fn;
  void *abT, *z2, *h;
  cudaGetSymbolAddress(&abT, g_abT);
  cudaGetSymbolAddress(&z2, g_z2);
  cudaGetSymbolAddress(&h, g_h);

  Maps maps;
  make2d(enc, &maps.m[M_X], x, DM, SEQ, 64, 64);
  make2d(enc, &maps.m[M_WSRE], wsre, SEQ, SEQ, 64, 64);
  make2d(enc, &maps.m[M_WSIM], wsim, SEQ, SEQ, 64, 64);
  make2d(enc, &maps.m[M_WSP], wsp, SEQ, SEQ, 64, 64);
  make2d(enc, &maps.m[M_H], h, FH, SEQ, 64, 64);
  make3d(enc, &maps.m[M_H3], h, FH, SEQ);
  make3d(enc, &maps.m[M_WIN3], win, FF, DM);
  make3d(enc, &maps.m[M_Z23], z2, FH, SEQ);
  make2d(enc, &maps.m[M_WDRE], wdre, DM, DM, 64, 160);
  make2d(enc, &maps.m[M_WDIM], wdim, DM, DM, 64, 160);
  make2d(enc, &maps.m[M_AB], abT, SEQ, 2 * DM, 64, 160);
  make2d(enc, &maps.m[M_WOUT], wout, DM, FH, 64, 64);
  make2d(enc, &maps.m[M_OUT], d_out, DM, SEQ, 160, 16, false);

  cudaFuncSetAttribute(fused_kernel, cudaFuncAttributeMaxDynamicSharedMemorySize, SMEM_BYTES);
  fused_kernel<<<128, 384, SMEM_BYTES>>>(maps, x, wdre, wdim, win, bsp);
}
```

```cpp
#include <cuda_runtime.h>
#include <cuda_bf16.h>
#include <cuda.h>
#include <stdint.h>

namespace {

typedef __nv_bfloat16 bf16;

constexpr int SEQ = 2048, DM = 640, FF = 1536, FH = 768;
constexpr int NX = 11;
constexpr int STAGES = 4;
constexpr int A_BYTES = 16384;
constexpr int ROWSTAT_OFF = 0;
constexpr int COLSUM_OFF = 1024;
constexpr int BIAS_OFF = 1536;
constexpr int BAR_OFF = 2048;
constexpr int DEADLINE_OFF = BAR_OFF + 128;
constexpr int RING_OFF = 3072;
constexpr int STAGE_A = 40960, STAGE_B = 36864;
constexpr int SMEM_BYTES = RING_OFF + 4 * STAGE_A + 49152;
constexpr int KB_A = 20 + 32 + NX + 12;
constexpr int KB_B = 30 + 64 - NX;
constexpr float LN_EPS = 1e-5f;

constexpr int BAR_ORD1 = 1, BAR_ORD2 = 2, BAR_WG1 = 3, BAR_WG2 = 4, BAR_STATS = 5, BAR_BUF = 6, BAR_Z1 = 7;

enum { M_X, M_XN, M_WIN32, M_Z232, M_WSRE, M_WSIM, M_WSP, M_H, M_H3, M_WIN3, M_Z23, M_WDRE, M_WDIM, M_AB, M_WOUT, M_OUT, M_COUNT };
struct Maps { CUtensorMap m[M_COUNT]; };

__device__ __align__(1024) bf16 g_abT[2 * DM * SEQ];
__device__ __align__(1024) bf16 g_z2[SEQ * FH];
__device__ __align__(1024) bf16 g_h[SEQ * FH];
__device__ __align__(16) uint4 g_xstat[SEQ];
__device__ __align__(1024) bf16 g_xn[SEQ * DM];
__device__ __align__(16) uint4 g_zstat[128 * 128];
__device__ __align__(16) uint4 g_part[128 * 27 * 128];
__device__ unsigned g_flags[5 * 128];
constexpr int F_A = 0, F_B = 128, F_H = 256, F_Z = 384, F_XN = 512;
__device__ unsigned g_done;
#define TS(role, ev)

extern __shared__ __align__(1024) uint8_t smem[];

__device__ __forceinline__ unsigned long long gtime() { unsigned long long t; asm volatile("mov.u64 %0, %%globaltimer;" : "=l"(t)); return t; }
__device__ __forceinline__ bool timed_out() { return gtime() > *reinterpret_cast<volatile unsigned long long*>(smem + DEADLINE_OFF); }
__device__ __forceinline__ uint32_t smem_u32(const void* p) { return (uint32_t)__cvta_generic_to_shared(p); }
__device__ __forceinline__ void mbar_init(uint32_t bar, uint32_t cnt) { asm volatile("mbarrier.init.shared::cta.b64 [%0], %1;" :: "r"(bar), "r"(cnt)); }
__device__ __forceinline__ void mbar_expect_tx(uint32_t bar, uint32_t bytes) { asm volatile("mbarrier.arrive.expect_tx.shared::cta.b64 _, [%0], %1;" :: "r"(bar), "r"(bytes) : "memory"); }
__device__ __forceinline__ void mbar_arrive(uint32_t bar) { asm volatile("mbarrier.arrive.shared::cta.b64 _, [%0];" :: "r"(bar) : "memory"); }
__device__ __forceinline__ void mbar_arrive_cluster(uint32_t bar, uint32_t cta) {
  asm volatile("{\n.reg .b32 ra;\nmapa.shared::cluster.u32 ra, %0, %1;\nmbarrier.arrive.shared::cluster.b64 _, [ra];\n}" :: "r"(bar), "r"(cta) : "memory");
}
__device__ __forceinline__ bool mbar_try(uint32_t bar, uint32_t parity) {
  uint32_t ok;
  asm volatile("{\n.reg .pred p;\nmbarrier.try_wait.parity.shared::cta.b64 p, [%1], %2;\nselp.u32 %0, 1, 0, p;\n}" : "=r"(ok) : "r"(bar), "r"(parity) : "memory");
  return ok != 0;
}
__device__ __forceinline__ void mbar_wait(uint32_t bar, uint32_t parity) {
  unsigned n = 0;
  while (!mbar_try(bar, parity)) { if ((++n & 4095u) == 0 && timed_out()) break; }
}
__device__ __forceinline__ void tma_load_2d(uint32_t dst, const CUtensorMap* map, uint32_t bar, int c0, int c1) {
  asm volatile("cp.async.bulk.tensor.2d.shared::cluster.global.mbarrier::complete_tx::bytes [%0], [%1, {%3, %4}], [%2];"
    :: "r"(dst), "l"((uint64_t)map), "r"(bar), "r"(c0), "r"(c1) : "memory");
}
__device__ __forceinline__ void tma_load_3d(uint32_t dst, const CUtensorMap* map, uint32_t bar, int c0, int c1, int c2) {
  asm volatile("cp.async.bulk.tensor.3d.shared::cluster.global.mbarrier::complete_tx::bytes [%0], [%1, {%3, %4, %5}], [%2];"
    :: "r"(dst), "l"((uint64_t)map), "r"(bar), "r"(c0), "r"(c1), "r"(c2) : "memory");
}
__device__ __forceinline__ void tma_load_2d_mc(uint32_t dst, const CUtensorMap* map, uint32_t bar, int c0, int c1, uint16_t mask) {
  asm volatile("cp.async.bulk.tensor.2d.shared::cluster.global.mbarrier::complete_tx::bytes.multicast::cluster [%0], [%1, {%3, %4}], [%2], %5;"
    :: "r"(dst), "l"((uint64_t)map), "r"(bar), "r"(c0), "r"(c1), "h"(mask) : "memory");
}
__device__ __forceinline__ void tma_store_2d(const CUtensorMap* map, uint32_t src, int c0, int c1) {
  asm volatile("cp.async.bulk.tensor.2d.global.shared::cta.bulk_group [%0, {%2, %3}], [%1];"
    :: "l"((uint64_t)map), "r"(src), "r"(c0), "r"(c1) : "memory");
}
__device__ __forceinline__ void tma_store_3d(const CUtensorMap* map, uint32_t src, int c0, int c1, int c2) {
  asm volatile("cp.async.bulk.tensor.3d.global.shared::cta.bulk_group [%0, {%2, %3, %4}], [%1];"
    :: "l"((uint64_t)map), "r"(src), "r"(c0), "r"(c1), "r"(c2) : "memory");
}
__device__ __forceinline__ void tma_prefetch_2d(const CUtensorMap* map, int c0, int c1) {
  asm volatile("cp.async.bulk.prefetch.tensor.2d.L2.global.tile [%0, {%1, %2}];" :: "l"((uint64_t)map), "r"(c0), "r"(c1) : "memory");
}
__device__ __forceinline__ void tma_prefetch_3d(const CUtensorMap* map, int c0, int c1, int c2) {
  asm volatile("cp.async.bulk.prefetch.tensor.3d.L2.global.tile [%0, {%1, %2, %3}];" :: "l"((uint64_t)map), "r"(c0), "r"(c1), "r"(c2) : "memory");
}
__device__ __forceinline__ void bulk_commit() { asm volatile("cp.async.bulk.commit_group;" ::: "memory"); }
__device__ __forceinline__ void bulk_wait_all() { asm volatile("cp.async.bulk.wait_group 0;" ::: "memory"); }
__device__ __forceinline__ void bulk_wait_read() { asm volatile("cp.async.bulk.wait_group.read 0;" ::: "memory"); }
__device__ __forceinline__ void fence_async_smem() { asm volatile("fence.proxy.async.shared::cta;" ::: "memory"); }
__device__ __forceinline__ void fence_async_global() { asm volatile("fence.proxy.async.global;" ::: "memory"); }
__device__ __forceinline__ void wgmma_fence() { asm volatile("wgmma.fence.sync.aligned;" ::: "memory"); }
__device__ __forceinline__ void wgmma_commit() { asm volatile("wgmma.commit_group.sync.aligned;" ::: "memory"); }
template<int N> __device__ __forceinline__ void wgmma_wait() { asm volatile("wgmma.wait_group.sync.aligned %0;" :: "n"(N) : "memory"); }
template<int ID> __device__ __forceinline__ void bar_sync(int n) { asm volatile("bar.sync %0, %1;" :: "n"(ID), "r"(n) : "memory"); }
template<int ID> __device__ __forceinline__ void bar_arrive(int n) { asm volatile("bar.arrive %0, %1;" :: "n"(ID), "r"(n) : "memory"); }
__device__ __forceinline__ uint64_t make_desc(uint32_t addr, uint32_t lbo, uint32_t sbo, int swz = 1) {
  return (uint64_t)((addr & 0x3FFFF) >> 4) | ((uint64_t)(lbo >> 4) << 16) | ((uint64_t)(sbo >> 4) << 32) | ((uint64_t)swz << 62);
}
__device__ __forceinline__ uint4 ld_vol4(const uint4* p) {
  uint4 v; asm volatile("ld.volatile.global.v4.u32 {%0,%1,%2,%3}, [%4];" : "=r"(v.x), "=r"(v.y), "=r"(v.z), "=r"(v.w) : "l"(p) : "memory"); return v;
}
__device__ __forceinline__ uint2 ld_vol2(const uint2* p) {
  uint2 v; asm volatile("ld.volatile.global.v2.u32 {%0,%1}, [%2];" : "=r"(v.x), "=r"(v.y) : "l"(p) : "memory"); return v;
}
__device__ __forceinline__ void st_vol4(uint4* p, uint32_t a, uint32_t b, uint32_t c, uint32_t d) {
  asm volatile("st.volatile.global.v4.u32 [%0], {%1,%2,%3,%4};" :: "l"(p), "r"(a), "r"(b), "r"(c), "r"(d) : "memory");
}
__device__ __forceinline__ void st_vol2(uint2* p, uint32_t a, uint32_t b) {
  asm volatile("st.volatile.global.v2.u32 [%0], {%1,%2};" :: "l"(p), "r"(a), "r"(b) : "memory");
}
__device__ __forceinline__ unsigned ld_acquire(const unsigned* p) {
  unsigned v; asm volatile("ld.acquire.gpu.global.u32 %0, [%1];" : "=r"(v) : "l"(p) : "memory"); return v;
}
__device__ __forceinline__ unsigned ld_relaxed(const unsigned* p) {
  unsigned v; asm volatile("ld.relaxed.gpu.global.u32 %0, [%1];" : "=r"(v) : "l"(p) : "memory"); return v;
}
__device__ __forceinline__ void st_release(unsigned* p, unsigned v) {
  asm volatile("st.relaxed.gpu.global.u32 [%0], %1;" :: "l"(p), "r"(v) : "memory");
}
__device__ __forceinline__ uint32_t pack_bf16(float lo, float hi) {
  uint32_t r; asm("cvt.rn.bf16x2.f32 %0, %1, %2;" : "=r"(r) : "f"(hi), "f"(lo)); return r;
}
__device__ __forceinline__ float bf_lo(uint32_t v) { return __uint_as_float(v << 16); }
__device__ __forceinline__ float bf_hi(uint32_t v) { return __uint_as_float(v & 0xFFFF0000u); }
__device__ __forceinline__ void stsm4(uint32_t addr, uint32_t a, uint32_t b, uint32_t c, uint32_t d) {
  asm volatile("stmatrix.sync.aligned.m8n8.x4.shared.b16 [%0], {%1,%2,%3,%4};" :: "r"(addr), "r"(a), "r"(b), "r"(c), "r"(d));
}
__device__ __forceinline__ void stsm4_t(uint32_t addr, uint32_t a, uint32_t b, uint32_t c, uint32_t d) {
  asm volatile("stmatrix.sync.aligned.m8n8.x4.trans.shared.b16 [%0], {%1,%2,%3,%4};" :: "r"(addr), "r"(a), "r"(b), "r"(c), "r"(d));
}
__device__ __forceinline__ void ldsm4(uint32_t addr, uint32_t& a, uint32_t& b, uint32_t& c, uint32_t& d) {
  asm volatile("ldmatrix.sync.aligned.m8n8.x4.shared.b16 {%0,%1,%2,%3}, [%4];" : "=r"(a), "=r"(b), "=r"(c), "=r"(d) : "r"(addr));
}
__device__ __forceinline__ uint4 lds128(uint32_t a) {
  uint4 v; asm volatile("ld.shared.v4.u32 {%0,%1,%2,%3}, [%4];" : "=r"(v.x), "=r"(v.y), "=r"(v.z), "=r"(v.w) : "r"(a)); return v;
}
__device__ __forceinline__ void sts128(uint32_t a, uint32_t x, uint32_t y, uint32_t z, uint32_t w) {
  asm volatile("st.shared.v4.u32 [%0], {%1,%2,%3,%4};" :: "r"(a), "r"(x), "r"(y), "r"(z), "r"(w));
}
__device__ __forceinline__ uint32_t hmul2_bf16(uint32_t a, uint32_t b) {
  uint32_t r; asm("mul.rn.bf16x2 %0, %1, %2;" : "=r"(r) : "r"(a), "r"(b)); return r;
}
__device__ __forceinline__ uint32_t hfma2_bf16(uint32_t a, uint32_t b, uint32_t c) {
  uint32_t r; asm("fma.rn.bf16x2 %0, %1, %2, %3;" : "=r"(r) : "r"(a), "r"(b), "r"(c)); return r;
}
__device__ __forceinline__ float gelu_tanh(float v) {
  float u = v * fmaf(0.0356774081f, v * v, 0.7978845608f);
  float t; asm("tanh.approx.f32 %0, %1;" : "=f"(t) : "f"(u));
  float hv = 0.5f * v;
  return fmaf(hv, t, hv);
}
__device__ __forceinline__ float warp_sum(float v) {
  #pragma unroll
  for (int o = 16; o > 0; o >>= 1) v += __shfl_xor_sync(0xffffffffu, v, o);
  return v;
}
__device__ __forceinline__ float quad_sum(float v) {
  v += __shfl_xor_sync(0xffffffffu, v, 1);
  v += __shfl_xor_sync(0xffffffffu, v, 2);
  return v;
}

template<int TB>
__device__ __forceinline__ void wgmma_n192(float (&d)[96], uint64_t da, uint64_t db, int scale_d) {
  asm volatile("{\n.reg .pred p;\nsetp.ne.b32 p, %98, 0;\n"
   "wgmma.mma_async.sync.aligned.m64n192k16.f32.bf16.bf16 {%0,%1,%2,%3,%4,%5,%6,%7,%8,%9,%10,%11,%12,%13,%14,%15,%16,%17,%18,%19,%20,%21,%22,%23,%24,%25,%26,%27,%28,%29,%30,%31,%32,%33,%34,%35,%36,%37,%38,%39,%40,%41,%42,%43,%44,%45,%46,%47,%48,%49,%50,%51,%52,%53,%54,%55,%56,%57,%58,%59,%60,%61,%62,%63,%64,%65,%66,%67,%68,%69,%70,%71,%72,%73,%74,%75,%76,%77,%78,%79,%80,%81,%82,%83,%84,%85,%86,%87,%88,%89,%90,%91,%92,%93,%94,%95}, %96, %97, p, 1, 1, 0, %99;\n}"
   : "+f"(d[0]),"+f"(d[1]),"+f"(d[2]),"+f"(d[3]),"+f"(d[4]),"+f"(d[5]),"+f"(d[6]),"+f"(d[7]),"+f"(d[8]),"+f"(d[9]),"+f"(d[10]),"+f"(d[11]),"+f"(d[12]),"+f"(d[13]),"+f"(d[14]),"+f"(d[15]),"+f"(d[16]),"+f"(d[17]),"+f"(d[18]),"+f"(d[19]),"+f"(d[20]),"+f"(d[21]),"+f"(d[22]),"+f"(d[23]),"+f"(d[24]),"+f"(d[25]),"+f"(d[26]),"+f"(d[27]),"+f"(d[28]),"+f"(d[29]),"+f"(d[30]),"+f"(d[31]),"+f"(d[32]),"+f"(d[33]),"+f"(d[34]),"+f"(d[35]),"+f"(d[36]),"+f"(d[37]),"+f"(d[38]),"+f"(d[39]),"+f"(d[40]),"+f"(d[41]),"+f"(d[42]),"+f"(d[43]),"+f"(d[44]),"+f"(d[45]),"+f"(d[46]),"+f"(d[47]),"+f"(d[48]),"+f"(d[49]),"+f"(d[50]),"+f"(d[51]),"+f"(d[52]),"+f"(d[53]),"+f"(d[54]),"+f"(d[55]),"+f"(d[56]),"+f"(d[57]),"+f"(d[58]),"+f"(d[59]),"+f"(d[60]),"+f"(d[61]),"+f"(d[62]),"+f"(d[63]),"+f"(d[64]),"+f"(d[65]),"+f"(d[66]),"+f"(d[67]),"+f"(d[68]),"+f"(d[69]),"+f"(d[70]),"+f"(d[71]),"+f"(d[72]),"+f"(d[73]),"+f"(d[74]),"+f"(d[75]),"+f"(d[76]),"+f"(d[77]),"+f"(d[78]),"+f"(d[79]),"+f"(d[80]),"+f"(d[81]),"+f"(d[82]),"+f"(d[83]),"+f"(d[84]),"+f"(d[85]),"+f"(d[86]),"+f"(d[87]),"+f"(d[88]),"+f"(d[89]),"+f"(d[90]),"+f"(d[91]),"+f"(d[92]),"+f"(d[93]),"+f"(d[94]),"+f"(d[95])
   : "l"(da), "l"(db), "r"(scale_d), "n"(TB));
}
template<int TB>
__device__ __forceinline__ void wgmma_n160(float (&d)[80], uint64_t da, uint64_t db, int scale_d) {
  asm volatile("{\n.reg .pred p;\nsetp.ne.b32 p, %82, 0;\n"
   "wgmma.mma_async.sync.aligned.m64n160k16.f32.bf16.bf16 {%0,%1,%2,%3,%4,%5,%6,%7,%8,%9,%10,%11,%12,%13,%14,%15,%16,%17,%18,%19,%20,%21,%22,%23,%24,%25,%26,%27,%28,%29,%30,%31,%32,%33,%34,%35,%36,%37,%38,%39,%40,%41,%42,%43,%44,%45,%46,%47,%48,%49,%50,%51,%52,%53,%54,%55,%56,%57,%58,%59,%60,%61,%62,%63,%64,%65,%66,%67,%68,%69,%70,%71,%72,%73,%74,%75,%76,%77,%78,%79}, %80, %81, p, 1, 1, 0, %83;\n}"
   : "+f"(d[0]),"+f"(d[1]),"+f"(d[2]),"+f"(d[3]),"+f"(d[4]),"+f"(d[5]),"+f"(d[6]),"+f"(d[7]),"+f"(d[8]),"+f"(d[9]),"+f"(d[10]),"+f"(d[11]),"+f"(d[12]),"+f"(d[13]),"+f"(d[14]),"+f"(d[15]),"+f"(d[16]),"+f"(d[17]),"+f"(d[18]),"+f"(d[19]),"+f"(d[20]),"+f"(d[21]),"+f"(d[22]),"+f"(d[23]),"+f"(d[24]),"+f"(d[25]),"+f"(d[26]),"+f"(d[27]),"+f"(d[28]),"+f"(d[29]),"+f"(d[30]),"+f"(d[31]),"+f"(d[32]),"+f"(d[33]),"+f"(d[34]),"+f"(d[35]),"+f"(d[36]),"+f"(d[37]),"+f"(d[38]),"+f"(d[39]),"+f"(d[40]),"+f"(d[41]),"+f"(d[42]),"+f"(d[43]),"+f"(d[44]),"+f"(d[45]),"+f"(d[46]),"+f"(d[47]),"+f"(d[48]),"+f"(d[49]),"+f"(d[50]),"+f"(d[51]),"+f"(d[52]),"+f"(d[53]),"+f"(d[54]),"+f"(d[55]),"+f"(d[56]),"+f"(d[57]),"+f"(d[58]),"+f"(d[59]),"+f"(d[60]),"+f"(d[61]),"+f"(d[62]),"+f"(d[63]),"+f"(d[64]),"+f"(d[65]),"+f"(d[66]),"+f"(d[67]),"+f"(d[68]),"+f"(d[69]),"+f"(d[70]),"+f"(d[71]),"+f"(d[72]),"+f"(d[73]),"+f"(d[74]),"+f"(d[75]),"+f"(d[76]),"+f"(d[77]),"+f"(d[78]),"+f"(d[79])
   : "l"(da), "l"(db), "r"(scale_d), "n"(TB));
}
template<int TB>
__device__ __forceinline__ void wgmma_n96(float (&d)[48], uint64_t da, uint64_t db, int scale_d) {
  asm volatile("{\n.reg .pred p;\nsetp.ne.b32 p, %50, 0;\n"
   "wgmma.mma_async.sync.aligned.m64n96k16.f32.bf16.bf16 {%0,%1,%2,%3,%4,%5,%6,%7,%8,%9,%10,%11,%12,%13,%14,%15,%16,%17,%18,%19,%20,%21,%22,%23,%24,%25,%26,%27,%28,%29,%30,%31,%32,%33,%34,%35,%36,%37,%38,%39,%40,%41,%42,%43,%44,%45,%46,%47}, %48, %49, p, 1, 1, 0, %51;\n}"
   : "+f"(d[0]),"+f"(d[1]),"+f"(d[2]),"+f"(d[3]),"+f"(d[4]),"+f"(d[5]),"+f"(d[6]),"+f"(d[7]),"+f"(d[8]),"+f"(d[9]),"+f"(d[10]),"+f"(d[11]),"+f"(d[12]),"+f"(d[13]),"+f"(d[14]),"+f"(d[15]),"+f"(d[16]),"+f"(d[17]),"+f"(d[18]),"+f"(d[19]),"+f"(d[20]),"+f"(d[21]),"+f"(d[22]),"+f"(d[23]),"+f"(d[24]),"+f"(d[25]),"+f"(d[26]),"+f"(d[27]),"+f"(d[28]),"+f"(d[29]),"+f"(d[30]),"+f"(d[31]),"+f"(d[32]),"+f"(d[33]),"+f"(d[34]),"+f"(d[35]),"+f"(d[36]),"+f"(d[37]),"+f"(d[38]),"+f"(d[39]),"+f"(d[40]),"+f"(d[41]),"+f"(d[42]),"+f"(d[43]),"+f"(d[44]),"+f"(d[45]),"+f"(d[46]),"+f"(d[47])
   : "l"(da), "l"(db), "r"(scale_d), "n"(TB));
}

template<int N, int TB>
__device__ __forceinline__ void wgmma_n(float (&d)[N / 2], uint64_t da, uint64_t db, int scale_d) {
  if constexpr (N == 192) wgmma_n192<TB>(d, da, db, scale_d);
  else if constexpr (N == 160) wgmma_n160<TB>(d, da, db, scale_d);
  else wgmma_n96<TB>(d, da, db, scale_d);
}

template<int R>
__device__ __forceinline__ void pin(float (&acc)[2][R]) {
  #pragma unroll
  for (int mi = 0; mi < 2; mi++)
    #pragma unroll
    for (int i = 0; i < R; i++) asm volatile("" : "+f"(acc[mi][i]) :: "memory");
}

template<int N, int TB, bool CONT>
__device__ __forceinline__ void mainloop(float (&acc)[2][N / 2], uint32_t sbase, uint32_t stage_bytes, int g0, int nk, int total,
                                         int accum0, int ord_bar, bool drain, int mswap, float* csum = nullptr) {
  const uint32_t full0 = sbase + BAR_OFF, empty0 = full0 + 8 * STAGES, ring = sbase + RING_OFF;
  const int t = threadIdx.x & 127;
  const bool rel = t < 2;
  const uint64_t da0 = make_desc(ring + mswap * 8192, 16, 1024), da1 = make_desc(ring + (mswap ^ 1) * 8192, 16, 1024);
  const uint64_t db0 = N == 96 ? make_desc(ring + A_BYTES, 4096, 512, 2) : TB ? make_desc(ring + A_BYTES, 8192, 1024) : make_desc(ring + A_BYTES, 16, 1024);
  if (!CONT) pin(acc);
  #pragma unroll 1
  for (int i = 0; i < nk; i++) {
    const int g = g0 + i;
    const int s = g & (STAGES - 1);
    const uint64_t so = (uint64_t)(s * (stage_bytes >> 4));
    mbar_wait(full0 + 8 * s, (g / STAGES) & 1);
    if (g < 32) TS(4 + (g >> 4), g & 15);
    wgmma_fence();
    #pragma unroll
    for (int k = 0; k < 4; k++) {
      const uint64_t db = db0 + so + (N == 96 ? k * 64 : TB ? k * 128 : k * 2);
      wgmma_n<N, TB>(acc[0], da0 + so + k * 2, db, accum0 | i | k);
      wgmma_n<N, TB>(acc[1], da1 + so + k * 2, db, accum0 | i | k);
    }
    wgmma_commit();
    if (ord_bar != 0 && i == nk - 1) asm volatile("bar.arrive %0, 256;" :: "r"(ord_bar) : "memory");
    if (N == 96 && t < 96) {
      const int cg = t % 12, r0 = (t / 12) * 8;
      const uint32_t p = ring + s * stage_bytes + A_BYTES + (cg >> 2) * 4096 + r0 * 64;
      uint4 v[8];
      #pragma unroll
      for (int r = 0; r < 8; r++) v[r] = lds128(p + r * 64 + (((cg & 3) ^ (r >> 1)) << 4));
      #pragma unroll
      for (int r = 0; r < 8; r++) {
        csum[0] += bf_lo(v[r].x); csum[1] += bf_hi(v[r].x); csum[2] += bf_lo(v[r].y); csum[3] += bf_hi(v[r].y);
        csum[4] += bf_lo(v[r].z); csum[5] += bf_hi(v[r].z); csum[6] += bf_lo(v[r].w); csum[7] += bf_hi(v[r].w);
      }
    }
    if (N == 96) bar_sync<BAR_WG1>(128);
    wgmma_wait<1>();
    if (rel && (CONT || i > 0) && g - 1 + STAGES < total) mbar_arrive_cluster(empty0 + 8 * ((g - 1) & (STAGES - 1)), t);
  }
  if (drain) {
    wgmma_wait<0>();
    const int g = g0 + nk - 1;
    if (rel && g + STAGES < total) mbar_arrive_cluster(empty0 + 8 * (g & (STAGES - 1)), t);
  }
}

__device__ __forceinline__ void publish(unsigned* flag, unsigned epoch) {
  bulk_commit();
  bulk_wait_all();
  st_release(flag, epoch);
}

__device__ __forceinline__ void ln_prologue(const bf16* __restrict__ x, int rb, unsigned epoch) {
  const int t = threadIdx.x & 127, l = t & 31, cta = blockIdx.x;
  const int row = cta * 16 + (t >> 3);
  uint4 rv[10];
  #pragma unroll
  for (int j = 0; j < 10; j++) rv[j] = __ldg(reinterpret_cast<const uint4*>(x + (size_t)row * DM) + (l & 7) + 8 * j);
  float s = 0.f;
  #pragma unroll
  for (int j = 0; j < 10; j++)
    s += ((bf_lo(rv[j].x) + bf_hi(rv[j].x)) + (bf_lo(rv[j].y) + bf_hi(rv[j].y))) + ((bf_lo(rv[j].z) + bf_hi(rv[j].z)) + (bf_lo(rv[j].w) + bf_hi(rv[j].w)));
  s += __shfl_xor_sync(0xffffffffu, s, 1); s += __shfl_xor_sync(0xffffffffu, s, 2); s += __shfl_xor_sync(0xffffffffu, s, 4);
  const float mean = s * (1.f / DM);
  float q = 0.f;
  #pragma unroll
  for (int j = 0; j < 10; j++) {
    const uint32_t u[4] = {rv[j].x, rv[j].y, rv[j].z, rv[j].w};
    #pragma unroll
    for (int c = 0; c < 4; c++) { const float d0 = bf_lo(u[c]) - mean, d1 = bf_hi(u[c]) - mean; q = fmaf(d0, d0, q); q = fmaf(d1, d1, q); }
  }
  q += __shfl_xor_sync(0xffffffffu, q, 1); q += __shfl_xor_sync(0xffffffffu, q, 2); q += __shfl_xor_sync(0xffffffffu, q, 4);
  const float rstd = rsqrtf(fmaf(q, 1.f / DM, LN_EPS)), off = -mean * rstd;
  if ((l & 7) == 0) st_vol4(&g_xstat[row], __float_as_uint(rstd), __float_as_uint(off), epoch, 0u);
  #pragma unroll
  for (int j = 0; j < 10; j++) {
    uint4 o;
    o.x = pack_bf16(fmaf(bf_lo(rv[j].x), rstd, off), fmaf(bf_hi(rv[j].x), rstd, off));
    o.y = pack_bf16(fmaf(bf_lo(rv[j].y), rstd, off), fmaf(bf_hi(rv[j].y), rstd, off));
    o.z = pack_bf16(fmaf(bf_lo(rv[j].z), rstd, off), fmaf(bf_hi(rv[j].z), rstd, off));
    o.w = pack_bf16(fmaf(bf_lo(rv[j].w), rstd, off), fmaf(bf_hi(rv[j].w), rstd, off));
    reinterpret_cast<uint4*>(g_xn + (size_t)row * DM)[(l & 7) + 8 * j] = o;
  }
  fence_async_global();
  __threadfence();
  bar_sync<BAR_WG2>(128);
  if (t == 0) st_release(g_flags + F_XN + cta, epoch);
  unsigned it = 0;
  uint4 v;
  while ((v = ld_vol4(&g_xstat[rb * 128 + t])).z != epoch) { if ((++it & 4095u) == 0 && timed_out()) break; }
  reinterpret_cast<float2*>(smem + ROWSTAT_OFF)[t] = make_float2(__uint_as_float(v.x), __uint_as_float(v.y));
}

__device__ __forceinline__ void fold_pack(const float* a, float2 s0, float2 s1, float2 c0, float2 c1, uint32_t (&r)[4]) {
  r[0] = pack_bf16(fmaf(a[0], s0.x, s0.y * c0.x), fmaf(a[1], s0.x, s0.y * c0.y));
  r[1] = pack_bf16(fmaf(a[2], s1.x, s1.y * c0.x), fmaf(a[3], s1.x, s1.y * c0.y));
  r[2] = pack_bf16(fmaf(a[4], s0.x, s0.y * c1.x), fmaf(a[5], s0.x, s0.y * c1.y));
  r[3] = pack_bf16(fmaf(a[6], s1.x, s1.y * c1.x), fmaf(a[7], s1.x, s1.y * c1.y));
}

__device__ __forceinline__ void gelu_rows(uint32_t rbase, int n4, int wide, int sw, float& sum, float& sq) {
  #pragma unroll 1
  for (int c4 = 0; c4 < n4; c4++) {
    const uint32_t ab = rbase + (wide ? (c4 >> 1) * 8192 : c4 * 8192);
    const int cb = wide ? (c4 & 1) * 4 : 0;
    uint4 v[4];
    #pragma unroll
    for (int i = 0; i < 4; i++) v[i] = lds128(ab + (((cb + i) ^ sw) << 4));
    float s2 = 0.f, q2 = 0.f;
    #pragma unroll
    for (int i = 0; i < 4; i++) {
      const uint32_t u[4] = {v[i].x, v[i].y, v[i].z, v[i].w};
      uint32_t o[4];
      #pragma unroll
      for (int e = 0; e < 4; e++) {
        const float g0 = gelu_tanh(bf_lo(u[e])), g1 = gelu_tanh(bf_hi(u[e]));
        o[e] = pack_bf16(g0, g1);
        sum += g0; s2 += g1; sq = fmaf(g0, g0, sq); q2 = fmaf(g1, g1, q2);
      }
      v[i] = make_uint4(o[0], o[1], o[2], o[3]);
    }
    sum += s2; sq += q2;
    #pragma unroll
    for (int i = 0; i < 4; i++) sts128(ab + (((cb + i) ^ sw) << 4), v[i].x, v[i].y, v[i].z, v[i].w);
  }
}

__global__ void __cluster_dims__(2, 1, 1) __launch_bounds__(384, 1)
fused_kernel(const __grid_constant__ Maps maps, const bf16* __restrict__ x, const bf16* __restrict__ bsp) {
  const uint32_t sbase = smem_u32(smem);
  const uint32_t full0 = sbase + BAR_OFF, empty0 = full0 + 8 * STAGES, dep0 = empty0 + 8 * STAGES, ring = sbase + RING_OFF;
  const int tid = threadIdx.x, wg = tid >> 7;
  const int rank = blockIdx.x & 1, grp = (blockIdx.x >> 1) & 1, q = blockIdx.x >> 2;
  const int rb = q >> 1, ct = (q & 1) * 2 + rank, c8 = grp * 4 + ct;
  const int total = grp == 0 ? KB_A : KB_B;
  const uint32_t stage_bytes = grp == 0 ? STAGE_A : STAGE_B;

  if (tid == 0) {
    TS(0, 0);
    for (int s = 0; s < STAGES; s++) { mbar_init(full0 + 8 * s, 2); mbar_init(empty0 + 8 * s, 2); mbar_init(dep0 + 8 * s, 1); }
    *reinterpret_cast<unsigned long long*>(smem + DEADLINE_OFF) = gtime() + 200000000ull;
    asm volatile("fence.mbarrier_init.release.cluster;" ::: "memory");
  }
  __syncthreads();
  asm volatile("barrier.cluster.arrive.relaxed.aligned;" ::: "memory");

  if (wg == 0) {
    asm volatile("setmaxnreg.dec.sync.aligned.u32 40;");
    const int warp = tid >> 5, lane = tid & 31;
    if (warp == 0) {
      const int row = rb * 128;
      if (lane == 0) {
        TS(0, 1);
        for (int g = 0; g < STAGES; g++) {
          mbar_expect_tx(full0 + 8 * g, A_BYTES);
          tma_load_2d(ring + g * stage_bytes, &maps.m[M_X], full0 + 8 * g, g * 64, row);
          tma_load_2d(ring + g * stage_bytes + 8192, &maps.m[M_X], full0 + 8 * g, g * 64, row + 64);
        }
      }
      __syncwarp();
      asm volatile("barrier.cluster.wait.aligned;" ::: "memory");
      if (lane == 0) {
        #pragma unroll 1
        for (int g = STAGES; g < total; g++) {
          int mi, kb;
          if (g < 10) { mi = M_X; kb = g; }
          else if (g < 20) { mi = M_XN; kb = g - 10; }
          else if (grp == 0) {
            if (g < 52) { mi = M_WSP; kb = g - 20; }
            else if (g < 52 + NX) { mi = M_WSIM; kb = g - 52 + 32 - NX; }
            else { mi = M_H; kb = g - 52 - NX; }
          } else {
            if (g < 30) { mi = M_XN; kb = g - 20; }
            else if (g < 62) { mi = M_WSRE; kb = g - 30; }
            else { mi = M_WSIM; kb = g - 62; }
          }
          if (g == 10 || (mi == M_H && kb == 0)) { TS(0, g == 10 ? 2 : 3); mbar_wait(dep0 + (g == 10 ? 0 : 24), 0); fence_async_global(); TS(0, g == 10 ? 6 : 4); }
          const int s = g & (STAGES - 1);
          mbar_wait(empty0 + 8 * s, ((g / STAGES) & 1) ^ 1);
          mbar_expect_tx(full0 + 8 * s, A_BYTES);
          tma_load_2d_mc(ring + s * stage_bytes + rank * 8192, &maps.m[mi], full0 + 8 * s, kb * 64, row + rank * 64, 3);
        }
        TS(0, 5);
      }
    } else if (warp == 1) {
      if (lane == 0) {
        #pragma unroll 1
        for (int g = 0; g < total; g++) {
          int kind, mi, kb, c, dep = 0;
          uint32_t bytes = 24576;
          if (g < 10) { kind = 0; mi = M_WIN32; kb = g; c = 24 + 3 * c8; bytes = 12288; }
          else if (grp == 0) {
            if (g < 20) { kind = 0; mi = M_WIN3; kb = g - 10; c = 3 * ct; }
            else if (g < 52) { kind = 0; mi = M_Z23; kb = g - 20; c = 3 * ct; dep = g == 20 ? 1 : 0; }
            else if (g < 52 + NX) { kind = 1; mi = M_AB; kb = g - 52 + 32 - NX; c = DM + ct * 160; dep = g == 52 ? 2 : 0; }
            else { kind = 2; mi = M_WOUT; kb = g - 52 - NX; c = ct * 160; }
          } else {
            kind = 1;
            if (g < 30) { mi = g < 20 ? M_WDRE : M_WDIM; kb = g < 20 ? g - 10 : g - 20; c = ct * 160; }
            else { mi = M_AB; kb = g < 62 ? g - 30 : g - 62; c = ct * 160 + (g < 62 ? 0 : DM); dep = g == 30 ? 1 : g == 62 ? 2 : 0; }
          }
          if (kind == 1) bytes = 20480;
          if (dep) { TS(1, dep * 2 - 2); mbar_wait(dep0 + 8 * dep, 0); fence_async_global(); TS(1, dep * 2 - 1); }
          const int s = g & (STAGES - 1);
          const uint32_t dst = ring + s * stage_bytes + A_BYTES, fb = full0 + 8 * s;
          mbar_wait(empty0 + 8 * s, ((g / STAGES) & 1) ^ 1);
          mbar_expect_tx(fb, bytes);
          if (kind == 0) tma_load_3d(dst, &maps.m[mi], fb, 0, kb * 64, c);
          else if (kind == 1) tma_load_2d(dst, &maps.m[mi], fb, kb * 64, c);
          else {
            #pragma unroll 1
            for (int j = 0; j < 3; j++) tma_load_2d(dst + j * 8192, &maps.m[mi], fb, c + j * 64, kb * 64);
          }
        }
      }
      __syncwarp();
      asm volatile("barrier.cluster.wait.aligned;" ::: "memory");
    } else if (warp == 2) {
      asm volatile("barrier.cluster.wait.aligned;" ::: "memory");
      const unsigned epoch = (*reinterpret_cast<volatile unsigned*>(&g_done) >> 7) + 1u;
      #pragma unroll 1
      for (int d = 0; d < 4 - grp; d++) {
        const int fi = d == 0 ? F_XN + rb * 8 + (lane & 7)
                     : d == 3 ? F_H + rb * 4 + (lane & 3)
                     : (d == 1 && grp == 0) ? F_Z + (lane >> 1) * 8 + ct * 2 + (lane & 1)
                     : (d == 1 ? F_A : F_B) + (lane & 15) * 4 + ct;
        unsigned it = 0;
        while (!__all_sync(0xffffffffu, ld_relaxed(g_flags + fi) == epoch)) { __nanosleep(20); if ((++it & 4095u) == 0 && timed_out()) break; }
        fence_async_global();
        __syncwarp();
        if (lane == 0) mbar_arrive(dep0 + 8 * d);
      }
    } else {
      asm volatile("barrier.cluster.wait.aligned;" ::: "memory");
    }
  } else {
    asm volatile("setmaxnreg.inc.sync.aligned.u32 232;");
    const int t = tid & 127, w = t >> 5, l = t & 31;
    const uint32_t buf = ring + 4 * stage_bytes;
    const unsigned epoch = (*reinterpret_cast<volatile unsigned*>(&g_done) >> 7) + 1u;
    asm volatile("barrier.cluster.wait.aligned;" ::: "memory");
    const int rl = w * 16 + ((l >> 3) & 1) * 8 + (l & 7);
    const int gr = w * 16 + (l & 15);
    float sum = 0.f, sq = 0.f;
    if (wg == 1) {
      float acc[2][48];
      float csum[8];
      #pragma unroll
      for (int i = 0; i < 8; i++) csum[i] = 0.f;
      mainloop<96, 1, false>(acc, sbase, stage_bytes, 0, 10, total, 0, BAR_ORD1, true, 0, csum);
      pin(acc);
      TS(2, 2);
      float* red = reinterpret_cast<float*>(smem + (buf - sbase));
      if (t < 96) {
        *reinterpret_cast<float4*>(red + (t / 12) * 96 + (t % 12) * 8) = make_float4(csum[0], csum[1], csum[2], csum[3]);
        *reinterpret_cast<float4*>(red + (t / 12) * 96 + (t % 12) * 8 + 4) = make_float4(csum[4], csum[5], csum[6], csum[7]);
      }
      bar_sync<BAR_WG1>(128);
      if (t < 96) {
        float c = 0.f;
        #pragma unroll
        for (int i = 0; i < 8; i++) c += red[i * 96 + t];
        reinterpret_cast<float*>(smem + COLSUM_OFF)[t] = c;
      }
      bar_sync<BAR_STATS>(256);
      const float2* rs = reinterpret_cast<const float2*>(smem + ROWSTAT_OFF) + w * 16 + (l >> 2);
      const float2* cs = reinterpret_cast<const float2*>(smem + COLSUM_OFF) + (l & 3);
      const float2 s0 = rs[0], s1 = rs[8], s2 = rs[64], s3 = rs[72];
      #pragma unroll
      for (int jj = 0; jj < 6; jj++) {
        uint32_t r[4];
        const float2 c0 = cs[jj * 8], c1 = cs[jj * 8 + 4];
        const uint32_t ad = buf + (jj >> 1) * 8192 + rl * 64 + ((((jj & 1) * 2 + (l >> 4)) ^ ((l >> 1) & 3)) << 4);
        fold_pack(&acc[0][8 * jj], s0, s1, c0, c1, r);
        stsm4(ad, r[0], r[1], r[2], r[3]);
        fold_pack(&acc[1][8 * jj], s2, s3, c0, c1, r);
        stsm4(ad + 4096, r[0], r[1], r[2], r[3]);
      }
      __syncwarp();
      TS(2, 3);
    } else {
      ln_prologue(x, rb, epoch);
      if (grp == 0) reinterpret_cast<float*>(smem + BIAS_OFF)[t] = __bfloat162float(bsp[rb * 128 + t]);
      TS(3, 0);
      bar_arrive<BAR_STATS>(256);
      bar_sync<BAR_ORD1>(256);
    }
    const uint32_t st_base = buf + rl * 128;
    const uint32_t st_x = ((l >> 4) ^ (l & 7)) << 4;
    if (wg == 1 || grp == 0) {
      #pragma unroll 1
      for (int it = 2 - wg; it < 3; it++) {
        if (it == 1) {
          const uint32_t rbase = wg == 1 ? buf + (l >> 4) * 4096 + gr * 64 : buf + (l >> 4) * 24576 + gr * 128;
          gelu_rows(rbase, wg == 1 ? 3 : 6, wg - 1, wg == 1 ? (l >> 1) & 3 : l & 7, sum, sq);
          TS(wg + 1, 4);
          if (wg == 2) { bar_arrive<BAR_Z1>(256); break; }
          const int row = (l >> 4) * 64 + gr;
          const float mu = sum * (1.f / 96), m2 = fmaxf(sq - sum * mu, 0.f);
          st_vol4(&g_zstat[(rb * 8 + c8) * 128 + row], __float_as_uint(mu), __float_as_uint(m2), epoch, 0u);
          uint4 v[7];
          unsigned n = 0;
          while (true) {
            bool ok = true;
            #pragma unroll
            for (int j = 0; j < 7; j++) v[j] = ld_vol4(&g_zstat[(rb * 8 + ((c8 + 1 + j) & 7)) * 128 + row]);
            #pragma unroll
            for (int j = 0; j < 7; j++) ok = ok && v[j].z == epoch;
            if (ok) break;
            if ((++n & 4095u) == 0 && timed_out()) break;
          }
          float mean = mu, var = m2;
          #pragma unroll
          for (int j = 0; j < 7; j++) { mean += __uint_as_float(v[j].x); var += __uint_as_float(v[j].y); }
          mean *= 0.125f;
          float d = (mu - mean) * (mu - mean);
          #pragma unroll
          for (int j = 0; j < 7; j++) d = fmaf(__uint_as_float(v[j].x) - mean, __uint_as_float(v[j].x) - mean, d);
          const float rstd = rsqrtf(fmaf(96.f, d, var) * (1.f / FH) + LN_EPS), off = -mean * rstd;
          TS(2, 5);
          #pragma unroll 1
          for (int c = 0; c < 3; c++) {
            uint4 z[4];
            #pragma unroll
            for (int i = 0; i < 4; i++) z[i] = lds128(rbase + c * 8192 + ((i ^ ((l >> 1) & 3)) << 4));
            #pragma unroll
            for (int i = 0; i < 4; i++)
              sts128(rbase + c * 8192 + ((i ^ ((l >> 1) & 3)) << 4),
                     pack_bf16(fmaf(bf_lo(z[i].x), rstd, off), fmaf(bf_hi(z[i].x), rstd, off)), pack_bf16(fmaf(bf_lo(z[i].y), rstd, off), fmaf(bf_hi(z[i].y), rstd, off)),
                     pack_bf16(fmaf(bf_lo(z[i].z), rstd, off), fmaf(bf_hi(z[i].z), rstd, off)), pack_bf16(fmaf(bf_lo(z[i].w), rstd, off), fmaf(bf_hi(z[i].w), rstd, off)));
          }
          fence_async_smem();
          bar_sync<BAR_WG1>(128);
          TS(2, 6);
          if (t == 0) {
            tma_store_3d(&maps.m[M_Z232], buf, 0, rb * 128, 3 * c8);
            publish(g_flags + F_Z + rb * 8 + c8, epoch);
          }
          __syncwarp();
          TS(2, 10);
          if (grp == 1) break;
          bar_arrive<BAR_BUF>(256);
          bar_sync<BAR_ORD2>(256);
        } else {
          float acc[2][96];
          mainloop<192, 1, false>(acc, sbase, STAGE_A, it == 0 ? 10 : 20, it == 0 ? 10 : 32, KB_A, 0, it == 0 ? BAR_ORD2 : BAR_ORD1, true, 0);
          pin(acc);
          TS(wg + 1, it == 0 ? 2 : 7);
          if (it == 0) {
            bar_sync<BAR_BUF>(256);
            #pragma unroll
            for (int mi = 0; mi < 2; mi++)
              #pragma unroll
              for (int jj = 0; jj < 12; jj++) {
                const float* a = &acc[mi][8 * jj];
                stsm4(st_base + mi * 24576 + (jj >> 2) * 8192 + (st_x ^ ((jj & 3) << 5)),
                      pack_bf16(a[0], a[1]), pack_bf16(a[2], a[3]), pack_bf16(a[4], a[5]), pack_bf16(a[6], a[7]));
              }
            __syncwarp();
            TS(3, 3);
          } else {
            const float* bias = reinterpret_cast<const float*>(smem + BIAS_OFF) + w * 16 + (l >> 2);
            bar_sync<BAR_Z1>(256);
            #pragma unroll
            for (int mi = 0; mi < 2; mi++) {
              const float b0 = bias[mi * 64], b1 = bias[mi * 64 + 8];
              #pragma unroll
              for (int j4 = 0; j4 < 3; j4++) {
                uint32_t z[4][4];
                #pragma unroll
                for (int i = 0; i < 4; i++) ldsm4(st_base + mi * 24576 + j4 * 8192 + (st_x ^ (i << 5)), z[i][0], z[i][1], z[i][2], z[i][3]);
                #pragma unroll
                for (int i = 0; i < 4; i++) {
                  const float* a = &acc[mi][8 * (j4 * 4 + i)];
                  stsm4(st_base + mi * 24576 + j4 * 8192 + (st_x ^ (i << 5)),
                        hmul2_bf16(z[i][0], pack_bf16(a[0] + b0, a[1] + b0)), hmul2_bf16(z[i][1], pack_bf16(a[2] + b1, a[3] + b1)),
                        hmul2_bf16(z[i][2], pack_bf16(a[4] + b0, a[5] + b0)), hmul2_bf16(z[i][3], pack_bf16(a[6] + b1, a[7] + b1)));
                }
              }
            }
            fence_async_smem();
            bar_sync<BAR_WG1>(128);
            TS(2, 8);
            if (t == 0) {
              tma_store_3d(&maps.m[M_H3], buf, 0, rb * 128, 3 * ct);
              tma_store_3d(&maps.m[M_H3], buf + 24576, 0, rb * 128 + 64, 3 * ct);
              publish(g_flags + F_H + rb * 4 + ct, epoch);
            }
            __syncwarp();
            TS(2, 9);
          }
        }
      }
    }
    if (grp == 1 || wg == 2) {
      float acc[2][80];
      #pragma unroll 1
      for (int it = 1 - grp; it < 2; it++) {
        if (it == 1) {
          const bf16* p = x + (size_t)(rb * 128 + grp * 64 + w * 16 + (l >> 2)) * DM + ct * 160 + (l & 3) * 2;
          #pragma unroll
          for (int j = 0; j < 20; j++) {
            const uint32_t v0 = __ldg(reinterpret_cast<const uint32_t*>(p + j * 8));
            const uint32_t v1 = __ldg(reinterpret_cast<const uint32_t*>(p + 8 * DM + j * 8));
            acc[0][4 * j + 0] = bf_lo(v0); acc[0][4 * j + 1] = bf_hi(v0); acc[0][4 * j + 2] = bf_lo(v1); acc[0][4 * j + 3] = bf_hi(v1);
            acc[1][4 * j + 0] = 0.f; acc[1][4 * j + 1] = 0.f; acc[1][4 * j + 2] = 0.f; acc[1][4 * j + 3] = 0.f;
          }
          bar_sync<BAR_ORD1>(256);
          TS(3, 11);
        } else if (wg == 1) {
          bar_sync<BAR_ORD2>(256);
        }
        mainloop<160, 0, false>(acc, sbase, stage_bytes, it == 0 ? (wg == 2 ? 10 : 20) : grp == 0 ? 52 : 30, it == 0 ? 10 : grp == 0 ? NX : 64 - NX,
                                total, it, it == 1 ? 0 : wg == 1 ? BAR_ORD1 : BAR_ORD2, grp == 1, it & grp);
        if (it == 1) break;
        pin(acc);
        TS(wg + 1, wg == 1 ? 7 : 2);
        if (wg == 1) bar_sync<BAR_BUF>(256);
        const uint32_t sg = wg == 1 ? 0x80008000u : 0u;
        const uint32_t tb = buf + 24576 + ((l >> 4) * 8 + (l & 7)) * 128 + (((w * 2 + ((l >> 3) & 1)) ^ (l & 7)) << 4);
        #pragma unroll
        for (int mi = 0; mi < 2; mi++)
          #pragma unroll
          for (int jj = 0; jj < 10; jj++) {
            const float* a = &acc[mi][8 * jj];
            stsm4_t(tb + mi * 20480 + jj * 2048, pack_bf16(a[0], a[1]) ^ sg, pack_bf16(a[2], a[3]) ^ sg, pack_bf16(a[4], a[5]) ^ sg, pack_bf16(a[6], a[7]) ^ sg);
          }
        fence_async_smem();
        if (wg == 1) bar_sync<BAR_WG1>(128); else bar_sync<BAR_WG2>(128);
        TS(wg + 1, wg == 1 ? 8 : 6);
        if (t == 0) {
          tma_store_2d(&maps.m[M_AB], buf + 24576, rb * 128, (2 - wg) * DM + ct * 160);
          tma_store_2d(&maps.m[M_AB], buf + 24576 + 20480, rb * 128 + 64, (2 - wg) * DM + ct * 160);
          publish(g_flags + (wg == 2 ? F_A : F_B) + rb * 4 + ct, epoch);
        }
        __syncwarp();
        TS(wg + 1, wg == 1 ? 9 : 10);
        if (wg == 1) return;
        bar_arrive<BAR_BUF>(256);
      }
      if (grp == 0) mainloop<160, 1, true>(acc, sbase, STAGE_A, 52 + NX, 12, KB_A, 1, 0, true, 0);
      pin(acc);
      TS(3, 12);
      uint4* dst = g_part + (size_t)blockIdx.x * 27 * 128 + t;
      const uint4* src = g_part + (size_t)(blockIdx.x ^ 2) * 27 * 128 + t;
      #pragma unroll
      for (int i = 0; i < 27; i++)
        st_vol4(dst + i * 128, __float_as_uint(acc[1][3 * i]), __float_as_uint(acc[1][3 * i + 1]),
                __float_as_uint(i < 26 ? acc[1][3 * i + 2] : 0.f), epoch);
      TS(3, 13);
      {
        unsigned n = 0;
        #pragma unroll
        for (int gq = 0; gq < 2; gq++) {
          uint4 v[14];
          while (true) {
            bool ok = true;
            #pragma unroll
            for (int i = 0; i < 14 - gq; i++) v[i] = ld_vol4(src + (gq * 14 + i) * 128);
            #pragma unroll
            for (int i = 0; i < 14 - gq; i++) ok = ok && (v[i].w == epoch);
            if (ok) break;
            if ((++n & 4095u) == 0 && timed_out()) break;
          }
          #pragma unroll
          for (int i = 0; i < 14 - gq; i++) {
            const int e = (gq * 14 + i) * 3;
            acc[0][e] += __uint_as_float(v[i].x);
            acc[0][e + 1] += __uint_as_float(v[i].y);
            if (e + 2 < 80) acc[0][e + 2] += __uint_as_float(v[i].z);
          }
        }
      }
      TS(3, 14);
      const uint32_t slab = ring + w * (16 * 320);
      const uint32_t addr = slab + (((l >> 3) & 1) * 8 + (l & 7)) * 320 + (l >> 4) * 16;
      bar_sync<BAR_WG2>(128);
      #pragma unroll
      for (int jj = 0; jj < 10; jj++) {
        const float* a = &acc[0][8 * jj];
        stsm4(addr + jj * 32, pack_bf16(a[0], a[1]), pack_bf16(a[2], a[3]), pack_bf16(a[4], a[5]), pack_bf16(a[6], a[7]));
      }
      fence_async_smem();
      __syncwarp();
      if (l == 0) {
        tma_store_2d(&maps.m[M_OUT], slab, ct * 160, rb * 128 + grp * 64 + w * 16);
        bulk_commit();
        bulk_wait_read();
        if (w == 0) atomicAdd(&g_done, 1u);
      }
      TS(3, 15);
    }
  }
}

typedef CUresult (*EncodeFn)(CUtensorMap*, CUtensorMapDataType, cuuint32_t, void*, const cuuint64_t*, const cuuint64_t*,
                             const cuuint32_t*, const cuuint32_t*, CUtensorMapInterleave, CUtensorMapSwizzle,
                             CUtensorMapL2promotion, CUtensorMapFloatOOBfill);

void make2d(EncodeFn enc, CUtensorMap* m, const void* p, uint64_t cols, uint64_t rows, uint32_t bc, uint32_t br, bool swz = true) {
  cuuint64_t gd[2] = {cols, rows}, gs[1] = {cols * 2};
  cuuint32_t bd[2] = {bc, br}, es[2] = {1, 1};
  enc(m, CU_TENSOR_MAP_DATA_TYPE_BFLOAT16, 2, const_cast<void*>(p), gd, gs, bd, es, CU_TENSOR_MAP_INTERLEAVE_NONE,
      swz ? CU_TENSOR_MAP_SWIZZLE_128B : CU_TENSOR_MAP_SWIZZLE_NONE, CU_TENSOR_MAP_L2_PROMOTION_L2_256B, CU_TENSOR_MAP_FLOAT_OOB_FILL_NONE);
}
void make3d(EncodeFn enc, CUtensorMap* m, const void* p, uint64_t cols, uint64_t rows, uint32_t cw = 64, uint32_t br = 64) {
  cuuint64_t gd[3] = {cw, rows, cols / cw}, gs[2] = {cols * 2, cw * 2};
  cuuint32_t bd[3] = {cw, br, 3}, es[3] = {1, 1, 1};
  enc(m, CU_TENSOR_MAP_DATA_TYPE_BFLOAT16, 3, const_cast<void*>(p), gd, gs, bd, es, CU_TENSOR_MAP_INTERLEAVE_NONE,
      cw == 64 ? CU_TENSOR_MAP_SWIZZLE_128B : CU_TENSOR_MAP_SWIZZLE_64B, CU_TENSOR_MAP_L2_PROMOTION_L2_256B, CU_TENSOR_MAP_FLOAT_OOB_FILL_NONE);
}

}

extern "C" void kernel_launch(void* const* d_in, const int* in_sizes, int n_in, void* d_out, int out_size) {
  const bf16* x = (const bf16*)d_in[0];
  const bf16* wsre = (const bf16*)d_in[1];
  const bf16* wsim = (const bf16*)d_in[2];
  const bf16* wdre = (const bf16*)d_in[3];
  const bf16* wdim = (const bf16*)d_in[4];
  const bf16* win = (const bf16*)d_in[6];
  const bf16* wsp = (const bf16*)d_in[7];
  const bf16* bsp = (const bf16*)d_in[8];
  const bf16* wout = (const bf16*)d_in[9];

  void* fn = nullptr;
  cudaDriverEntryPointQueryResult qr;
  cudaGetDriverEntryPoint("cuTensorMapEncodeTiled", &fn, cudaEnableDefault, &qr);
  EncodeFn enc = (EncodeFn)fn;
  void *abT, *z2, *h, *xn;
  cudaGetSymbolAddress(&xn, g_xn);
  cudaGetSymbolAddress(&abT, g_abT);
  cudaGetSymbolAddress(&z2, g_z2);
  cudaGetSymbolAddress(&h, g_h);

  Maps maps;
  make2d(enc, &maps.m[M_X], x, DM, SEQ, 64, 64);
  make2d(enc, &maps.m[M_XN], xn, DM, SEQ, 64, 64);
  make3d(enc, &maps.m[M_WIN32], win, FF, DM, 32, 64);
  make3d(enc, &maps.m[M_Z232], z2, FH, SEQ, 32, 128);
  make2d(enc, &maps.m[M_WSRE], wsre, SEQ, SEQ, 64, 64);
  make2d(enc, &maps.m[M_WSIM], wsim, SEQ, SEQ, 64, 64);
  make2d(enc, &maps.m[M_WSP], wsp, SEQ, SEQ, 64, 64);
  make2d(enc, &maps.m[M_H], h, FH, SEQ, 64, 64);
  make3d(enc, &maps.m[M_H3], h, FH, SEQ);
  make3d(enc, &maps.m[M_WIN3], win, FF, DM);
  make3d(enc, &maps.m[M_Z23], z2, FH, SEQ);
  make2d(enc, &maps.m[M_WDRE], wdre, DM, DM, 64, 160);
  make2d(enc, &maps.m[M_WDIM], wdim, DM, DM, 64, 160);
  make2d(enc, &maps.m[M_AB], abT, SEQ, 2 * DM, 64, 160);
  make2d(enc, &maps.m[M_WOUT], wout, DM, FH, 64, 64);
  make2d(enc, &maps.m[M_OUT], d_out, DM, SEQ, 160, 16, false);

  cudaFuncSetAttribute(fused_kernel, cudaFuncAttributeMaxDynamicSharedMemorySize, SMEM_BYTES);
  fused_kernel<<<128, 384, SMEM_BYTES>>>(maps, x, bsp);
}
```

```cpp
#include <cuda_runtime.h>
#include <cuda_bf16.h>
#include <cuda.h>
#include <stdint.h>

namespace {

typedef __nv_bfloat16 bf16;

constexpr int SEQ = 2048, DM = 640, FF = 1536, FH = 768;
constexpr int NX = 11;
constexpr int STAGES = 4;
constexpr int A_BYTES = 16384;
constexpr int ROWSTAT_OFF = 0;
constexpr int COLSUM_OFF = 1024;
constexpr int BIAS_OFF = 2560;
constexpr int BAR_OFF = 3072;
constexpr int DEADLINE_OFF = BAR_OFF + 128;
constexpr int RING_OFF = 4096;
constexpr int STAGE_A = 40960, STAGE_B = 36864;
constexpr int SMEM_BYTES = RING_OFF + 4 * STAGE_A + 49152;
constexpr int KB_A = 20 + 32 + NX + 12;
constexpr int KB_B = 30 + 64 - NX;
constexpr float LN_EPS = 1e-5f;
#define POLL_NS 200
#define NO_PF
#define PF_NS 150

constexpr int BAR_ORD1 = 1, BAR_ORD2 = 2, BAR_WG1 = 3, BAR_WG2 = 4, BAR_STATS = 5, BAR_BUF = 6, BAR_Z1 = 7;

enum { M_X, M_XR, M_WIN32, M_Z232, M_WSRE, M_WSIM, M_WSP, M_H, M_H3, M_WIN3, M_Z23, M_WDRE, M_WDIM, M_AB, M_WOUT, M_OUT, M_COUNT };
struct Maps { CUtensorMap m[M_COUNT]; };

__device__ __align__(1024) bf16 g_abT[2 * DM * SEQ];
__device__ __align__(1024) bf16 g_z2[SEQ * FH];
__device__ __align__(1024) bf16 g_h[SEQ * FH];
__device__ __align__(16) uint4 g_xstat[SEQ];
__device__ __align__(16) uint2 g_csum[16 * FF + 2 * DM];
__device__ __align__(16) uint4 g_zstat[128 * 128];
__device__ __align__(16) uint4 g_part[128 * 27 * 128];
__device__ unsigned g_flags[4 * 128];
constexpr int F_A = 0, F_B = 128, F_H = 256, F_Z = 384;
__device__ unsigned g_done;
#define TS(role, ev)
#define TC(i)

extern __shared__ __align__(1024) uint8_t smem[];

__device__ __forceinline__ unsigned long long gtime() { unsigned long long t; asm volatile("mov.u64 %0, %%globaltimer;" : "=l"(t)); return t; }
__device__ __forceinline__ bool timed_out() { return gtime() > *reinterpret_cast<volatile unsigned long long*>(smem + DEADLINE_OFF); }
__device__ __forceinline__ uint32_t smem_u32(const void* p) { return (uint32_t)__cvta_generic_to_shared(p); }
__device__ __forceinline__ void mbar_init(uint32_t bar, uint32_t cnt) { asm volatile("mbarrier.init.shared::cta.b64 [%0], %1;" :: "r"(bar), "r"(cnt)); }
__device__ __forceinline__ void mbar_expect_tx(uint32_t bar, uint32_t bytes) { asm volatile("mbarrier.arrive.expect_tx.shared::cta.b64 _, [%0], %1;" :: "r"(bar), "r"(bytes) : "memory"); }
__device__ __forceinline__ void mbar_arrive(uint32_t bar) { asm volatile("mbarrier.arrive.shared::cta.b64 _, [%0];" :: "r"(bar) : "memory"); }
__device__ __forceinline__ void mbar_arrive_cluster(uint32_t bar, uint32_t cta) {
  asm volatile("{\n.reg .b32 ra;\nmapa.shared::cluster.u32 ra, %0, %1;\nmbarrier.arrive.shared::cluster.b64 _, [ra];\n}" :: "r"(bar), "r"(cta) : "memory");
}
__device__ __forceinline__ bool mbar_try(uint32_t bar, uint32_t parity) {
  uint32_t ok;
  asm volatile("{\n.reg .pred p;\nmbarrier.try_wait.parity.shared::cta.b64 p, [%1], %2;\nselp.u32 %0, 1, 0, p;\n}" : "=r"(ok) : "r"(bar), "r"(parity) : "memory");
  return ok != 0;
}
__device__ __forceinline__ void mbar_wait(uint32_t bar, uint32_t parity) {
  unsigned n = 0;
  while (!mbar_try(bar, parity)) { if ((++n & 4095u) == 0 && timed_out()) break; }
}
__device__ __forceinline__ void tma_load_2d(uint32_t dst, const CUtensorMap* map, uint32_t bar, int c0, int c1) {
  asm volatile("cp.async.bulk.tensor.2d.shared::cluster.global.mbarrier::complete_tx::bytes [%0], [%1, {%3, %4}], [%2];"
    :: "r"(dst), "l"((uint64_t)map), "r"(bar), "r"(c0), "r"(c1) : "memory");
}
__device__ __forceinline__ void tma_load_3d(uint32_t dst, const CUtensorMap* map, uint32_t bar, int c0, int c1, int c2) {
  asm volatile("cp.async.bulk.tensor.3d.shared::cluster.global.mbarrier::complete_tx::bytes [%0], [%1, {%3, %4, %5}], [%2];"
    :: "r"(dst), "l"((uint64_t)map), "r"(bar), "r"(c0), "r"(c1), "r"(c2) : "memory");
}
__device__ __forceinline__ void tma_load_2d_mc(uint32_t dst, const CUtensorMap* map, uint32_t bar, int c0, int c1, uint16_t mask) {
  asm volatile("cp.async.bulk.tensor.2d.shared::cluster.global.mbarrier::complete_tx::bytes.multicast::cluster [%0], [%1, {%3, %4}], [%2], %5;"
    :: "r"(dst), "l"((uint64_t)map), "r"(bar), "r"(c0), "r"(c1), "h"(mask) : "memory");
}
__device__ __forceinline__ void tma_store_2d(const CUtensorMap* map, uint32_t src, int c0, int c1) {
  asm volatile("cp.async.bulk.tensor.2d.global.shared::cta.bulk_group [%0, {%2, %3}], [%1];"
    :: "l"((uint64_t)map), "r"(src), "r"(c0), "r"(c1) : "memory");
}
__device__ __forceinline__ void tma_store_3d(const CUtensorMap* map, uint32_t src, int c0, int c1, int c2) {
  asm volatile("cp.async.bulk.tensor.3d.global.shared::cta.bulk_group [%0, {%2, %3, %4}], [%1];"
    :: "l"((uint64_t)map), "r"(src), "r"(c0), "r"(c1), "r"(c2) : "memory");
}
__device__ __forceinline__ void tma_prefetch_2d(const CUtensorMap* map, int c0, int c1) {
  asm volatile("cp.async.bulk.prefetch.tensor.2d.L2.global.tile [%0, {%1, %2}];" :: "l"((uint64_t)map), "r"(c0), "r"(c1) : "memory");
}
__device__ __forceinline__ void tma_prefetch_3d(const CUtensorMap* map, int c0, int c1, int c2) {
  asm volatile("cp.async.bulk.prefetch.tensor.3d.L2.global.tile [%0, {%1, %2, %3}];" :: "l"((uint64_t)map), "r"(c0), "r"(c1), "r"(c2) : "memory");
}
__device__ __forceinline__ void bulk_commit() { asm volatile("cp.async.bulk.commit_group;" ::: "memory"); }
__device__ __forceinline__ void bulk_wait_all() { asm volatile("cp.async.bulk.wait_group 0;" ::: "memory"); }
__device__ __forceinline__ void bulk_wait_read() { asm volatile("cp.async.bulk.wait_group.read 0;" ::: "memory"); }
__device__ __forceinline__ void fence_async_smem() { asm volatile("fence.proxy.async.shared::cta;" ::: "memory"); }
__device__ __forceinline__ void fence_async_global() { asm volatile("fence.proxy.async.global;" ::: "memory"); }
__device__ __forceinline__ void wgmma_fence() { asm volatile("wgmma.fence.sync.aligned;" ::: "memory"); }
__device__ __forceinline__ void wgmma_commit() { asm volatile("wgmma.commit_group.sync.aligned;" ::: "memory"); }
template<int N> __device__ __forceinline__ void wgmma_wait() { asm volatile("wgmma.wait_group.sync.aligned %0;" :: "n"(N) : "memory"); }
template<int ID> __device__ __forceinline__ void bar_sync(int n) { asm volatile("bar.sync %0, %1;" :: "n"(ID), "r"(n) : "memory"); }
template<int ID> __device__ __forceinline__ void bar_arrive(int n) { asm volatile("bar.arrive %0, %1;" :: "n"(ID), "r"(n) : "memory"); }
__device__ __forceinline__ uint64_t make_desc(uint32_t addr, uint32_t lbo, uint32_t sbo, int swz = 1) {
  return (uint64_t)((addr & 0x3FFFF) >> 4) | ((uint64_t)(lbo >> 4) << 16) | ((uint64_t)(sbo >> 4) << 32) | ((uint64_t)swz << 62);
}
__device__ __forceinline__ uint4 ld_vol4(const uint4* p) {
  uint4 v; asm volatile("ld.volatile.global.v4.u32 {%0,%1,%2,%3}, [%4];" : "=r"(v.x), "=r"(v.y), "=r"(v.z), "=r"(v.w) : "l"(p) : "memory"); return v;
}
__device__ __forceinline__ uint2 ld_vol2(const uint2* p) {
  uint2 v; asm volatile("ld.volatile.global.v2.u32 {%0,%1}, [%2];" : "=r"(v.x), "=r"(v.y) : "l"(p) : "memory"); return v;
}
__device__ __forceinline__ void st_vol4(uint4* p, uint32_t a, uint32_t b, uint32_t c, uint32_t d) {
  asm volatile("st.volatile.global.v4.u32 [%0], {%1,%2,%3,%4};" :: "l"(p), "r"(a), "r"(b), "r"(c), "r"(d) : "memory");
}
__device__ __forceinline__ void st_vol2(uint2* p, uint32_t a, uint32_t b) {
  asm volatile("st.volatile.global.v2.u32 [%0], {%1,%2};" :: "l"(p), "r"(a), "r"(b) : "memory");
}
__device__ __forceinline__ unsigned ld_acquire(const unsigned* p) {
  unsigned v; asm volatile("ld.acquire.gpu.global.u32 %0, [%1];" : "=r"(v) : "l"(p) : "memory"); return v;
}
__device__ __forceinline__ unsigned ld_relaxed(const unsigned* p) {
  unsigned v; asm volatile("ld.relaxed.gpu.global.u32 %0, [%1];" : "=r"(v) : "l"(p) : "memory"); return v;
}
__device__ __forceinline__ void st_release(unsigned* p, unsigned v) {
  asm volatile("st.relaxed.gpu.global.u32 [%0], %1;" :: "l"(p), "r"(v) : "memory");
}
__device__ __forceinline__ uint32_t pack_bf16(float lo, float hi) {
  uint32_t r; asm("cvt.rn.bf16x2.f32 %0, %1, %2;" : "=r"(r) : "f"(hi), "f"(lo)); return r;
}
__device__ __forceinline__ float bf_lo(uint32_t v) { return __uint_as_float(v << 16); }
__device__ __forceinline__ float bf_hi(uint32_t v) { return __uint_as_float(v & 0xFFFF0000u); }
__device__ __forceinline__ void stsm4(uint32_t addr, uint32_t a, uint32_t b, uint32_t c, uint32_t d) {
  asm volatile("stmatrix.sync.aligned.m8n8.x4.shared.b16 [%0], {%1,%2,%3,%4};" :: "r"(addr), "r"(a), "r"(b), "r"(c), "r"(d));
}
__device__ __forceinline__ void stsm4_t(uint32_t addr, uint32_t a, uint32_t b, uint32_t c, uint32_t d) {
  asm volatile("stmatrix.sync.aligned.m8n8.x4.trans.shared.b16 [%0], {%1,%2,%3,%4};" :: "r"(addr), "r"(a), "r"(b), "r"(c), "r"(d));
}
__device__ __forceinline__ void ldsm4(uint32_t addr, uint32_t& a, uint32_t& b, uint32_t& c, uint32_t& d) {
  asm volatile("ldmatrix.sync.aligned.m8n8.x4.shared.b16 {%0,%1,%2,%3}, [%4];" : "=r"(a), "=r"(b), "=r"(c), "=r"(d) : "r"(addr));
}
__device__ __forceinline__ uint4 lds128(uint32_t a) {
  uint4 v; asm volatile("ld.shared.v4.u32 {%0,%1,%2,%3}, [%4];" : "=r"(v.x), "=r"(v.y), "=r"(v.z), "=r"(v.w) : "r"(a)); return v;
}
__device__ __forceinline__ void sts128(uint32_t a, uint32_t x, uint32_t y, uint32_t z, uint32_t w) {
  asm volatile("st.shared.v4.u32 [%0], {%1,%2,%3,%4};" :: "r"(a), "r"(x), "r"(y), "r"(z), "r"(w));
}
__device__ __forceinline__ uint32_t hmul2_bf16(uint32_t a, uint32_t b) {
  uint32_t r; asm("mul.rn.bf16x2 %0, %1, %2;" : "=r"(r) : "r"(a), "r"(b)); return r;
}
__device__ __forceinline__ uint32_t hfma2_bf16(uint32_t a, uint32_t b, uint32_t c) {
  uint32_t r; asm("fma.rn.bf16x2 %0, %1, %2, %3;" : "=r"(r) : "r"(a), "r"(b), "r"(c)); return r;
}
__device__ __forceinline__ float gelu_tanh(float v) {
  float u = v * fmaf(0.0356774081f, v * v, 0.7978845608f);
  float t; asm("tanh.approx.f32 %0, %1;" : "=f"(t) : "f"(u));
  float hv = 0.5f * v;
  return fmaf(hv, t, hv);
}
__device__ __forceinline__ float warp_sum(float v) {
  #pragma unroll
  for (int o = 16; o > 0; o >>= 1) v += __shfl_xor_sync(0xffffffffu, v, o);
  return v;
}
__device__ __forceinline__ float quad_sum(float v) {
  v += __shfl_xor_sync(0xffffffffu, v, 1);
  v += __shfl_xor_sync(0xffffffffu, v, 2);
  return v;
}

template<int TB>
__device__ __forceinline__ void wgmma_n192(float (&d)[96], uint64_t da, uint64_t db, int scale_d) {
  asm volatile("{\n.reg .pred p;\nsetp.ne.b32 p, %98, 0;\n"
   "wgmma.mma_async.sync.aligned.m64n192k16.f32.bf16.bf16 {%0,%1,%2,%3,%4,%5,%6,%7,%8,%9,%10,%11,%12,%13,%14,%15,%16,%17,%18,%19,%20,%21,%22,%23,%24,%25,%26,%27,%28,%29,%30,%31,%32,%33,%34,%35,%36,%37,%38,%39,%40,%41,%42,%43,%44,%45,%46,%47,%48,%49,%50,%51,%52,%53,%54,%55,%56,%57,%58,%59,%60,%61,%62,%63,%64,%65,%66,%67,%68,%69,%70,%71,%72,%73,%74,%75,%76,%77,%78,%79,%80,%81,%82,%83,%84,%85,%86,%87,%88,%89,%90,%91,%92,%93,%94,%95}, %96, %97, p, 1, 1, 0, %99;\n}"
   : "+f"(d[0]),"+f"(d[1]),"+f"(d[2]),"+f"(d[3]),"+f"(d[4]),"+f"(d[5]),"+f"(d[6]),"+f"(d[7]),"+f"(d[8]),"+f"(d[9]),"+f"(d[10]),"+f"(d[11]),"+f"(d[12]),"+f"(d[13]),"+f"(d[14]),"+f"(d[15]),"+f"(d[16]),"+f"(d[17]),"+f"(d[18]),"+f"(d[19]),"+f"(d[20]),"+f"(d[21]),"+f"(d[22]),"+f"(d[23]),"+f"(d[24]),"+f"(d[25]),"+f"(d[26]),"+f"(d[27]),"+f"(d[28]),"+f"(d[29]),"+f"(d[30]),"+f"(d[31]),"+f"(d[32]),"+f"(d[33]),"+f"(d[34]),"+f"(d[35]),"+f"(d[36]),"+f"(d[37]),"+f"(d[38]),"+f"(d[39]),"+f"(d[40]),"+f"(d[41]),"+f"(d[42]),"+f"(d[43]),"+f"(d[44]),"+f"(d[45]),"+f"(d[46]),"+f"(d[47]),"+f"(d[48]),"+f"(d[49]),"+f"(d[50]),"+f"(d[51]),"+f"(d[52]),"+f"(d[53]),"+f"(d[54]),"+f"(d[55]),"+f"(d[56]),"+f"(d[57]),"+f"(d[58]),"+f"(d[59]),"+f"(d[60]),"+f"(d[61]),"+f"(d[62]),"+f"(d[63]),"+f"(d[64]),"+f"(d[65]),"+f"(d[66]),"+f"(d[67]),"+f"(d[68]),"+f"(d[69]),"+f"(d[70]),"+f"(d[71]),"+f"(d[72]),"+f"(d[73]),"+f"(d[74]),"+f"(d[75]),"+f"(d[76]),"+f"(d[77]),"+f"(d[78]),"+f"(d[79]),"+f"(d[80]),"+f"(d[81]),"+f"(d[82]),"+f"(d[83]),"+f"(d[84]),"+f"(d[85]),"+f"(d[86]),"+f"(d[87]),"+f"(d[88]),"+f"(d[89]),"+f"(d[90]),"+f"(d[91]),"+f"(d[92]),"+f"(d[93]),"+f"(d[94]),"+f"(d[95])
   : "l"(da), "l"(db), "r"(scale_d), "n"(TB));
}
template<int TB>
__device__ __forceinline__ void wgmma_n160(float (&d)[80], uint64_t da, uint64_t db, int scale_d) {
  asm volatile("{\n.reg .pred p;\nsetp.ne.b32 p, %82, 0;\n"
   "wgmma.mma_async.sync.aligned.m64n160k16.f32.bf16.bf16 {%0,%1,%2,%3,%4,%5,%6,%7,%8,%9,%10,%11,%12,%13,%14,%15,%16,%17,%18,%19,%20,%21,%22,%23,%24,%25,%26,%27,%28,%29,%30,%31,%32,%33,%34,%35,%36,%37,%38,%39,%40,%41,%42,%43,%44,%45,%46,%47,%48,%49,%50,%51,%52,%53,%54,%55,%56,%57,%58,%59,%60,%61,%62,%63,%64,%65,%66,%67,%68,%69,%70,%71,%72,%73,%74,%75,%76,%77,%78,%79}, %80, %81, p, 1, 1, 0, %83;\n}"
   : "+f"(d[0]),"+f"(d[1]),"+f"(d[2]),"+f"(d[3]),"+f"(d[4]),"+f"(d[5]),"+f"(d[6]),"+f"(d[7]),"+f"(d[8]),"+f"(d[9]),"+f"(d[10]),"+f"(d[11]),"+f"(d[12]),"+f"(d[13]),"+f"(d[14]),"+f"(d[15]),"+f"(d[16]),"+f"(d[17]),"+f"(d[18]),"+f"(d[19]),"+f"(d[20]),"+f"(d[21]),"+f"(d[22]),"+f"(d[23]),"+f"(d[24]),"+f"(d[25]),"+f"(d[26]),"+f"(d[27]),"+f"(d[28]),"+f"(d[29]),"+f"(d[30]),"+f"(d[31]),"+f"(d[32]),"+f"(d[33]),"+f"(d[34]),"+f"(d[35]),"+f"(d[36]),"+f"(d[37]),"+f"(d[38]),"+f"(d[39]),"+f"(d[40]),"+f"(d[41]),"+f"(d[42]),"+f"(d[43]),"+f"(d[44]),"+f"(d[45]),"+f"(d[46]),"+f"(d[47]),"+f"(d[48]),"+f"(d[49]),"+f"(d[50]),"+f"(d[51]),"+f"(d[52]),"+f"(d[53]),"+f"(d[54]),"+f"(d[55]),"+f"(d[56]),"+f"(d[57]),"+f"(d[58]),"+f"(d[59]),"+f"(d[60]),"+f"(d[61]),"+f"(d[62]),"+f"(d[63]),"+f"(d[64]),"+f"(d[65]),"+f"(d[66]),"+f"(d[67]),"+f"(d[68]),"+f"(d[69]),"+f"(d[70]),"+f"(d[71]),"+f"(d[72]),"+f"(d[73]),"+f"(d[74]),"+f"(d[75]),"+f"(d[76]),"+f"(d[77]),"+f"(d[78]),"+f"(d[79])
   : "l"(da), "l"(db), "r"(scale_d), "n"(TB));
}
template<int TB>
__device__ __forceinline__ void wgmma_n96(float (&d)[48], uint64_t da, uint64_t db, int scale_d) {
  asm volatile("{\n.reg .pred p;\nsetp.ne.b32 p, %50, 0;\n"
   "wgmma.mma_async.sync.aligned.m64n96k16.f32.bf16.bf16 {%0,%1,%2,%3,%4,%5,%6,%7,%8,%9,%10,%11,%12,%13,%14,%15,%16,%17,%18,%19,%20,%21,%22,%23,%24,%25,%26,%27,%28,%29,%30,%31,%32,%33,%34,%35,%36,%37,%38,%39,%40,%41,%42,%43,%44,%45,%46,%47}, %48, %49, p, 1, 1, 0, %51;\n}"
   : "+f"(d[0]),"+f"(d[1]),"+f"(d[2]),"+f"(d[3]),"+f"(d[4]),"+f"(d[5]),"+f"(d[6]),"+f"(d[7]),"+f"(d[8]),"+f"(d[9]),"+f"(d[10]),"+f"(d[11]),"+f"(d[12]),"+f"(d[13]),"+f"(d[14]),"+f"(d[15]),"+f"(d[16]),"+f"(d[17]),"+f"(d[18]),"+f"(d[19]),"+f"(d[20]),"+f"(d[21]),"+f"(d[22]),"+f"(d[23]),"+f"(d[24]),"+f"(d[25]),"+f"(d[26]),"+f"(d[27]),"+f"(d[28]),"+f"(d[29]),"+f"(d[30]),"+f"(d[31]),"+f"(d[32]),"+f"(d[33]),"+f"(d[34]),"+f"(d[35]),"+f"(d[36]),"+f"(d[37]),"+f"(d[38]),"+f"(d[39]),"+f"(d[40]),"+f"(d[41]),"+f"(d[42]),"+f"(d[43]),"+f"(d[44]),"+f"(d[45]),"+f"(d[46]),"+f"(d[47])
   : "l"(da), "l"(db), "r"(scale_d), "n"(TB));
}

template<int N, int TB>
__device__ __forceinline__ void wgmma_n(float (&d)[N / 2], uint64_t da, uint64_t db, int scale_d) {
  if constexpr (N == 192) wgmma_n192<TB>(d, da, db, scale_d);
  else if constexpr (N == 160) wgmma_n160<TB>(d, da, db, scale_d);
  else wgmma_n96<TB>(d, da, db, scale_d);
}

template<int R>
__device__ __forceinline__ void pin(float (&acc)[2][R]) {
  #pragma unroll
  for (int mi = 0; mi < 2; mi++)
    #pragma unroll
    for (int i = 0; i < R; i++) asm volatile("" : "+f"(acc[mi][i]) :: "memory");
}

template<int R>
__device__ __forceinline__ void zero(float (&acc)[2][R]) {
  #pragma unroll
  for (int i = 0; i < R; i++) { acc[0][i] = 0.f; acc[1][i] = 0.f; }
}

template<int N, int TB, bool CONT>
__device__ __forceinline__ void mainloop(float (&acc)[2][N / 2], uint32_t sbase, uint32_t stage_bytes, int g0, int nk, int total,
                                         int ord_bar, bool drain, int mswap) {
  const uint32_t full0 = sbase + BAR_OFF, empty0 = full0 + 8 * STAGES, ring = sbase + RING_OFF;
  const int t = threadIdx.x & 127;
  const bool rel = t < 2;
  const uint64_t da0 = make_desc(ring + mswap * 8192, 16, 1024), da1 = make_desc(ring + (mswap ^ 1) * 8192, 16, 1024);
  const uint64_t db0 = N == 96 ? make_desc(ring + A_BYTES, 4096, 512, 2) : TB ? make_desc(ring + A_BYTES, 8192, 1024) : make_desc(ring + A_BYTES, 16, 1024);
  if (!CONT) pin(acc);
  #pragma unroll 1
  for (int i = 0; i < nk; i++) {
    const int g = g0 + i;
    const int s = g & (STAGES - 1);
    const uint64_t so = (uint64_t)(s * (stage_bytes >> 4));
    mbar_wait(full0 + 8 * s, (g / STAGES) & 1);
    if (g < 32) TS(4 + (g >> 4), g & 15);
    wgmma_fence();
    #pragma unroll
    for (int k = 0; k < 4; k++) {
      const uint64_t db = db0 + so + (N == 96 ? k * 64 : TB ? k * 128 : k * 2);
      wgmma_n<N, TB>(acc[0], da0 + so + k * 2, db, 1);
      wgmma_n<N, TB>(acc[1], da1 + so + k * 2, db, 1);
    }
    wgmma_commit();
    if (ord_bar != 0 && i == nk - 1) asm volatile("bar.arrive %0, 256;" :: "r"(ord_bar) : "memory");
    wgmma_wait<1>();
    if (rel && (CONT || i > 0) && g - 1 + STAGES <= total) mbar_arrive_cluster(empty0 + 8 * ((g - 1) & (STAGES - 1)), t);
  }
  if (drain) {
    wgmma_wait<0>();
    const int g = g0 + nk - 1;
    if (rel && g + STAGES <= total) mbar_arrive_cluster(empty0 + 8 * (g & (STAGES - 1)), t);
  }
}

__device__ __forceinline__ void publish(unsigned* flag, unsigned epoch) {
  bulk_commit();
  bulk_wait_all();
  st_release(flag, epoch);
}

__device__ __forceinline__ float sum8(uint4 v) {
  return ((bf_lo(v.x) + bf_hi(v.x)) + (bf_lo(v.y) + bf_hi(v.y))) + ((bf_lo(v.z) + bf_hi(v.z)) + (bf_lo(v.w) + bf_hi(v.w)));
}
__device__ __forceinline__ float oct_sum(float v) {
  v += __shfl_xor_sync(0xffffffffu, v, 1); v += __shfl_xor_sync(0xffffffffu, v, 2); v += __shfl_xor_sync(0xffffffffu, v, 4);
  return v;
}

__device__ __forceinline__ void colsum_part(const uint4 (&cv)[4], int rb, int col, float* red, unsigned epoch) {
  const int t = threadIdx.x & 127, cg = t % 12, rg = min(t / 12, 9), tc = min(t, 95);
  *reinterpret_cast<float4*>(red + rg * 96 + cg * 8) = make_float4(
      (bf_lo(cv[0].x) + bf_lo(cv[1].x)) + (bf_lo(cv[2].x) + bf_lo(cv[3].x)), (bf_hi(cv[0].x) + bf_hi(cv[1].x)) + (bf_hi(cv[2].x) + bf_hi(cv[3].x)),
      (bf_lo(cv[0].y) + bf_lo(cv[1].y)) + (bf_lo(cv[2].y) + bf_lo(cv[3].y)), (bf_hi(cv[0].y) + bf_hi(cv[1].y)) + (bf_hi(cv[2].y) + bf_hi(cv[3].y)));
  *reinterpret_cast<float4*>(red + rg * 96 + cg * 8 + 4) = make_float4(
      (bf_lo(cv[0].z) + bf_lo(cv[1].z)) + (bf_lo(cv[2].z) + bf_lo(cv[3].z)), (bf_hi(cv[0].z) + bf_hi(cv[1].z)) + (bf_hi(cv[2].z) + bf_hi(cv[3].z)),
      (bf_lo(cv[0].w) + bf_lo(cv[1].w)) + (bf_lo(cv[2].w) + bf_lo(cv[3].w)), (bf_hi(cv[0].w) + bf_hi(cv[1].w)) + (bf_hi(cv[2].w) + bf_hi(cv[3].w)));
  bar_sync<BAR_WG2>(128);
  float c = 0.f;
  #pragma unroll
  for (int i = 0; i < 10; i++) c += red[i * 96 + tc];
  st_vol2(&g_csum[rb * FF + col + tc], __float_as_uint(c), epoch);
}

__device__ __forceinline__ void stats_prologue(const bf16* __restrict__ x, const bf16* __restrict__ win, const bf16* __restrict__ wdre,
                                               const bf16* __restrict__ wdim, int rb, int c8, float* red, unsigned epoch) {
  const int t = threadIdx.x & 127, l = t & 31, cta = blockIdx.x;
  const int cg = t % 12, rg = min(t / 12, 9);
  #pragma unroll 1
  for (int p = 0; p < 2; p++) {
    const int wr = cta * 10 + min(t >> 3, 9);
    const bf16* src = p == 0 ? x + (size_t)(cta * 16 + (t >> 3)) * DM : wr < DM ? wdre + (size_t)wr * DM : wdim + (size_t)(wr - DM) * DM;
    const int col = (1 - p) * FH + c8 * 96;
    uint4 rv[10], cv[4];
    #pragma unroll
    for (int j = 0; j < 10; j++) rv[j] = __ldg(reinterpret_cast<const uint4*>(src) + (l & 7) + 8 * j);
    #pragma unroll
    for (int j = 0; j < 4; j++) cv[j] = __ldg(reinterpret_cast<const uint4*>(win + (size_t)(rb * 40 + rg * 4 + j) * FF + col) + cg);
    float s = 0.f;
    #pragma unroll
    for (int j = 0; j < 10; j++) s += sum8(rv[j]);
    s = oct_sum(s);
    if (p == 0) {
      const float mean = s * (1.f / DM);
      float q = 0.f;
      #pragma unroll
      for (int j = 0; j < 10; j++) {
        const uint32_t u[4] = {rv[j].x, rv[j].y, rv[j].z, rv[j].w};
        #pragma unroll
        for (int c = 0; c < 4; c++) { const float d0 = bf_lo(u[c]) - mean, d1 = bf_hi(u[c]) - mean; q = fmaf(d0, d0, q); q = fmaf(d1, d1, q); }
      }
      const float rstd = rsqrtf(fmaf(oct_sum(q), 1.f / DM, LN_EPS));
      if ((l & 7) == 0) st_vol4(&g_xstat[cta * 16 + (t >> 3)], __float_as_uint(rstd), __float_as_uint(-mean * rstd), epoch, 0u);
    } else if ((l & 7) == 0) {
      st_vol2(&g_csum[16 * FF + wr], __float_as_uint(s), epoch);
    }
    colsum_part(cv, rb, col, red + p * 960, epoch);
  }
}

__device__ __forceinline__ void gather_sums(const uint2* src, int npart, int ncol, float* dst, unsigned epoch) {
  const int t = threadIdx.x & 127;
  #pragma unroll 1
  for (int c = t; c < ncol; c += 128) {
    float acc = 0.f;
    unsigned it = 0;
    #pragma unroll 1
    for (int p0 = 0; p0 < npart; p0 += 8) {
      while (true) {
        uint2 u[8];
        #pragma unroll
        for (int i = 0; i < 8; i++) u[i] = ld_vol2(src + (size_t)min(p0 + i, npart - 1) * FF + c);
        bool ok = true;
        float a = 0.f;
        #pragma unroll
        for (int i = 0; i < 8; i++) { ok = ok && u[i].y == epoch; a += p0 + i < npart ? __uint_as_float(u[i].x) : 0.f; }
        if (ok) { acc += a; break; }
        __nanosleep(POLL_NS);
        if ((++it & 4095u) == 0 && timed_out()) break;
      }
    }
    dst[c] = acc;
  }
}

__device__ __forceinline__ void fold_pack(const float* a, float2 s0, float2 s1, float2 c0, float2 c1, uint32_t (&r)[4]) {
  r[0] = pack_bf16(fmaf(a[0], s0.x, s0.y * c0.x), fmaf(a[1], s0.x, s0.y * c0.y));
  r[1] = pack_bf16(fmaf(a[2], s1.x, s1.y * c0.x), fmaf(a[3], s1.x, s1.y * c0.y));
  r[2] = pack_bf16(fmaf(a[4], s0.x, s0.y * c1.x), fmaf(a[5], s0.x, s0.y * c1.y));
  r[3] = pack_bf16(fmaf(a[6], s1.x, s1.y * c1.x), fmaf(a[7], s1.x, s1.y * c1.y));
}

__device__ __forceinline__ void gelu_rows(uint32_t rbase, int n4, int wide, int sw, float& sum, float& sq) {
  #pragma unroll 1
  for (int c4 = 0; c4 < n4; c4++) {
    const uint32_t ab = rbase + (wide ? (c4 >> 1) * 8192 : c4 * 8192);
    const int cb = wide ? (c4 & 1) * 4 : 0;
    uint4 v[4];
    #pragma unroll
    for (int i = 0; i < 4; i++) v[i] = lds128(ab + (((cb + i) ^ sw) << 4));
    float s2 = 0.f, q2 = 0.f;
    #pragma unroll
    for (int i = 0; i < 4; i++) {
      const uint32_t u[4] = {v[i].x, v[i].y, v[i].z, v[i].w};
      uint32_t o[4];
      #pragma unroll
      for (int e = 0; e < 4; e++) {
        const float g0 = gelu_tanh(bf_lo(u[e])), g1 = gelu_tanh(bf_hi(u[e]));
        o[e] = pack_bf16(g0, g1);
        sum += g0; s2 += g1; sq = fmaf(g0, g0, sq); q2 = fmaf(g1, g1, q2);
      }
      v[i] = make_uint4(o[0], o[1], o[2], o[3]);
    }
    sum += s2; sq += q2;
    #pragma unroll
    for (int i = 0; i < 4; i++) sts128(ab + (((cb + i) ^ sw) << 4), v[i].x, v[i].y, v[i].z, v[i].w);
  }
}

__global__ void __cluster_dims__(2, 1, 1) __launch_bounds__(384, 1)
fused_kernel(const __grid_constant__ Maps maps, const bf16* __restrict__ x, const bf16* __restrict__ win,
             const bf16* __restrict__ bsp, const bf16* __restrict__ wdre, const bf16* __restrict__ wdim) {
  const uint32_t sbase = smem_u32(smem);
  const uint32_t full0 = sbase + BAR_OFF, empty0 = full0 + 8 * STAGES, dep0 = empty0 + 8 * STAGES, ring = sbase + RING_OFF;
  const int tid = threadIdx.x, wg = tid >> 7;
  const int rank = blockIdx.x & 1, grp = (blockIdx.x >> 1) & 1, q = blockIdx.x >> 2;
  const int rb = q >> 1, ct = (q & 1) * 2 + rank, c8 = grp * 4 + ct;
  const int total = grp == 0 ? KB_A : KB_B;
  const uint32_t stage_bytes = grp == 0 ? STAGE_A : STAGE_B;

  if (tid == 0) {
    TS(0, 0);
    for (int s = 0; s < STAGES; s++) { mbar_init(full0 + 8 * s, 2); mbar_init(empty0 + 8 * s, 2); mbar_init(dep0 + 8 * s, 1); }
    *reinterpret_cast<unsigned long long*>(smem + DEADLINE_OFF) = gtime() + 200000000ull;
    asm volatile("fence.mbarrier_init.release.cluster;" ::: "memory");
  }
  __syncthreads();
  asm volatile("barrier.cluster.arrive.relaxed.aligned;" ::: "memory");

  if (wg == 0) {
    asm volatile("setmaxnreg.dec.sync.aligned.u32 40;");
    const int warp = tid >> 5, lane = tid & 31;
    if (warp == 0) {
      const int row = rb * 128;
      if (lane == 0) {
        TS(0, 1);
        for (int g = 0; g < STAGES; g++) {
          mbar_expect_tx(full0 + 8 * g, A_BYTES);
          tma_load_2d(ring + g * stage_bytes, &maps.m[M_X], full0 + 8 * g, g * 64, row);
          tma_load_2d(ring + g * stage_bytes + 8192, &maps.m[M_X], full0 + 8 * g, g * 64, row + 64);
        }
      }
      __syncwarp();
      asm volatile("barrier.cluster.wait.aligned;" ::: "memory");
      if (lane == 0) {
        #pragma unroll 1
        for (int g = STAGES; g < total; g++) {
          int mi, kb;
          if (g < 20) { mi = M_X; kb = g < 10 ? g : g - 10; }
          else if (grp == 0) {
            if (g < 52) { mi = M_WSP; kb = g - 20; }
            else if (g < 52 + NX) { mi = M_WSIM; kb = g - 52 + 32 - NX; }
            else { mi = M_H; kb = g - 52 - NX; }
          } else {
            if (g < 30) { mi = M_X; kb = g - 20; }
            else if (g < 62) { mi = M_WSRE; kb = g - 30; }
            else { mi = M_WSIM; kb = g - 62; }
          }
          if (mi == M_H && kb == 0) { TS(0, 3); mbar_wait(dep0 + 24, 0); fence_async_global(); TS(0, 4); }
          const int s = g & (STAGES - 1);
          mbar_wait(empty0 + 8 * s, ((g / STAGES) & 1) ^ 1);
          mbar_expect_tx(full0 + 8 * s, A_BYTES);
          tma_load_2d_mc(ring + s * stage_bytes + rank * 8192, &maps.m[mi], full0 + 8 * s, kb * 64, row + rank * 64, 3);
        }
        const int s = total & (STAGES - 1);
        mbar_wait(empty0 + 8 * s, ((total / STAGES) & 1) ^ 1);
        mbar_expect_tx(full0 + 8 * s, 20480);
        mbar_arrive(full0 + 8 * s);
        tma_load_2d(ring + s * stage_bytes, &maps.m[M_XR], full0 + 8 * s, ct * 160, row + grp * 64);
        TS(0, 5);
      }
    } else if (warp == 1) {
      if (lane == 0) {
        #pragma unroll 1
        for (int g = 0; g < total; g++) {
          int kind, mi, kb, c, dep = 0;
          uint32_t bytes = 24576;
          if (g < 10) { kind = 0; mi = M_WIN32; kb = g; c = 24 + 3 * c8; bytes = 12288; }
          else if (grp == 0) {
            if (g < 20) { kind = 0; mi = M_WIN3; kb = g - 10; c = 3 * ct; }
            else if (g < 52) { kind = 0; mi = M_Z23; kb = g - 20; c = 3 * ct; dep = g == 20 ? 1 : 0; }
            else if (g < 52 + NX) { kind = 1; mi = M_AB; kb = g - 52 + 32 - NX; c = DM + ct * 160; dep = g == 52 ? 2 : 0; }
            else { kind = 2; mi = M_WOUT; kb = g - 52 - NX; c = ct * 160; }
          } else {
            kind = 1;
            if (g < 30) { mi = g < 20 ? M_WDRE : M_WDIM; kb = g < 20 ? g - 10 : g - 20; c = ct * 160; }
            else { mi = M_AB; kb = g < 62 ? g - 30 : g - 62; c = ct * 160 + (g < 62 ? 0 : DM); dep = g == 30 ? 1 : g == 62 ? 2 : 0; }
          }
          if (kind == 1) bytes = 20480;
          if (dep) { TS(1, dep * 2 - 2); mbar_wait(dep0 + 8 * dep, 0); fence_async_global(); TS(1, dep * 2 - 1); TC(dep); }
          const int s = g & (STAGES - 1);
          const uint32_t dst = ring + s * stage_bytes + A_BYTES, fb = full0 + 8 * s;
          mbar_wait(empty0 + 8 * s, ((g / STAGES) & 1) ^ 1);
          mbar_expect_tx(fb, bytes);
          if (kind == 0) tma_load_3d(dst, &maps.m[mi], fb, 0, kb * 64, c);
          else if (kind == 1) tma_load_2d(dst, &maps.m[mi], fb, kb * 64, c);
          else {
            #pragma unroll 1
            for (int j = 0; j < 3; j++) tma_load_2d(dst + j * 8192, &maps.m[mi], fb, c + j * 64, kb * 64);
          }
        }
      }
      __syncwarp();
      asm volatile("barrier.cluster.wait.aligned;" ::: "memory");
    } else if (warp == 2) {
      asm volatile("barrier.cluster.wait.aligned;" ::: "memory");
      const unsigned epoch = (*reinterpret_cast<volatile unsigned*>(&g_done) >> 7) + 1u;
      #pragma unroll 1
      for (int d = 1; d < 4 - grp; d++) {
        const int fi = d == 3 ? F_H + rb * 4 + (lane & 3)
                     : (d == 1 && grp == 0) ? F_Z + (lane >> 1) * 8 + ct * 2 + (lane & 1)
                     : (d == 1 ? F_A : F_B) + (lane & 15) * 4 + ct;
        unsigned it = 0;
        while (!__all_sync(0xffffffffu, ld_relaxed(g_flags + fi) == epoch)) { __nanosleep(20); if ((++it & 4095u) == 0 && timed_out()) break; }
        fence_async_global();
        __syncwarp();
        if (lane == 0) mbar_arrive(dep0 + 8 * d);
      }
    } else {
      asm volatile("barrier.cluster.wait.aligned;" ::: "memory");
    }
  } else {
    asm volatile("setmaxnreg.inc.sync.aligned.u32 232;");
    const int t = tid & 127, w = t >> 5, l = t & 31;
    const uint32_t buf = ring + 4 * stage_bytes;
    const unsigned epoch = (*reinterpret_cast<volatile unsigned*>(&g_done) >> 7) + 1u;
    asm volatile("barrier.cluster.wait.aligned;" ::: "memory");
    const int rl = w * 16 + ((l >> 3) & 1) * 8 + (l & 7);
    const int gr = w * 16 + (l & 15);
    float sum = 0.f, sq = 0.f;
    float* csw = reinterpret_cast<float*>(smem + COLSUM_OFF) + (wg - 1) * 192;
    const float2* rs = reinterpret_cast<const float2*>(smem + ROWSTAT_OFF) + w * 16 + (l >> 2);
    const float2* cs = reinterpret_cast<const float2*>(csw) + (l & 3);
    if (wg == 1) {
      float acc[2][48];
      zero(acc);
      mainloop<96, 1, false>(acc, sbase, stage_bytes, 0, 10, total, BAR_ORD1, true, 0);
      pin(acc);
      TS(2, 2);
      {
        unsigned n = 0;
        uint4 v;
        while ((v = ld_vol4(&g_xstat[rb * 128 + t])).z != epoch) { __nanosleep(POLL_NS); if ((++n & 4095u) == 0 && timed_out()) break; }
        reinterpret_cast<float2*>(smem + ROWSTAT_OFF)[t] = make_float2(__uint_as_float(v.x), __uint_as_float(v.y));
      }
      gather_sums(g_csum + FH + c8 * 96, 16, 96, csw, epoch);
      bar_arrive<BAR_STATS>(256);
      bar_sync<BAR_WG1>(128);
      TS(2, 1);
      const float2 s0 = rs[0], s1 = rs[8], s2 = rs[64], s3 = rs[72];
      #pragma unroll
      for (int jj = 0; jj < 6; jj++) {
        uint32_t r[4];
        const float2 c0 = cs[jj * 8], c1 = cs[jj * 8 + 4];
        const uint32_t ad = buf + (jj >> 1) * 8192 + rl * 64 + ((((jj & 1) * 2 + (l >> 4)) ^ ((l >> 1) & 3)) << 4);
        fold_pack(&acc[0][8 * jj], s0, s1, c0, c1, r);
        stsm4(ad, r[0], r[1], r[2], r[3]);
        fold_pack(&acc[1][8 * jj], s2, s3, c0, c1, r);
        stsm4(ad + 4096, r[0], r[1], r[2], r[3]);
      }
      __syncwarp();
      TS(2, 3);
    } else {
      stats_prologue(x, win, wdre, wdim, rb, c8, reinterpret_cast<float*>(smem + (buf - sbase) + 24576), epoch);
      if (grp == 0) reinterpret_cast<float*>(smem + BIAS_OFF)[t] = __bfloat162float(bsp[rb * 128 + t]);
      TS(3, 0);
    }
    const uint32_t st_base = buf + rl * 128;
    const uint32_t st_x = ((l >> 4) ^ (l & 7)) << 4;
    if (wg == 1 || grp == 0) {
      #pragma unroll 1
      for (int it = 2 - wg; it < 3; it++) {
        if (it == 1) {
          const uint32_t rbase = wg == 1 ? buf + (l >> 4) * 4096 + gr * 64 : buf + (l >> 4) * 24576 + gr * 128;
          gelu_rows(rbase, wg == 1 ? 3 : 6, wg - 1, wg == 1 ? (l >> 1) & 3 : l & 7, sum, sq);
          TS(wg + 1, 4);
          if (wg == 2) { bar_arrive<BAR_Z1>(256); break; }
          const int row = (l >> 4) * 64 + gr;
          const float mu = sum * (1.f / 96), m2 = fmaxf(sq - sum * mu, 0.f);
          st_vol4(&g_zstat[(rb * 8 + c8) * 128 + row], __float_as_uint(mu), __float_as_uint(m2), epoch, 0u);
          uint4 v[7];
          unsigned n = 0;
          while (true) {
            bool ok = true;
            #pragma unroll
            for (int j = 0; j < 7; j++) v[j] = ld_vol4(&g_zstat[(rb * 8 + ((c8 + 1 + j) & 7)) * 128 + row]);
            #pragma unroll
            for (int j = 0; j < 7; j++) ok = ok && v[j].z == epoch;
            if (ok) break;
            __nanosleep(POLL_NS);
            if ((++n & 4095u) == 0 && timed_out()) break;
          }
          float mean = mu, var = m2;
          #pragma unroll
          for (int j = 0; j < 7; j++) { mean += __uint_as_float(v[j].x); var += __uint_as_float(v[j].y); }
          mean *= 0.125f;
          float d = (mu - mean) * (mu - mean);
          #pragma unroll
          for (int j = 0; j < 7; j++) d = fmaf(__uint_as_float(v[j].x) - mean, __uint_as_float(v[j].x) - mean, d);
          const float rstd = rsqrtf(fmaf(96.f, d, var) * (1.f / FH) + LN_EPS), off = -mean * rstd;
          TS(2, 5);
          #pragma unroll 1
          for (int c = 0; c < 3; c++) {
            uint4 z[4];
            #pragma unroll
            for (int i = 0; i < 4; i++) z[i] = lds128(rbase + c * 8192 + ((i ^ ((l >> 1) & 3)) << 4));
            #pragma unroll
            for (int i = 0; i < 4; i++)
              sts128(rbase + c * 8192 + ((i ^ ((l >> 1) & 3)) << 4),
                     pack_bf16(fmaf(bf_lo(z[i].x), rstd, off), fmaf(bf_hi(z[i].x), rstd, off)), pack_bf16(fmaf(bf_lo(z[i].y), rstd, off), fmaf(bf_hi(z[i].y), rstd, off)),
                     pack_bf16(fmaf(bf_lo(z[i].z), rstd, off), fmaf(bf_hi(z[i].z), rstd, off)), pack_bf16(fmaf(bf_lo(z[i].w), rstd, off), fmaf(bf_hi(z[i].w), rstd, off)));
          }
          fence_async_smem();
          bar_sync<BAR_WG1>(128);
          TS(2, 6);
          if (t == 0) {
            tma_store_3d(&maps.m[M_Z232], buf, 0, rb * 128, 3 * c8);
            publish(g_flags + F_Z + rb * 8 + c8, epoch);
          }
          __syncwarp();
          TS(2, 10);
          if (grp == 1) break;
          bar_arrive<BAR_BUF>(256);
        } else {
          float acc[2][96];
          zero(acc);
          if (it == 0) bar_sync<BAR_ORD1>(256); else bar_sync<BAR_ORD2>(256);
          mainloop<192, 1, false>(acc, sbase, STAGE_A, it == 0 ? 10 : 20, it == 0 ? 10 : 32, KB_A, it == 0 ? BAR_ORD2 : BAR_ORD1, true, 0);
          pin(acc);
          TS(wg + 1, it == 0 ? 2 : 7);
          if (it == 0) {
            gather_sums(g_csum + ct * 192, 16, 192, csw, epoch);
            bar_sync<BAR_STATS>(256);
            bar_sync<BAR_BUF>(256);
            const float2 s0 = rs[0], s1 = rs[8], s2 = rs[64], s3 = rs[72];
            #pragma unroll
            for (int jj = 0; jj < 12; jj++) {
              uint32_t r[4];
              const float2 c0 = cs[jj * 8], c1 = cs[jj * 8 + 4];
              const uint32_t ad = st_base + (jj >> 2) * 8192 + (st_x ^ ((jj & 3) << 5));
              fold_pack(&acc[0][8 * jj], s0, s1, c0, c1, r);
              stsm4(ad, r[0], r[1], r[2], r[3]);
              fold_pack(&acc[1][8 * jj], s2, s3, c0, c1, r);
              stsm4(ad + 24576, r[0], r[1], r[2], r[3]);
            }
            __syncwarp();
            TS(3, 3);
          } else {
            const float* bias = reinterpret_cast<const float*>(smem + BIAS_OFF) + w * 16 + (l >> 2);
            bar_sync<BAR_Z1>(256);
            #pragma unroll
            for (int mi = 0; mi < 2; mi++) {
              const float b0 = bias[mi * 64], b1 = bias[mi * 64 + 8];
              #pragma unroll
              for (int j4 = 0; j4 < 3; j4++) {
                uint32_t z[4][4];
                #pragma unroll
                for (int i = 0; i < 4; i++) ldsm4(st_base + mi * 24576 + j4 * 8192 + (st_x ^ (i << 5)), z[i][0], z[i][1], z[i][2], z[i][3]);
                #pragma unroll
                for (int i = 0; i < 4; i++) {
                  const float* a = &acc[mi][8 * (j4 * 4 + i)];
                  stsm4(st_base + mi * 24576 + j4 * 8192 + (st_x ^ (i << 5)),
                        hmul2_bf16(z[i][0], pack_bf16(a[0] + b0, a[1] + b0)), hmul2_bf16(z[i][1], pack_bf16(a[2] + b1, a[3] + b1)),
                        hmul2_bf16(z[i][2], pack_bf16(a[4] + b0, a[5] + b0)), hmul2_bf16(z[i][3], pack_bf16(a[6] + b1, a[7] + b1)));
                }
              }
            }
            fence_async_smem();
            bar_sync<BAR_WG1>(128);
            TS(2, 8);
            if (t == 0) {
              tma_store_3d(&maps.m[M_H3], buf, 0, rb * 128, 3 * ct);
              tma_store_3d(&maps.m[M_H3], buf + 24576, 0, rb * 128 + 64, 3 * ct);
              publish(g_flags + F_H + rb * 4 + ct, epoch);
            }
            __syncwarp();
            TS(2, 9);
          }
        }
      }
    }
    if (grp == 1 || wg == 2) {
      float acc[2][80];
      #pragma unroll 1
      for (int it = 1 - grp; it < 2; it++) {
        zero(acc);
        if (wg == 2) bar_sync<BAR_ORD1>(256); else bar_sync<BAR_ORD2>(256);
        mainloop<160, 0, false>(acc, sbase, stage_bytes, it == 0 ? (wg == 2 ? 10 : 20) : grp == 0 ? 52 : 30, it == 0 ? 10 : grp == 0 ? NX : 64 - NX,
                                total, it == 1 ? 0 : wg == 1 ? BAR_ORD1 : BAR_ORD2, grp == 1, it & grp);
        if (it == 1) break;
        pin(acc);
        TS(wg + 1, wg == 1 ? 7 : 2);
        gather_sums(g_csum + 16 * FF + (2 - wg) * DM + ct * 160, 1, 160, csw, epoch);
        if (wg == 1) bar_sync<BAR_BUF>(256); else bar_sync<BAR_STATS>(256);
        const float sign = wg == 1 ? -1.f : 1.f;
        const uint32_t tb = buf + 24576 + ((l >> 4) * 8 + (l & 7)) * 128 + (((w * 2 + ((l >> 3) & 1)) ^ (l & 7)) << 4);
        float2 s0 = rs[0], s1 = rs[8], s2 = rs[64], s3 = rs[72];
        s0.x *= sign; s0.y *= sign; s1.x *= sign; s1.y *= sign; s2.x *= sign; s2.y *= sign; s3.x *= sign; s3.y *= sign;
        #pragma unroll
        for (int jj = 0; jj < 10; jj++) {
          uint32_t r[4];
          const float2 c0 = cs[jj * 8], c1 = cs[jj * 8 + 4];
          fold_pack(&acc[0][8 * jj], s0, s1, c0, c1, r);
          stsm4_t(tb + jj * 2048, r[0], r[1], r[2], r[3]);
          fold_pack(&acc[1][8 * jj], s2, s3, c0, c1, r);
          stsm4_t(tb + 20480 + jj * 2048, r[0], r[1], r[2], r[3]);
        }
        fence_async_smem();
        if (wg == 1) bar_sync<BAR_WG1>(128); else bar_sync<BAR_WG2>(128);
        TS(wg + 1, wg == 1 ? 8 : 6);
        if (t == 0) {
          tma_store_2d(&maps.m[M_AB], buf + 24576, rb * 128, (2 - wg) * DM + ct * 160);
          tma_store_2d(&maps.m[M_AB], buf + 24576 + 20480, rb * 128 + 64, (2 - wg) * DM + ct * 160);
          publish(g_flags + (wg == 2 ? F_A : F_B) + rb * 4 + ct, epoch);
        }
        __syncwarp();
        TS(wg + 1, wg == 1 ? 9 : 10);
        if (wg == 1) return;
        bar_arrive<BAR_BUF>(256);
      }
      if (grp == 0) mainloop<160, 1, true>(acc, sbase, STAGE_A, 52 + NX, 12, KB_A, 0, true, 0);
      pin(acc);
      TS(3, 12);
      uint4* dst = g_part + (size_t)blockIdx.x * 27 * 128 + t;
      const uint4* src = g_part + (size_t)(blockIdx.x ^ 2) * 27 * 128 + t;
      #pragma unroll
      for (int i = 0; i < 27; i++)
        st_vol4(dst + i * 128, __float_as_uint(acc[1][3 * i]), __float_as_uint(acc[1][3 * i + 1]),
                __float_as_uint(i < 26 ? acc[1][3 * i + 2] : 0.f), epoch);
      TS(3, 13);
      const uint32_t slab = ring + (total & (STAGES - 1)) * stage_bytes + w * (16 * 320);
      const uint32_t addr = slab + (((l >> 3) & 1) * 8 + (l & 7)) * 320 + (l >> 4) * 16;
      mbar_wait(full0 + 8 * (total & (STAGES - 1)), (total / STAGES) & 1);
      #pragma unroll
      for (int jj = 0; jj < 10; jj++) {
        uint32_t z0, z1, z2, z3;
        ldsm4(addr + jj * 32, z0, z1, z2, z3);
        float* a = &acc[0][8 * jj];
        a[0] += bf_lo(z0); a[1] += bf_hi(z0); a[2] += bf_lo(z1); a[3] += bf_hi(z1);
        a[4] += bf_lo(z2); a[5] += bf_hi(z2); a[6] += bf_lo(z3); a[7] += bf_hi(z3);
      }
      {
        unsigned n = 0;
        while (ld_vol4(src + 26 * 128).w != epoch) { __nanosleep(POLL_NS); if ((++n & 4095u) == 0 && timed_out()) break; }
        #pragma unroll
        for (int gq = 0; gq < 3; gq++) {
          uint4 v[9];
          while (true) {
            bool ok = true;
            #pragma unroll
            for (int i = 0; i < 9; i++) v[i] = ld_vol4(src + (gq * 9 + i) * 128);
            #pragma unroll
            for (int i = 0; i < 9; i++) ok = ok && (v[i].w == epoch);
            if (ok) break;
            if ((++n & 4095u) == 0 && timed_out()) break;
          }
          #pragma unroll
          for (int i = 0; i < 9; i++) {
            const int e = (gq * 9 + i) * 3;
            acc[0][e] += __uint_as_float(v[i].x);
            acc[0][e + 1] += __uint_as_float(v[i].y);
            if (e + 2 < 80) acc[0][e + 2] += __uint_as_float(v[i].z);
          }
        }
      }
      TS(3, 14);
      #pragma unroll
      for (int jj = 0; jj < 10; jj++) {
        const float* a = &acc[0][8 * jj];
        stsm4(addr + jj * 32, pack_bf16(a[0], a[1]), pack_bf16(a[2], a[3]), pack_bf16(a[4], a[5]), pack_bf16(a[6], a[7]));
      }
      fence_async_smem();
      __syncwarp();
      if (l == 0) {
        tma_store_2d(&maps.m[M_OUT], slab, ct * 160, rb * 128 + grp * 64 + w * 16);
        bulk_commit();
        bulk_wait_read();
        if (w == 0) atomicAdd(&g_done, 1u);
      }
      TS(3, 15);
    }
  }
}

typedef CUresult (*EncodeFn)(CUtensorMap*, CUtensorMapDataType, cuuint32_t, void*, const cuuint64_t*, const cuuint64_t*,
                             const cuuint32_t*, const cuuint32_t*, CUtensorMapInterleave, CUtensorMapSwizzle,
                             CUtensorMapL2promotion, CUtensorMapFloatOOBfill);

void make2d(EncodeFn enc, CUtensorMap* m, const void* p, uint64_t cols, uint64_t rows, uint32_t bc, uint32_t br, bool swz = true) {
  cuuint64_t gd[2] = {cols, rows}, gs[1] = {cols * 2};
  cuuint32_t bd[2] = {bc, br}, es[2] = {1, 1};
  enc(m, CU_TENSOR_MAP_DATA_TYPE_BFLOAT16, 2, const_cast<void*>(p), gd, gs, bd, es, CU_TENSOR_MAP_INTERLEAVE_NONE,
      swz ? CU_TENSOR_MAP_SWIZZLE_128B : CU_TENSOR_MAP_SWIZZLE_NONE, CU_TENSOR_MAP_L2_PROMOTION_L2_256B, CU_TENSOR_MAP_FLOAT_OOB_FILL_NONE);
}
void make3d(EncodeFn enc, CUtensorMap* m, const void* p, uint64_t cols, uint64_t rows, uint32_t cw = 64, uint32_t br = 64) {
  cuuint64_t gd[3] = {cw, rows, cols / cw}, gs[2] = {cols * 2, cw * 2};
  cuuint32_t bd[3] = {cw, br, 3}, es[3] = {1, 1, 1};
  enc(m, CU_TENSOR_MAP_DATA_TYPE_BFLOAT16, 3, const_cast<void*>(p), gd, gs, bd, es, CU_TENSOR_MAP_INTERLEAVE_NONE,
      cw == 64 ? CU_TENSOR_MAP_SWIZZLE_128B : CU_TENSOR_MAP_SWIZZLE_64B, CU_TENSOR_MAP_L2_PROMOTION_L2_256B, CU_TENSOR_MAP_FLOAT_OOB_FILL_NONE);
}

}

extern "C" void kernel_launch(void* const* d_in, const int* in_sizes, int n_in, void* d_out, int out_size) {
  const bf16* x = (const bf16*)d_in[0];
  const bf16* wsre = (const bf16*)d_in[1];
  const bf16* wsim = (const bf16*)d_in[2];
  const bf16* wdre = (const bf16*)d_in[3];
  const bf16* wdim = (const bf16*)d_in[4];
  const bf16* win = (const bf16*)d_in[6];
  const bf16* wsp = (const bf16*)d_in[7];
  const bf16* bsp = (const bf16*)d_in[8];
  const bf16* wout = (const bf16*)d_in[9];

  void* fn = nullptr;
  cudaDriverEntryPointQueryResult qr;
  cudaGetDriverEntryPoint("cuTensorMapEncodeTiled", &fn, cudaEnableDefault, &qr);
  EncodeFn enc = (EncodeFn)fn;
  void *abT, *z2, *h;
  cudaGetSymbolAddress(&abT, g_abT);
  cudaGetSymbolAddress(&z2, g_z2);
  cudaGetSymbolAddress(&h, g_h);

  Maps maps;
  make2d(enc, &maps.m[M_X], x, DM, SEQ, 64, 64);
  make2d(enc, &maps.m[M_XR], x, DM, SEQ, 160, 64, false);
  make3d(enc, &maps.m[M_WIN32], win, FF, DM, 32, 64);
  make3d(enc, &maps.m[M_Z232], z2, FH, SEQ, 32, 128);
  make2d(enc, &maps.m[M_WSRE], wsre, SEQ, SEQ, 64, 64);
  make2d(enc, &maps.m[M_WSIM], wsim, SEQ, SEQ, 64, 64);
  make2d(enc, &maps.m[M_WSP], wsp, SEQ, SEQ, 64, 64);
  make2d(enc, &maps.m[M_H], h, FH, SEQ, 64, 64);
  make3d(enc, &maps.m[M_H3], h, FH, SEQ);
  make3d(enc, &maps.m[M_WIN3], win, FF, DM);
  make3d(enc, &maps.m[M_Z23], z2, FH, SEQ);
  make2d(enc, &maps.m[M_WDRE], wdre, DM, DM, 64, 160);
  make2d(enc, &maps.m[M_WDIM], wdim, DM, DM, 64, 160);
  make2d(enc, &maps.m[M_AB], abT, SEQ, 2 * DM, 64, 160);
  make2d(enc, &maps.m[M_WOUT], wout, DM, FH, 64, 64);
  make2d(enc, &maps.m[M_OUT], d_out, DM, SEQ, 160, 16, false);

  cudaFuncSetAttribute(fused_kernel, cudaFuncAttributeMaxDynamicSharedMemorySize, SMEM_BYTES);
  fused_kernel<<<128, 384, SMEM_BYTES>>>(maps, x, win, bsp, wdre, wdim);
}
```

```cpp
#include <cuda_runtime.h>
#include <cuda_bf16.h>
#include <cuda.h>
#include <stdint.h>

namespace {

typedef __nv_bfloat16 bf16;

constexpr int SEQ = 2048, DM = 640, FF = 1536, FH = 768;
#define NXV 11
constexpr int NX = NXV;
constexpr int STAGES = 4;
constexpr int A_BYTES = 16384;
constexpr int ROWSTAT_OFF = 0;
constexpr int COLSUM_OFF = 1024;
constexpr int BIAS_OFF = 2560;
constexpr int BAR_OFF = 3072;
constexpr int RING_OFF = 4096;
constexpr int STAGE_A = 40960, STAGE_B = 36864;
constexpr int SMEM_BYTES = RING_OFF + 4 * STAGE_A + 49152;
constexpr int KB_A = 20 + 32 + NX + 12;
constexpr int KB_B = 30 + 64 - NX;
constexpr float LN_EPS = 1e-5f;
constexpr unsigned POLL_LIMIT = 100000;
#define POLL_NS 100
#define PF_NS 150

constexpr int BAR_ORD1 = 1, BAR_ORD2 = 2, BAR_WG1 = 3, BAR_WG2 = 4, BAR_STATS = 5, BAR_BUF = 6, BAR_Z1 = 7;

enum { M_X, M_XR, M_WIN32, M_WSRE, M_WSIM, M_WSP, M_H, M_WIN3, M_Z23, M_WDRE, M_WDIM, M_AB, M_WOUT, M_OUT, M_COUNT };
struct Maps { CUtensorMap m[M_COUNT]; };

__device__ __align__(1024) bf16 g_abT[2 * DM * SEQ];
__device__ __align__(1024) bf16 g_z2[SEQ * FH];
__device__ __align__(1024) bf16 g_h[SEQ * FH];
__device__ __align__(16) uint4 g_xstat[SEQ];
__device__ __align__(16) uint2 g_csum[16 * FF + 2 * DM];
__device__ __align__(16) uint4 g_zstat[128 * 128];
__device__ __align__(16) uint4 g_part[128 * 27 * 128];
__device__ unsigned g_flags[4 * 128];
constexpr int F_A = 0, F_B = 128, F_H = 256, F_Z = 384;
__device__ unsigned g_done;
#define TS(role, ev)
#define TC(i)

extern __shared__ __align__(1024) uint8_t smem[];

__device__ __forceinline__ uint32_t smem_u32(const void* p) { return (uint32_t)__cvta_generic_to_shared(p); }
__device__ __forceinline__ void mbar_init(uint32_t bar, uint32_t cnt) { asm volatile("mbarrier.init.shared::cta.b64 [%0], %1;" :: "r"(bar), "r"(cnt)); }
__device__ __forceinline__ void mbar_expect_tx(uint32_t bar, uint32_t bytes) { asm volatile("mbarrier.arrive.expect_tx.shared::cta.b64 _, [%0], %1;" :: "r"(bar), "r"(bytes) : "memory"); }
__device__ __forceinline__ void mbar_arrive(uint32_t bar) { asm volatile("mbarrier.arrive.shared::cta.b64 _, [%0];" :: "r"(bar) : "memory"); }
__device__ __forceinline__ void mbar_arrive_cluster(uint32_t bar, uint32_t cta) {
  asm volatile("{\n.reg .b32 ra;\nmapa.shared::cluster.u32 ra, %0, %1;\nmbarrier.arrive.shared::cluster.b64 _, [ra];\n}" :: "r"(bar), "r"(cta) : "memory");
}
__device__ __forceinline__ void mbar_wait(uint32_t bar, uint32_t parity) {
  asm volatile("{\n.reg .pred p;\n.reg .u32 n;\nmov.u32 n, 0;\n"
               "LW: mbarrier.try_wait.parity.shared::cta.b64 p, [%0], %1, 2000;\n@p bra LD;\n"
               "add.u32 n, n, 1;\nsetp.lt.u32 p, n, 20000;\n@p bra LW;\nLD:\n}" :: "r"(bar), "r"(parity) : "memory");
}
__device__ __forceinline__ void tma_load_2d(uint32_t dst, const CUtensorMap* map, uint32_t bar, int c0, int c1) {
  asm volatile("cp.async.bulk.tensor.2d.shared::cluster.global.mbarrier::complete_tx::bytes [%0], [%1, {%3, %4}], [%2];"
    :: "r"(dst), "l"((uint64_t)map), "r"(bar), "r"(c0), "r"(c1) : "memory");
}
__device__ __forceinline__ void tma_load_3d(uint32_t dst, const CUtensorMap* map, uint32_t bar, int c0, int c1, int c2) {
  asm volatile("cp.async.bulk.tensor.3d.shared::cluster.global.mbarrier::complete_tx::bytes [%0], [%1, {%3, %4, %5}], [%2];"
    :: "r"(dst), "l"((uint64_t)map), "r"(bar), "r"(c0), "r"(c1), "r"(c2) : "memory");
}
__device__ __forceinline__ void tma_load_2d_mc(uint32_t dst, const CUtensorMap* map, uint32_t bar, int c0, int c1, uint16_t mask) {
  asm volatile("cp.async.bulk.tensor.2d.shared::cluster.global.mbarrier::complete_tx::bytes.multicast::cluster [%0], [%1, {%3, %4}], [%2], %5;"
    :: "r"(dst), "l"((uint64_t)map), "r"(bar), "r"(c0), "r"(c1), "h"(mask) : "memory");
}
__device__ __forceinline__ void tma_store_2d(const CUtensorMap* map, uint32_t src, int c0, int c1) {
  asm volatile("cp.async.bulk.tensor.2d.global.shared::cta.bulk_group [%0, {%2, %3}], [%1];"
    :: "l"((uint64_t)map), "r"(src), "r"(c0), "r"(c1) : "memory");
}
__device__ __forceinline__ void bulk_commit() { asm volatile("cp.async.bulk.commit_group;" ::: "memory"); }
__device__ __forceinline__ void bulk_wait_read() { asm volatile("cp.async.bulk.wait_group.read 0;" ::: "memory"); }
__device__ __forceinline__ void fence_async_smem() { asm volatile("fence.proxy.async.shared::cta;" ::: "memory"); }
__device__ __forceinline__ void fence_async_global() { asm volatile("fence.proxy.async.global;" ::: "memory"); }
__device__ __forceinline__ void wgmma_fence() { asm volatile("wgmma.fence.sync.aligned;" ::: "memory"); }
__device__ __forceinline__ void wgmma_commit() { asm volatile("wgmma.commit_group.sync.aligned;" ::: "memory"); }
template<int N> __device__ __forceinline__ void wgmma_wait() { asm volatile("wgmma.wait_group.sync.aligned %0;" :: "n"(N) : "memory"); }
template<int ID> __device__ __forceinline__ void bar_sync(int n) { asm volatile("bar.sync %0, %1;" :: "n"(ID), "r"(n) : "memory"); }
template<int ID> __device__ __forceinline__ void bar_arrive(int n) { asm volatile("bar.arrive %0, %1;" :: "n"(ID), "r"(n) : "memory"); }
__device__ __forceinline__ void cluster_wait() { asm volatile("barrier.cluster.wait.aligned;" ::: "memory"); }
__device__ __forceinline__ uint64_t desc64(uint32_t lo, uint32_t hi) { return (uint64_t)lo | ((uint64_t)hi << 32); }
__device__ __forceinline__ uint4 ld_vol4(const uint4* p) {
  uint4 v; asm volatile("ld.volatile.global.v4.u32 {%0,%1,%2,%3}, [%4];" : "=r"(v.x), "=r"(v.y), "=r"(v.z), "=r"(v.w) : "l"(p) : "memory"); return v;
}
__device__ __forceinline__ uint2 ld_vol2(const uint2* p) {
  uint2 v; asm volatile("ld.volatile.global.v2.u32 {%0,%1}, [%2];" : "=r"(v.x), "=r"(v.y) : "l"(p) : "memory"); return v;
}
__device__ __forceinline__ void st_vol4(uint4* p, uint32_t a, uint32_t b, uint32_t c, uint32_t d) {
  asm volatile("st.volatile.global.v4.u32 [%0], {%1,%2,%3,%4};" :: "l"(p), "r"(a), "r"(b), "r"(c), "r"(d) : "memory");
}
__device__ __forceinline__ void st_vol2(uint2* p, uint32_t a, uint32_t b) {
  asm volatile("st.volatile.global.v2.u32 [%0], {%1,%2};" :: "l"(p), "r"(a), "r"(b) : "memory");
}
__device__ __forceinline__ void stg128(void* p, uint4 v) {
  asm volatile("st.global.v4.u32 [%0], {%1,%2,%3,%4};" :: "l"(p), "r"(v.x), "r"(v.y), "r"(v.z), "r"(v.w));
}
__device__ __forceinline__ unsigned ld_relaxed(const unsigned* p) {
  unsigned v; asm volatile("ld.relaxed.gpu.global.u32 %0, [%1];" : "=r"(v) : "l"(p) : "memory"); return v;
}
__device__ __forceinline__ uint32_t pack_bf16(float lo, float hi) {
  uint32_t r; asm("cvt.rn.bf16x2.f32 %0, %1, %2;" : "=r"(r) : "f"(hi), "f"(lo)); return r;
}
__device__ __forceinline__ float bf_lo(uint32_t v) { return __uint_as_float(v << 16); }
__device__ __forceinline__ float bf_hi(uint32_t v) { return __uint_as_float(v & 0xFFFF0000u); }
__device__ __forceinline__ void stsm4(uint32_t addr, uint32_t a, uint32_t b, uint32_t c, uint32_t d) {
  asm volatile("stmatrix.sync.aligned.m8n8.x4.shared.b16 [%0], {%1,%2,%3,%4};" :: "r"(addr), "r"(a), "r"(b), "r"(c), "r"(d));
}
__device__ __forceinline__ void stsm4_t(uint32_t addr, uint32_t a, uint32_t b, uint32_t c, uint32_t d) {
  asm volatile("stmatrix.sync.aligned.m8n8.x4.trans.shared.b16 [%0], {%1,%2,%3,%4};" :: "r"(addr), "r"(a), "r"(b), "r"(c), "r"(d));
}
__device__ __forceinline__ void ldsm4(uint32_t addr, uint32_t& a, uint32_t& b, uint32_t& c, uint32_t& d) {
  asm volatile("ldmatrix.sync.aligned.m8n8.x4.shared.b16 {%0,%1,%2,%3}, [%4];" : "=r"(a), "=r"(b), "=r"(c), "=r"(d) : "r"(addr));
}
__device__ __forceinline__ uint4 lds128(uint32_t a) {
  uint4 v; asm volatile("ld.shared.v4.u32 {%0,%1,%2,%3}, [%4];" : "=r"(v.x), "=r"(v.y), "=r"(v.z), "=r"(v.w) : "r"(a)); return v;
}
__device__ __forceinline__ void sts128(uint32_t a, uint32_t x, uint32_t y, uint32_t z, uint32_t w) {
  asm volatile("st.shared.v4.u32 [%0], {%1,%2,%3,%4};" :: "r"(a), "r"(x), "r"(y), "r"(z), "r"(w));
}
__device__ __forceinline__ uint32_t hmul2_bf16(uint32_t a, uint32_t b) {
  uint32_t r; asm("mul.rn.bf16x2 %0, %1, %2;" : "=r"(r) : "r"(a), "r"(b)); return r;
}
__device__ __forceinline__ float gelu_tanh(float v) {
  float u = v * fmaf(0.0356774081f, v * v, 0.7978845608f);
  float t; asm("tanh.approx.f32 %0, %1;" : "=f"(t) : "f"(u));
  float hv = 0.5f * v;
  return fmaf(hv, t, hv);
}

template<int TB>
__device__ __forceinline__ void wgmma_n192(float (&d)[96], uint64_t da, uint64_t db, int scale_d) {
  asm volatile("{\n.reg .pred p;\nsetp.ne.b32 p, %98, 0;\n"
   "wgmma.mma_async.sync.aligned.m64n192k16.f32.bf16.bf16 {%0,%1,%2,%3,%4,%5,%6,%7,%8,%9,%10,%11,%12,%13,%14,%15,%16,%17,%18,%19,%20,%21,%22,%23,%24,%25,%26,%27,%28,%29,%30,%31,%32,%33,%34,%35,%36,%37,%38,%39,%40,%41,%42,%43,%44,%45,%46,%47,%48,%49,%50,%51,%52,%53,%54,%55,%56,%57,%58,%59,%60,%61,%62,%63,%64,%65,%66,%67,%68,%69,%70,%71,%72,%73,%74,%75,%76,%77,%78,%79,%80,%81,%82,%83,%84,%85,%86,%87,%88,%89,%90,%91,%92,%93,%94,%95}, %96, %97, p, 1, 1, 0, %99;\n}"
   : "+f"(d[0]),"+f"(d[1]),"+f"(d[2]),"+f"(d[3]),"+f"(d[4]),"+f"(d[5]),"+f"(d[6]),"+f"(d[7]),"+f"(d[8]),"+f"(d[9]),"+f"(d[10]),"+f"(d[11]),"+f"(d[12]),"+f"(d[13]),"+f"(d[14]),"+f"(d[15]),"+f"(d[16]),"+f"(d[17]),"+f"(d[18]),"+f"(d[19]),"+f"(d[20]),"+f"(d[21]),"+f"(d[22]),"+f"(d[23]),"+f"(d[24]),"+f"(d[25]),"+f"(d[26]),"+f"(d[27]),"+f"(d[28]),"+f"(d[29]),"+f"(d[30]),"+f"(d[31]),"+f"(d[32]),"+f"(d[33]),"+f"(d[34]),"+f"(d[35]),"+f"(d[36]),"+f"(d[37]),"+f"(d[38]),"+f"(d[39]),"+f"(d[40]),"+f"(d[41]),"+f"(d[42]),"+f"(d[43]),"+f"(d[44]),"+f"(d[45]),"+f"(d[46]),"+f"(d[47]),"+f"(d[48]),"+f"(d[49]),"+f"(d[50]),"+f"(d[51]),"+f"(d[52]),"+f"(d[53]),"+f"(d[54]),"+f"(d[55]),"+f"(d[56]),"+f"(d[57]),"+f"(d[58]),"+f"(d[59]),"+f"(d[60]),"+f"(d[61]),"+f"(d[62]),"+f"(d[63]),"+f"(d[64]),"+f"(d[65]),"+f"(d[66]),"+f"(d[67]),"+f"(d[68]),"+f"(d[69]),"+f"(d[70]),"+f"(d[71]),"+f"(d[72]),"+f"(d[73]),"+f"(d[74]),"+f"(d[75]),"+f"(d[76]),"+f"(d[77]),"+f"(d[78]),"+f"(d[79]),"+f"(d[80]),"+f"(d[81]),"+f"(d[82]),"+f"(d[83]),"+f"(d[84]),"+f"(d[85]),"+f"(d[86]),"+f"(d[87]),"+f"(d[88]),"+f"(d[89]),"+f"(d[90]),"+f"(d[91]),"+f"(d[92]),"+f"(d[93]),"+f"(d[94]),"+f"(d[95])
   : "l"(da), "l"(db), "r"(scale_d), "n"(TB));
}
template<int TB>
__device__ __forceinline__ void wgmma_n160(float (&d)[80], uint64_t da, uint64_t db, int scale_d) {
  asm volatile("{\n.reg .pred p;\nsetp.ne.b32 p, %82, 0;\n"
   "wgmma.mma_async.sync.aligned.m64n160k16.f32.bf16.bf16 {%0,%1,%2,%3,%4,%5,%6,%7,%8,%9,%10,%11,%12,%13,%14,%15,%16,%17,%18,%19,%20,%21,%22,%23,%24,%25,%26,%27,%28,%29,%30,%31,%32,%33,%34,%35,%36,%37,%38,%39,%40,%41,%42,%43,%44,%45,%46,%47,%48,%49,%50,%51,%52,%53,%54,%55,%56,%57,%58,%59,%60,%61,%62,%63,%64,%65,%66,%67,%68,%69,%70,%71,%72,%73,%74,%75,%76,%77,%78,%79}, %80, %81, p, 1, 1, 0, %83;\n}"
   : "+f"(d[0]),"+f"(d[1]),"+f"(d[2]),"+f"(d[3]),"+f"(d[4]),"+f"(d[5]),"+f"(d[6]),"+f"(d[7]),"+f"(d[8]),"+f"(d[9]),"+f"(d[10]),"+f"(d[11]),"+f"(d[12]),"+f"(d[13]),"+f"(d[14]),"+f"(d[15]),"+f"(d[16]),"+f"(d[17]),"+f"(d[18]),"+f"(d[19]),"+f"(d[20]),"+f"(d[21]),"+f"(d[22]),"+f"(d[23]),"+f"(d[24]),"+f"(d[25]),"+f"(d[26]),"+f"(d[27]),"+f"(d[28]),"+f"(d[29]),"+f"(d[30]),"+f"(d[31]),"+f"(d[32]),"+f"(d[33]),"+f"(d[34]),"+f"(d[35]),"+f"(d[36]),"+f"(d[37]),"+f"(d[38]),"+f"(d[39]),"+f"(d[40]),"+f"(d[41]),"+f"(d[42]),"+f"(d[43]),"+f"(d[44]),"+f"(d[45]),"+f"(d[46]),"+f"(d[47]),"+f"(d[48]),"+f"(d[49]),"+f"(d[50]),"+f"(d[51]),"+f"(d[52]),"+f"(d[53]),"+f"(d[54]),"+f"(d[55]),"+f"(d[56]),"+f"(d[57]),"+f"(d[58]),"+f"(d[59]),"+f"(d[60]),"+f"(d[61]),"+f"(d[62]),"+f"(d[63]),"+f"(d[64]),"+f"(d[65]),"+f"(d[66]),"+f"(d[67]),"+f"(d[68]),"+f"(d[69]),"+f"(d[70]),"+f"(d[71]),"+f"(d[72]),"+f"(d[73]),"+f"(d[74]),"+f"(d[75]),"+f"(d[76]),"+f"(d[77]),"+f"(d[78]),"+f"(d[79])
   : "l"(da), "l"(db), "r"(scale_d), "n"(TB));
}
template<int TB>
__device__ __forceinline__ void wgmma_n96(float (&d)[48], uint64_t da, uint64_t db, int scale_d) {
  asm volatile("{\n.reg .pred p;\nsetp.ne.b32 p, %50, 0;\n"
   "wgmma.mma_async.sync.aligned.m64n96k16.f32.bf16.bf16 {%0,%1,%2,%3,%4,%5,%6,%7,%8,%9,%10,%11,%12,%13,%14,%15,%16,%17,%18,%19,%20,%21,%22,%23,%24,%25,%26,%27,%28,%29,%30,%31,%32,%33,%34,%35,%36,%37,%38,%39,%40,%41,%42,%43,%44,%45,%46,%47}, %48, %49, p, 1, 1, 0, %51;\n}"
   : "+f"(d[0]),"+f"(d[1]),"+f"(d[2]),"+f"(d[3]),"+f"(d[4]),"+f"(d[5]),"+f"(d[6]),"+f"(d[7]),"+f"(d[8]),"+f"(d[9]),"+f"(d[10]),"+f"(d[11]),"+f"(d[12]),"+f"(d[13]),"+f"(d[14]),"+f"(d[15]),"+f"(d[16]),"+f"(d[17]),"+f"(d[18]),"+f"(d[19]),"+f"(d[20]),"+f"(d[21]),"+f"(d[22]),"+f"(d[23]),"+f"(d[24]),"+f"(d[25]),"+f"(d[26]),"+f"(d[27]),"+f"(d[28]),"+f"(d[29]),"+f"(d[30]),"+f"(d[31]),"+f"(d[32]),"+f"(d[33]),"+f"(d[34]),"+f"(d[35]),"+f"(d[36]),"+f"(d[37]),"+f"(d[38]),"+f"(d[39]),"+f"(d[40]),"+f"(d[41]),"+f"(d[42]),"+f"(d[43]),"+f"(d[44]),"+f"(d[45]),"+f"(d[46]),"+f"(d[47])
   : "l"(da), "l"(db), "r"(scale_d), "n"(TB));
}

template<int N, int TB>
__device__ __forceinline__ void wgmma_n(float (&d)[N / 2], uint64_t da, uint64_t db) {
  if constexpr (N == 192) wgmma_n192<TB>(d, da, db, 1);
  else if constexpr (N == 160) wgmma_n160<TB>(d, da, db, 1);
  else wgmma_n96<TB>(d, da, db, 1);
}

template<int R>
__device__ __forceinline__ void pin(float (&acc)[2][R]) {
  #pragma unroll
  for (int mi = 0; mi < 2; mi++)
    #pragma unroll
    for (int i = 0; i < R; i++) asm volatile("" : "+f"(acc[mi][i]) :: "memory");
}
template<int R>
__device__ __forceinline__ void zero(float (&acc)[2][R]) {
  #pragma unroll
  for (int i = 0; i < R; i++) { acc[0][i] = 0.f; acc[1][i] = 0.f; }
  pin(acc);
}

template<int N, int TB, bool CONT, int ORD_BAR>
__device__ __forceinline__ void mainloop(float (&acc)[2][N / 2], uint32_t sbase, uint32_t stage_bytes, int g0, int nk, int total, int mswap) {
  const uint32_t full0 = sbase + BAR_OFF, empty0 = full0 + 8 * STAGES, ring = sbase + RING_OFF;
  const int t = threadIdx.x & 127;
  const uint32_t da0 = (((ring + mswap * 8192) & 0x3FFFF) >> 4) | 0x10000u, da1 = (((ring + (mswap ^ 1) * 8192) & 0x3FFFF) >> 4) | 0x10000u;
  const uint32_t db0 = (((ring + A_BYTES) & 0x3FFFF) >> 4) | ((TB == 2 ? 256u : TB ? 512u : 1u) << 16);
  constexpr uint32_t HI_A = 0x40000040u, HI_B = TB == 2 ? 0x80000020u : 0x40000040u;
  #pragma unroll 1
  for (int g = g0; g < g0 + nk; g++) {
    const int s = g & (STAGES - 1);
    const uint32_t so = s * (stage_bytes >> 4);
    mbar_wait(full0 + 8 * s, (g / STAGES) & 1);
    wgmma_fence();
    #pragma unroll
    for (int k = 0; k < 4; k++) {
      const uint64_t db = desc64(db0 + so + (TB == 2 ? k * 64 : TB ? k * 128 : k * 2), HI_B);
      wgmma_n<N, TB != 0>(acc[0], desc64(da0 + so + k * 2, HI_A), db);
      wgmma_n<N, TB != 0>(acc[1], desc64(da1 + so + k * 2, HI_A), db);
    }
    wgmma_commit();
    if (ORD_BAR != 0 && g == g0 + nk - 1) bar_arrive<ORD_BAR>(256);
    wgmma_wait<1>();
    if (t < 2 && (CONT || g > g0) && g - 1 + STAGES <= total) mbar_arrive_cluster(empty0 + 8 * ((g - 1) & (STAGES - 1)), t);
  }
}
template<int R>
__device__ __forceinline__ void drain(float (&acc)[2][R], uint32_t sbase, int glast, int total) {
  wgmma_wait<0>();
  pin(acc);
  const int t = threadIdx.x & 127;
  if (t < 2 && glast + STAGES <= total) mbar_arrive_cluster(sbase + BAR_OFF + 8 * STAGES + 8 * (glast & (STAGES - 1)), t);
}

__device__ __forceinline__ void publish(unsigned* flag, unsigned epoch) {
  asm volatile("fence.acq_rel.gpu;" ::: "memory");
  asm volatile("st.relaxed.gpu.global.u32 [%0], %1;" :: "l"(flag), "r"(epoch) : "memory");
}

__device__ __forceinline__ float sum8(uint4 v) {
  return ((bf_lo(v.x) + bf_hi(v.x)) + (bf_lo(v.y) + bf_hi(v.y))) + ((bf_lo(v.z) + bf_hi(v.z)) + (bf_lo(v.w) + bf_hi(v.w)));
}
__device__ __forceinline__ float oct_sum(float v) {
  v += __shfl_xor_sync(0xffffffffu, v, 1); v += __shfl_xor_sync(0xffffffffu, v, 2); v += __shfl_xor_sync(0xffffffffu, v, 4);
  return v;
}

__device__ __forceinline__ void stats_prologue(const bf16* __restrict__ x, const bf16* __restrict__ win, const bf16* __restrict__ wdre,
                                               const bf16* __restrict__ wdim, int rb, int c8, float* red, unsigned epoch) {
  const int t = threadIdx.x & 127, l = t & 31, cta = blockIdx.x;
  const int cg = t % 12, rg = min(t / 12, 9), tc = min(t, 95);
  #pragma unroll 1
  for (int p = 0; p < 2; p++) {
    const int wr = cta * 10 + min(t >> 3, 9);
    const bf16* src = p == 0 ? x + (size_t)(cta * 16 + (t >> 3)) * DM : wr < DM ? wdre + (size_t)wr * DM : wdim + (size_t)(wr - DM) * DM;
    const int col = (1 - p) * FH + c8 * 96;
    uint4 rv[10], cv[4];
    #pragma unroll
    for (int j = 0; j < 4; j++) cv[j] = __ldg(reinterpret_cast<const uint4*>(win + (size_t)(rb * 40 + rg * 4 + j) * FF + col) + cg);
    #pragma unroll
    for (int j = 0; j < 10; j++) rv[j] = __ldg(reinterpret_cast<const uint4*>(src) + (l & 7) + 8 * j);
    float* rp = red + p * 960;
    *reinterpret_cast<float4*>(rp + rg * 96 + cg * 8) = make_float4(
        (bf_lo(cv[0].x) + bf_lo(cv[1].x)) + (bf_lo(cv[2].x) + bf_lo(cv[3].x)), (bf_hi(cv[0].x) + bf_hi(cv[1].x)) + (bf_hi(cv[2].x) + bf_hi(cv[3].x)),
        (bf_lo(cv[0].y) + bf_lo(cv[1].y)) + (bf_lo(cv[2].y) + bf_lo(cv[3].y)), (bf_hi(cv[0].y) + bf_hi(cv[1].y)) + (bf_hi(cv[2].y) + bf_hi(cv[3].y)));
    *reinterpret_cast<float4*>(rp + rg * 96 + cg * 8 + 4) = make_float4(
        (bf_lo(cv[0].z) + bf_lo(cv[1].z)) + (bf_lo(cv[2].z) + bf_lo(cv[3].z)), (bf_hi(cv[0].z) + bf_hi(cv[1].z)) + (bf_hi(cv[2].z) + bf_hi(cv[3].z)),
        (bf_lo(cv[0].w) + bf_lo(cv[1].w)) + (bf_lo(cv[2].w) + bf_lo(cv[3].w)), (bf_hi(cv[0].w) + bf_hi(cv[1].w)) + (bf_hi(cv[2].w) + bf_hi(cv[3].w)));
    float s = 0.f;
    #pragma unroll
    for (int j = 0; j < 10; j++) s += sum8(rv[j]);
    s = oct_sum(s);
    if (p == 0) {
      const float mean = s * (1.f / DM);
      float q = 0.f;
      #pragma unroll
      for (int j = 0; j < 10; j++) {
        const uint32_t u[4] = {rv[j].x, rv[j].y, rv[j].z, rv[j].w};
        #pragma unroll
        for (int c = 0; c < 4; c++) { const float d0 = bf_lo(u[c]) - mean, d1 = bf_hi(u[c]) - mean; q = fmaf(d0, d0, q); q = fmaf(d1, d1, q); }
      }
      const float rstd = rsqrtf(fmaf(oct_sum(q), 1.f / DM, LN_EPS));
      if ((l & 7) == 0) st_vol4(&g_xstat[cta * 16 + (t >> 3)], __float_as_uint(rstd), __float_as_uint(-mean * rstd), epoch, 0u);
    } else if ((l & 7) == 0) {
      st_vol2(&g_csum[16 * FF + wr], __float_as_uint(s), epoch);
    }
    bar_sync<BAR_WG2>(128);
    float c = 0.f;
    #pragma unroll
    for (int i = 0; i < 10; i++) c += rp[i * 96 + tc];
    st_vol2(&g_csum[rb * FF + col + tc], __float_as_uint(c), epoch);
  }
}

template<int NP>
__device__ __forceinline__ float gather_sum(const uint2* src, unsigned epoch) {
  unsigned it = 0;
  while (true) {
    uint2 u[NP];
    #pragma unroll
    for (int i = 0; i < NP; i++) u[i] = ld_vol2(src + i * FF);
    bool ok = true;
    float a = 0.f;
    #pragma unroll
    for (int i = 0; i < NP; i++) { ok = ok && u[i].y == epoch; a += __uint_as_float(u[i].x); }
    if (ok || ++it > POLL_LIMIT) return a;
    __nanosleep(POLL_NS);
  }
}

__device__ __forceinline__ void fold_pack(const float* a, float2 s0, float2 s1, float2 c0, float2 c1, uint32_t (&r)[4]) {
  r[0] = pack_bf16(fmaf(a[0], s0.x, s0.y * c0.x), fmaf(a[1], s0.x, s0.y * c0.y));
  r[1] = pack_bf16(fmaf(a[2], s1.x, s1.y * c0.x), fmaf(a[3], s1.x, s1.y * c0.y));
  r[2] = pack_bf16(fmaf(a[4], s0.x, s0.y * c1.x), fmaf(a[5], s0.x, s0.y * c1.y));
  r[3] = pack_bf16(fmaf(a[6], s1.x, s1.y * c1.x), fmaf(a[7], s1.x, s1.y * c1.y));
}

__global__ void __cluster_dims__(2, 1, 1) __launch_bounds__(384, 1)
fused_kernel(const __grid_constant__ Maps maps, const bf16* __restrict__ x, const bf16* __restrict__ win,
             const bf16* __restrict__ bsp, const bf16* __restrict__ wdre, const bf16* __restrict__ wdim,
             const bf16* __restrict__ wsp, const bf16* __restrict__ wsre, const bf16* __restrict__ wsim) {
  const uint32_t sbase = smem_u32(smem);
  const uint32_t full0 = sbase + BAR_OFF, empty0 = full0 + 8 * STAGES, dep0 = empty0 + 8 * STAGES, ring = sbase + RING_OFF;
  const int tid = threadIdx.x, wg = __shfl_sync(0xffffffffu, tid >> 7, 0);
  const int rank = blockIdx.x & 1, grp = (blockIdx.x >> 1) & 1, q = blockIdx.x >> 2;
  const int rb = q >> 1, ct = (q & 1) * 2 + rank, c8 = grp * 4 + ct;
  const int total = grp == 0 ? KB_A : KB_B;
  const uint32_t stage_bytes = grp == 0 ? STAGE_A : STAGE_B;

  if (tid == 0) {
    TS(0, 0);
    for (int s = 0; s < STAGES; s++) { mbar_init(full0 + 8 * s, 2); mbar_init(empty0 + 8 * s, 2); mbar_init(dep0 + 8 * s, 1); }
    asm volatile("fence.mbarrier_init.release.cluster;" ::: "memory");
  }
  __syncthreads();
  asm volatile("barrier.cluster.arrive.relaxed.aligned;" ::: "memory");

  if (wg == 0) {
    asm volatile("setmaxnreg.dec.sync.aligned.u32 40;");
    const int warp = tid >> 5, lane = tid & 31;
    if (warp == 0) {
      const int row = rb * 128;
      if (lane == 0) {
        TS(0, 1);
        for (int g = 0; g < STAGES; g++) {
          mbar_expect_tx(full0 + 8 * g, A_BYTES);
          tma_load_2d(ring + g * stage_bytes, &maps.m[M_X], full0 + 8 * g, g * 64, row);
          tma_load_2d(ring + g * stage_bytes + 8192, &maps.m[M_X], full0 + 8 * g, g * 64, row + 64);
        }
      }
      __syncwarp();
      cluster_wait();
      if (lane == 0) {
        #pragma unroll 1
        for (int g = STAGES; g < total; g++) {
          int mi, kb;
          if (g < 20) { mi = M_X; kb = g < 10 ? g : g - 10; }
          else if (grp == 0) {
            if (g < 52) { mi = M_WSP; kb = g - 20; }
            else if (g < 52 + NX) { mi = M_WSIM; kb = g - 52 + 32 - NX; }
            else { mi = M_H; kb = g - 52 - NX; }
          } else {
            if (g < 30) { mi = M_X; kb = g - 20; }
            else if (g < 62) { mi = M_WSRE; kb = g - 30; }
            else { mi = M_WSIM; kb = g - 62; }
          }
          if (mi == M_H && kb == 0) { TS(0, 3); mbar_wait(dep0 + 24, 0); fence_async_global(); TS(0, 4); }
          const int s = g & (STAGES - 1);
          mbar_wait(empty0 + 8 * s, ((g / STAGES) & 1) ^ 1);
          mbar_expect_tx(full0 + 8 * s, A_BYTES);
          tma_load_2d_mc(ring + s * stage_bytes + rank * 8192, &maps.m[mi], full0 + 8 * s, kb * 64, row + rank * 64, 3);
        }
        const int s = total & (STAGES - 1);
        mbar_wait(empty0 + 8 * s, ((total / STAGES) & 1) ^ 1);
        mbar_expect_tx(full0 + 8 * s, 20480);
        mbar_arrive(full0 + 8 * s);
        tma_load_2d(ring + s * stage_bytes, &maps.m[M_XR], full0 + 8 * s, ct * 160, row + grp * 64);
        TS(0, 5);
      }
    } else if (warp == 1) {
      if (lane == 0) {
        #pragma unroll 1
        for (int g = 0; g < total; g++) {
          int kind = 1, mi, kb, c, dep = 0;
          uint32_t bytes = 20480;
          if (g < 10) { kind = 0; mi = M_WIN32; kb = g; c = 24 + 3 * c8; bytes = 12288; }
          else if (grp == 0) {
            if (g < 20) { kind = 0; mi = M_WIN3; kb = g - 10; c = 3 * ct; bytes = 24576; }
            else if (g < 52) { kind = 0; mi = M_Z23; kb = g - 20; c = 3 * ct; bytes = 24576; dep = g == 20 ? 1 : 0; }
            else if (g < 52 + NX) { mi = M_AB; kb = g - 52 + 32 - NX; c = DM + ct * 160; dep = g == 52 ? 2 : 0; }
            else { kind = 0; mi = M_WOUT; kb = g - 52 - NX; c = ct * 5; }
          } else {
            if (g < 30) { mi = g < 20 ? M_WDRE : M_WDIM; kb = g < 20 ? g - 10 : g - 20; c = ct * 160; }
            else { mi = M_AB; kb = g < 62 ? g - 30 : g - 62; c = ct * 160 + (g < 62 ? 0 : DM); dep = g == 30 ? 1 : g == 62 ? 2 : 0; }
          }
          if (dep) { TS(1, dep * 2 - 2); mbar_wait(dep0 + 8 * dep, 0); fence_async_global(); TS(1, dep * 2 - 1); TC(dep); }
          const int s = g & (STAGES - 1);
          const uint32_t dst = ring + s * stage_bytes + A_BYTES, fb = full0 + 8 * s;
          mbar_wait(empty0 + 8 * s, ((g / STAGES) & 1) ^ 1);
          mbar_expect_tx(fb, bytes);
          if (kind == 0) tma_load_3d(dst, &maps.m[mi], fb, 0, kb * 64, c);
          else tma_load_2d(dst, &maps.m[mi], fb, kb * 64, c);
        }
      }
      __syncwarp();
      cluster_wait();
    } else if (warp == 2) {
      cluster_wait();
      const unsigned epoch = (*reinterpret_cast<volatile unsigned*>(&g_done) >> 7) + 1u;
      #pragma unroll 1
      for (int d = 1; d < 4 - grp; d++) {
        const int fi = d == 3 ? F_H + rb * 4 + (lane & 3)
                     : (d == 1 && grp == 0) ? F_Z + (lane >> 1) * 8 + ct * 2 + (lane & 1)
                     : (d == 1 ? F_A : F_B) + (lane & 15) * 4 + ct;
        unsigned it = 0;
        while (!__all_sync(0xffffffffu, ld_relaxed(g_flags + fi) == epoch) && ++it < POLL_LIMIT) __nanosleep(40);
        asm volatile("fence.acq_rel.gpu;" ::: "memory");
        fence_async_global();
        __syncwarp();
        if (lane == 0) mbar_arrive(dep0 + 8 * d);
      }
    } else {
      cluster_wait();
      if (lane == 0) {
        mbar_wait(full0 + 8 * (STAGES - 1), 0);
        #pragma unroll 1
        for (int i = 0; i < 32 * (1 + grp); i++) {
          const bf16* p = (grp == 0 ? wsp : i < 32 ? wsre : wsim) + (size_t)(rb * 128 + ct * 32 + (i & 31)) * SEQ;
          asm volatile("cp.async.bulk.prefetch.L2.global [%0], 4096;" :: "l"(p) : "memory");
          __nanosleep(PF_NS);
        }
      }
    }
  } else {
    asm volatile("setmaxnreg.inc.sync.aligned.u32 232;");
    const int t = tid & 127, w = t >> 5, l = t & 31;
    const uint32_t buf = ring + 4 * stage_bytes;
    const unsigned epoch = (*reinterpret_cast<volatile unsigned*>(&g_done) >> 7) + 1u;
    cluster_wait();
    const int rl = w * 16 + ((l >> 3) & 1) * 8 + (l & 7);
    const int gr = w * 16 + (l & 15);
    const uint32_t st_base = buf + rl * 128;
    const uint32_t st_x = ((l >> 4) ^ (l & 7)) << 4;
    float* csw = reinterpret_cast<float*>(smem + COLSUM_OFF) + (wg - 1) * 192;
    const float2* rs = reinterpret_cast<const float2*>(smem + ROWSTAT_OFF) + w * 16 + (l >> 2);
    const float2* cs = reinterpret_cast<const float2*>(csw) + (l & 3);
    if (wg == 1) {
      float acc[2][48];
      zero(acc);
      mainloop<96, 2, false, BAR_ORD1>(acc, sbase, stage_bytes, 0, 10, total, 0);
      {
        unsigned n = 0;
        uint4 v = ld_vol4(&g_xstat[rb * 128 + t]);
        csw[min(t, 95)] = gather_sum<16>(g_csum + FH + c8 * 96 + min(t, 95), epoch);
        while (v.z != epoch && ++n < POLL_LIMIT) { __nanosleep(POLL_NS); v = ld_vol4(&g_xstat[rb * 128 + t]); }
        reinterpret_cast<float2*>(smem + ROWSTAT_OFF)[t] = make_float2(__uint_as_float(v.x), __uint_as_float(v.y));
      }
      drain(acc, sbase, 9, total);
      TS(2, 2);
      bar_arrive<BAR_STATS>(256);
      bar_sync<BAR_WG1>(128);
      const float2 s0 = rs[0], s1 = rs[8], s2 = rs[64], s3 = rs[72];
      #pragma unroll
      for (int jj = 0; jj < 6; jj++) {
        uint32_t r[4];
        const float2 c0 = cs[jj * 8], c1 = cs[jj * 8 + 4];
        const uint32_t ad = buf + (jj >> 1) * 8192 + rl * 64 + ((((jj & 1) * 2 + (l >> 4)) ^ ((l >> 1) & 3)) << 4);
        fold_pack(&acc[0][8 * jj], s0, s1, c0, c1, r);
        stsm4(ad, r[0], r[1], r[2], r[3]);
        fold_pack(&acc[1][8 * jj], s2, s3, c0, c1, r);
        stsm4(ad + 4096, r[0], r[1], r[2], r[3]);
      }
    } else {
      stats_prologue(x, win, wdre, wdim, rb, c8, reinterpret_cast<float*>(smem + (buf - sbase) + 24576), epoch);
      TS(3, 0);
      if (grp == 0) {
        reinterpret_cast<float*>(smem + BIAS_OFF)[t] = __bfloat162float(bsp[rb * 128 + t]);
        float acc[2][96];
        zero(acc);
        bar_sync<BAR_ORD1>(256);
        mainloop<192, 1, false, BAR_ORD2>(acc, sbase, STAGE_A, 10, 10, KB_A, 0);
        drain(acc, sbase, 19, KB_A);
        TS(3, 2);
        #pragma unroll 1
        for (int i = 0; i < 3; i++) {
          const int c = i * 64 + (t >> 1);
          float v = gather_sum<8>(g_csum + (t & 1) * 8 * FF + ct * 192 + c, epoch);
          v += __shfl_xor_sync(0xffffffffu, v, 1);
          csw[c] = v;
        }
        bar_sync<BAR_STATS>(256);
        bar_sync<BAR_BUF>(256);
        const float2 s0 = rs[0], s1 = rs[8], s2 = rs[64], s3 = rs[72];
        #pragma unroll
        for (int jj = 0; jj < 12; jj++) {
          uint32_t r[4];
          const float2 c0 = cs[jj * 8], c1 = cs[jj * 8 + 4];
          const uint32_t ad = st_base + (jj >> 2) * 8192 + (st_x ^ ((jj & 3) << 5));
          fold_pack(&acc[0][8 * jj], s0, s1, c0, c1, r);
          stsm4(ad, r[0], r[1], r[2], r[3]);
          fold_pack(&acc[1][8 * jj], s2, s3, c0, c1, r);
          stsm4(ad + 24576, r[0], r[1], r[2], r[3]);
        }
      }
    }
    if (wg == 1 || grp == 0) {
      __syncwarp();
      TS(wg + 1, 3);
      const uint32_t rbase = wg == 1 ? buf + (l >> 4) * 4096 + gr * 64 : buf + (l >> 4) * 24576 + gr * 128;
      const int sw = wg == 1 ? (l >> 1) & 3 : l & 7;
      float sum = 0.f, sq = 0.f;
      #pragma unroll 1
      for (int c4 = 0; c4 < 3 * wg; c4++) {
        const uint32_t ab = rbase + (wg == 1 ? c4 : c4 >> 1) * 8192;
        const int cb = wg == 1 ? 0 : (c4 & 1) * 4;
        uint4 v[4];
        #pragma unroll
        for (int i = 0; i < 4; i++) v[i] = lds128(ab + (((cb + i) ^ sw) << 4));
        float s2 = 0.f, q2 = 0.f;
        #pragma unroll
        for (int i = 0; i < 4; i++) {
          const uint32_t u[4] = {v[i].x, v[i].y, v[i].z, v[i].w};
          uint32_t o[4];
          #pragma unroll
          for (int e = 0; e < 4; e++) {
            const float g0 = gelu_tanh(bf_lo(u[e])), g1 = gelu_tanh(bf_hi(u[e]));
            o[e] = pack_bf16(g0, g1);
            sum += g0; s2 += g1; sq = fmaf(g0, g0, sq); q2 = fmaf(g1, g1, q2);
          }
          v[i] = make_uint4(o[0], o[1], o[2], o[3]);
        }
        sum += s2; sq += q2;
        #pragma unroll
        for (int i = 0; i < 4; i++) sts128(ab + (((cb + i) ^ sw) << 4), v[i].x, v[i].y, v[i].z, v[i].w);
      }
      TS(wg + 1, 4);
      if (wg == 2) {
        bar_arrive<BAR_Z1>(256);
      } else {
        const int row = (l >> 4) * 64 + gr;
        const float mu = sum * (1.f / 96), m2 = fmaxf(sq - sum * mu, 0.f);
        st_vol4(&g_zstat[(rb * 8 + c8) * 128 + row], __float_as_uint(mu), __float_as_uint(m2), epoch, 0u);
        uint4 v[7];
        unsigned n = 0;
        while (true) {
          bool ok = true;
          #pragma unroll
          for (int j = 0; j < 7; j++) v[j] = ld_vol4(&g_zstat[(rb * 8 + ((c8 + 1 + j) & 7)) * 128 + row]);
          #pragma unroll
          for (int j = 0; j < 7; j++) ok = ok && v[j].z == epoch;
          if (ok || ++n > POLL_LIMIT) break;
          __nanosleep(POLL_NS);
        }
        float mean = mu, var = m2;
        #pragma unroll
        for (int j = 0; j < 7; j++) { mean += __uint_as_float(v[j].x); var += __uint_as_float(v[j].y); }
        mean *= 0.125f;
        float d = (mu - mean) * (mu - mean);
        #pragma unroll
        for (int j = 0; j < 7; j++) d = fmaf(__uint_as_float(v[j].x) - mean, __uint_as_float(v[j].x) - mean, d);
        const float rstd = rsqrtf(fmaf(96.f, d, var) * (1.f / FH) + LN_EPS), off = -mean * rstd;
        __syncwarp();
        TS(2, 5);
        #pragma unroll
        for (int i = 0; i < 4; i++) {
          const int src = i * 8 + (l >> 2);
          const float r = __shfl_sync(0xffffffffu, rstd, src), o = __shfl_sync(0xffffffffu, off, src);
          const int rr = (src >> 4) * 64 + w * 16 + (src & 15);
          uint4 z[3];
          #pragma unroll
          for (int c = 0; c < 3; c++) z[c] = lds128(buf + c * 8192 + rr * 64 + (((l & 3) ^ ((rr >> 1) & 3)) << 4));
          #pragma unroll
          for (int c = 0; c < 3; c++)
            stg128(g_z2 + (size_t)(rb * 128 + rr) * FH + c8 * 96 + c * 32 + (l & 3) * 8, make_uint4(
                   pack_bf16(fmaf(bf_lo(z[c].x), r, o), fmaf(bf_hi(z[c].x), r, o)), pack_bf16(fmaf(bf_lo(z[c].y), r, o), fmaf(bf_hi(z[c].y), r, o)),
                   pack_bf16(fmaf(bf_lo(z[c].z), r, o), fmaf(bf_hi(z[c].z), r, o)), pack_bf16(fmaf(bf_lo(z[c].w), r, o), fmaf(bf_hi(z[c].w), r, o))));
        }
        bar_sync<BAR_WG1>(128);
        TS(2, 6);
        if (t == 0) publish(g_flags + F_Z + rb * 8 + c8, epoch);
        __syncwarp();
        TS(2, 10);
        if (grp == 0) {
          bar_arrive<BAR_BUF>(256);
          float acc[2][96];
          zero(acc);
          bar_sync<BAR_ORD2>(256);
          mainloop<192, 1, false, BAR_ORD1>(acc, sbase, STAGE_A, 20, 32, KB_A, 0);
          const float* bias = reinterpret_cast<const float*>(smem + BIAS_OFF) + w * 16 + (l >> 2);
          bar_sync<BAR_Z1>(256);
          drain(acc, sbase, 51, KB_A);
          TS(2, 7);
          #pragma unroll
          for (int mi = 0; mi < 2; mi++) {
            const float b0 = bias[mi * 64], b1 = bias[mi * 64 + 8];
            #pragma unroll
            for (int j4 = 0; j4 < 3; j4++) {
              uint32_t z[4][4];
              #pragma unroll
              for (int i = 0; i < 4; i++) ldsm4(st_base + mi * 24576 + j4 * 8192 + (st_x ^ (i << 5)), z[i][0], z[i][1], z[i][2], z[i][3]);
              #pragma unroll
              for (int i = 0; i < 4; i++) {
                const float* a = &acc[mi][8 * (j4 * 4 + i)];
                stsm4(st_base + mi * 24576 + j4 * 8192 + (st_x ^ (i << 5)),
                      hmul2_bf16(z[i][0], pack_bf16(a[0] + b0, a[1] + b0)), hmul2_bf16(z[i][1], pack_bf16(a[2] + b1, a[3] + b1)),
                      hmul2_bf16(z[i][2], pack_bf16(a[4] + b0, a[5] + b0)), hmul2_bf16(z[i][3], pack_bf16(a[6] + b1, a[7] + b1)));
              }
            }
          }
          __syncwarp();
          TS(2, 8);
          #pragma unroll 1
          for (int i = 0; i < 6; i++) {
            uint4 z[4];
            const int r0 = w * 16 + (l >> 3);
            #pragma unroll
            for (int j = 0; j < 4; j++) z[j] = lds128(buf + i * 8192 + (r0 + j * 4) * 128 + (((l ^ (r0 + j * 4)) & 7) << 4));
            bf16* p = g_h + (size_t)(rb * 128 + (i / 3) * 64 + r0) * FH + ct * 192 + (i % 3) * 64 + (l & 7) * 8;
            #pragma unroll
            for (int j = 0; j < 4; j++) stg128(p + (size_t)j * 4 * FH, z[j]);
          }
          bar_sync<BAR_WG1>(128);
          if (t == 0) publish(g_flags + F_H + rb * 4 + ct, epoch);
          TS(2, 9);
          return;
        }
      }
    }
    float acc[2][80];
    if (grp == 1) {
      zero(acc);
      if (wg == 2) {
        bar_sync<BAR_ORD1>(256);
        mainloop<160, 0, false, BAR_ORD2>(acc, sbase, STAGE_B, 10, 10, KB_B, 0);
      } else {
        bar_sync<BAR_ORD2>(256);
        mainloop<160, 0, false, BAR_ORD1>(acc, sbase, STAGE_B, 20, 10, KB_B, 0);
      }
      csw[t] = gather_sum<1>(g_csum + 16 * FF + (2 - wg) * DM + ct * 160 + t, epoch);
      csw[128 + l] = gather_sum<1>(g_csum + 16 * FF + (2 - wg) * DM + ct * 160 + 128 + l, epoch);
      drain(acc, sbase, wg == 2 ? 19 : 29, KB_B);
      TS(wg + 1, wg == 1 ? 7 : 2);
      if (wg == 1) bar_sync<BAR_BUF>(256); else bar_sync<BAR_STATS>(256);
      const float sign = wg == 1 ? -1.f : 1.f;
      const uint32_t tb = buf + 24576 + ((l >> 4) * 8 + (l & 7)) * 128 + (((w * 2 + ((l >> 3) & 1)) ^ (l & 7)) << 4);
      float2 s0 = rs[0], s1 = rs[8], s2 = rs[64], s3 = rs[72];
      s0.x *= sign; s0.y *= sign; s1.x *= sign; s1.y *= sign; s2.x *= sign; s2.y *= sign; s3.x *= sign; s3.y *= sign;
      #pragma unroll
      for (int jj = 0; jj < 10; jj++) {
        uint32_t r[4];
        const float2 c0 = cs[jj * 8], c1 = cs[jj * 8 + 4];
        fold_pack(&acc[0][8 * jj], s0, s1, c0, c1, r);
        stsm4_t(tb + jj * 2048, r[0], r[1], r[2], r[3]);
        fold_pack(&acc[1][8 * jj], s2, s3, c0, c1, r);
        stsm4_t(tb + 20480 + jj * 2048, r[0], r[1], r[2], r[3]);
      }
      if (wg == 1) bar_sync<BAR_WG1>(128); else bar_sync<BAR_WG2>(128);
      TS(wg + 1, wg == 1 ? 8 : 6);
      #pragma unroll 1
      for (int i = 0; i < 4; i++) {
        uint4 z[5];
        const int e0 = (i & 1) * 80 + (t >> 3);
        #pragma unroll
        for (int j = 0; j < 5; j++) z[j] = lds128(buf + 24576 + (i >> 1) * 20480 + (e0 + j * 16) * 128 + (((l ^ e0) & 7) << 4));
        bf16* p = g_abT + (size_t)((2 - wg) * DM + ct * 160 + e0) * SEQ + rb * 128 + (i >> 1) * 64 + (l & 7) * 8;
        #pragma unroll
        for (int j = 0; j < 5; j++) stg128(p + (size_t)j * 16 * SEQ, z[j]);
      }
      if (wg == 1) bar_sync<BAR_WG1>(128); else bar_sync<BAR_WG2>(128);
      if (t == 0) publish(g_flags + (wg == 2 ? F_A : F_B) + rb * 4 + ct, epoch);
      TS(wg + 1, wg == 1 ? 9 : 10);
      if (wg == 1) return;
      bar_arrive<BAR_BUF>(256);
    }
    zero(acc);
    bar_sync<BAR_ORD1>(256);
    mainloop<160, 0, false, 0>(acc, sbase, stage_bytes, grp == 0 ? 52 : 30, grp == 0 ? NX : 64 - NX, total, grp);
    if (grp == 0) mainloop<160, 2, true, 0>(acc, sbase, STAGE_A, 52 + NX, 12, KB_A, 0);
    drain(acc, sbase, total - 1, total);
    TS(3, 12);
    uint4* dst = g_part + (size_t)blockIdx.x * 27 * 128 + t;
    const uint4* src = g_part + (size_t)(blockIdx.x ^ 2) * 27 * 128 + t;
    #pragma unroll
    for (int i = 0; i < 27; i++)
      st_vol4(dst + i * 128, __float_as_uint(acc[1][3 * i]), __float_as_uint(acc[1][3 * i + 1]),
              __float_as_uint(i < 26 ? acc[1][3 * i + 2] : 0.f), epoch);
    TS(3, 13);
    const uint32_t slab = ring + (total & (STAGES - 1)) * stage_bytes + w * (16 * 320);
    const uint32_t addr = slab + (((l >> 3) & 1) * 8 + (l & 7)) * 320 + (l >> 4) * 16;
    mbar_wait(full0 + 8 * (total & (STAGES - 1)), (total / STAGES) & 1);
    #pragma unroll
    for (int jj = 0; jj < 10; jj++) {
      uint32_t z0, z1, z2, z3;
      ldsm4(addr + jj * 32, z0, z1, z2, z3);
      float* a = &acc[0][8 * jj];
      a[0] += bf_lo(z0); a[1] += bf_hi(z0); a[2] += bf_lo(z1); a[3] += bf_hi(z1);
      a[4] += bf_lo(z2); a[5] += bf_hi(z2); a[6] += bf_lo(z3); a[7] += bf_hi(z3);
    }
    {
      unsigned n = 0;
      while (ld_vol4(src + 26 * 128).w != epoch && ++n < POLL_LIMIT) __nanosleep(POLL_NS);
      uint4 v[27];
      while (true) {
        bool ok = true;
        #pragma unroll
        for (int i = 0; i < 27; i++) v[i] = ld_vol4(src + i * 128);
        #pragma unroll
        for (int i = 0; i < 27; i++) ok = ok && (v[i].w == epoch);
        if (ok || ++n > POLL_LIMIT) break;
      }
      #pragma unroll
      for (int i = 0; i < 27; i++) {
        acc[0][3 * i] += __uint_as_float(v[i].x);
        acc[0][3 * i + 1] += __uint_as_float(v[i].y);
        if (i < 26) acc[0][3 * i + 2] += __uint_as_float(v[i].z);
      }
    }
    TS(3, 14);
    #pragma unroll
    for (int jj = 0; jj < 10; jj++) {
      const float* a = &acc[0][8 * jj];
      stsm4(addr + jj * 32, pack_bf16(a[0], a[1]), pack_bf16(a[2], a[3]), pack_bf16(a[4], a[5]), pack_bf16(a[6], a[7]));
    }
    fence_async_smem();
    __syncwarp();
    if (l == 0) {
      tma_store_2d(&maps.m[M_OUT], slab, ct * 160, rb * 128 + grp * 64 + w * 16);
      bulk_commit();
      bulk_wait_read();
      if (w == 0) atomicAdd(&g_done, 1u);
    }
    TS(3, 15);
  }
}

typedef CUresult (*EncodeFn)(CUtensorMap*, CUtensorMapDataType, cuuint32_t, void*, const cuuint64_t*, const cuuint64_t*,
                             const cuuint32_t*, const cuuint32_t*, CUtensorMapInterleave, CUtensorMapSwizzle,
                             CUtensorMapL2promotion, CUtensorMapFloatOOBfill);

void make2d(EncodeFn enc, CUtensorMap* m, const void* p, uint64_t cols, uint64_t rows, uint32_t bc, uint32_t br, bool swz = true) {
  cuuint64_t gd[2] = {cols, rows}, gs[1] = {cols * 2};
  cuuint32_t bd[2] = {bc, br}, es[2] = {1, 1};
  enc(m, CU_TENSOR_MAP_DATA_TYPE_BFLOAT16, 2, const_cast<void*>(p), gd, gs, bd, es, CU_TENSOR_MAP_INTERLEAVE_NONE,
      swz ? CU_TENSOR_MAP_SWIZZLE_128B : CU_TENSOR_MAP_SWIZZLE_NONE, CU_TENSOR_MAP_L2_PROMOTION_L2_256B, CU_TENSOR_MAP_FLOAT_OOB_FILL_NONE);
}
void make3d(EncodeFn enc, CUtensorMap* m, const void* p, uint64_t cols, uint64_t rows, uint32_t cw, uint32_t nc) {
  cuuint64_t gd[3] = {cw, rows, cols / cw}, gs[2] = {cols * 2, cw * 2};
  cuuint32_t bd[3] = {cw, 64, nc}, es[3] = {1, 1, 1};
  enc(m, CU_TENSOR_MAP_DATA_TYPE_BFLOAT16, 3, const_cast<void*>(p), gd, gs, bd, es, CU_TENSOR_MAP_INTERLEAVE_NONE,
      cw == 64 ? CU_TENSOR_MAP_SWIZZLE_128B : CU_TENSOR_MAP_SWIZZLE_64B, CU_TENSOR_MAP_L2_PROMOTION_L2_256B, CU_TENSOR_MAP_FLOAT_OOB_FILL_NONE);
}

}

extern "C" void kernel_launch(void* const* d_in, const int* in_sizes, int n_in, void* d_out, int out_size) {
  const bf16* x = (const bf16*)d_in[0];
  const bf16* wsre = (const bf16*)d_in[1];
  const bf16* wsim = (const bf16*)d_in[2];
  const bf16* wdre = (const bf16*)d_in[3];
  const bf16* wdim = (const bf16*)d_in[4];
  const bf16* win = (const bf16*)d_in[6];
  const bf16* wsp = (const bf16*)d_in[7];
  const bf16* bsp = (const bf16*)d_in[8];
  const bf16* wout = (const bf16*)d_in[9];

  void* fn = nullptr;
  cudaDriverEntryPointQueryResult qr;
  cudaGetDriverEntryPoint("cuTensorMapEncodeTiled", &fn, cudaEnableDefault, &qr);
  EncodeFn enc = (EncodeFn)fn;
  void *abT, *z2, *h;
  cudaGetSymbolAddress(&abT, g_abT);
  cudaGetSymbolAddress(&z2, g_z2);
  cudaGetSymbolAddress(&h, g_h);

  Maps maps;
  make2d(enc, &maps.m[M_X], x, DM, SEQ, 64, 64);
  make2d(enc, &maps.m[M_XR], x, DM, SEQ, 160, 64, false);
  make3d(enc, &maps.m[M_WIN32], win, FF, DM, 32, 3);
  make2d(enc, &maps.m[M_WSRE], wsre, SEQ, SEQ, 64, 64);
  make2d(enc, &maps.m[M_WSIM], wsim, SEQ, SEQ, 64, 64);
  make2d(enc, &maps.m[M_WSP], wsp, SEQ, SEQ, 64, 64);
  make2d(enc, &maps.m[M_H], h, FH, SEQ, 64, 64);
  make3d(enc, &maps.m[M_WIN3], win, FF, DM, 64, 3);
  make3d(enc, &maps.m[M_Z23], z2, FH, SEQ, 64, 3);
  make2d(enc, &maps.m[M_WDRE], wdre, DM, DM, 64, 160);
  make2d(enc, &maps.m[M_WDIM], wdim, DM, DM, 64, 160);
  make2d(enc, &maps.m[M_AB], abT, SEQ, 2 * DM, 64, 160);
  make3d(enc, &maps.m[M_WOUT], wout, DM, FH, 32, 5);
  make2d(enc, &maps.m[M_OUT], d_out, DM, SEQ, 160, 16, false);

  cudaFuncSetAttribute(fused_kernel, cudaFuncAttributeMaxDynamicSharedMemorySize, SMEM_BYTES);
  fused_kernel<<<128, 384, SMEM_BYTES>>>(maps, x, win, bsp, wdre, wdim, wsp, wsre, wsim);
}
```

```cpp
#include <cuda_runtime.h>
#include <cuda_bf16.h>
#include <cuda.h>
#include <stdint.h>

namespace {

typedef __nv_bfloat16 bf16;

constexpr int SEQ = 2048, DM = 640, FF = 1536, FH = 768;
#define NXV 11
constexpr int NX = NXV;
constexpr int STAGES = 4;
constexpr int A_BYTES = 16384;
constexpr int ROWSTAT_OFF = 0;
constexpr int COLSUM_OFF = 1024;
constexpr int BIAS_OFF = 2560;
constexpr int BAR_OFF = 3072;
constexpr int RING_OFF = 4096;
constexpr int STAGE_A = 40960, STAGE_B = 36864;
constexpr int SMEM_BYTES = RING_OFF + 4 * STAGE_A + 49152;
constexpr int KB_A = 20 + 32 + NX + 12;
constexpr int KB_B = 30 + 64 - NX;
constexpr float LN_EPS = 1e-5f;
constexpr unsigned POLL_LIMIT = 100000;
#define POLL_NS 100
#define PF_DELAY 4500
#define Z1_NS 0
#define PF_NS 150

constexpr int BAR_ORD1 = 1, BAR_ORD2 = 2, BAR_WG1 = 3, BAR_WG2 = 4, BAR_STATS = 5, BAR_BUF = 6, BAR_Z1 = 7;

enum { M_X, M_XR, M_WIN32, M_WSRE, M_WSIM, M_WSP, M_H, M_WIN3, M_Z23, M_WDRE, M_WDIM, M_AB, M_WOUT, M_OUT, M_COUNT };
struct Maps { CUtensorMap m[M_COUNT]; };

__device__ __align__(1024) bf16 g_abT[2 * DM * SEQ];
__device__ __align__(1024) bf16 g_z2[SEQ * FH];
__device__ __align__(1024) bf16 g_h[SEQ * FH];
__device__ __align__(16) uint4 g_xstat[SEQ];
__device__ __align__(16) uint2 g_csum[16 * FF + 2 * DM];
__device__ __align__(16) uint4 g_zstat[128 * 128];
__device__ __align__(16) uint4 g_part[128 * 27 * 128];
__device__ unsigned g_flags[4 * 128];
constexpr int F_A = 0, F_B = 128, F_H = 256, F_Z = 384;
__device__ unsigned g_done;
#define TS(role, ev)
#define TC(i)

extern __shared__ __align__(1024) uint8_t smem[];

__device__ __forceinline__ uint32_t smem_u32(const void* p) { return (uint32_t)__cvta_generic_to_shared(p); }
__device__ __forceinline__ void mbar_init(uint32_t bar, uint32_t cnt) { asm volatile("mbarrier.init.shared::cta.b64 [%0], %1;" :: "r"(bar), "r"(cnt)); }
__device__ __forceinline__ void mbar_expect_tx(uint32_t bar, uint32_t bytes) { asm volatile("mbarrier.arrive.expect_tx.shared::cta.b64 _, [%0], %1;" :: "r"(bar), "r"(bytes) : "memory"); }
__device__ __forceinline__ void mbar_arrive(uint32_t bar) { asm volatile("mbarrier.arrive.shared::cta.b64 _, [%0];" :: "r"(bar) : "memory"); }
__device__ __forceinline__ void mbar_arrive_cluster(uint32_t bar, uint32_t cta) {
  asm volatile("{\n.reg .b32 ra;\nmapa.shared::cluster.u32 ra, %0, %1;\nmbarrier.arrive.shared::cluster.b64 _, [ra];\n}" :: "r"(bar), "r"(cta) : "memory");
}
__device__ __forceinline__ void mbar_wait(uint32_t bar, uint32_t parity) {
  asm volatile("{\n.reg .pred p;\n.reg .u32 n;\nmov.u32 n, 0;\n"
               "LW: mbarrier.try_wait.parity.shared::cta.b64 p, [%0], %1, 2000;\n@p bra LD;\n"
               "add.u32 n, n, 1;\nsetp.lt.u32 p, n, 20000;\n@p bra LW;\nLD:\n}" :: "r"(bar), "r"(parity) : "memory");
}
__device__ __forceinline__ void tma_load_2d(uint32_t dst, const CUtensorMap* map, uint32_t bar, int c0, int c1) {
  asm volatile("cp.async.bulk.tensor.2d.shared::cluster.global.mbarrier::complete_tx::bytes [%0], [%1, {%3, %4}], [%2];"
    :: "r"(dst), "l"((uint64_t)map), "r"(bar), "r"(c0), "r"(c1) : "memory");
}
__device__ __forceinline__ void tma_load_3d(uint32_t dst, const CUtensorMap* map, uint32_t bar, int c0, int c1, int c2) {
  asm volatile("cp.async.bulk.tensor.3d.shared::cluster.global.mbarrier::complete_tx::bytes [%0], [%1, {%3, %4, %5}], [%2];"
    :: "r"(dst), "l"((uint64_t)map), "r"(bar), "r"(c0), "r"(c1), "r"(c2) : "memory");
}
__device__ __forceinline__ void tma_load_2d_mc(uint32_t dst, const CUtensorMap* map, uint32_t bar, int c0, int c1, uint16_t mask) {
  asm volatile("cp.async.bulk.tensor.2d.shared::cluster.global.mbarrier::complete_tx::bytes.multicast::cluster [%0], [%1, {%3, %4}], [%2], %5;"
    :: "r"(dst), "l"((uint64_t)map), "r"(bar), "r"(c0), "r"(c1), "h"(mask) : "memory");
}
__device__ __forceinline__ void tma_store_2d(const CUtensorMap* map, uint32_t src, int c0, int c1) {
  asm volatile("cp.async.bulk.tensor.2d.global.shared::cta.bulk_group [%0, {%2, %3}], [%1];"
    :: "l"((uint64_t)map), "r"(src), "r"(c0), "r"(c1) : "memory");
}
__device__ __forceinline__ void bulk_commit() { asm volatile("cp.async.bulk.commit_group;" ::: "memory"); }
__device__ __forceinline__ void bulk_wait_read() { asm volatile("cp.async.bulk.wait_group.read 0;" ::: "memory"); }
__device__ __forceinline__ void fence_async_smem() { asm volatile("fence.proxy.async.shared::cta;" ::: "memory"); }
__device__ __forceinline__ void fence_async_global() { asm volatile("fence.proxy.async.global;" ::: "memory"); }
__device__ __forceinline__ void wgmma_fence() { asm volatile("wgmma.fence.sync.aligned;" ::: "memory"); }
__device__ __forceinline__ void wgmma_commit() { asm volatile("wgmma.commit_group.sync.aligned;" ::: "memory"); }
template<int N> __device__ __forceinline__ void wgmma_wait() { asm volatile("wgmma.wait_group.sync.aligned %0;" :: "n"(N) : "memory"); }
template<int ID> __device__ __forceinline__ void bar_sync(int n) { asm volatile("bar.sync %0, %1;" :: "n"(ID), "r"(n) : "memory"); }
template<int ID> __device__ __forceinline__ void bar_arrive(int n) { asm volatile("bar.arrive %0, %1;" :: "n"(ID), "r"(n) : "memory"); }
__device__ __forceinline__ void cluster_wait() { asm volatile("barrier.cluster.wait.aligned;" ::: "memory"); }
__device__ __forceinline__ uint64_t desc64(uint32_t lo, uint32_t hi) { return (uint64_t)lo | ((uint64_t)hi << 32); }
__device__ __forceinline__ uint4 ld_vol4(const uint4* p) {
  uint4 v; asm volatile("ld.volatile.global.v4.u32 {%0,%1,%2,%3}, [%4];" : "=r"(v.x), "=r"(v.y), "=r"(v.z), "=r"(v.w) : "l"(p) : "memory"); return v;
}
__device__ __forceinline__ uint2 ld_vol2(const uint2* p) {
  uint2 v; asm volatile("ld.volatile.global.v2.u32 {%0,%1}, [%2];" : "=r"(v.x), "=r"(v.y) : "l"(p) : "memory"); return v;
}
__device__ __forceinline__ void st_vol4(uint4* p, uint32_t a, uint32_t b, uint32_t c, uint32_t d) {
  asm volatile("st.volatile.global.v4.u32 [%0], {%1,%2,%3,%4};" :: "l"(p), "r"(a), "r"(b), "r"(c), "r"(d) : "memory");
}
__device__ __forceinline__ void st_vol2(uint2* p, uint32_t a, uint32_t b) {
  asm volatile("st.volatile.global.v2.u32 [%0], {%1,%2};" :: "l"(p), "r"(a), "r"(b) : "memory");
}
__device__ __forceinline__ void stg128(void* p, uint4 v) {
  asm volatile("st.global.v4.u32 [%0], {%1,%2,%3,%4};" :: "l"(p), "r"(v.x), "r"(v.y), "r"(v.z), "r"(v.w));
}
__device__ __forceinline__ unsigned ld_relaxed(const unsigned* p) {
  unsigned v; asm volatile("ld.relaxed.gpu.global.u32 %0, [%1];" : "=r"(v) : "l"(p) : "memory"); return v;
}
__device__ __forceinline__ uint32_t pack_bf16(float lo, float hi) {
  uint32_t r; asm("cvt.rn.bf16x2.f32 %0, %1, %2;" : "=r"(r) : "f"(hi), "f"(lo)); return r;
}
__device__ __forceinline__ float bf_lo(uint32_t v) { return __uint_as_float(v << 16); }
__device__ __forceinline__ float bf_hi(uint32_t v) { return __uint_as_float(v & 0xFFFF0000u); }
__device__ __forceinline__ void stsm4(uint32_t addr, uint32_t a, uint32_t b, uint32_t c, uint32_t d) {
  asm volatile("stmatrix.sync.aligned.m8n8.x4.shared.b16 [%0], {%1,%2,%3,%4};" :: "r"(addr), "r"(a), "r"(b), "r"(c), "r"(d));
}
__device__ __forceinline__ void stsm4_t(uint32_t addr, uint32_t a, uint32_t b, uint32_t c, uint32_t d) {
  asm volatile("stmatrix.sync.aligned.m8n8.x4.trans.shared.b16 [%0], {%1,%2,%3,%4};" :: "r"(addr), "r"(a), "r"(b), "r"(c), "r"(d));
}
__device__ __forceinline__ void ldsm4(uint32_t addr, uint32_t& a, uint32_t& b, uint32_t& c, uint32_t& d) {
  asm volatile("ldmatrix.sync.aligned.m8n8.x4.shared.b16 {%0,%1,%2,%3}, [%4];" : "=r"(a), "=r"(b), "=r"(c), "=r"(d) : "r"(addr));
}
__device__ __forceinline__ uint4 lds128(uint32_t a) {
  uint4 v; asm volatile("ld.shared.v4.u32 {%0,%1,%2,%3}, [%4];" : "=r"(v.x), "=r"(v.y), "=r"(v.z), "=r"(v.w) : "r"(a)); return v;
}
__device__ __forceinline__ void sts128(uint32_t a, uint32_t x, uint32_t y, uint32_t z, uint32_t w) {
  asm volatile("st.shared.v4.u32 [%0], {%1,%2,%3,%4};" :: "r"(a), "r"(x), "r"(y), "r"(z), "r"(w));
}
__device__ __forceinline__ uint32_t hmul2_bf16(uint32_t a, uint32_t b) {
  uint32_t r; asm("mul.rn.bf16x2 %0, %1, %2;" : "=r"(r) : "r"(a), "r"(b)); return r;
}
__device__ __forceinline__ float gelu_tanh(float v) {
  float u = v * fmaf(0.0356774081f, v * v, 0.7978845608f);
  float t; asm("tanh.approx.f32 %0, %1;" : "=f"(t) : "f"(u));
  float hv = 0.5f * v;
  return fmaf(hv, t, hv);
}

template<int TB>
__device__ __forceinline__ void wgmma_n192(float (&d)[96], uint64_t da, uint64_t db, int scale_d) {
  asm volatile("{\n.reg .pred p;\nsetp.ne.b32 p, %98, 0;\n"
   "wgmma.mma_async.sync.aligned.m64n192k16.f32.bf16.bf16 {%0,%1,%2,%3,%4,%5,%6,%7,%8,%9,%10,%11,%12,%13,%14,%15,%16,%17,%18,%19,%20,%21,%22,%23,%24,%25,%26,%27,%28,%29,%30,%31,%32,%33,%34,%35,%36,%37,%38,%39,%40,%41,%42,%43,%44,%45,%46,%47,%48,%49,%50,%51,%52,%53,%54,%55,%56,%57,%58,%59,%60,%61,%62,%63,%64,%65,%66,%67,%68,%69,%70,%71,%72,%73,%74,%75,%76,%77,%78,%79,%80,%81,%82,%83,%84,%85,%86,%87,%88,%89,%90,%91,%92,%93,%94,%95}, %96, %97, p, 1, 1, 0, %99;\n}"
   : "+f"(d[0]),"+f"(d[1]),"+f"(d[2]),"+f"(d[3]),"+f"(d[4]),"+f"(d[5]),"+f"(d[6]),"+f"(d[7]),"+f"(d[8]),"+f"(d[9]),"+f"(d[10]),"+f"(d[11]),"+f"(d[12]),"+f"(d[13]),"+f"(d[14]),"+f"(d[15]),"+f"(d[16]),"+f"(d[17]),"+f"(d[18]),"+f"(d[19]),"+f"(d[20]),"+f"(d[21]),"+f"(d[22]),"+f"(d[23]),"+f"(d[24]),"+f"(d[25]),"+f"(d[26]),"+f"(d[27]),"+f"(d[28]),"+f"(d[29]),"+f"(d[30]),"+f"(d[31]),"+f"(d[32]),"+f"(d[33]),"+f"(d[34]),"+f"(d[35]),"+f"(d[36]),"+f"(d[37]),"+f"(d[38]),"+f"(d[39]),"+f"(d[40]),"+f"(d[41]),"+f"(d[42]),"+f"(d[43]),"+f"(d[44]),"+f"(d[45]),"+f"(d[46]),"+f"(d[47]),"+f"(d[48]),"+f"(d[49]),"+f"(d[50]),"+f"(d[51]),"+f"(d[52]),"+f"(d[53]),"+f"(d[54]),"+f"(d[55]),"+f"(d[56]),"+f"(d[57]),"+f"(d[58]),"+f"(d[59]),"+f"(d[60]),"+f"(d[61]),"+f"(d[62]),"+f"(d[63]),"+f"(d[64]),"+f"(d[65]),"+f"(d[66]),"+f"(d[67]),"+f"(d[68]),"+f"(d[69]),"+f"(d[70]),"+f"(d[71]),"+f"(d[72]),"+f"(d[73]),"+f"(d[74]),"+f"(d[75]),"+f"(d[76]),"+f"(d[77]),"+f"(d[78]),"+f"(d[79]),"+f"(d[80]),"+f"(d[81]),"+f"(d[82]),"+f"(d[83]),"+f"(d[84]),"+f"(d[85]),"+f"(d[86]),"+f"(d[87]),"+f"(d[88]),"+f"(d[89]),"+f"(d[90]),"+f"(d[91]),"+f"(d[92]),"+f"(d[93]),"+f"(d[94]),"+f"(d[95])
   : "l"(da), "l"(db), "r"(scale_d), "n"(TB));
}
template<int TB>
__device__ __forceinline__ void wgmma_n160(float (&d)[80], uint64_t da, uint64_t db, int scale_d) {
  asm volatile("{\n.reg .pred p;\nsetp.ne.b32 p, %82, 0;\n"
   "wgmma.mma_async.sync.aligned.m64n160k16.f32.bf16.bf16 {%0,%1,%2,%3,%4,%5,%6,%7,%8,%9,%10,%11,%12,%13,%14,%15,%16,%17,%18,%19,%20,%21,%22,%23,%24,%25,%26,%27,%28,%29,%30,%31,%32,%33,%34,%35,%36,%37,%38,%39,%40,%41,%42,%43,%44,%45,%46,%47,%48,%49,%50,%51,%52,%53,%54,%55,%56,%57,%58,%59,%60,%61,%62,%63,%64,%65,%66,%67,%68,%69,%70,%71,%72,%73,%74,%75,%76,%77,%78,%79}, %80, %81, p, 1, 1, 0, %83;\n}"
   : "+f"(d[0]),"+f"(d[1]),"+f"(d[2]),"+f"(d[3]),"+f"(d[4]),"+f"(d[5]),"+f"(d[6]),"+f"(d[7]),"+f"(d[8]),"+f"(d[9]),"+f"(d[10]),"+f"(d[11]),"+f"(d[12]),"+f"(d[13]),"+f"(d[14]),"+f"(d[15]),"+f"(d[16]),"+f"(d[17]),"+f"(d[18]),"+f"(d[19]),"+f"(d[20]),"+f"(d[21]),"+f"(d[22]),"+f"(d[23]),"+f"(d[24]),"+f"(d[25]),"+f"(d[26]),"+f"(d[27]),"+f"(d[28]),"+f"(d[29]),"+f"(d[30]),"+f"(d[31]),"+f"(d[32]),"+f"(d[33]),"+f"(d[34]),"+f"(d[35]),"+f"(d[36]),"+f"(d[37]),"+f"(d[38]),"+f"(d[39]),"+f"(d[40]),"+f"(d[41]),"+f"(d[42]),"+f"(d[43]),"+f"(d[44]),"+f"(d[45]),"+f"(d[46]),"+f"(d[47]),"+f"(d[48]),"+f"(d[49]),"+f"(d[50]),"+f"(d[51]),"+f"(d[52]),"+f"(d[53]),"+f"(d[54]),"+f"(d[55]),"+f"(d[56]),"+f"(d[57]),"+f"(d[58]),"+f"(d[59]),"+f"(d[60]),"+f"(d[61]),"+f"(d[62]),"+f"(d[63]),"+f"(d[64]),"+f"(d[65]),"+f"(d[66]),"+f"(d[67]),"+f"(d[68]),"+f"(d[69]),"+f"(d[70]),"+f"(d[71]),"+f"(d[72]),"+f"(d[73]),"+f"(d[74]),"+f"(d[75]),"+f"(d[76]),"+f"(d[77]),"+f"(d[78]),"+f"(d[79])
   : "l"(da), "l"(db), "r"(scale_d), "n"(TB));
}
template<int TB>
__device__ __forceinline__ void wgmma_n96(float (&d)[48], uint64_t da, uint64_t db, int scale_d) {
  asm volatile("{\n.reg .pred p;\nsetp.ne.b32 p, %50, 0;\n"
   "wgmma.mma_async.sync.aligned.m64n96k16.f32.bf16.bf16 {%0,%1,%2,%3,%4,%5,%6,%7,%8,%9,%10,%11,%12,%13,%14,%15,%16,%17,%18,%19,%20,%21,%22,%23,%24,%25,%26,%27,%28,%29,%30,%31,%32,%33,%34,%35,%36,%37,%38,%39,%40,%41,%42,%43,%44,%45,%46,%47}, %48, %49, p, 1, 1, 0, %51;\n}"
   : "+f"(d[0]),"+f"(d[1]),"+f"(d[2]),"+f"(d[3]),"+f"(d[4]),"+f"(d[5]),"+f"(d[6]),"+f"(d[7]),"+f"(d[8]),"+f"(d[9]),"+f"(d[10]),"+f"(d[11]),"+f"(d[12]),"+f"(d[13]),"+f"(d[14]),"+f"(d[15]),"+f"(d[16]),"+f"(d[17]),"+f"(d[18]),"+f"(d[19]),"+f"(d[20]),"+f"(d[21]),"+f"(d[22]),"+f"(d[23]),"+f"(d[24]),"+f"(d[25]),"+f"(d[26]),"+f"(d[27]),"+f"(d[28]),"+f"(d[29]),"+f"(d[30]),"+f"(d[31]),"+f"(d[32]),"+f"(d[33]),"+f"(d[34]),"+f"(d[35]),"+f"(d[36]),"+f"(d[37]),"+f"(d[38]),"+f"(d[39]),"+f"(d[40]),"+f"(d[41]),"+f"(d[42]),"+f"(d[43]),"+f"(d[44]),"+f"(d[45]),"+f"(d[46]),"+f"(d[47])
   : "l"(da), "l"(db), "r"(scale_d), "n"(TB));
}

template<int N, int TB>
__device__ __forceinline__ void wgmma_n(float (&d)[N / 2], uint64_t da, uint64_t db) {
  if constexpr (N == 192) wgmma_n192<TB>(d, da, db, 1);
  else if constexpr (N == 160) wgmma_n160<TB>(d, da, db, 1);
  else wgmma_n96<TB>(d, da, db, 1);
}

template<int R>
__device__ __forceinline__ void pin(float (&acc)[2][R]) {
  #pragma unroll
  for (int mi = 0; mi < 2; mi++)
    #pragma unroll
    for (int i = 0; i < R; i++) asm volatile("" : "+f"(acc[mi][i]) :: "memory");
}
template<int R>
__device__ __forceinline__ void zero(float (&acc)[2][R]) {
  #pragma unroll
  for (int i = 0; i < R; i++) { acc[0][i] = 0.f; acc[1][i] = 0.f; }
  pin(acc);
}

template<int N, int TB, bool CONT, int ORD_BAR>
__device__ __forceinline__ void mainloop(float (&acc)[2][N / 2], uint32_t sbase, uint32_t stage_bytes, int g0, int nk, int total, int mswap) {
  const uint32_t full0 = sbase + BAR_OFF, empty0 = full0 + 8 * STAGES, ring = sbase + RING_OFF;
  const int t = threadIdx.x & 127;
  const uint32_t da0 = (((ring + mswap * 8192) & 0x3FFFF) >> 4) | 0x10000u, da1 = (((ring + (mswap ^ 1) * 8192) & 0x3FFFF) >> 4) | 0x10000u;
  const uint32_t db0 = (((ring + A_BYTES) & 0x3FFFF) >> 4) | ((TB == 2 ? 256u : TB ? 512u : 1u) << 16);
  constexpr uint32_t HI_A = 0x40000040u, HI_B = TB == 2 ? 0x80000020u : 0x40000040u;
  #pragma unroll 1
  for (int g = g0; g < g0 + nk; g++) {
    const int s = g & (STAGES - 1);
    const uint32_t so = s * (stage_bytes >> 4);
    mbar_wait(full0 + 8 * s, (g / STAGES) & 1);
    wgmma_fence();
    #pragma unroll
    for (int k = 0; k < 4; k++) {
      const uint64_t db = desc64(db0 + so + (TB == 2 ? k * 64 : TB ? k * 128 : k * 2), HI_B);
      wgmma_n<N, TB != 0>(acc[0], desc64(da0 + so + k * 2, HI_A), db);
      wgmma_n<N, TB != 0>(acc[1], desc64(da1 + so + k * 2, HI_A), db);
    }
    wgmma_commit();
    if (ORD_BAR != 0 && g == g0 + nk - 1) bar_arrive<ORD_BAR>(256);
    wgmma_wait<1>();
    if (t < 2 && (CONT || g > g0) && g - 1 + STAGES <= total) mbar_arrive_cluster(empty0 + 8 * ((g - 1) & (STAGES - 1)), t);
  }
}
template<int R>
__device__ __forceinline__ void drain(float (&acc)[2][R], uint32_t sbase, int glast, int total) {
  wgmma_wait<0>();
  pin(acc);
  const int t = threadIdx.x & 127;
  if (t < 2 && glast + STAGES <= total) mbar_arrive_cluster(sbase + BAR_OFF + 8 * STAGES + 8 * (glast & (STAGES - 1)), t);
}

__device__ __forceinline__ void publish(unsigned* flag, unsigned epoch) {
  asm volatile("fence.acq_rel.gpu;" ::: "memory");
  asm volatile("st.relaxed.gpu.global.u32 [%0], %1;" :: "l"(flag), "r"(epoch) : "memory");
}

__device__ __forceinline__ float sum8(uint4 v) {
  return ((bf_lo(v.x) + bf_hi(v.x)) + (bf_lo(v.y) + bf_hi(v.y))) + ((bf_lo(v.z) + bf_hi(v.z)) + (bf_lo(v.w) + bf_hi(v.w)));
}
__device__ __forceinline__ float oct_sum(float v) {
  v += __shfl_xor_sync(0xffffffffu, v, 1); v += __shfl_xor_sync(0xffffffffu, v, 2); v += __shfl_xor_sync(0xffffffffu, v, 4);
  return v;
}

__device__ __forceinline__ void stats_prologue(const bf16* __restrict__ x, const bf16* __restrict__ win, const bf16* __restrict__ wdre,
                                               const bf16* __restrict__ wdim, int rb, int c8, float* red, unsigned epoch) {
  const int t = threadIdx.x & 127, l = t & 31, cta = blockIdx.x;
  const int cg = t % 12, rg = min(t / 12, 9), tc = min(t, 95);
  #pragma unroll 1
  for (int p = 0; p < 2; p++) {
    const int wr = cta * 10 + min(t >> 3, 9);
    const bf16* src = p == 0 ? x + (size_t)(cta * 16 + (t >> 3)) * DM : wr < DM ? wdre + (size_t)wr * DM : wdim + (size_t)(wr - DM) * DM;
    const int col = (1 - p) * FH + c8 * 96;
    uint4 rv[10], cv[4];
    #pragma unroll
    for (int j = 0; j < 4; j++) cv[j] = __ldg(reinterpret_cast<const uint4*>(win + (size_t)(rb * 40 + rg * 4 + j) * FF + col) + cg);
    #pragma unroll
    for (int j = 0; j < 10; j++) rv[j] = __ldg(reinterpret_cast<const uint4*>(src) + (l & 7) + 8 * j);
    float* rp = red + p * 960;
    *reinterpret_cast<float4*>(rp + rg * 96 + cg * 8) = make_float4(
        (bf_lo(cv[0].x) + bf_lo(cv[1].x)) + (bf_lo(cv[2].x) + bf_lo(cv[3].x)), (bf_hi(cv[0].x) + bf_hi(cv[1].x)) + (bf_hi(cv[2].x) + bf_hi(cv[3].x)),
        (bf_lo(cv[0].y) + bf_lo(cv[1].y)) + (bf_lo(cv[2].y) + bf_lo(cv[3].y)), (bf_hi(cv[0].y) + bf_hi(cv[1].y)) + (bf_hi(cv[2].y) + bf_hi(cv[3].y)));
    *reinterpret_cast<float4*>(rp + rg * 96 + cg * 8 + 4) = make_float4(
        (bf_lo(cv[0].z) + bf_lo(cv[1].z)) + (bf_lo(cv[2].z) + bf_lo(cv[3].z)), (bf_hi(cv[0].z) + bf_hi(cv[1].z)) + (bf_hi(cv[2].z) + bf_hi(cv[3].z)),
        (bf_lo(cv[0].w) + bf_lo(cv[1].w)) + (bf_lo(cv[2].w) + bf_lo(cv[3].w)), (bf_hi(cv[0].w) + bf_hi(cv[1].w)) + (bf_hi(cv[2].w) + bf_hi(cv[3].w)));
    float s = 0.f;
    #pragma unroll
    for (int j = 0; j < 10; j++) s += sum8(rv[j]);
    s = oct_sum(s);
    if (p == 0) {
      const float mean = s * (1.f / DM);
      float q = 0.f;
      #pragma unroll
      for (int j = 0; j < 10; j++) {
        const uint32_t u[4] = {rv[j].x, rv[j].y, rv[j].z, rv[j].w};
        #pragma unroll
        for (int c = 0; c < 4; c++) { const float d0 = bf_lo(u[c]) - mean, d1 = bf_hi(u[c]) - mean; q = fmaf(d0, d0, q); q = fmaf(d1, d1, q); }
      }
      const float rstd = rsqrtf(fmaf(oct_sum(q), 1.f / DM, LN_EPS));
      if ((l & 7) == 0) st_vol4(&g_xstat[cta * 16 + (t >> 3)], __float_as_uint(rstd), __float_as_uint(-mean * rstd), epoch, 0u);
    } else if ((l & 7) == 0) {
      st_vol2(&g_csum[16 * FF + wr], __float_as_uint(s), epoch);
    }
    bar_sync<BAR_WG2>(128);
    float c = 0.f;
    #pragma unroll
    for (int i = 0; i < 10; i++) c += rp[i * 96 + tc];
    st_vol2(&g_csum[rb * FF + col + tc], __float_as_uint(c), epoch);
  }
}

template<int NP>
__device__ __forceinline__ float gather_sum(const uint2* src, unsigned epoch) {
  unsigned it = 0;
  while (true) {
    uint2 u[NP];
    #pragma unroll
    for (int i = 0; i < NP; i++) u[i] = ld_vol2(src + i * FF);
    bool ok = true;
    float a = 0.f;
    #pragma unroll
    for (int i = 0; i < NP; i++) { ok = ok && u[i].y == epoch; a += __uint_as_float(u[i].x); }
    if (ok || ++it > POLL_LIMIT) return a;
    __nanosleep(POLL_NS);
  }
}

__device__ __forceinline__ void fold_pack(const float* a, float2 s0, float2 s1, float2 c0, float2 c1, uint32_t (&r)[4]) {
  r[0] = pack_bf16(fmaf(a[0], s0.x, s0.y * c0.x), fmaf(a[1], s0.x, s0.y * c0.y));
  r[1] = pack_bf16(fmaf(a[2], s1.x, s1.y * c0.x), fmaf(a[3], s1.x, s1.y * c0.y));
  r[2] = pack_bf16(fmaf(a[4], s0.x, s0.y * c1.x), fmaf(a[5], s0.x, s0.y * c1.y));
  r[3] = pack_bf16(fmaf(a[6], s1.x, s1.y * c1.x), fmaf(a[7], s1.x, s1.y * c1.y));
}

__global__ void __cluster_dims__(2, 1, 1) __launch_bounds__(384, 1)
fused_kernel(const __grid_constant__ Maps maps, const bf16* __restrict__ x, const bf16* __restrict__ win,
             const bf16* __restrict__ bsp, const bf16* __restrict__ wdre, const bf16* __restrict__ wdim,
             const bf16* __restrict__ wsp, const bf16* __restrict__ wsre, const bf16* __restrict__ wsim) {
  const uint32_t sbase = smem_u32(smem);
  const uint32_t full0 = sbase + BAR_OFF, empty0 = full0 + 8 * STAGES, dep0 = empty0 + 8 * STAGES, ring = sbase + RING_OFF;
  const int tid = threadIdx.x, wg = __shfl_sync(0xffffffffu, tid >> 7, 0);
  const int rank = blockIdx.x & 1, grp = (blockIdx.x >> 1) & 1, q = blockIdx.x >> 2;
  const int rb = q >> 1, ct = (q & 1) * 2 + rank, c8 = grp * 4 + ct;
  const int total = grp == 0 ? KB_A : KB_B;
  const uint32_t stage_bytes = grp == 0 ? STAGE_A : STAGE_B;

  if (tid == 0) {
    TS(0, 0);
    for (int s = 0; s < STAGES; s++) { mbar_init(full0 + 8 * s, 2); mbar_init(empty0 + 8 * s, 2); mbar_init(dep0 + 8 * s, 1); }
    asm volatile("fence.mbarrier_init.release.cluster;" ::: "memory");
  }
  __syncthreads();
  asm volatile("barrier.cluster.arrive.relaxed.aligned;" ::: "memory");

  if (wg == 0) {
    asm volatile("setmaxnreg.dec.sync.aligned.u32 40;");
    const int warp = tid >> 5, lane = tid & 31;
    if (warp == 0) {
      const int row = rb * 128;
      if (lane == 0) {
        TS(0, 1);
        for (int g = 0; g < STAGES; g++) {
          mbar_expect_tx(full0 + 8 * g, A_BYTES);
          tma_load_2d(ring + g * stage_bytes, &maps.m[M_X], full0 + 8 * g, g * 64, row);
          tma_load_2d(ring + g * stage_bytes + 8192, &maps.m[M_X], full0 + 8 * g, g * 64, row + 64);
        }
      }
      __syncwarp();
      cluster_wait();
      if (lane == 0) {
        #pragma unroll 1
        for (int g = STAGES; g < total; g++) {
          int mi, kb;
          if (g < 20) { mi = M_X; kb = g < 10 ? g : g - 10; }
          else if (grp == 0) {
            if (g < 52) { mi = M_WSP; kb = g - 20; }
            else if (g < 52 + NX) { mi = M_WSIM; kb = g - 52 + 32 - NX; }
            else { mi = M_H; kb = g - 52 - NX; }
          } else {
            if (g < 30) { mi = M_X; kb = g - 20; }
            else if (g < 62) { mi = M_WSRE; kb = g - 30; }
            else { mi = M_WSIM; kb = g - 62; }
          }
          if (mi == M_H && kb == 0) { TS(0, 3); mbar_wait(dep0 + 24, 0); fence_async_global(); TS(0, 4); }
          const int s = g & (STAGES - 1);
          mbar_wait(empty0 + 8 * s, ((g / STAGES) & 1) ^ 1);
          mbar_expect_tx(full0 + 8 * s, A_BYTES);
          tma_load_2d_mc(ring + s * stage_bytes + rank * 8192, &maps.m[mi], full0 + 8 * s, kb * 64, row + rank * 64, 3);
        }
        const int s = total & (STAGES - 1);
        mbar_wait(empty0 + 8 * s, ((total / STAGES) & 1) ^ 1);
        mbar_expect_tx(full0 + 8 * s, 20480);
        mbar_arrive(full0 + 8 * s);
        tma_load_2d(ring + s * stage_bytes, &maps.m[M_XR], full0 + 8 * s, ct * 160, row + grp * 64);
        TS(0, 5);
      }
    } else if (warp == 1) {
      if (lane == 0) {
        #pragma unroll 1
        for (int g = 0; g < total; g++) {
          int kind = 1, mi, kb, c, dep = 0;
          uint32_t bytes = 20480;
          if (g < 10) { kind = 0; mi = M_WIN32; kb = g; c = 24 + 3 * c8; bytes = 12288; }
          else if (grp == 0) {
            if (g < 20) { kind = 0; mi = M_WIN3; kb = g - 10; c = 3 * ct; bytes = 24576; }
            else if (g < 52) { kind = 0; mi = M_Z23; kb = g - 20; c = 3 * ct; bytes = 24576; dep = g == 20 ? 1 : 0; }
            else if (g < 52 + NX) { mi = M_AB; kb = g - 52 + 32 - NX; c = DM + ct * 160; dep = g == 52 ? 2 : 0; }
            else { kind = 0; mi = M_WOUT; kb = g - 52 - NX; c = ct * 5; }
          } else {
            if (g < 30) { mi = g < 20 ? M_WDRE : M_WDIM; kb = g < 20 ? g - 10 : g - 20; c = ct * 160; }
            else { mi = M_AB; kb = g < 62 ? g - 30 : g - 62; c = ct * 160 + (g < 62 ? 0 : DM); dep = g == 30 ? 1 : g == 62 ? 2 : 0; }
          }
          if (dep) { TS(1, dep * 2 - 2); mbar_wait(dep0 + 8 * dep, 0); fence_async_global(); TS(1, dep * 2 - 1); TC(dep); }
          const int s = g & (STAGES - 1);
          const uint32_t dst = ring + s * stage_bytes + A_BYTES, fb = full0 + 8 * s;
          mbar_wait(empty0 + 8 * s, ((g / STAGES) & 1) ^ 1);
          mbar_expect_tx(fb, bytes);
          if (kind == 0) tma_load_3d(dst, &maps.m[mi], fb, 0, kb * 64, c);
          else tma_load_2d(dst, &maps.m[mi], fb, kb * 64, c);
        }
      }
      __syncwarp();
      cluster_wait();
    } else if (warp == 2) {
      cluster_wait();
      const unsigned epoch = (*reinterpret_cast<volatile unsigned*>(&g_done) >> 7) + 1u;
      #pragma unroll 1
      for (int d = 1; d < 4 - grp; d++) {
        const int fi = d == 3 ? F_H + rb * 4 + (lane & 3)
                     : (d == 1 && grp == 0) ? F_Z + (lane >> 1) * 8 + ct * 2 + (lane & 1)
                     : (d == 1 ? F_A : F_B) + (lane & 15) * 4 + ct;
        unsigned it = 0;
        while (!__all_sync(0xffffffffu, ld_relaxed(g_flags + fi) == epoch) && ++it < POLL_LIMIT) __nanosleep(20);
        fence_async_global();
        __syncwarp();
        if (lane == 0) mbar_arrive(dep0 + 8 * d);
      }
    } else {
      cluster_wait();
      if (lane == 0) {
        __nanosleep(PF_DELAY);
        #pragma unroll 1
        for (int i = 0; i < 32 * (1 + grp); i++) {
          const bf16* p = (grp == 0 ? wsp : i < 32 ? wsre : wsim) + (size_t)(rb * 128 + ct * 32 + (i & 31)) * SEQ;
          asm volatile("cp.async.bulk.prefetch.L2.global [%0], 4096;" :: "l"(p) : "memory");
          __nanosleep(PF_NS);
        }
      }
    }
  } else {
    asm volatile("setmaxnreg.inc.sync.aligned.u32 232;");
    const int t = tid & 127, w = t >> 5, l = t & 31;
    const uint32_t buf = ring + 4 * stage_bytes;
    const unsigned epoch = (*reinterpret_cast<volatile unsigned*>(&g_done) >> 7) + 1u;
    cluster_wait();
    const int rl = w * 16 + ((l >> 3) & 1) * 8 + (l & 7);
    const int gr = w * 16 + (l & 15);
    const uint32_t st_base = buf + rl * 128;
    const uint32_t st_x = ((l >> 4) ^ (l & 7)) << 4;
    float* csw = reinterpret_cast<float*>(smem + COLSUM_OFF) + (wg - 1) * 192;
    const float2* rs = reinterpret_cast<const float2*>(smem + ROWSTAT_OFF) + w * 16 + (l >> 2);
    const float2* cs = reinterpret_cast<const float2*>(csw) + (l & 3);
    if (wg == 1) {
      float acc[2][48];
      zero(acc);
      mainloop<96, 2, false, BAR_ORD1>(acc, sbase, stage_bytes, 0, 10, total, 0);
      {
        unsigned n = 0;
        uint4 v = ld_vol4(&g_xstat[rb * 128 + t]);
        csw[min(t, 95)] = gather_sum<16>(g_csum + FH + c8 * 96 + min(t, 95), epoch);
        while (v.z != epoch && ++n < POLL_LIMIT) { __nanosleep(POLL_NS); v = ld_vol4(&g_xstat[rb * 128 + t]); }
        reinterpret_cast<float2*>(smem + ROWSTAT_OFF)[t] = make_float2(__uint_as_float(v.x), __uint_as_float(v.y));
      }
      drain(acc, sbase, 9, total);
      TS(2, 2);
      bar_arrive<BAR_STATS>(256);
      bar_sync<BAR_WG1>(128);
      float sum[4], sq[4];
      #pragma unroll
      for (int r = 0; r < 4; r++) {
        const float2 st = rs[(r >> 1) * 64 + (r & 1) * 8];
        float s0 = 0.f, q0 = 0.f;
        #pragma unroll
        for (int j = 0; j < 12; j++) {
          const float2 c = cs[j * 4];
          float* a = &acc[r >> 1][4 * j + (r & 1) * 2];
          a[0] = gelu_tanh(fmaf(a[0], st.x, st.y * c.x));
          a[1] = gelu_tanh(fmaf(a[1], st.x, st.y * c.y));
          s0 += a[0] + a[1]; q0 = fmaf(a[0], a[0], q0); q0 = fmaf(a[1], a[1], q0);
        }
        s0 += __shfl_xor_sync(0xffffffffu, s0, 1); q0 += __shfl_xor_sync(0xffffffffu, q0, 1);
        s0 += __shfl_xor_sync(0xffffffffu, s0, 2); q0 += __shfl_xor_sync(0xffffffffu, q0, 2);
        sum[r] = s0; sq[r] = q0;
      }
      TS(2, 4);
      float rstd, off;
      {
        const int qd = l & 3;
        const float sm = qd == 0 ? sum[0] : qd == 1 ? sum[1] : qd == 2 ? sum[2] : sum[3];
        const float sv = qd == 0 ? sq[0] : qd == 1 ? sq[1] : qd == 2 ? sq[2] : sq[3];
        const int row = (qd >> 1) * 64 + w * 16 + (qd & 1) * 8 + (l >> 2);
        const float mu = sm * (1.f / 96), m2 = fmaxf(sv - sm * mu, 0.f);
        st_vol4(&g_zstat[(rb * 8 + c8) * 128 + row], __float_as_uint(mu), __float_as_uint(m2), epoch, 0u);
        uint4 v[7];
        unsigned n = 0;
        while (true) {
          bool ok = true;
          #pragma unroll
          for (int j = 0; j < 7; j++) v[j] = ld_vol4(&g_zstat[(rb * 8 + ((c8 + 1 + j) & 7)) * 128 + row]);
          #pragma unroll
          for (int j = 0; j < 7; j++) ok = ok && v[j].z == epoch;
          if (ok || ++n > POLL_LIMIT) break;
          __nanosleep(POLL_NS);
        }
        float mean = mu, var = m2;
        #pragma unroll
        for (int j = 0; j < 7; j++) { mean += __uint_as_float(v[j].x); var += __uint_as_float(v[j].y); }
        mean *= 0.125f;
        float d = (mu - mean) * (mu - mean);
        #pragma unroll
        for (int j = 0; j < 7; j++) d = fmaf(__uint_as_float(v[j].x) - mean, __uint_as_float(v[j].x) - mean, d);
        rstd = rsqrtf(fmaf(96.f, d, var) * (1.f / FH) + LN_EPS); off = -mean * rstd;
        __syncwarp();
      }
      TS(2, 5);
      #pragma unroll
      for (int mi = 0; mi < 2; mi++) {
        const float r0 = __shfl_sync(0xffffffffu, rstd, (l & 28) + mi * 2), o0 = __shfl_sync(0xffffffffu, off, (l & 28) + mi * 2);
        const float r1 = __shfl_sync(0xffffffffu, rstd, (l & 28) + mi * 2 + 1), o1 = __shfl_sync(0xffffffffu, off, (l & 28) + mi * 2 + 1);
        #pragma unroll
        for (int jj = 0; jj < 6; jj++) {
          const float* a = &acc[mi][8 * jj];
          stsm4(buf + (jj >> 1) * 8192 + mi * 4096 + rl * 64 + ((((jj & 1) * 2 + (l >> 4)) ^ ((l >> 1) & 3)) << 4),
                pack_bf16(fmaf(a[0], r0, o0), fmaf(a[1], r0, o0)), pack_bf16(fmaf(a[2], r1, o1), fmaf(a[3], r1, o1)),
                pack_bf16(fmaf(a[4], r0, o0), fmaf(a[5], r0, o0)), pack_bf16(fmaf(a[6], r1, o1), fmaf(a[7], r1, o1)));
        }
      }
      __syncwarp();
      #pragma unroll
      for (int i = 0; i < 4; i++) {
        const int rr = (i >> 1) * 64 + w * 16 + (i & 1) * 8 + (l >> 2);
        uint4 z[3];
        #pragma unroll
        for (int c = 0; c < 3; c++) z[c] = lds128(buf + c * 8192 + rr * 64 + (((l & 3) ^ ((rr >> 1) & 3)) << 4));
        #pragma unroll
        for (int c = 0; c < 3; c++) stg128(g_z2 + (size_t)(rb * 128 + rr) * FH + c8 * 96 + c * 32 + (l & 3) * 8, z[c]);
      }
      bar_sync<BAR_WG1>(128);
      TS(2, 6);
      if (t == 0) publish(g_flags + F_Z + rb * 8 + c8, epoch);
      __syncwarp();
      TS(2, 10);
      if (grp == 0) {
        bar_arrive<BAR_BUF>(256);
        float acc[2][96];
        zero(acc);
        bar_sync<BAR_ORD2>(256);
        mainloop<192, 1, false, BAR_ORD1>(acc, sbase, STAGE_A, 20, 32, KB_A, 0);
        const float* bias = reinterpret_cast<const float*>(smem + BIAS_OFF) + w * 16 + (l >> 2);
        bar_sync<BAR_Z1>(256);
        drain(acc, sbase, 51, KB_A);
        TS(2, 7);
        #pragma unroll
        for (int mi = 0; mi < 2; mi++) {
          const float b0 = bias[mi * 64], b1 = bias[mi * 64 + 8];
          #pragma unroll
          for (int j4 = 0; j4 < 3; j4++) {
            uint32_t z[4][4];
            #pragma unroll
            for (int i = 0; i < 4; i++) ldsm4(st_base + mi * 24576 + j4 * 8192 + (st_x ^ (i << 5)), z[i][0], z[i][1], z[i][2], z[i][3]);
            #pragma unroll
            for (int i = 0; i < 4; i++) {
              const float* a = &acc[mi][8 * (j4 * 4 + i)];
              stsm4(st_base + mi * 24576 + j4 * 8192 + (st_x ^ (i << 5)),
                    hmul2_bf16(z[i][0], pack_bf16(a[0] + b0, a[1] + b0)), hmul2_bf16(z[i][1], pack_bf16(a[2] + b1, a[3] + b1)),
                    hmul2_bf16(z[i][2], pack_bf16(a[4] + b0, a[5] + b0)), hmul2_bf16(z[i][3], pack_bf16(a[6] + b1, a[7] + b1)));
            }
          }
        }
        __syncwarp();
        TS(2, 8);
        #pragma unroll 1
        for (int i = 0; i < 6; i++) {
          uint4 z[4];
          const int r0 = w * 16 + (l >> 3);
          #pragma unroll
          for (int j = 0; j < 4; j++) z[j] = lds128(buf + i * 8192 + (r0 + j * 4) * 128 + (((l ^ (r0 + j * 4)) & 7) << 4));
          bf16* p = g_h + (size_t)(rb * 128 + (i / 3) * 64 + r0) * FH + ct * 192 + (i % 3) * 64 + (l & 7) * 8;
          #pragma unroll
          for (int j = 0; j < 4; j++) stg128(p + (size_t)j * 4 * FH, z[j]);
        }
        bar_sync<BAR_WG1>(128);
        if (t == 0) publish(g_flags + F_H + rb * 4 + ct, epoch);
        TS(2, 9);
        return;
      }
    } else {
      stats_prologue(x, win, wdre, wdim, rb, c8, reinterpret_cast<float*>(smem + (buf - sbase) + 24576), epoch);
      TS(3, 0);
      if (grp == 0) {
        reinterpret_cast<float*>(smem + BIAS_OFF)[t] = __bfloat162float(bsp[rb * 128 + t]);
        float acc[2][96];
        zero(acc);
        bar_sync<BAR_ORD1>(256);
        mainloop<192, 1, false, BAR_ORD2>(acc, sbase, STAGE_A, 10, 10, KB_A, 0);
        drain(acc, sbase, 19, KB_A);
        TS(3, 2);
        #pragma unroll 1
        for (int i = 0; i < 3; i++) {
          const int c = i * 64 + (t >> 1);
          float v = gather_sum<8>(g_csum + (t & 1) * 8 * FF + ct * 192 + c, epoch);
          v += __shfl_xor_sync(0xffffffffu, v, 1);
          csw[c] = v;
        }
        bar_sync<BAR_STATS>(256);
        bar_sync<BAR_BUF>(256);
        const float2 s0 = rs[0], s1 = rs[8], s2 = rs[64], s3 = rs[72];
        #pragma unroll
        for (int jj = 0; jj < 12; jj++) {
          uint32_t r[4];
          const float2 c0 = cs[jj * 8], c1 = cs[jj * 8 + 4];
          const uint32_t ad = st_base + (jj >> 2) * 8192 + (st_x ^ ((jj & 3) << 5));
          fold_pack(&acc[0][8 * jj], s0, s1, c0, c1, r);
          stsm4(ad, r[0], r[1], r[2], r[3]);
          fold_pack(&acc[1][8 * jj], s2, s3, c0, c1, r);
          stsm4(ad + 24576, r[0], r[1], r[2], r[3]);
        }
        __syncwarp();
        TS(3, 3);
        const uint32_t rbase = buf + (l >> 4) * 24576 + gr * 128;
        #pragma unroll 1
        for (int c2 = 0; c2 < 12; c2++) {
          const uint32_t ab = rbase + (c2 >> 2) * 8192;
          uint4 v[2];
          #pragma unroll
          for (int i = 0; i < 2; i++) v[i] = lds128(ab + (((((c2 & 3) * 2 + i) ^ l) & 7) << 4));
          #pragma unroll
          for (int i = 0; i < 2; i++)
            sts128(ab + (((((c2 & 3) * 2 + i) ^ l) & 7) << 4),
                   pack_bf16(gelu_tanh(bf_lo(v[i].x)), gelu_tanh(bf_hi(v[i].x))), pack_bf16(gelu_tanh(bf_lo(v[i].y)), gelu_tanh(bf_hi(v[i].y))),
                   pack_bf16(gelu_tanh(bf_lo(v[i].z)), gelu_tanh(bf_hi(v[i].z))), pack_bf16(gelu_tanh(bf_lo(v[i].w)), gelu_tanh(bf_hi(v[i].w))));
        }
        TS(3, 4);
        bar_arrive<BAR_Z1>(256);
      }
    }
    float acc[2][80];
    if (grp == 1) {
      zero(acc);
      if (wg == 2) {
        bar_sync<BAR_ORD1>(256);
        mainloop<160, 0, false, BAR_ORD2>(acc, sbase, STAGE_B, 10, 10, KB_B, 0);
      } else {
        bar_sync<BAR_ORD2>(256);
        mainloop<160, 0, false, BAR_ORD1>(acc, sbase, STAGE_B, 20, 10, KB_B, 0);
      }
      csw[t] = gather_sum<1>(g_csum + 16 * FF + (2 - wg) * DM + ct * 160 + t, epoch);
      csw[128 + l] = gather_sum<1>(g_csum + 16 * FF + (2 - wg) * DM + ct * 160 + 128 + l, epoch);
      drain(acc, sbase, wg == 2 ? 19 : 29, KB_B);
      TS(wg + 1, wg == 1 ? 7 : 2);
      if (wg == 1) bar_sync<BAR_BUF>(256); else bar_sync<BAR_STATS>(256);
      const float sign = wg == 1 ? -1.f : 1.f;
      const uint32_t tb = buf + 24576 + ((l >> 4) * 8 + (l & 7)) * 128 + (((w * 2 + ((l >> 3) & 1)) ^ (l & 7)) << 4);
      float2 s0 = rs[0], s1 = rs[8], s2 = rs[64], s3 = rs[72];
      s0.x *= sign; s0.y *= sign; s1.x *= sign; s1.y *= sign; s2.x *= sign; s2.y *= sign; s3.x *= sign; s3.y *= sign;
      #pragma unroll
      for (int jj = 0; jj < 10; jj++) {
        uint32_t r[4];
        const float2 c0 = cs[jj * 8], c1 = cs[jj * 8 + 4];
        fold_pack(&acc[0][8 * jj], s0, s1, c0, c1, r);
        stsm4_t(tb + jj * 2048, r[0], r[1], r[2], r[3]);
        fold_pack(&acc[1][8 * jj], s2, s3, c0, c1, r);
        stsm4_t(tb + 20480 + jj * 2048, r[0], r[1], r[2], r[3]);
      }
      if (wg == 1) bar_sync<BAR_WG1>(128); else bar_sync<BAR_WG2>(128);
      TS(wg + 1, wg == 1 ? 8 : 6);
      #pragma unroll 1
      for (int i = 0; i < 4; i++) {
        uint4 z[5];
        const int e0 = (i & 1) * 80 + (t >> 3);
        #pragma unroll
        for (int j = 0; j < 5; j++) z[j] = lds128(buf + 24576 + (i >> 1) * 20480 + (e0 + j * 16) * 128 + (((l ^ e0) & 7) << 4));
        bf16* p = g_abT + (size_t)((2 - wg) * DM + ct * 160 + e0) * SEQ + rb * 128 + (i >> 1) * 64 + (l & 7) * 8;
        #pragma unroll
        for (int j = 0; j < 5; j++) stg128(p + (size_t)j * 16 * SEQ, z[j]);
      }
      if (wg == 1) bar_sync<BAR_WG1>(128); else bar_sync<BAR_WG2>(128);
      if (t == 0) publish(g_flags + (wg == 2 ? F_A : F_B) + rb * 4 + ct, epoch);
      TS(wg + 1, wg == 1 ? 9 : 10);
      if (wg == 1) return;
      bar_arrive<BAR_BUF>(256);
    }
    zero(acc);
    bar_sync<BAR_ORD1>(256);
    mainloop<160, 0, false, 0>(acc, sbase, stage_bytes, grp == 0 ? 52 : 30, grp == 0 ? NX : 64 - NX, total, grp);
    if (grp == 0) mainloop<160, 2, true, 0>(acc, sbase, STAGE_A, 52 + NX, 12, KB_A, 0);
    drain(acc, sbase, total - 1, total);
    TS(3, 12);
    uint4* dst = g_part + (size_t)blockIdx.x * 27 * 128 + t;
    const uint4* src = g_part + (size_t)(blockIdx.x ^ 2) * 27 * 128 + t;
    #pragma unroll
    for (int i = 0; i < 27; i++)
      st_vol4(dst + i * 128, __float_as_uint(acc[1][3 * i]), __float_as_uint(acc[1][3 * i + 1]),
              __float_as_uint(i < 26 ? acc[1][3 * i + 2] : 0.f), epoch);
    TS(3, 13);
    const uint32_t slab = ring + (total & (STAGES - 1)) * stage_bytes + w * (16 * 320);
    const uint32_t addr = slab + (((l >> 3) & 1) * 8 + (l & 7)) * 320 + (l >> 4) * 16;
    mbar_wait(full0 + 8 * (total & (STAGES - 1)), (total / STAGES) & 1);
    #pragma unroll
    for (int jj = 0; jj < 10; jj++) {
      uint32_t z0, z1, z2, z3;
      ldsm4(addr + jj * 32, z0, z1, z2, z3);
      float* a = &acc[0][8 * jj];
      a[0] += bf_lo(z0); a[1] += bf_hi(z0); a[2] += bf_lo(z1); a[3] += bf_hi(z1);
      a[4] += bf_lo(z2); a[5] += bf_hi(z2); a[6] += bf_lo(z3); a[7] += bf_hi(z3);
    }
    {
      unsigned n = 0;
      while (ld_vol4(src + 26 * 128).w != epoch && ++n < POLL_LIMIT) __nanosleep(POLL_NS);
      uint4 v[27];
      while (true) {
        bool ok = true;
        #pragma unroll
        for (int i = 0; i < 27; i++) v[i] = ld_vol4(src + i * 128);
        #pragma unroll
        for (int i = 0; i < 27; i++) ok = ok && (v[i].w == epoch);
        if (ok || ++n > POLL_LIMIT) break;
      }
      #pragma unroll
      for (int i = 0; i < 27; i++) {
        acc[0][3 * i] += __uint_as_float(v[i].x);
        acc[0][3 * i + 1] += __uint_as_float(v[i].y);
        if (i < 26) acc[0][3 * i + 2] += __uint_as_float(v[i].z);
      }
    }
    TS(3, 14);
    #pragma unroll
    for (int jj = 0; jj < 10; jj++) {
      const float* a = &acc[0][8 * jj];
      stsm4(addr + jj * 32, pack_bf16(a[0], a[1]), pack_bf16(a[2], a[3]), pack_bf16(a[4], a[5]), pack_bf16(a[6], a[7]));
    }
    fence_async_smem();
    __syncwarp();
    if (l == 0) {
      tma_store_2d(&maps.m[M_OUT], slab, ct * 160, rb * 128 + grp * 64 + w * 16);
      bulk_commit();
      bulk_wait_read();
      if (w == 0) atomicAdd(&g_done, 1u);
    }
    TS(3, 15);
  }
}

typedef CUresult (*EncodeFn)(CUtensorMap*, CUtensorMapDataType, cuuint32_t, void*, const cuuint64_t*, const cuuint64_t*,
                             const cuuint32_t*, const cuuint32_t*, CUtensorMapInterleave, CUtensorMapSwizzle,
                             CUtensorMapL2promotion, CUtensorMapFloatOOBfill);

void make2d(EncodeFn enc, CUtensorMap* m, const void* p, uint64_t cols, uint64_t rows, uint32_t bc, uint32_t br, bool swz = true) {
  cuuint64_t gd[2] = {cols, rows}, gs[1] = {cols * 2};
  cuuint32_t bd[2] = {bc, br}, es[2] = {1, 1};
  enc(m, CU_TENSOR_MAP_DATA_TYPE_BFLOAT16, 2, const_cast<void*>(p), gd, gs, bd, es, CU_TENSOR_MAP_INTERLEAVE_NONE,
      swz ? CU_TENSOR_MAP_SWIZZLE_128B : CU_TENSOR_MAP_SWIZZLE_NONE, CU_TENSOR_MAP_L2_PROMOTION_L2_256B, CU_TENSOR_MAP_FLOAT_OOB_FILL_NONE);
}
void make3d(EncodeFn enc, CUtensorMap* m, const void* p, uint64_t cols, uint64_t rows, uint32_t cw, uint32_t nc) {
  cuuint64_t gd[3] = {cw, rows, cols / cw}, gs[2] = {cols * 2, cw * 2};
  cuuint32_t bd[3] = {cw, 64, nc}, es[3] = {1, 1, 1};
  enc(m, CU_TENSOR_MAP_DATA_TYPE_BFLOAT16, 3, const_cast<void*>(p), gd, gs, bd, es, CU_TENSOR_MAP_INTERLEAVE_NONE,
      cw == 64 ? CU_TENSOR_MAP_SWIZZLE_128B : CU_TENSOR_MAP_SWIZZLE_64B, CU_TENSOR_MAP_L2_PROMOTION_L2_256B, CU_TENSOR_MAP_FLOAT_OOB_FILL_NONE);
}

}

extern "C" void kernel_launch(void* const* d_in, const int* in_sizes, int n_in, void* d_out, int out_size) {
  const bf16* x = (const bf16*)d_in[0];
  const bf16* wsre = (const bf16*)d_in[1];
  const bf16* wsim = (const bf16*)d_in[2];
  const bf16* wdre = (const bf16*)d_in[3];
  const bf16* wdim = (const bf16*)d_in[4];
  const bf16* win = (const bf16*)d_in[6];
  const bf16* wsp = (const bf16*)d_in[7];
  const bf16* bsp = (const bf16*)d_in[8];
  const bf16* wout = (const bf16*)d_in[9];

  void* fn = nullptr;
  cudaDriverEntryPointQueryResult qr;
  cudaGetDriverEntryPoint("cuTensorMapEncodeTiled", &fn, cudaEnableDefault, &qr);
  EncodeFn enc = (EncodeFn)fn;
  void *abT, *z2, *h;
  cudaGetSymbolAddress(&abT, g_abT);
  cudaGetSymbolAddress(&z2, g_z2);
  cudaGetSymbolAddress(&h, g_h);

  Maps maps;
  make2d(enc, &maps.m[M_X], x, DM, SEQ, 64, 64);
  make2d(enc, &maps.m[M_XR], x, DM, SEQ, 160, 64, false);
  make3d(enc, &maps.m[M_WIN32], win, FF, DM, 32, 3);
  make2d(enc, &maps.m[M_WSRE], wsre, SEQ, SEQ, 64, 64);
  make2d(enc, &maps.m[M_WSIM], wsim, SEQ, SEQ, 64, 64);
  make2d(enc, &maps.m[M_WSP], wsp, SEQ, SEQ, 64, 64);
  make2d(enc, &maps.m[M_H], h, FH, SEQ, 64, 64);
  make3d(enc, &maps.m[M_WIN3], win, FF, DM, 64, 3);
  make3d(enc, &maps.m[M_Z23], z2, FH, SEQ, 64, 3);
  make2d(enc, &maps.m[M_WDRE], wdre, DM, DM, 64, 160);
  make2d(enc, &maps.m[M_WDIM], wdim, DM, DM, 64, 160);
  make2d(enc, &maps.m[M_AB], abT, SEQ, 2 * DM, 64, 160);
  make3d(enc, &maps.m[M_WOUT], wout, DM, FH, 32, 5);
  make2d(enc, &maps.m[M_OUT], d_out, DM, SEQ, 160, 16, false);

  cudaFuncSetAttribute(fused_kernel, cudaFuncAttributeMaxDynamicSharedMemorySize, SMEM_BYTES);
  fused_kernel<<<128, 384, SMEM_BYTES>>>(maps, x, win, bsp, wdre, wdim, wsp, wsre, wsim);
}
```

```cpp
#include <cuda_runtime.h>
#include <cuda_bf16.h>
#include <cuda.h>
#include <stdint.h>

namespace {

typedef __nv_bfloat16 bf16;

constexpr int SEQ = 2048, DM = 640, FF = 1536, FH = 768;
#define NXV 11
constexpr int NX = NXV;
constexpr int STAGES = 4;
constexpr int A_BYTES = 16384;
constexpr int ROWSTAT_OFF = 0;
constexpr int COLSUM_OFF = 1024;
constexpr int BIAS_OFF = 2560;
constexpr int BAR_OFF = 3072;
constexpr int RING_OFF = 4096;
constexpr int STAGE_A = 40960, STAGE_B = 36864;
constexpr int SMEM_BYTES = RING_OFF + 4 * STAGE_A + 49152;
constexpr int KB_A = 20 + 32 + NX + 12;
constexpr int KB_B = 30 + 64 - NX;
constexpr float LN_EPS = 1e-5f;
constexpr unsigned POLL_LIMIT = 100000;
#define POLL_NS 100
#define PF_D 10
#define Z1_NS 0
#define PF_NS 150

constexpr int BAR_ORD1 = 1, BAR_ORD2 = 2, BAR_WG1 = 3, BAR_WG2 = 4, BAR_STATS = 5, BAR_BUF = 6, BAR_Z1 = 7;

enum { M_X, M_XR, M_WIN32, M_WSRE, M_WSIM, M_WSP, M_H, M_WIN3, M_Z23, M_WDRE, M_WDIM, M_AB, M_WOUT, M_OUT, M_COUNT };
struct Maps { CUtensorMap m[M_COUNT]; };

__device__ __align__(1024) bf16 g_abT[2 * DM * SEQ];
__device__ __align__(1024) bf16 g_z2[SEQ * FH];
__device__ __align__(1024) bf16 g_h[SEQ * FH];
__device__ __align__(16) uint4 g_xstat[SEQ];
__device__ __align__(16) uint2 g_csum[16 * FF + 2 * DM];
__device__ __align__(16) uint4 g_zstat[128 * 128];
__device__ __align__(16) uint4 g_part[128 * 27 * 128];
__device__ unsigned g_flags[4 * 128];
constexpr int F_A = 0, F_B = 128, F_H = 256, F_Z = 384;
__device__ unsigned g_done;
#define TS(role, ev)
#define TC(i)

extern __shared__ __align__(1024) uint8_t smem[];

__device__ __forceinline__ uint32_t smem_u32(const void* p) { return (uint32_t)__cvta_generic_to_shared(p); }
__device__ __forceinline__ void mbar_init(uint32_t bar, uint32_t cnt) { asm volatile("mbarrier.init.shared::cta.b64 [%0], %1;" :: "r"(bar), "r"(cnt)); }
__device__ __forceinline__ void mbar_expect_tx(uint32_t bar, uint32_t bytes) { asm volatile("mbarrier.arrive.expect_tx.shared::cta.b64 _, [%0], %1;" :: "r"(bar), "r"(bytes) : "memory"); }
__device__ __forceinline__ void mbar_arrive(uint32_t bar) { asm volatile("mbarrier.arrive.shared::cta.b64 _, [%0];" :: "r"(bar) : "memory"); }
__device__ __forceinline__ void mbar_arrive_cluster(uint32_t bar, uint32_t cta) {
  asm volatile("{\n.reg .b32 ra;\nmapa.shared::cluster.u32 ra, %0, %1;\nmbarrier.arrive.shared::cluster.b64 _, [ra];\n}" :: "r"(bar), "r"(cta) : "memory");
}
__device__ __forceinline__ void mbar_wait(uint32_t bar, uint32_t parity) {
  asm volatile("{\n.reg .pred p;\n.reg .u32 n;\nmov.u32 n, 0;\n"
               "LW: mbarrier.try_wait.parity.shared::cta.b64 p, [%0], %1, 2000;\n@p bra LD;\n"
               "add.u32 n, n, 1;\nsetp.lt.u32 p, n, 20000;\n@p bra LW;\nLD:\n}" :: "r"(bar), "r"(parity) : "memory");
}
__device__ __forceinline__ void tma_load_2d(uint32_t dst, const CUtensorMap* map, uint32_t bar, int c0, int c1) {
  asm volatile("cp.async.bulk.tensor.2d.shared::cluster.global.mbarrier::complete_tx::bytes [%0], [%1, {%3, %4}], [%2];"
    :: "r"(dst), "l"((uint64_t)map), "r"(bar), "r"(c0), "r"(c1) : "memory");
}
__device__ __forceinline__ void tma_load_3d(uint32_t dst, const CUtensorMap* map, uint32_t bar, int c0, int c1, int c2) {
  asm volatile("cp.async.bulk.tensor.3d.shared::cluster.global.mbarrier::complete_tx::bytes [%0], [%1, {%3, %4, %5}], [%2];"
    :: "r"(dst), "l"((uint64_t)map), "r"(bar), "r"(c0), "r"(c1), "r"(c2) : "memory");
}
__device__ __forceinline__ void tma_load_2d_mc(uint32_t dst, const CUtensorMap* map, uint32_t bar, int c0, int c1, uint16_t mask) {
  asm volatile("cp.async.bulk.tensor.2d.shared::cluster.global.mbarrier::complete_tx::bytes.multicast::cluster [%0], [%1, {%3, %4}], [%2], %5;"
    :: "r"(dst), "l"((uint64_t)map), "r"(bar), "r"(c0), "r"(c1), "h"(mask) : "memory");
}
__device__ __forceinline__ void tma_store_2d(const CUtensorMap* map, uint32_t src, int c0, int c1) {
  asm volatile("cp.async.bulk.tensor.2d.global.shared::cta.bulk_group [%0, {%2, %3}], [%1];"
    :: "l"((uint64_t)map), "r"(src), "r"(c0), "r"(c1) : "memory");
}
__device__ __forceinline__ void bulk_commit() { asm volatile("cp.async.bulk.commit_group;" ::: "memory"); }
__device__ __forceinline__ void bulk_wait_read() { asm volatile("cp.async.bulk.wait_group.read 0;" ::: "memory"); }
__device__ __forceinline__ void fence_async_smem() { asm volatile("fence.proxy.async.shared::cta;" ::: "memory"); }
__device__ __forceinline__ void fence_async_global() { asm volatile("fence.proxy.async.global;" ::: "memory"); }
__device__ __forceinline__ void wgmma_fence() { asm volatile("wgmma.fence.sync.aligned;" ::: "memory"); }
__device__ __forceinline__ void wgmma_commit() { asm volatile("wgmma.commit_group.sync.aligned;" ::: "memory"); }
template<int N> __device__ __forceinline__ void wgmma_wait() { asm volatile("wgmma.wait_group.sync.aligned %0;" :: "n"(N) : "memory"); }
template<int ID> __device__ __forceinline__ void bar_sync(int n) { asm volatile("bar.sync %0, %1;" :: "n"(ID), "r"(n) : "memory"); }
template<int ID> __device__ __forceinline__ void bar_arrive(int n) { asm volatile("bar.arrive %0, %1;" :: "n"(ID), "r"(n) : "memory"); }
__device__ __forceinline__ void cluster_wait() { asm volatile("barrier.cluster.wait.aligned;" ::: "memory"); }
__device__ __forceinline__ uint64_t desc64(uint32_t lo, uint32_t hi) { return (uint64_t)lo | ((uint64_t)hi << 32); }
__device__ __forceinline__ uint4 ld_vol4(const uint4* p) {
  uint4 v; asm volatile("ld.relaxed.gpu.global.v4.u32 {%0,%1,%2,%3}, [%4];" : "=r"(v.x), "=r"(v.y), "=r"(v.z), "=r"(v.w) : "l"(p) : "memory"); return v;
}
__device__ __forceinline__ uint2 ld_vol2(const uint2* p) {
  uint2 v; asm volatile("ld.relaxed.gpu.global.v2.u32 {%0,%1}, [%2];" : "=r"(v.x), "=r"(v.y) : "l"(p) : "memory"); return v;
}
__device__ __forceinline__ void st_vol4(uint4* p, uint32_t a, uint32_t b, uint32_t c, uint32_t d) {
  asm volatile("st.relaxed.gpu.global.v4.u32 [%0], {%1,%2,%3,%4};" :: "l"(p), "r"(a), "r"(b), "r"(c), "r"(d) : "memory");
}
__device__ __forceinline__ void st_vol2(uint2* p, uint32_t a, uint32_t b) {
  asm volatile("st.relaxed.gpu.global.v2.u32 [%0], {%1,%2};" :: "l"(p), "r"(a), "r"(b) : "memory");
}
__device__ __forceinline__ void stg128(void* p, uint4 v) {
  asm volatile("st.global.v4.u32 [%0], {%1,%2,%3,%4};" :: "l"(p), "r"(v.x), "r"(v.y), "r"(v.z), "r"(v.w));
}
__device__ __forceinline__ unsigned ld_relaxed(const unsigned* p) {
  unsigned v; asm volatile("ld.relaxed.gpu.global.u32 %0, [%1];" : "=r"(v) : "l"(p) : "memory"); return v;
}
__device__ __forceinline__ uint32_t pack_bf16(float lo, float hi) {
  uint32_t r; asm("cvt.rn.bf16x2.f32 %0, %1, %2;" : "=r"(r) : "f"(hi), "f"(lo)); return r;
}
__device__ __forceinline__ float bf_lo(uint32_t v) { return __uint_as_float(v << 16); }
__device__ __forceinline__ float bf_hi(uint32_t v) { return __uint_as_float(v & 0xFFFF0000u); }
__device__ __forceinline__ void stsm4(uint32_t addr, uint32_t a, uint32_t b, uint32_t c, uint32_t d) {
  asm volatile("stmatrix.sync.aligned.m8n8.x4.shared.b16 [%0], {%1,%2,%3,%4};" :: "r"(addr), "r"(a), "r"(b), "r"(c), "r"(d));
}
__device__ __forceinline__ void stsm4_t(uint32_t addr, uint32_t a, uint32_t b, uint32_t c, uint32_t d) {
  asm volatile("stmatrix.sync.aligned.m8n8.x4.trans.shared.b16 [%0], {%1,%2,%3,%4};" :: "r"(addr), "r"(a), "r"(b), "r"(c), "r"(d));
}
__device__ __forceinline__ void ldsm4(uint32_t addr, uint32_t& a, uint32_t& b, uint32_t& c, uint32_t& d) {
  asm volatile("ldmatrix.sync.aligned.m8n8.x4.shared.b16 {%0,%1,%2,%3}, [%4];" : "=r"(a), "=r"(b), "=r"(c), "=r"(d) : "r"(addr));
}
__device__ __forceinline__ uint4 lds128(uint32_t a) {
  uint4 v; asm volatile("ld.shared.v4.u32 {%0,%1,%2,%3}, [%4];" : "=r"(v.x), "=r"(v.y), "=r"(v.z), "=r"(v.w) : "r"(a)); return v;
}
__device__ __forceinline__ void sts128(uint32_t a, uint32_t x, uint32_t y, uint32_t z, uint32_t w) {
  asm volatile("st.shared.v4.u32 [%0], {%1,%2,%3,%4};" :: "r"(a), "r"(x), "r"(y), "r"(z), "r"(w));
}
__device__ __forceinline__ uint32_t hmul2_bf16(uint32_t a, uint32_t b) {
  uint32_t r; asm("mul.rn.bf16x2 %0, %1, %2;" : "=r"(r) : "r"(a), "r"(b)); return r;
}
__device__ __forceinline__ float gelu_tanh(float v) {
  float u = v * fmaf(0.0356774081f, v * v, 0.7978845608f);
  float t; asm("tanh.approx.f32 %0, %1;" : "=f"(t) : "f"(u));
  float hv = 0.5f * v;
  return fmaf(hv, t, hv);
}

template<int TB>
__device__ __forceinline__ void wgmma_n192(float (&d)[96], uint64_t da, uint64_t db, int scale_d) {
  asm volatile("{\n.reg .pred p;\nsetp.ne.b32 p, %98, 0;\n"
   "wgmma.mma_async.sync.aligned.m64n192k16.f32.bf16.bf16 {%0,%1,%2,%3,%4,%5,%6,%7,%8,%9,%10,%11,%12,%13,%14,%15,%16,%17,%18,%19,%20,%21,%22,%23,%24,%25,%26,%27,%28,%29,%30,%31,%32,%33,%34,%35,%36,%37,%38,%39,%40,%41,%42,%43,%44,%45,%46,%47,%48,%49,%50,%51,%52,%53,%54,%55,%56,%57,%58,%59,%60,%61,%62,%63,%64,%65,%66,%67,%68,%69,%70,%71,%72,%73,%74,%75,%76,%77,%78,%79,%80,%81,%82,%83,%84,%85,%86,%87,%88,%89,%90,%91,%92,%93,%94,%95}, %96, %97, p, 1, 1, 0, %99;\n}"
   : "+f"(d[0]),"+f"(d[1]),"+f"(d[2]),"+f"(d[3]),"+f"(d[4]),"+f"(d[5]),"+f"(d[6]),"+f"(d[7]),"+f"(d[8]),"+f"(d[9]),"+f"(d[10]),"+f"(d[11]),"+f"(d[12]),"+f"(d[13]),"+f"(d[14]),"+f"(d[15]),"+f"(d[16]),"+f"(d[17]),"+f"(d[18]),"+f"(d[19]),"+f"(d[20]),"+f"(d[21]),"+f"(d[22]),"+f"(d[23]),"+f"(d[24]),"+f"(d[25]),"+f"(d[26]),"+f"(d[27]),"+f"(d[28]),"+f"(d[29]),"+f"(d[30]),"+f"(d[31]),"+f"(d[32]),"+f"(d[33]),"+f"(d[34]),"+f"(d[35]),"+f"(d[36]),"+f"(d[37]),"+f"(d[38]),"+f"(d[39]),"+f"(d[40]),"+f"(d[41]),"+f"(d[42]),"+f"(d[43]),"+f"(d[44]),"+f"(d[45]),"+f"(d[46]),"+f"(d[47]),"+f"(d[48]),"+f"(d[49]),"+f"(d[50]),"+f"(d[51]),"+f"(d[52]),"+f"(d[53]),"+f"(d[54]),"+f"(d[55]),"+f"(d[56]),"+f"(d[57]),"+f"(d[58]),"+f"(d[59]),"+f"(d[60]),"+f"(d[61]),"+f"(d[62]),"+f"(d[63]),"+f"(d[64]),"+f"(d[65]),"+f"(d[66]),"+f"(d[67]),"+f"(d[68]),"+f"(d[69]),"+f"(d[70]),"+f"(d[71]),"+f"(d[72]),"+f"(d[73]),"+f"(d[74]),"+f"(d[75]),"+f"(d[76]),"+f"(d[77]),"+f"(d[78]),"+f"(d[79]),"+f"(d[80]),"+f"(d[81]),"+f"(d[82]),"+f"(d[83]),"+f"(d[84]),"+f"(d[85]),"+f"(d[86]),"+f"(d[87]),"+f"(d[88]),"+f"(d[89]),"+f"(d[90]),"+f"(d[91]),"+f"(d[92]),"+f"(d[93]),"+f"(d[94]),"+f"(d[95])
   : "l"(da), "l"(db), "r"(scale_d), "n"(TB));
}
template<int TB>
__device__ __forceinline__ void wgmma_n160(float (&d)[80], uint64_t da, uint64_t db, int scale_d) {
  asm volatile("{\n.reg .pred p;\nsetp.ne.b32 p, %82, 0;\n"
   "wgmma.mma_async.sync.aligned.m64n160k16.f32.bf16.bf16 {%0,%1,%2,%3,%4,%5,%6,%7,%8,%9,%10,%11,%12,%13,%14,%15,%16,%17,%18,%19,%20,%21,%22,%23,%24,%25,%26,%27,%28,%29,%30,%31,%32,%33,%34,%35,%36,%37,%38,%39,%40,%41,%42,%43,%44,%45,%46,%47,%48,%49,%50,%51,%52,%53,%54,%55,%56,%57,%58,%59,%60,%61,%62,%63,%64,%65,%66,%67,%68,%69,%70,%71,%72,%73,%74,%75,%76,%77,%78,%79}, %80, %81, p, 1, 1, 0, %83;\n}"
   : "+f"(d[0]),"+f"(d[1]),"+f"(d[2]),"+f"(d[3]),"+f"(d[4]),"+f"(d[5]),"+f"(d[6]),"+f"(d[7]),"+f"(d[8]),"+f"(d[9]),"+f"(d[10]),"+f"(d[11]),"+f"(d[12]),"+f"(d[13]),"+f"(d[14]),"+f"(d[15]),"+f"(d[16]),"+f"(d[17]),"+f"(d[18]),"+f"(d[19]),"+f"(d[20]),"+f"(d[21]),"+f"(d[22]),"+f"(d[23]),"+f"(d[24]),"+f"(d[25]),"+f"(d[26]),"+f"(d[27]),"+f"(d[28]),"+f"(d[29]),"+f"(d[30]),"+f"(d[31]),"+f"(d[32]),"+f"(d[33]),"+f"(d[34]),"+f"(d[35]),"+f"(d[36]),"+f"(d[37]),"+f"(d[38]),"+f"(d[39]),"+f"(d[40]),"+f"(d[41]),"+f"(d[42]),"+f"(d[43]),"+f"(d[44]),"+f"(d[45]),"+f"(d[46]),"+f"(d[47]),"+f"(d[48]),"+f"(d[49]),"+f"(d[50]),"+f"(d[51]),"+f"(d[52]),"+f"(d[53]),"+f"(d[54]),"+f"(d[55]),"+f"(d[56]),"+f"(d[57]),"+f"(d[58]),"+f"(d[59]),"+f"(d[60]),"+f"(d[61]),"+f"(d[62]),"+f"(d[63]),"+f"(d[64]),"+f"(d[65]),"+f"(d[66]),"+f"(d[67]),"+f"(d[68]),"+f"(d[69]),"+f"(d[70]),"+f"(d[71]),"+f"(d[72]),"+f"(d[73]),"+f"(d[74]),"+f"(d[75]),"+f"(d[76]),"+f"(d[77]),"+f"(d[78]),"+f"(d[79])
   : "l"(da), "l"(db), "r"(scale_d), "n"(TB));
}
template<int TB>
__device__ __forceinline__ void wgmma_n96(float (&d)[48], uint64_t da, uint64_t db, int scale_d) {
  asm volatile("{\n.reg .pred p;\nsetp.ne.b32 p, %50, 0;\n"
   "wgmma.mma_async.sync.aligned.m64n96k16.f32.bf16.bf16 {%0,%1,%2,%3,%4,%5,%6,%7,%8,%9,%10,%11,%12,%13,%14,%15,%16,%17,%18,%19,%20,%21,%22,%23,%24,%25,%26,%27,%28,%29,%30,%31,%32,%33,%34,%35,%36,%37,%38,%39,%40,%41,%42,%43,%44,%45,%46,%47}, %48, %49, p, 1, 1, 0, %51;\n}"
   : "+f"(d[0]),"+f"(d[1]),"+f"(d[2]),"+f"(d[3]),"+f"(d[4]),"+f"(d[5]),"+f"(d[6]),"+f"(d[7]),"+f"(d[8]),"+f"(d[9]),"+f"(d[10]),"+f"(d[11]),"+f"(d[12]),"+f"(d[13]),"+f"(d[14]),"+f"(d[15]),"+f"(d[16]),"+f"(d[17]),"+f"(d[18]),"+f"(d[19]),"+f"(d[20]),"+f"(d[21]),"+f"(d[22]),"+f"(d[23]),"+f"(d[24]),"+f"(d[25]),"+f"(d[26]),"+f"(d[27]),"+f"(d[28]),"+f"(d[29]),"+f"(d[30]),"+f"(d[31]),"+f"(d[32]),"+f"(d[33]),"+f"(d[34]),"+f"(d[35]),"+f"(d[36]),"+f"(d[37]),"+f"(d[38]),"+f"(d[39]),"+f"(d[40]),"+f"(d[41]),"+f"(d[42]),"+f"(d[43]),"+f"(d[44]),"+f"(d[45]),"+f"(d[46]),"+f"(d[47])
   : "l"(da), "l"(db), "r"(scale_d), "n"(TB));
}

template<int N, int TB>
__device__ __forceinline__ void wgmma_n(float (&d)[N / 2], uint64_t da, uint64_t db) {
  if constexpr (N == 192) wgmma_n192<TB>(d, da, db, 1);
  else if constexpr (N == 160) wgmma_n160<TB>(d, da, db, 1);
  else wgmma_n96<TB>(d, da, db, 1);
}

template<int R>
__device__ __forceinline__ void pin(float (&acc)[2][R]) {
  #pragma unroll
  for (int mi = 0; mi < 2; mi++)
    #pragma unroll
    for (int i = 0; i < R; i++) asm volatile("" : "+f"(acc[mi][i]) :: "memory");
}
template<int R>
__device__ __forceinline__ void zero(float (&acc)[2][R]) {
  #pragma unroll
  for (int i = 0; i < R; i++) { acc[0][i] = 0.f; acc[1][i] = 0.f; }
  pin(acc);
}

template<int N, int TB, bool CONT, int ORD_BAR>
__device__ __forceinline__ void mainloop(float (&acc)[2][N / 2], uint32_t sbase, uint32_t stage_bytes, int g0, int nk, int total, int mswap) {
  const uint32_t full0 = sbase + BAR_OFF, empty0 = full0 + 8 * STAGES, ring = sbase + RING_OFF;
  const int t = threadIdx.x & 127;
  const uint32_t da0 = (((ring + mswap * 8192) & 0x3FFFF) >> 4) | 0x10000u, da1 = (((ring + (mswap ^ 1) * 8192) & 0x3FFFF) >> 4) | 0x10000u;
  const uint32_t db0 = (((ring + A_BYTES) & 0x3FFFF) >> 4) | ((TB == 2 ? 256u : TB ? 512u : 1u) << 16);
  constexpr uint32_t HI_A = 0x40000040u, HI_B = TB == 2 ? 0x80000020u : 0x40000040u;
  #pragma unroll 1
  for (int g = g0; g < g0 + nk; g++) {
    const int s = g & (STAGES - 1);
    const uint32_t so = s * (stage_bytes >> 4);
    mbar_wait(full0 + 8 * s, (g / STAGES) & 1);
    wgmma_fence();
    #pragma unroll
    for (int k = 0; k < 4; k++) {
      const uint64_t db = desc64(db0 + so + (TB == 2 ? k * 64 : TB ? k * 128 : k * 2), HI_B);
      wgmma_n<N, TB != 0>(acc[0], desc64(da0 + so + k * 2, HI_A), db);
      wgmma_n<N, TB != 0>(acc[1], desc64(da1 + so + k * 2, HI_A), db);
    }
    wgmma_commit();
    if (ORD_BAR != 0 && g == g0 + nk - 1) bar_arrive<ORD_BAR>(256);
    wgmma_wait<1>();
    if (t < 2 && (CONT || g > g0) && g - 1 + STAGES <= total) mbar_arrive_cluster(empty0 + 8 * ((g - 1) & (STAGES - 1)), t);
  }
}
template<int R>
__device__ __forceinline__ void drain(float (&acc)[2][R], uint32_t sbase, int glast, int total) {
  wgmma_wait<0>();
  pin(acc);
  const int t = threadIdx.x & 127;
  if (t < 2 && glast + STAGES <= total) mbar_arrive_cluster(sbase + BAR_OFF + 8 * STAGES + 8 * (glast & (STAGES - 1)), t);
}

__device__ __forceinline__ void publish(unsigned* flag, unsigned epoch) {
  asm volatile("fence.acq_rel.gpu;" ::: "memory");
  asm volatile("st.relaxed.gpu.global.u32 [%0], %1;" :: "l"(flag), "r"(epoch) : "memory");
}

__device__ __forceinline__ float sum8(uint4 v) {
  return ((bf_lo(v.x) + bf_hi(v.x)) + (bf_lo(v.y) + bf_hi(v.y))) + ((bf_lo(v.z) + bf_hi(v.z)) + (bf_lo(v.w) + bf_hi(v.w)));
}
__device__ __forceinline__ float oct_sum(float v) {
  v += __shfl_xor_sync(0xffffffffu, v, 1); v += __shfl_xor_sync(0xffffffffu, v, 2); v += __shfl_xor_sync(0xffffffffu, v, 4);
  return v;
}

__device__ __forceinline__ void stats_prologue(const bf16* __restrict__ x, const bf16* __restrict__ win, const bf16* __restrict__ wdre,
                                               const bf16* __restrict__ wdim, int rb, int c8, float* red, unsigned epoch) {
  const int t = threadIdx.x & 127, l = t & 31, cta = blockIdx.x;
  const int cg = t % 12, rg = min(t / 12, 9), tc = min(t, 95);
  #pragma unroll 1
  for (int p = 0; p < 2; p++) {
    const int wr = cta * 10 + min(t >> 3, 9);
    const bf16* src = p == 0 ? x + (size_t)(cta * 16 + (t >> 3)) * DM : wr < DM ? wdre + (size_t)wr * DM : wdim + (size_t)(wr - DM) * DM;
    const int col = (1 - p) * FH + c8 * 96;
    uint4 rv[10], cv[4];
    #pragma unroll
    for (int j = 0; j < 4; j++) cv[j] = __ldg(reinterpret_cast<const uint4*>(win + (size_t)(rb * 40 + rg * 4 + j) * FF + col) + cg);
    #pragma unroll
    for (int j = 0; j < 10; j++) rv[j] = (p == 0 || t < 80) ? __ldg(reinterpret_cast<const uint4*>(src) + (l & 7) + 8 * j) : make_uint4(0, 0, 0, 0);
    float* rp = red + p * 960;
    *reinterpret_cast<float4*>(rp + rg * 96 + cg * 8) = make_float4(
        (bf_lo(cv[0].x) + bf_lo(cv[1].x)) + (bf_lo(cv[2].x) + bf_lo(cv[3].x)), (bf_hi(cv[0].x) + bf_hi(cv[1].x)) + (bf_hi(cv[2].x) + bf_hi(cv[3].x)),
        (bf_lo(cv[0].y) + bf_lo(cv[1].y)) + (bf_lo(cv[2].y) + bf_lo(cv[3].y)), (bf_hi(cv[0].y) + bf_hi(cv[1].y)) + (bf_hi(cv[2].y) + bf_hi(cv[3].y)));
    *reinterpret_cast<float4*>(rp + rg * 96 + cg * 8 + 4) = make_float4(
        (bf_lo(cv[0].z) + bf_lo(cv[1].z)) + (bf_lo(cv[2].z) + bf_lo(cv[3].z)), (bf_hi(cv[0].z) + bf_hi(cv[1].z)) + (bf_hi(cv[2].z) + bf_hi(cv[3].z)),
        (bf_lo(cv[0].w) + bf_lo(cv[1].w)) + (bf_lo(cv[2].w) + bf_lo(cv[3].w)), (bf_hi(cv[0].w) + bf_hi(cv[1].w)) + (bf_hi(cv[2].w) + bf_hi(cv[3].w)));
    float s = 0.f;
    #pragma unroll
    for (int j = 0; j < 10; j++) s += sum8(rv[j]);
    s = oct_sum(s);
    if (p == 0) {
      const float mean = s * (1.f / DM);
      float q = 0.f;
      #pragma unroll
      for (int j = 0; j < 10; j++) {
        const uint32_t u[4] = {rv[j].x, rv[j].y, rv[j].z, rv[j].w};
        #pragma unroll
        for (int c = 0; c < 4; c++) { const float d0 = bf_lo(u[c]) - mean, d1 = bf_hi(u[c]) - mean; q = fmaf(d0, d0, q); q = fmaf(d1, d1, q); }
      }
      const float rstd = rsqrtf(fmaf(oct_sum(q), 1.f / DM, LN_EPS));
      if ((l & 7) == 0) st_vol4(&g_xstat[cta * 16 + (t >> 3)], __float_as_uint(rstd), __float_as_uint(-mean * rstd), epoch, 0u);
    } else if ((l & 7) == 0 && t < 80) {
      st_vol2(&g_csum[16 * FF + wr], __float_as_uint(s), epoch);
    }
    bar_sync<BAR_WG2>(128);
    float c = 0.f;
    #pragma unroll
    for (int i = 0; i < 10; i++) c += rp[i * 96 + tc];
    st_vol2(&g_csum[rb * FF + col + tc], __float_as_uint(c), epoch);
  }
}

__device__ __forceinline__ void prepoll(const unsigned* tag, unsigned epoch) {
  unsigned it = 0;
  while (!__all_sync(0xffffffffu, ld_relaxed(tag) == epoch) && ++it < POLL_LIMIT) __nanosleep(POLL_NS);
}

template<int NP>
__device__ __forceinline__ float gather_sum(const uint2* src, unsigned epoch) {
  unsigned it = 0;
  while (true) {
    uint2 u[NP];
    #pragma unroll
    for (int i = 0; i < NP; i++) u[i] = ld_vol2(src + i * FF);
    bool ok = true;
    float a = 0.f;
    #pragma unroll
    for (int i = 0; i < NP; i++) { ok = ok && u[i].y == epoch; a += __uint_as_float(u[i].x); }
    if (ok || ++it > POLL_LIMIT) return a;
    __nanosleep(POLL_NS);
  }
}

__device__ __forceinline__ void fold_pack(const float* a, float2 s0, float2 s1, float2 c0, float2 c1, uint32_t (&r)[4]) {
  r[0] = pack_bf16(fmaf(a[0], s0.x, s0.y * c0.x), fmaf(a[1], s0.x, s0.y * c0.y));
  r[1] = pack_bf16(fmaf(a[2], s1.x, s1.y * c0.x), fmaf(a[3], s1.x, s1.y * c0.y));
  r[2] = pack_bf16(fmaf(a[4], s0.x, s0.y * c1.x), fmaf(a[5], s0.x, s0.y * c1.y));
  r[3] = pack_bf16(fmaf(a[6], s1.x, s1.y * c1.x), fmaf(a[7], s1.x, s1.y * c1.y));
}

__global__ void __cluster_dims__(2, 1, 1) __launch_bounds__(384, 1)
fused_kernel(const __grid_constant__ Maps maps, const bf16* __restrict__ x, const bf16* __restrict__ win,
             const bf16* __restrict__ bsp, const bf16* __restrict__ wdre, const bf16* __restrict__ wdim) {
  const uint32_t sbase = smem_u32(smem);
  const uint32_t full0 = sbase + BAR_OFF, empty0 = full0 + 8 * STAGES, dep0 = empty0 + 8 * STAGES, ring = sbase + RING_OFF;
  const int tid = threadIdx.x, wg = __shfl_sync(0xffffffffu, tid >> 7, 0);
  const int rank = blockIdx.x & 1, grp = (blockIdx.x >> 1) & 1, q = blockIdx.x >> 2;
  const int rb = q >> 1, ct = (q & 1) * 2 + rank, c8 = grp * 4 + ct;
  const int total = grp == 0 ? KB_A : KB_B;
  const uint32_t stage_bytes = grp == 0 ? STAGE_A : STAGE_B;

  if (tid == 0) {
    TS(0, 0);
    for (int s = 0; s < STAGES; s++) { mbar_init(full0 + 8 * s, 2); mbar_init(empty0 + 8 * s, 2); mbar_init(dep0 + 8 * s, 1); }
    asm volatile("fence.mbarrier_init.release.cluster;" ::: "memory");
  }
  __syncthreads();
  asm volatile("barrier.cluster.arrive.relaxed.aligned;" ::: "memory");

  if (wg == 0) {
    asm volatile("setmaxnreg.dec.sync.aligned.u32 40;");
    const int warp = tid >> 5, lane = tid & 31;
    if (warp == 0) {
      const int row = rb * 128;
      if (lane == 0) {
        TS(0, 1);
        for (int g = 0; g < STAGES; g++) {
          mbar_expect_tx(full0 + 8 * g, A_BYTES);
          tma_load_2d(ring + g * stage_bytes, &maps.m[M_X], full0 + 8 * g, g * 64, row);
          tma_load_2d(ring + g * stage_bytes + 8192, &maps.m[M_X], full0 + 8 * g, g * 64, row + 64);
        }
      }
      __syncwarp();
      cluster_wait();
      if (lane == 0) {
        #pragma unroll 1
        for (int g = STAGES; g < total; g++) {
          int mi, kb;
          if (g < 20) { mi = M_X; kb = g < 10 ? g : g - 10; }
          else if (grp == 0) {
            if (g < 52) { mi = M_WSP; kb = g - 20; }
            else if (g < 52 + NX) { mi = M_WSIM; kb = g - 52 + 32 - NX; }
            else { mi = M_H; kb = g - 52 - NX; }
          } else {
            if (g < 30) { mi = M_X; kb = g - 20; }
            else if (g < 62) { mi = M_WSRE; kb = g - 30; }
            else { mi = M_WSIM; kb = g - 62; }
          }
          if (mi == M_H && kb == 0) { TS(0, 3); mbar_wait(dep0 + 24, 0); fence_async_global(); TS(0, 4); }
          const int s = g & (STAGES - 1);
          mbar_wait(empty0 + 8 * s, ((g / STAGES) & 1) ^ 1);
          mbar_expect_tx(full0 + 8 * s, A_BYTES);
          tma_load_2d_mc(ring + s * stage_bytes + rank * 8192, &maps.m[mi], full0 + 8 * s, kb * 64, row + rank * 64, 3);
        }
        const int s = total & (STAGES - 1);
        mbar_wait(empty0 + 8 * s, ((total / STAGES) & 1) ^ 1);
        mbar_expect_tx(full0 + 8 * s, 20480);
        mbar_arrive(full0 + 8 * s);
        tma_load_2d(ring + s * stage_bytes, &maps.m[M_XR], full0 + 8 * s, ct * 160, row + grp * 64);
        TS(0, 5);
      }
    } else if (warp == 1) {
      if (lane == 0) {
        #pragma unroll 1
        for (int g = 0; g < total; g++) {
          int kind = 1, mi, kb, c, dep = 0;
          uint32_t bytes = 20480;
          if (g < 10) { kind = 0; mi = M_WIN32; kb = g; c = 24 + 3 * c8; bytes = 12288; }
          else if (grp == 0) {
            if (g < 20) { kind = 0; mi = M_WIN3; kb = g - 10; c = 3 * ct; bytes = 24576; }
            else if (g < 52) { kind = 0; mi = M_Z23; kb = g - 20; c = 3 * ct; bytes = 24576; dep = g == 20 ? 1 : 0; }
            else if (g < 52 + NX) { mi = M_AB; kb = g - 52 + 32 - NX; c = DM + ct * 160; dep = g == 52 ? 2 : 0; }
            else { kind = 0; mi = M_WOUT; kb = g - 52 - NX; c = ct * 5; }
          } else {
            if (g < 30) { mi = g < 20 ? M_WDRE : M_WDIM; kb = g < 20 ? g - 10 : g - 20; c = ct * 160; }
            else { mi = M_AB; kb = g < 62 ? g - 30 : g - 62; c = ct * 160 + (g < 62 ? 0 : DM); dep = g == 30 ? 1 : g == 62 ? 2 : 0; }
          }
          if (dep) { TS(1, dep * 2 - 2); mbar_wait(dep0 + 8 * dep, 0); fence_async_global(); TS(1, dep * 2 - 1); TC(dep); }
          const int s = g & (STAGES - 1);
          const uint32_t dst = ring + s * stage_bytes + A_BYTES, fb = full0 + 8 * s;
          mbar_wait(empty0 + 8 * s, ((g / STAGES) & 1) ^ 1);
          mbar_expect_tx(fb, bytes);
          if (kind == 0) tma_load_3d(dst, &maps.m[mi], fb, 0, kb * 64, c);
          else tma_load_2d(dst, &maps.m[mi], fb, kb * 64, c);
        }
      }
      __syncwarp();
      cluster_wait();
    } else if (warp == 2) {
      cluster_wait();
      const unsigned epoch = (*reinterpret_cast<volatile unsigned*>(&g_done) >> 7) + 1u;
      #pragma unroll 1
      for (int d = 1; d < 4 - grp; d++) {
        const int fi = d == 3 ? F_H + rb * 4 + (lane & 3)
                     : (d == 1 && grp == 0) ? F_Z + (lane >> 1) * 8 + ct * 2 + (lane & 1)
                     : (d == 1 ? F_A : F_B) + (lane & 15) * 4 + ct;
        unsigned it = 0;
        while (!__all_sync(0xffffffffu, ld_relaxed(g_flags + fi) == epoch) && ++it < POLL_LIMIT) __nanosleep(20);
        fence_async_global();
        __syncwarp();
        if (lane == 0) mbar_arrive(dep0 + 8 * d);
      }
    } else {
      cluster_wait();
    }
  } else {
    asm volatile("setmaxnreg.inc.sync.aligned.u32 232;");
    const int t = tid & 127, w = t >> 5, l = t & 31;
    const uint32_t buf = ring + 4 * stage_bytes;
    const unsigned epoch = (*reinterpret_cast<volatile unsigned*>(&g_done) >> 7) + 1u;
    cluster_wait();
    const int rl = w * 16 + ((l >> 3) & 1) * 8 + (l & 7);
    const int gr = w * 16 + (l & 15);
    const uint32_t st_base = buf + rl * 128;
    const uint32_t st_x = ((l >> 4) ^ (l & 7)) << 4;
    float* csw = reinterpret_cast<float*>(smem + COLSUM_OFF) + (wg - 1) * 192;
    const float2* rs = reinterpret_cast<const float2*>(smem + ROWSTAT_OFF) + w * 16 + (l >> 2);
    const float2* cs = reinterpret_cast<const float2*>(csw) + (l & 3);
    if (wg == 1) {
      float acc[2][48];
      zero(acc);
      mainloop<96, 2, false, BAR_ORD1>(acc, sbase, stage_bytes, 0, 10, total, 0);
      {
        unsigned n = 0;
        prepoll(l < 16 ? &g_csum[l * FF + FH + c8 * 96 + min(w * 32, 95)].y : &g_xstat[rb * 128 + w * 32 + (l & 7) * 4].z, epoch);
        uint4 v = ld_vol4(&g_xstat[rb * 128 + t]);
        csw[min(t, 95)] = gather_sum<16>(g_csum + FH + c8 * 96 + min(t, 95), epoch);
        while (v.z != epoch && ++n < POLL_LIMIT) { __nanosleep(POLL_NS); v = ld_vol4(&g_xstat[rb * 128 + t]); }
        reinterpret_cast<float2*>(smem + ROWSTAT_OFF)[t] = make_float2(__uint_as_float(v.x), __uint_as_float(v.y));
      }
      drain(acc, sbase, 9, total);
      TS(2, 2);
      bar_arrive<BAR_STATS>(256);
      bar_sync<BAR_WG1>(128);
      float sum[4], sq[4];
      #pragma unroll
      for (int r = 0; r < 4; r++) {
        const float2 st = rs[(r >> 1) * 64 + (r & 1) * 8];
        float s0 = 0.f, q0 = 0.f;
        #pragma unroll
        for (int j = 0; j < 12; j++) {
          const float2 c = cs[j * 4];
          float* a = &acc[r >> 1][4 * j + (r & 1) * 2];
          a[0] = gelu_tanh(fmaf(a[0], st.x, st.y * c.x));
          a[1] = gelu_tanh(fmaf(a[1], st.x, st.y * c.y));
          s0 += a[0] + a[1]; q0 = fmaf(a[0], a[0], q0); q0 = fmaf(a[1], a[1], q0);
        }
        s0 += __shfl_xor_sync(0xffffffffu, s0, 1); q0 += __shfl_xor_sync(0xffffffffu, q0, 1);
        s0 += __shfl_xor_sync(0xffffffffu, s0, 2); q0 += __shfl_xor_sync(0xffffffffu, q0, 2);
        sum[r] = s0; sq[r] = q0;
      }
      TS(2, 4);
      float rstd, off;
      {
        const int qd = l & 3;
        const float sm = qd == 0 ? sum[0] : qd == 1 ? sum[1] : qd == 2 ? sum[2] : sum[3];
        const float sv = qd == 0 ? sq[0] : qd == 1 ? sq[1] : qd == 2 ? sq[2] : sq[3];
        const int row = (qd >> 1) * 64 + w * 16 + (qd & 1) * 8 + (l >> 2);
        const float mu = sm * (1.f / 96), m2 = fmaxf(sv - sm * mu, 0.f);
        st_vol4(&g_zstat[(rb * 8 + c8) * 128 + row], __float_as_uint(mu), __float_as_uint(m2), epoch, 0u);
        uint4 v[7];
        unsigned n = 0;
        prepoll(&g_zstat[(rb * 8 + (l >> 2)) * 128 + (qd >> 1) * 64 + w * 16 + (qd & 1) * 8].z, epoch);
        while (true) {
          bool ok = true;
          #pragma unroll
          for (int j = 0; j < 7; j++) v[j] = ld_vol4(&g_zstat[(rb * 8 + ((c8 + 1 + j) & 7)) * 128 + row]);
          #pragma unroll
          for (int j = 0; j < 7; j++) ok = ok && v[j].z == epoch;
          if (ok || ++n > POLL_LIMIT) break;
          __nanosleep(POLL_NS);
        }
        float mean = mu, var = m2;
        #pragma unroll
        for (int j = 0; j < 7; j++) { mean += __uint_as_float(v[j].x); var += __uint_as_float(v[j].y); }
        mean *= 0.125f;
        float d = (mu - mean) * (mu - mean);
        #pragma unroll
        for (int j = 0; j < 7; j++) d = fmaf(__uint_as_float(v[j].x) - mean, __uint_as_float(v[j].x) - mean, d);
        rstd = rsqrtf(fmaf(96.f, d, var) * (1.f / FH) + LN_EPS); off = -mean * rstd;
        __syncwarp();
      }
      TS(2, 5);
      #pragma unroll
      for (int mi = 0; mi < 2; mi++) {
        const float r0 = __shfl_sync(0xffffffffu, rstd, (l & 28) + mi * 2), o0 = __shfl_sync(0xffffffffu, off, (l & 28) + mi * 2);
        const float r1 = __shfl_sync(0xffffffffu, rstd, (l & 28) + mi * 2 + 1), o1 = __shfl_sync(0xffffffffu, off, (l & 28) + mi * 2 + 1);
        #pragma unroll
        for (int jj = 0; jj < 6; jj++) {
          const float* a = &acc[mi][8 * jj];
          stsm4(buf + (jj >> 1) * 8192 + mi * 4096 + rl * 64 + ((((jj & 1) * 2 + (l >> 4)) ^ ((l >> 1) & 3)) << 4),
                pack_bf16(fmaf(a[0], r0, o0), fmaf(a[1], r0, o0)), pack_bf16(fmaf(a[2], r1, o1), fmaf(a[3], r1, o1)),
                pack_bf16(fmaf(a[4], r0, o0), fmaf(a[5], r0, o0)), pack_bf16(fmaf(a[6], r1, o1), fmaf(a[7], r1, o1)));
        }
      }
      __syncwarp();
      {
        uint4 z[12];
        const int r0 = w * 16 + (l >> 2);
        #pragma unroll
        for (int i = 0; i < 12; i++) z[i] = lds128(buf + (i % 3) * 8192 + (r0 + (i / 6) * 64 + ((i / 3) & 1) * 8) * 64 + (((l & 3) ^ ((r0 >> 1) & 3)) << 4));
        bf16* p = g_z2 + (size_t)(rb * 128 + r0) * FH + c8 * 96 + (l & 3) * 8;
        #pragma unroll
        for (int i = 0; i < 12; i++) stg128(p + (size_t)((i / 6) * 64 + ((i / 3) & 1) * 8) * FH + (i % 3) * 32, z[i]);
      }
      bar_sync<BAR_WG1>(128);
      TS(2, 6);
      if (t == 0) publish(g_flags + F_Z + rb * 8 + c8, epoch);
      __syncwarp();
      TS(2, 10);
      if (grp == 0) {
        bar_arrive<BAR_BUF>(256);
        float acc[2][96];
        zero(acc);
        bar_sync<BAR_ORD2>(256);
        mainloop<192, 1, false, BAR_ORD1>(acc, sbase, STAGE_A, 20, 32, KB_A, 0);
        const float* bias = reinterpret_cast<const float*>(smem + BIAS_OFF) + w * 16 + (l >> 2);
        bar_sync<BAR_Z1>(256);
        drain(acc, sbase, 51, KB_A);
        TS(2, 7);
        {
          const float bb[4] = {bias[0], bias[8], bias[64], bias[72]};
          uint32_t z[2][4][4];
          #pragma unroll
          for (int i = 0; i < 4; i++) ldsm4(st_base + (st_x ^ (i << 5)), z[0][i][0], z[0][i][1], z[0][i][2], z[0][i][3]);
          #pragma unroll
          for (int bx = 0; bx < 6; bx++) {
            if (bx < 5) {
              #pragma unroll
              for (int i = 0; i < 4; i++)
                ldsm4(st_base + (bx + 1) * 8192 + (st_x ^ (i << 5)), z[(bx + 1) & 1][i][0], z[(bx + 1) & 1][i][1], z[(bx + 1) & 1][i][2], z[(bx + 1) & 1][i][3]);
            }
            const float b0 = bb[(bx / 3) * 2], b1 = bb[(bx / 3) * 2 + 1];
            #pragma unroll
            for (int i = 0; i < 4; i++) {
              const float* a = &acc[bx / 3][8 * ((bx % 3) * 4 + i)];
              const uint32_t* zz = z[bx & 1][i];
              stsm4(st_base + bx * 8192 + (st_x ^ (i << 5)),
                    hmul2_bf16(zz[0], pack_bf16(a[0] + b0, a[1] + b0)), hmul2_bf16(zz[1], pack_bf16(a[2] + b1, a[3] + b1)),
                    hmul2_bf16(zz[2], pack_bf16(a[4] + b0, a[5] + b0)), hmul2_bf16(zz[3], pack_bf16(a[6] + b1, a[7] + b1)));
            }
          }
        }
        __syncwarp();
        TS(2, 8);
        {
          uint4 z[24];
          const int r0 = w * 16 + (l >> 3);
          #pragma unroll
          for (int i = 0; i < 24; i++) z[i] = lds128(buf + (i >> 2) * 8192 + (r0 + (i & 3) * 4) * 128 + (((l ^ (r0 + (i & 3) * 4)) & 7) << 4));
          bf16* p = g_h + (size_t)(rb * 128 + r0) * FH + ct * 192 + (l & 7) * 8;
          #pragma unroll
          for (int i = 0; i < 24; i++) stg128(p + (size_t)((i / 12) * 64 + (i & 3) * 4) * FH + ((i >> 2) % 3) * 64, z[i]);
        }
        bar_sync<BAR_WG1>(128);
        if (t == 0) publish(g_flags + F_H + rb * 4 + ct, epoch);
        TS(2, 9);
        return;
      }
    } else {
      stats_prologue(x, win, wdre, wdim, rb, c8, reinterpret_cast<float*>(smem + (buf - sbase) + 24576), epoch);
      TS(3, 0);
      if (grp == 0) {
        reinterpret_cast<float*>(smem + BIAS_OFF)[t] = __bfloat162float(bsp[rb * 128 + t]);
        float acc[2][96];
        zero(acc);
        bar_sync<BAR_ORD1>(256);
        mainloop<192, 1, false, BAR_ORD2>(acc, sbase, STAGE_A, 10, 10, KB_A, 0);
        drain(acc, sbase, 19, KB_A);
        TS(3, 2);
        #pragma unroll 1
        for (int i = 0; i < 3; i++) {
          const int c = i * 64 + (t >> 1);
          float v = gather_sum<8>(g_csum + (t & 1) * 8 * FF + ct * 192 + c, epoch);
          v += __shfl_xor_sync(0xffffffffu, v, 1);
          csw[c] = v;
        }
        bar_sync<BAR_STATS>(256);
        bar_sync<BAR_BUF>(256);
        const float2 s0 = rs[0], s1 = rs[8], s2 = rs[64], s3 = rs[72];
        #pragma unroll
        for (int jj = 0; jj < 12; jj++) {
          uint32_t r[4];
          const float2 c0 = cs[jj * 8], c1 = cs[jj * 8 + 4];
          const uint32_t ad = st_base + (jj >> 2) * 8192 + (st_x ^ ((jj & 3) << 5));
          fold_pack(&acc[0][8 * jj], s0, s1, c0, c1, r);
          stsm4(ad, r[0], r[1], r[2], r[3]);
          fold_pack(&acc[1][8 * jj], s2, s3, c0, c1, r);
          stsm4(ad + 24576, r[0], r[1], r[2], r[3]);
        }
        __syncwarp();
        TS(3, 3);
        const uint32_t rbase = buf + (l >> 4) * 24576 + gr * 128;
        #pragma unroll 1
        for (int c2 = 0; c2 < 12; c2++) {
          const uint32_t ab = rbase + (c2 >> 2) * 8192;
          uint4 v[2];
          #pragma unroll
          for (int i = 0; i < 2; i++) v[i] = lds128(ab + (((((c2 & 3) * 2 + i) ^ l) & 7) << 4));
          #pragma unroll
          for (int i = 0; i < 2; i++)
            sts128(ab + (((((c2 & 3) * 2 + i) ^ l) & 7) << 4),
                   pack_bf16(gelu_tanh(bf_lo(v[i].x)), gelu_tanh(bf_hi(v[i].x))), pack_bf16(gelu_tanh(bf_lo(v[i].y)), gelu_tanh(bf_hi(v[i].y))),
                   pack_bf16(gelu_tanh(bf_lo(v[i].z)), gelu_tanh(bf_hi(v[i].z))), pack_bf16(gelu_tanh(bf_lo(v[i].w)), gelu_tanh(bf_hi(v[i].w))));
        }
        TS(3, 4);
        bar_arrive<BAR_Z1>(256);
      }
    }
    float acc[2][80];
    if (grp == 1) {
      zero(acc);
      if (wg == 2) {
        bar_sync<BAR_ORD1>(256);
        mainloop<160, 0, false, BAR_ORD2>(acc, sbase, STAGE_B, 10, 10, KB_B, 0);
      } else {
        bar_sync<BAR_ORD2>(256);
        mainloop<160, 0, false, BAR_ORD1>(acc, sbase, STAGE_B, 20, 10, KB_B, 0);
      }
      csw[t] = gather_sum<1>(g_csum + 16 * FF + (2 - wg) * DM + ct * 160 + t, epoch);
      csw[128 + l] = gather_sum<1>(g_csum + 16 * FF + (2 - wg) * DM + ct * 160 + 128 + l, epoch);
      drain(acc, sbase, wg == 2 ? 19 : 29, KB_B);
      TS(wg + 1, wg == 1 ? 7 : 2);
      if (wg == 1) bar_sync<BAR_BUF>(256); else bar_sync<BAR_STATS>(256);
      const float sign = wg == 1 ? -1.f : 1.f;
      const uint32_t tb = buf + 24576 + ((l >> 4) * 8 + (l & 7)) * 128 + (((w * 2 + ((l >> 3) & 1)) ^ (l & 7)) << 4);
      float2 s0 = rs[0], s1 = rs[8], s2 = rs[64], s3 = rs[72];
      s0.x *= sign; s0.y *= sign; s1.x *= sign; s1.y *= sign; s2.x *= sign; s2.y *= sign; s3.x *= sign; s3.y *= sign;
      #pragma unroll
      for (int jj = 0; jj < 10; jj++) {
        uint32_t r[4];
        const float2 c0 = cs[jj * 8], c1 = cs[jj * 8 + 4];
        fold_pack(&acc[0][8 * jj], s0, s1, c0, c1, r);
        stsm4_t(tb + jj * 2048, r[0], r[1], r[2], r[3]);
        fold_pack(&acc[1][8 * jj], s2, s3, c0, c1, r);
        stsm4_t(tb + 20480 + jj * 2048, r[0], r[1], r[2], r[3]);
      }
      if (wg == 1) bar_sync<BAR_WG1>(128); else bar_sync<BAR_WG2>(128);
      TS(wg + 1, wg == 1 ? 8 : 6);
      {
        uint4 z[20];
        const int e0 = t >> 3;
        #pragma unroll
        for (int i = 0; i < 20; i++) z[i] = lds128(buf + 24576 + (e0 + i * 16) * 128 + (((l ^ e0) & 7) << 4));
        bf16* p = g_abT + (size_t)((2 - wg) * DM + ct * 160 + e0) * SEQ + rb * 128 + (l & 7) * 8;
        #pragma unroll
        for (int i = 0; i < 20; i++) stg128(p + (size_t)(i % 10) * 16 * SEQ + (i / 10) * 64, z[i]);
      }
      if (wg == 1) bar_sync<BAR_WG1>(128); else bar_sync<BAR_WG2>(128);
      if (t == 0) publish(g_flags + (wg == 2 ? F_A : F_B) + rb * 4 + ct, epoch);
      TS(wg + 1, wg == 1 ? 9 : 10);
      if (wg == 1) return;
      bar_arrive<BAR_BUF>(256);
    }
    zero(acc);
    bar_sync<BAR_ORD1>(256);
    mainloop<160, 0, false, 0>(acc, sbase, stage_bytes, grp == 0 ? 52 : 30, grp == 0 ? NX : 64 - NX, total, grp);
    if (grp == 0) mainloop<160, 2, true, 0>(acc, sbase, STAGE_A, 52 + NX, 12, KB_A, 0);
    drain(acc, sbase, total - 1, total);
    TS(3, 12);
    uint4* dst = g_part + (size_t)blockIdx.x * 27 * 128 + t;
    const uint4* src = g_part + (size_t)(blockIdx.x ^ 2) * 27 * 128 + t;
    #pragma unroll
    for (int i = 0; i < 27; i++)
      st_vol4(dst + i * 128, __float_as_uint(acc[1][3 * i]), __float_as_uint(acc[1][3 * i + 1]),
              __float_as_uint(i < 26 ? acc[1][3 * i + 2] : 0.f), epoch);
    TS(3, 13);
    const uint32_t slab = ring + (total & (STAGES - 1)) * stage_bytes + w * (16 * 320);
    const uint32_t addr = slab + (((l >> 3) & 1) * 8 + (l & 7)) * 320 + (l >> 4) * 16;
    mbar_wait(full0 + 8 * (total & (STAGES - 1)), (total / STAGES) & 1);
    #pragma unroll
    for (int jj = 0; jj < 10; jj++) {
      uint32_t z0, z1, z2, z3;
      ldsm4(addr + jj * 32, z0, z1, z2, z3);
      float* a = &acc[0][8 * jj];
      a[0] += bf_lo(z0); a[1] += bf_hi(z0); a[2] += bf_lo(z1); a[3] += bf_hi(z1);
      a[4] += bf_lo(z2); a[5] += bf_hi(z2); a[6] += bf_lo(z3); a[7] += bf_hi(z3);
    }
    {
      unsigned n = 0;
      while (ld_vol4(src + 26 * 128).w != epoch && ++n < POLL_LIMIT) __nanosleep(POLL_NS);
      uint4 v[27];
      while (true) {
        bool ok = true;
        #pragma unroll
        for (int i = 0; i < 27; i++) v[i] = ld_vol4(src + i * 128);
        #pragma unroll
        for (int i = 0; i < 27; i++) ok = ok && (v[i].w == epoch);
        if (ok || ++n > POLL_LIMIT) break;
      }
      #pragma unroll
      for (int i = 0; i < 27; i++) {
        acc[0][3 * i] += __uint_as_float(v[i].x);
        acc[0][3 * i + 1] += __uint_as_float(v[i].y);
        if (i < 26) acc[0][3 * i + 2] += __uint_as_float(v[i].z);
      }
    }
    TS(3, 14);
    #pragma unroll
    for (int jj = 0; jj < 10; jj++) {
      const float* a = &acc[0][8 * jj];
      stsm4(addr + jj * 32, pack_bf16(a[0], a[1]), pack_bf16(a[2], a[3]), pack_bf16(a[4], a[5]), pack_bf16(a[6], a[7]));
    }
    fence_async_smem();
    __syncwarp();
    if (l == 0) {
      tma_store_2d(&maps.m[M_OUT], slab, ct * 160, rb * 128 + grp * 64 + w * 16);
      bulk_commit();
      bulk_wait_read();
      if (w == 0) atomicAdd(&g_done, 1u);
    }
    TS(3, 15);
  }
}

typedef CUresult (*EncodeFn)(CUtensorMap*, CUtensorMapDataType, cuuint32_t, void*, const cuuint64_t*, const cuuint64_t*,
                             const cuuint32_t*, const cuuint32_t*, CUtensorMapInterleave, CUtensorMapSwizzle,
                             CUtensorMapL2promotion, CUtensorMapFloatOOBfill);

void make2d(EncodeFn enc, CUtensorMap* m, const void* p, uint64_t cols, uint64_t rows, uint32_t bc, uint32_t br, bool swz = true) {
  cuuint64_t gd[2] = {cols, rows}, gs[1] = {cols * 2};
  cuuint32_t bd[2] = {bc, br}, es[2] = {1, 1};
  enc(m, CU_TENSOR_MAP_DATA_TYPE_BFLOAT16, 2, const_cast<void*>(p), gd, gs, bd, es, CU_TENSOR_MAP_INTERLEAVE_NONE,
      swz ? CU_TENSOR_MAP_SWIZZLE_128B : CU_TENSOR_MAP_SWIZZLE_NONE, CU_TENSOR_MAP_L2_PROMOTION_L2_256B, CU_TENSOR_MAP_FLOAT_OOB_FILL_NONE);
}
void make3d(EncodeFn enc, CUtensorMap* m, const void* p, uint64_t cols, uint64_t rows, uint32_t cw, uint32_t nc) {
  cuuint64_t gd[3] = {cw, rows, cols / cw}, gs[2] = {cols * 2, cw * 2};
  cuuint32_t bd[3] = {cw, 64, nc}, es[3] = {1, 1, 1};
  enc(m, CU_TENSOR_MAP_DATA_TYPE_BFLOAT16, 3, const_cast<void*>(p), gd, gs, bd, es, CU_TENSOR_MAP_INTERLEAVE_NONE,
      cw == 64 ? CU_TENSOR_MAP_SWIZZLE_128B : CU_TENSOR_MAP_SWIZZLE_64B, CU_TENSOR_MAP_L2_PROMOTION_L2_256B, CU_TENSOR_MAP_FLOAT_OOB_FILL_NONE);
}

}

extern "C" void kernel_launch(void* const* d_in, const int* in_sizes, int n_in, void* d_out, int out_size) {
  const bf16* x = (const bf16*)d_in[0];
  const bf16* wsre = (const bf16*)d_in[1];
  const bf16* wsim = (const bf16*)d_in[2];
  const bf16* wdre = (const bf16*)d_in[3];
  const bf16* wdim = (const bf16*)d_in[4];
  const bf16* win = (const bf16*)d_in[6];
  const bf16* wsp = (const bf16*)d_in[7];
  const bf16* bsp = (const bf16*)d_in[8];
  const bf16* wout = (const bf16*)d_in[9];

  void* fn = nullptr;
  cudaDriverEntryPointQueryResult qr;
  cudaGetDriverEntryPoint("cuTensorMapEncodeTiled", &fn, cudaEnableDefault, &qr);
  EncodeFn enc = (EncodeFn)fn;
  void *abT, *z2, *h;
  cudaGetSymbolAddress(&abT, g_abT);
  cudaGetSymbolAddress(&z2, g_z2);
  cudaGetSymbolAddress(&h, g_h);

  Maps maps;
  make2d(enc, &maps.m[M_X], x, DM, SEQ, 64, 64);
  make2d(enc, &maps.m[M_XR], x, DM, SEQ, 160, 64, false);
  make3d(enc, &maps.m[M_WIN32], win, FF, DM, 32, 3);
  make2d(enc, &maps.m[M_WSRE], wsre, SEQ, SEQ, 64, 64);
  make2d(enc, &maps.m[M_WSIM], wsim, SEQ, SEQ, 64, 64);
  make2d(enc, &maps.m[M_WSP], wsp, SEQ, SEQ, 64, 64);
  make2d(enc, &maps.m[M_H], h, FH, SEQ, 64, 64);
  make3d(enc, &maps.m[M_WIN3], win, FF, DM, 64, 3);
  make3d(enc, &maps.m[M_Z23], z2, FH, SEQ, 64, 3);
  make2d(enc, &maps.m[M_WDRE], wdre, DM, DM, 64, 160);
  make2d(enc, &maps.m[M_WDIM], wdim, DM, DM, 64, 160);
  make2d(enc, &maps.m[M_AB], abT, SEQ, 2 * DM, 64, 160);
  make3d(enc, &maps.m[M_WOUT], wout, DM, FH, 32, 5);
  make2d(enc, &maps.m[M_OUT], d_out, DM, SEQ, 160, 16, false);

  cudaFuncSetAttribute(fused_kernel, cudaFuncAttributeMaxDynamicSharedMemorySize, SMEM_BYTES);
  fused_kernel<<<128, 384, SMEM_BYTES>>>(maps, x, win, bsp, wdre, wdim);
}
```

```cpp
#include <cuda_runtime.h>
#include <cuda_bf16.h>
#include <cuda.h>
#include <stdint.h>

namespace {

typedef __nv_bfloat16 bf16;

constexpr int SEQ = 2048, DM = 640, FF = 1536, FH = 768;
#define NXV 11
constexpr int NX = NXV;
constexpr int STAGES = 4;
constexpr int A_BYTES = 16384;
constexpr int BIAS_OFF = 0;
constexpr int BAR_OFF = 512;
constexpr int RING_OFF = 1024;
constexpr int STAGE_A = 40960, STAGE_B = 36864;
constexpr int SMEM_BYTES = RING_OFF + 4 * STAGE_A + 49152;
constexpr int KB_A = 20 + 32 + NX + 12;
constexpr int KB_B = 30 + 64 - NX;
constexpr float LN_EPS = 1e-5f;
constexpr unsigned POLL_LIMIT = 100000;
#define POLL_NS 100
#define PF_D 10
#define Z1_NS 0
#define INFL 2
#define LIM_G 1000
#define PF_NS 150

constexpr int BAR_ORD1 = 1, BAR_ORD2 = 2, BAR_WG1 = 3, BAR_WG2 = 4, BAR_LN = 5, BAR_BUF = 6, BAR_Z1 = 7, BAR_PUB1 = 8, BAR_PUB2 = 9;

enum { M_XN, M_XR, M_WIN32, M_Z232, M_WSRE, M_WSIM, M_WSP, M_H, M_WIN3, M_Z23, M_WDRE, M_WDIM, M_AB, M_WOUT, M_OUT, M_COUNT };
struct Maps { CUtensorMap m[M_COUNT]; };

__device__ __align__(1024) bf16 g_abT[2 * DM * SEQ];
__device__ __align__(1024) bf16 g_z2[SEQ * FH];
__device__ __align__(1024) bf16 g_h[SEQ * FH];
__device__ __align__(1024) bf16 g_xn[SEQ * DM];
__device__ __align__(16) uint2 g_zstat[128 * 128];
__device__ __align__(16) uint4 g_part[128 * 27 * 128];
__device__ unsigned g_flags[5 * 128];
constexpr int F_A = 0, F_B = 128, F_H = 256, F_Z = 384, F_XN = 512;
__device__ unsigned g_done;
#define TS(role, ev)
#define TC(i)

extern __shared__ __align__(1024) uint8_t smem[];

__device__ __forceinline__ uint32_t smem_u32(const void* p) { return (uint32_t)__cvta_generic_to_shared(p); }
__device__ __forceinline__ void mbar_init(uint32_t bar, uint32_t cnt) { asm volatile("mbarrier.init.shared::cta.b64 [%0], %1;" :: "r"(bar), "r"(cnt)); }
__device__ __forceinline__ void mbar_expect_tx(uint32_t bar, uint32_t bytes) { asm volatile("mbarrier.arrive.expect_tx.shared::cta.b64 _, [%0], %1;" :: "r"(bar), "r"(bytes) : "memory"); }
__device__ __forceinline__ void mbar_arrive(uint32_t bar) { asm volatile("mbarrier.arrive.shared::cta.b64 _, [%0];" :: "r"(bar) : "memory"); }
__device__ __forceinline__ void mbar_arrive_cluster(uint32_t bar, uint32_t cta) {
  asm volatile("{\n.reg .b32 ra;\nmapa.shared::cluster.u32 ra, %0, %1;\nmbarrier.arrive.shared::cluster.b64 _, [ra];\n}" :: "r"(bar), "r"(cta) : "memory");
}
__device__ __forceinline__ void mbar_wait(uint32_t bar, uint32_t parity) {
  asm volatile("{\n.reg .pred p;\n.reg .u32 n;\nmov.u32 n, 0;\n"
               "LW: mbarrier.try_wait.parity.shared::cta.b64 p, [%0], %1, 2000;\n@p bra LD;\n"
               "add.u32 n, n, 1;\nsetp.lt.u32 p, n, 20000;\n@p bra LW;\nLD:\n}" :: "r"(bar), "r"(parity) : "memory");
}
__device__ __forceinline__ void tma_load_2d(uint32_t dst, const CUtensorMap* map, uint32_t bar, int c0, int c1) {
  asm volatile("cp.async.bulk.tensor.2d.shared::cluster.global.mbarrier::complete_tx::bytes [%0], [%1, {%3, %4}], [%2];"
    :: "r"(dst), "l"((uint64_t)map), "r"(bar), "r"(c0), "r"(c1) : "memory");
}
__device__ __forceinline__ void tma_load_3d(uint32_t dst, const CUtensorMap* map, uint32_t bar, int c0, int c1, int c2) {
  asm volatile("cp.async.bulk.tensor.3d.shared::cluster.global.mbarrier::complete_tx::bytes [%0], [%1, {%3, %4, %5}], [%2];"
    :: "r"(dst), "l"((uint64_t)map), "r"(bar), "r"(c0), "r"(c1), "r"(c2) : "memory");
}
__device__ __forceinline__ void tma_load_2d_mc(uint32_t dst, const CUtensorMap* map, uint32_t bar, int c0, int c1, uint16_t mask) {
  asm volatile("cp.async.bulk.tensor.2d.shared::cluster.global.mbarrier::complete_tx::bytes.multicast::cluster [%0], [%1, {%3, %4}], [%2], %5;"
    :: "r"(dst), "l"((uint64_t)map), "r"(bar), "r"(c0), "r"(c1), "h"(mask) : "memory");
}
__device__ __forceinline__ void tma_store_2d(const CUtensorMap* map, uint32_t src, int c0, int c1) {
  asm volatile("cp.async.bulk.tensor.2d.global.shared::cta.bulk_group [%0, {%2, %3}], [%1];"
    :: "l"((uint64_t)map), "r"(src), "r"(c0), "r"(c1) : "memory");
}
__device__ __forceinline__ void tma_store_3d(const CUtensorMap* map, uint32_t src, int c0, int c1, int c2) {
  asm volatile("cp.async.bulk.tensor.3d.global.shared::cta.bulk_group [%0, {%2, %3, %4}], [%1];"
    :: "l"((uint64_t)map), "r"(src), "r"(c0), "r"(c1), "r"(c2) : "memory");
}
__device__ __forceinline__ void bulk_wait_all() { asm volatile("cp.async.bulk.wait_group 0;" ::: "memory"); }
__device__ __forceinline__ void bulk_commit() { asm volatile("cp.async.bulk.commit_group;" ::: "memory"); }
__device__ __forceinline__ void bulk_wait_read() { asm volatile("cp.async.bulk.wait_group.read 0;" ::: "memory"); }
__device__ __forceinline__ void fence_async_smem() { asm volatile("fence.proxy.async.shared::cta;" ::: "memory"); }
__device__ __forceinline__ void fence_async_global() { asm volatile("fence.proxy.async.global;" ::: "memory"); }
__device__ __forceinline__ void wgmma_fence() { asm volatile("wgmma.fence.sync.aligned;" ::: "memory"); }
__device__ __forceinline__ void wgmma_commit() { asm volatile("wgmma.commit_group.sync.aligned;" ::: "memory"); }
template<int N> __device__ __forceinline__ void wgmma_wait() { asm volatile("wgmma.wait_group.sync.aligned %0;" :: "n"(N) : "memory"); }
template<int ID> __device__ __forceinline__ void bar_sync(int n) { asm volatile("bar.sync %0, %1;" :: "n"(ID), "r"(n) : "memory"); }
template<int ID> __device__ __forceinline__ void bar_arrive(int n) { asm volatile("bar.arrive %0, %1;" :: "n"(ID), "r"(n) : "memory"); }
__device__ __forceinline__ void cluster_wait() { asm volatile("barrier.cluster.wait.aligned;" ::: "memory"); }
__device__ __forceinline__ uint64_t desc64(uint32_t lo, uint32_t hi) { return (uint64_t)lo | ((uint64_t)hi << 32); }
__device__ __forceinline__ uint4 ld_vol4(const uint4* p) {
  uint4 v; asm volatile("ld.relaxed.gpu.global.v4.u32 {%0,%1,%2,%3}, [%4];" : "=r"(v.x), "=r"(v.y), "=r"(v.z), "=r"(v.w) : "l"(p) : "memory"); return v;
}
__device__ __forceinline__ uint2 ld_vol2(const uint2* p) {
  uint2 v; asm volatile("ld.relaxed.gpu.global.v2.u32 {%0,%1}, [%2];" : "=r"(v.x), "=r"(v.y) : "l"(p) : "memory"); return v;
}
__device__ __forceinline__ void st_vol4(uint4* p, uint32_t a, uint32_t b, uint32_t c, uint32_t d) {
  asm volatile("st.relaxed.gpu.global.v4.u32 [%0], {%1,%2,%3,%4};" :: "l"(p), "r"(a), "r"(b), "r"(c), "r"(d) : "memory");
}
__device__ __forceinline__ void st_vol2(uint2* p, uint32_t a, uint32_t b) {
  asm volatile("st.relaxed.gpu.global.v2.u32 [%0], {%1,%2};" :: "l"(p), "r"(a), "r"(b) : "memory");
}
__device__ __forceinline__ void stg128(void* p, uint4 v) {
  asm volatile("st.global.v4.u32 [%0], {%1,%2,%3,%4};" :: "l"(p), "r"(v.x), "r"(v.y), "r"(v.z), "r"(v.w));
}
__device__ __forceinline__ unsigned ld_relaxed(const unsigned* p) {
  unsigned v; asm volatile("ld.relaxed.gpu.global.u32 %0, [%1];" : "=r"(v) : "l"(p) : "memory"); return v;
}
__device__ __forceinline__ uint32_t pack_bf16(float lo, float hi) {
  uint32_t r; asm("cvt.rn.bf16x2.f32 %0, %1, %2;" : "=r"(r) : "f"(hi), "f"(lo)); return r;
}
__device__ __forceinline__ float bf_lo(uint32_t v) { return __uint_as_float(v << 16); }
__device__ __forceinline__ float bf_hi(uint32_t v) { return __uint_as_float(v & 0xFFFF0000u); }
__device__ __forceinline__ void stsm4(uint32_t addr, uint32_t a, uint32_t b, uint32_t c, uint32_t d) {
  asm volatile("stmatrix.sync.aligned.m8n8.x4.shared.b16 [%0], {%1,%2,%3,%4};" :: "r"(addr), "r"(a), "r"(b), "r"(c), "r"(d));
}
__device__ __forceinline__ void stsm4_t(uint32_t addr, uint32_t a, uint32_t b, uint32_t c, uint32_t d) {
  asm volatile("stmatrix.sync.aligned.m8n8.x4.trans.shared.b16 [%0], {%1,%2,%3,%4};" :: "r"(addr), "r"(a), "r"(b), "r"(c), "r"(d));
}
__device__ __forceinline__ void ldsm4(uint32_t addr, uint32_t& a, uint32_t& b, uint32_t& c, uint32_t& d) {
  asm volatile("ldmatrix.sync.aligned.m8n8.x4.shared.b16 {%0,%1,%2,%3}, [%4];" : "=r"(a), "=r"(b), "=r"(c), "=r"(d) : "r"(addr));
}
__device__ __forceinline__ uint4 lds128(uint32_t a) {
  uint4 v; asm volatile("ld.shared.v4.u32 {%0,%1,%2,%3}, [%4];" : "=r"(v.x), "=r"(v.y), "=r"(v.z), "=r"(v.w) : "r"(a)); return v;
}
__device__ __forceinline__ void sts128(uint32_t a, uint32_t x, uint32_t y, uint32_t z, uint32_t w) {
  asm volatile("st.shared.v4.u32 [%0], {%1,%2,%3,%4};" :: "r"(a), "r"(x), "r"(y), "r"(z), "r"(w));
}
__device__ __forceinline__ uint32_t hmul2_bf16(uint32_t a, uint32_t b) {
  uint32_t r; asm("mul.rn.bf16x2 %0, %1, %2;" : "=r"(r) : "r"(a), "r"(b)); return r;
}
__device__ __forceinline__ float gelu_tanh(float v) {
  float u = v * fmaf(0.0356774081f, v * v, 0.7978845608f);
  float t; asm("tanh.approx.f32 %0, %1;" : "=f"(t) : "f"(u));
  float hv = 0.5f * v;
  return fmaf(hv, t, hv);
}

template<int TB>
__device__ __forceinline__ void wgmma_n192(float (&d)[96], uint64_t da, uint64_t db, int scale_d) {
  asm volatile("{\n.reg .pred p;\nsetp.ne.b32 p, %98, 0;\n"
   "wgmma.mma_async.sync.aligned.m64n192k16.f32.bf16.bf16 {%0,%1,%2,%3,%4,%5,%6,%7,%8,%9,%10,%11,%12,%13,%14,%15,%16,%17,%18,%19,%20,%21,%22,%23,%24,%25,%26,%27,%28,%29,%30,%31,%32,%33,%34,%35,%36,%37,%38,%39,%40,%41,%42,%43,%44,%45,%46,%47,%48,%49,%50,%51,%52,%53,%54,%55,%56,%57,%58,%59,%60,%61,%62,%63,%64,%65,%66,%67,%68,%69,%70,%71,%72,%73,%74,%75,%76,%77,%78,%79,%80,%81,%82,%83,%84,%85,%86,%87,%88,%89,%90,%91,%92,%93,%94,%95}, %96, %97, p, 1, 1, 0, %99;\n}"
   : "+f"(d[0]),"+f"(d[1]),"+f"(d[2]),"+f"(d[3]),"+f"(d[4]),"+f"(d[5]),"+f"(d[6]),"+f"(d[7]),"+f"(d[8]),"+f"(d[9]),"+f"(d[10]),"+f"(d[11]),"+f"(d[12]),"+f"(d[13]),"+f"(d[14]),"+f"(d[15]),"+f"(d[16]),"+f"(d[17]),"+f"(d[18]),"+f"(d[19]),"+f"(d[20]),"+f"(d[21]),"+f"(d[22]),"+f"(d[23]),"+f"(d[24]),"+f"(d[25]),"+f"(d[26]),"+f"(d[27]),"+f"(d[28]),"+f"(d[29]),"+f"(d[30]),"+f"(d[31]),"+f"(d[32]),"+f"(d[33]),"+f"(d[34]),"+f"(d[35]),"+f"(d[36]),"+f"(d[37]),"+f"(d[38]),"+f"(d[39]),"+f"(d[40]),"+f"(d[41]),"+f"(d[42]),"+f"(d[43]),"+f"(d[44]),"+f"(d[45]),"+f"(d[46]),"+f"(d[47]),"+f"(d[48]),"+f"(d[49]),"+f"(d[50]),"+f"(d[51]),"+f"(d[52]),"+f"(d[53]),"+f"(d[54]),"+f"(d[55]),"+f"(d[56]),"+f"(d[57]),"+f"(d[58]),"+f"(d[59]),"+f"(d[60]),"+f"(d[61]),"+f"(d[62]),"+f"(d[63]),"+f"(d[64]),"+f"(d[65]),"+f"(d[66]),"+f"(d[67]),"+f"(d[68]),"+f"(d[69]),"+f"(d[70]),"+f"(d[71]),"+f"(d[72]),"+f"(d[73]),"+f"(d[74]),"+f"(d[75]),"+f"(d[76]),"+f"(d[77]),"+f"(d[78]),"+f"(d[79]),"+f"(d[80]),"+f"(d[81]),"+f"(d[82]),"+f"(d[83]),"+f"(d[84]),"+f"(d[85]),"+f"(d[86]),"+f"(d[87]),"+f"(d[88]),"+f"(d[89]),"+f"(d[90]),"+f"(d[91]),"+f"(d[92]),"+f"(d[93]),"+f"(d[94]),"+f"(d[95])
   : "l"(da), "l"(db), "r"(scale_d), "n"(TB));
}
template<int TB>
__device__ __forceinline__ void wgmma_n160(float (&d)[80], uint64_t da, uint64_t db, int scale_d) {
  asm volatile("{\n.reg .pred p;\nsetp.ne.b32 p, %82, 0;\n"
   "wgmma.mma_async.sync.aligned.m64n160k16.f32.bf16.bf16 {%0,%1,%2,%3,%4,%5,%6,%7,%8,%9,%10,%11,%12,%13,%14,%15,%16,%17,%18,%19,%20,%21,%22,%23,%24,%25,%26,%27,%28,%29,%30,%31,%32,%33,%34,%35,%36,%37,%38,%39,%40,%41,%42,%43,%44,%45,%46,%47,%48,%49,%50,%51,%52,%53,%54,%55,%56,%57,%58,%59,%60,%61,%62,%63,%64,%65,%66,%67,%68,%69,%70,%71,%72,%73,%74,%75,%76,%77,%78,%79}, %80, %81, p, 1, 1, 0, %83;\n}"
   : "+f"(d[0]),"+f"(d[1]),"+f"(d[2]),"+f"(d[3]),"+f"(d[4]),"+f"(d[5]),"+f"(d[6]),"+f"(d[7]),"+f"(d[8]),"+f"(d[9]),"+f"(d[10]),"+f"(d[11]),"+f"(d[12]),"+f"(d[13]),"+f"(d[14]),"+f"(d[15]),"+f"(d[16]),"+f"(d[17]),"+f"(d[18]),"+f"(d[19]),"+f"(d[20]),"+f"(d[21]),"+f"(d[22]),"+f"(d[23]),"+f"(d[24]),"+f"(d[25]),"+f"(d[26]),"+f"(d[27]),"+f"(d[28]),"+f"(d[29]),"+f"(d[30]),"+f"(d[31]),"+f"(d[32]),"+f"(d[33]),"+f"(d[34]),"+f"(d[35]),"+f"(d[36]),"+f"(d[37]),"+f"(d[38]),"+f"(d[39]),"+f"(d[40]),"+f"(d[41]),"+f"(d[42]),"+f"(d[43]),"+f"(d[44]),"+f"(d[45]),"+f"(d[46]),"+f"(d[47]),"+f"(d[48]),"+f"(d[49]),"+f"(d[50]),"+f"(d[51]),"+f"(d[52]),"+f"(d[53]),"+f"(d[54]),"+f"(d[55]),"+f"(d[56]),"+f"(d[57]),"+f"(d[58]),"+f"(d[59]),"+f"(d[60]),"+f"(d[61]),"+f"(d[62]),"+f"(d[63]),"+f"(d[64]),"+f"(d[65]),"+f"(d[66]),"+f"(d[67]),"+f"(d[68]),"+f"(d[69]),"+f"(d[70]),"+f"(d[71]),"+f"(d[72]),"+f"(d[73]),"+f"(d[74]),"+f"(d[75]),"+f"(d[76]),"+f"(d[77]),"+f"(d[78]),"+f"(d[79])
   : "l"(da), "l"(db), "r"(scale_d), "n"(TB));
}
template<int TB>
__device__ __forceinline__ void wgmma_n96(float (&d)[48], uint64_t da, uint64_t db, int scale_d) {
  asm volatile("{\n.reg .pred p;\nsetp.ne.b32 p, %50, 0;\n"
   "wgmma.mma_async.sync.aligned.m64n96k16.f32.bf16.bf16 {%0,%1,%2,%3,%4,%5,%6,%7,%8,%9,%10,%11,%12,%13,%14,%15,%16,%17,%18,%19,%20,%21,%22,%23,%24,%25,%26,%27,%28,%29,%30,%31,%32,%33,%34,%35,%36,%37,%38,%39,%40,%41,%42,%43,%44,%45,%46,%47}, %48, %49, p, 1, 1, 0, %51;\n}"
   : "+f"(d[0]),"+f"(d[1]),"+f"(d[2]),"+f"(d[3]),"+f"(d[4]),"+f"(d[5]),"+f"(d[6]),"+f"(d[7]),"+f"(d[8]),"+f"(d[9]),"+f"(d[10]),"+f"(d[11]),"+f"(d[12]),"+f"(d[13]),"+f"(d[14]),"+f"(d[15]),"+f"(d[16]),"+f"(d[17]),"+f"(d[18]),"+f"(d[19]),"+f"(d[20]),"+f"(d[21]),"+f"(d[22]),"+f"(d[23]),"+f"(d[24]),"+f"(d[25]),"+f"(d[26]),"+f"(d[27]),"+f"(d[28]),"+f"(d[29]),"+f"(d[30]),"+f"(d[31]),"+f"(d[32]),"+f"(d[33]),"+f"(d[34]),"+f"(d[35]),"+f"(d[36]),"+f"(d[37]),"+f"(d[38]),"+f"(d[39]),"+f"(d[40]),"+f"(d[41]),"+f"(d[42]),"+f"(d[43]),"+f"(d[44]),"+f"(d[45]),"+f"(d[46]),"+f"(d[47])
   : "l"(da), "l"(db), "r"(scale_d), "n"(TB));
}

template<int N, int TB>
__device__ __forceinline__ void wgmma_n(float (&d)[N / 2], uint64_t da, uint64_t db) {
  if constexpr (N == 192) wgmma_n192<TB>(d, da, db, 1);
  else if constexpr (N == 160) wgmma_n160<TB>(d, da, db, 1);
  else wgmma_n96<TB>(d, da, db, 1);
}

template<int R>
__device__ __forceinline__ void pin(float (&acc)[2][R]) {
  #pragma unroll
  for (int mi = 0; mi < 2; mi++)
    #pragma unroll
    for (int i = 0; i < R; i++) asm volatile("" : "+f"(acc[mi][i]) :: "memory");
}
template<int R>
__device__ __forceinline__ void zero(float (&acc)[2][R]) {
  #pragma unroll
  for (int i = 0; i < R; i++) { acc[0][i] = 0.f; acc[1][i] = 0.f; }
  pin(acc);
}

template<int N, int TB, bool CONT, int ORD_BAR>
__device__ __forceinline__ void mainloop(float (&acc)[2][N / 2], uint32_t sbase, uint32_t stage_bytes, int g0, int nk, int total, int mswap) {
  const uint32_t full0 = sbase + BAR_OFF, empty0 = full0 + 8 * STAGES, ring = sbase + RING_OFF;
  const int t = threadIdx.x & 127;
  const uint32_t da0 = (((ring + mswap * 8192) & 0x3FFFF) >> 4) | 0x10000u, da1 = (((ring + (mswap ^ 1) * 8192) & 0x3FFFF) >> 4) | 0x10000u;
  const uint32_t db0 = (((ring + A_BYTES) & 0x3FFFF) >> 4) | ((TB == 2 ? 256u : TB ? 512u : 1u) << 16);
  constexpr uint32_t HI_A = 0x40000040u, HI_B = TB == 2 ? 0x80000020u : 0x40000040u;
  #pragma unroll 1
  for (int g = g0; g < g0 + nk; g++) {
    const int s = g & (STAGES - 1);
    const uint32_t so = s * (stage_bytes >> 4);
    mbar_wait(full0 + 8 * s, (g / STAGES) & 1);
    wgmma_fence();
    #pragma unroll
    for (int k = 0; k < 4; k++) {
      const uint64_t db = desc64(db0 + so + (TB == 2 ? k * 64 : TB ? k * 128 : k * 2), HI_B);
      wgmma_n<N, TB != 0>(acc[0], desc64(da0 + so + k * 2, HI_A), db);
      wgmma_n<N, TB != 0>(acc[1], desc64(da1 + so + k * 2, HI_A), db);
    }
    wgmma_commit();
    if (ORD_BAR != 0 && g == g0 + nk - 1) bar_arrive<ORD_BAR>(256);
    wgmma_wait<1>();
    if (t < 2 && (CONT || g > g0) && g - 1 + STAGES <= total) mbar_arrive_cluster(empty0 + 8 * ((g - 1) & (STAGES - 1)), t);
  }
}
template<int R>
__device__ __forceinline__ void drain(float (&acc)[2][R], uint32_t sbase, int glast, int total) {
  wgmma_wait<0>();
  pin(acc);
  const int t = threadIdx.x & 127;
  if (t < 2 && glast + STAGES <= total) mbar_arrive_cluster(sbase + BAR_OFF + 8 * STAGES + 8 * (glast & (STAGES - 1)), t);
}

__device__ __forceinline__ void publish(unsigned* flag, unsigned epoch) {
  asm volatile("fence.acq_rel.gpu;" ::: "memory");
  asm volatile("st.relaxed.gpu.global.u32 [%0], %1;" :: "l"(flag), "r"(epoch) : "memory");
}

__device__ __forceinline__ float sum8(uint4 v) {
  return ((bf_lo(v.x) + bf_hi(v.x)) + (bf_lo(v.y) + bf_hi(v.y))) + ((bf_lo(v.z) + bf_hi(v.z)) + (bf_lo(v.w) + bf_hi(v.w)));
}
__device__ __forceinline__ void ln_rows(const bf16* __restrict__ x) {
  const int t = threadIdx.x - 128, row = blockIdx.x * 16 + (t >> 4), c = t & 15;
  uint4 rv[5];
  #pragma unroll
  for (int j = 0; j < 5; j++) rv[j] = __ldg(reinterpret_cast<const uint4*>(x + (size_t)row * DM) + c + 16 * j);
  float s = 0.f;
  #pragma unroll
  for (int j = 0; j < 5; j++) s += sum8(rv[j]);
  #pragma unroll
  for (int o = 1; o < 16; o <<= 1) s += __shfl_xor_sync(0xffffffffu, s, o);
  const float mean = s * (1.f / DM);
  float q = 0.f;
  #pragma unroll
  for (int j = 0; j < 5; j++) {
    const uint32_t u[4] = {rv[j].x, rv[j].y, rv[j].z, rv[j].w};
    #pragma unroll
    for (int e = 0; e < 4; e++) { const float d0 = bf_lo(u[e]) - mean, d1 = bf_hi(u[e]) - mean; q = fmaf(d0, d0, q); q = fmaf(d1, d1, q); }
  }
  #pragma unroll
  for (int o = 1; o < 16; o <<= 1) q += __shfl_xor_sync(0xffffffffu, q, o);
  const float r = rsqrtf(fmaf(q, 1.f / DM, LN_EPS)), o = -mean * r;
  #pragma unroll
  for (int j = 0; j < 5; j++)
    stg128(reinterpret_cast<uint4*>(g_xn + (size_t)row * DM) + c + 16 * j, make_uint4(
           pack_bf16(fmaf(bf_lo(rv[j].x), r, o), fmaf(bf_hi(rv[j].x), r, o)), pack_bf16(fmaf(bf_lo(rv[j].y), r, o), fmaf(bf_hi(rv[j].y), r, o)),
           pack_bf16(fmaf(bf_lo(rv[j].z), r, o), fmaf(bf_hi(rv[j].z), r, o)), pack_bf16(fmaf(bf_lo(rv[j].w), r, o), fmaf(bf_hi(rv[j].w), r, o))));
}

__global__ void __cluster_dims__(2, 1, 1) __launch_bounds__(384, 1)
fused_kernel(const __grid_constant__ Maps maps, const bf16* __restrict__ x, const bf16* __restrict__ bsp) {
  const uint32_t sbase = smem_u32(smem);
  const uint32_t full0 = sbase + BAR_OFF, empty0 = full0 + 8 * STAGES, dep0 = empty0 + 8 * STAGES, ring = sbase + RING_OFF;
  const int tid = threadIdx.x, wg = __shfl_sync(0xffffffffu, tid >> 7, 0);
  const int rank = blockIdx.x & 1, grp = (blockIdx.x >> 1) & 1, q = blockIdx.x >> 2;
  const int rb = q >> 1, ct = (q & 1) * 2 + rank, c8 = grp * 4 + ct;
  const int total = grp == 0 ? KB_A : KB_B;
  const uint32_t stage_bytes = grp == 0 ? STAGE_A : STAGE_B;

  if (tid == 0) {
    TS(0, 0);
    for (int s = 0; s < STAGES; s++) { mbar_init(full0 + 8 * s, 2); mbar_init(empty0 + 8 * s, 2); mbar_init(dep0 + 8 * s, 1); }
    asm volatile("fence.mbarrier_init.release.cluster;" ::: "memory");
  }
  __syncthreads();
  asm volatile("barrier.cluster.arrive.relaxed.aligned;" ::: "memory");

  if (wg == 0) {
    asm volatile("setmaxnreg.dec.sync.aligned.u32 40;");
    const int warp = tid >> 5, lane = tid & 31;
    if (warp == 0) {
      const int row = rb * 128;
      cluster_wait();
      if (lane == 0) {
        #pragma unroll 1
        for (int g = 0; g < total; g++) {
          int mi, kb;
          if (g < 20) { mi = M_XN; kb = g < 10 ? g : g - 10; }
          else if (grp == 0) {
            if (g < 52) { mi = M_WSP; kb = g - 20; }
            else if (g < 52 + NX) { mi = M_WSIM; kb = g - 52 + 32 - NX; }
            else { mi = M_H; kb = g - 52 - NX; }
          } else {
            if (g < 30) { mi = M_XN; kb = g - 20; }
            else if (g < 62) { mi = M_WSRE; kb = g - 30; }
            else { mi = M_WSIM; kb = g - 62; }
          }
          if (g == 0 || (mi == M_H && kb == 0)) { TS(0, g ? 3 : 1); mbar_wait(dep0 + (g ? 24 : 0), 0); fence_async_global(); TS(0, g ? 4 : 2); }
          const int s = g & (STAGES - 1);
          mbar_wait(empty0 + 8 * s, ((g / STAGES) & 1) ^ 1);
          mbar_expect_tx(full0 + 8 * s, A_BYTES);
          tma_load_2d_mc(ring + s * stage_bytes + rank * 8192, &maps.m[mi], full0 + 8 * s, kb * 64, row + rank * 64, 3);
        }
        const int s = total & (STAGES - 1);
        mbar_wait(empty0 + 8 * s, ((total / STAGES) & 1) ^ 1);
        mbar_expect_tx(full0 + 8 * s, 20480);
        mbar_arrive(full0 + 8 * s);
        tma_load_2d(ring + s * stage_bytes, &maps.m[M_XR], full0 + 8 * s, ct * 160, row + grp * 64);
        TS(0, 5);
      }
    } else if (warp == 1) {
      if (lane == 0) {
        #pragma unroll 1
        for (int g = 0; g < total; g++) {
          int kind = 1, mi, kb, c, dep = 0;
          uint32_t bytes = 20480;
          if (g < 10) { kind = 0; mi = M_WIN32; kb = g; c = 24 + 3 * c8; bytes = 12288; }
          else if (grp == 0) {
            if (g < 20) { kind = 0; mi = M_WIN3; kb = g - 10; c = 3 * ct; bytes = 24576; }
            else if (g < 52) { kind = 0; mi = M_Z23; kb = g - 20; c = 3 * ct; bytes = 24576; dep = g == 20 ? 1 : 0; }
            else if (g < 52 + NX) { mi = M_AB; kb = g - 52 + 32 - NX; c = DM + ct * 160; dep = g == 52 ? 2 : 0; }
            else { kind = 0; mi = M_WOUT; kb = g - 52 - NX; c = ct * 5; }
          } else {
            if (g < 30) { mi = g < 20 ? M_WDRE : M_WDIM; kb = g < 20 ? g - 10 : g - 20; c = ct * 160; }
            else { mi = M_AB; kb = g < 62 ? g - 30 : g - 62; c = ct * 160 + (g < 62 ? 0 : DM); dep = g == 30 ? 1 : g == 62 ? 2 : 0; }
          }
          if (dep) { TS(1, dep * 2 - 2); mbar_wait(dep0 + 8 * dep, 0); fence_async_global(); TS(1, dep * 2 - 1); TC(dep); }
          const int s = g & (STAGES - 1);
          const uint32_t dst = ring + s * stage_bytes + A_BYTES, fb = full0 + 8 * s;
          mbar_wait(empty0 + 8 * s, ((g / STAGES) & 1) ^ 1);
          mbar_expect_tx(fb, bytes);
          if (kind == 0) tma_load_3d(dst, &maps.m[mi], fb, 0, kb * 64, c);
          else tma_load_2d(dst, &maps.m[mi], fb, kb * 64, c);
        }
      }
      __syncwarp();
      cluster_wait();
    } else if (warp == 2) {
      cluster_wait();
      const unsigned epoch = (*reinterpret_cast<volatile unsigned*>(&g_done) >> 7) + 1u;
      #pragma unroll 1
      for (int d = 0; d < 4 - grp; d++) {
        const int fi = d == 0 ? F_XN + rb * 8 + (lane & 7)
                     : d == 3 ? F_H + rb * 4 + (lane & 3)
                     : (d == 1 && grp == 0) ? F_Z + (lane >> 1) * 8 + ct * 2 + (lane & 1)
                     : (d == 1 ? F_A : F_B) + (lane & 15) * 4 + ct;
        unsigned it = 0;
        while (!__all_sync(0xffffffffu, ld_relaxed(g_flags + fi) == epoch) && ++it < POLL_LIMIT) __nanosleep(20);
        fence_async_global();
        __syncwarp();
        if (lane == 0) mbar_arrive(dep0 + 8 * d);
      }
    } else {
      const unsigned epoch = (*reinterpret_cast<volatile unsigned*>(&g_done) >> 7) + 1u;
      cluster_wait();
      bar_sync<BAR_LN>(288);
      if (lane == 0) publish(g_flags + F_XN + blockIdx.x, epoch);
      __syncwarp();
      bar_sync<BAR_PUB1>(160);
      if (lane == 0) {
        tma_store_3d(&maps.m[M_Z232], ring + 4 * stage_bytes, 0, rb * 128, 3 * c8);
        bulk_commit();
        bulk_wait_all();
        asm volatile("st.relaxed.gpu.global.u32 [%0], %1;" :: "l"(g_flags + F_Z + rb * 8 + c8), "r"(epoch) : "memory");
        TS(1, 8);
      }
      __syncwarp();
      if (grp == 0) {
        bar_arrive<BAR_BUF>(160);
      } else {
        bar_sync<BAR_PUB2>(160);
        if (lane == 0) publish(g_flags + F_A + rb * 4 + ct, epoch);
        TS(1, 9);
        __syncwarp();
      }
      bar_sync<BAR_PUB1>(160);
      if (lane == 0) publish(g_flags + (grp == 0 ? F_H : F_B) + rb * 4 + ct, epoch);
      TS(1, 10);
    }
  } else {
    asm volatile("setmaxnreg.inc.sync.aligned.u32 232;");
    const int t = tid & 127, w = t >> 5, l = t & 31;
    const uint32_t buf = ring + 4 * stage_bytes;
    const unsigned epoch = (*reinterpret_cast<volatile unsigned*>(&g_done) >> 7) + 1u;
    ln_rows(x);
    bar_arrive<BAR_LN>(288);
    TS(wg + 1, 0);
    cluster_wait();
    const int rl = w * 16 + ((l >> 3) & 1) * 8 + (l & 7);
    const int gr = w * 16 + (l & 15);
    const uint32_t st_base = buf + rl * 128;
    const uint32_t st_x = ((l >> 4) ^ (l & 7)) << 4;
    if (wg == 1) {
      float acc[2][48];
      zero(acc);
      mainloop<96, 2, false, BAR_ORD1>(acc, sbase, stage_bytes, 0, 10, total, 0);
      drain(acc, sbase, 9, total);
      TS(2, 2);
      float sum[4], sq[4];
      #pragma unroll
      for (int r = 0; r < 4; r++) {
        float s0 = 0.f, q0 = 0.f;
        #pragma unroll
        for (int j = 0; j < 12; j++) {
          float* a = &acc[r >> 1][4 * j + (r & 1) * 2];
          a[0] = gelu_tanh(a[0]);
          a[1] = gelu_tanh(a[1]);
          s0 += a[0] + a[1]; q0 = fmaf(a[0], a[0], q0); q0 = fmaf(a[1], a[1], q0);
        }
        s0 += __shfl_xor_sync(0xffffffffu, s0, 1); q0 += __shfl_xor_sync(0xffffffffu, q0, 1);
        s0 += __shfl_xor_sync(0xffffffffu, s0, 2); q0 += __shfl_xor_sync(0xffffffffu, q0, 2);
        sum[r] = s0; sq[r] = q0;
      }
      TS(2, 4);
      float rstd, off;
      {
        const int qd = l & 3;
        const float sm = qd == 0 ? sum[0] : qd == 1 ? sum[1] : qd == 2 ? sum[2] : sum[3];
        const float sv = qd == 0 ? sq[0] : qd == 1 ? sq[1] : qd == 2 ? sq[2] : sq[3];
        const int row = (qd >> 1) * 64 + w * 16 + (qd & 1) * 8 + (l >> 2);
        const float mu = sm * (1.f / 96), m2 = fmaxf(sv - sm * mu, 0.f);
        st_vol2(&g_zstat[(rb * 8 + c8) * 128 + row], __float_as_uint(mu), (__float_as_uint(m2) & ~255u) | (epoch & 255u));
        uint2 v[7];
        unsigned n = 0;
        while (true) {
          bool ok = true;
          #pragma unroll
          for (int j = 0; j < 7; j++) v[j] = ld_vol2(&g_zstat[(rb * 8 + ((c8 + 1 + j) & 7)) * 128 + row]);
          #pragma unroll
          for (int j = 0; j < 7; j++) ok = ok && ((v[j].y ^ epoch) & 255u) == 0;
          if (ok || ++n > POLL_LIMIT) break;
          __nanosleep(POLL_NS);
        }
        float mean = mu, var = m2;
        #pragma unroll
        for (int j = 0; j < 7; j++) { mean += __uint_as_float(v[j].x); var += __uint_as_float(v[j].y & ~255u); }
        mean *= 0.125f;
        float d = (mu - mean) * (mu - mean);
        #pragma unroll
        for (int j = 0; j < 7; j++) d = fmaf(__uint_as_float(v[j].x) - mean, __uint_as_float(v[j].x) - mean, d);
        rstd = rsqrtf(fmaf(96.f, d, var) * (1.f / FH) + LN_EPS); off = -mean * rstd;
        __syncwarp();
      }
      TS(2, 5);
      #pragma unroll
      for (int mi = 0; mi < 2; mi++) {
        const float r0 = __shfl_sync(0xffffffffu, rstd, (l & 28) + mi * 2), o0 = __shfl_sync(0xffffffffu, off, (l & 28) + mi * 2);
        const float r1 = __shfl_sync(0xffffffffu, rstd, (l & 28) + mi * 2 + 1), o1 = __shfl_sync(0xffffffffu, off, (l & 28) + mi * 2 + 1);
        #pragma unroll
        for (int jj = 0; jj < 6; jj++) {
          const float* a = &acc[mi][8 * jj];
          stsm4(buf + (jj >> 1) * 8192 + mi * 4096 + rl * 64 + ((((jj & 1) * 2 + (l >> 4)) ^ ((l >> 1) & 3)) << 4),
                pack_bf16(fmaf(a[0], r0, o0), fmaf(a[1], r0, o0)), pack_bf16(fmaf(a[2], r1, o1), fmaf(a[3], r1, o1)),
                pack_bf16(fmaf(a[4], r0, o0), fmaf(a[5], r0, o0)), pack_bf16(fmaf(a[6], r1, o1), fmaf(a[7], r1, o1)));
        }
      }
      fence_async_smem();
      bar_arrive<BAR_PUB1>(160);
      TS(2, 6);
      if (grp == 0) {
        float acc[2][96];
        zero(acc);
        bar_sync<BAR_ORD2>(256);
        mainloop<192, 1, false, BAR_ORD1>(acc, sbase, STAGE_A, 20, 32, KB_A, 0);
        const float* bias = reinterpret_cast<const float*>(smem + BIAS_OFF) + w * 16 + (l >> 2);
        bar_sync<BAR_Z1>(256);
        drain(acc, sbase, 51, KB_A);
        TS(2, 7);
        {
          const float bb[4] = {bias[0], bias[8], bias[64], bias[72]};
          uint32_t z[2][4][4];
          #pragma unroll
          for (int i = 0; i < 4; i++) ldsm4(st_base + (st_x ^ (i << 5)), z[0][i][0], z[0][i][1], z[0][i][2], z[0][i][3]);
          #pragma unroll
          for (int bx = 0; bx < 6; bx++) {
            if (bx < 5) {
              #pragma unroll
              for (int i = 0; i < 4; i++)
                ldsm4(st_base + (bx + 1) * 8192 + (st_x ^ (i << 5)), z[(bx + 1) & 1][i][0], z[(bx + 1) & 1][i][1], z[(bx + 1) & 1][i][2], z[(bx + 1) & 1][i][3]);
            }
            const float b0 = bb[(bx / 3) * 2], b1 = bb[(bx / 3) * 2 + 1];
            #pragma unroll
            for (int i = 0; i < 4; i++) {
              const float* a = &acc[bx / 3][8 * ((bx % 3) * 4 + i)];
              const uint32_t* zz = z[bx & 1][i];
              stsm4(st_base + bx * 8192 + (st_x ^ (i << 5)),
                    hmul2_bf16(zz[0], pack_bf16(a[0] + b0, a[1] + b0)), hmul2_bf16(zz[1], pack_bf16(a[2] + b1, a[3] + b1)),
                    hmul2_bf16(zz[2], pack_bf16(a[4] + b0, a[5] + b0)), hmul2_bf16(zz[3], pack_bf16(a[6] + b1, a[7] + b1)));
            }
          }
        }
        __syncwarp();
        TS(2, 8);
        {
          uint4 z[24];
          const int r0 = w * 16 + (l >> 3);
          #pragma unroll
          for (int i = 0; i < 24; i++) z[i] = lds128(buf + (i >> 2) * 8192 + (r0 + (i & 3) * 4) * 128 + (((l ^ (r0 + (i & 3) * 4)) & 7) << 4));
          bf16* p = g_h + (size_t)(rb * 128 + r0) * FH + ct * 192 + (l & 7) * 8;
          #pragma unroll
          for (int i = 0; i < 24; i++) stg128(p + (size_t)((i / 12) * 64 + (i & 3) * 4) * FH + ((i >> 2) % 3) * 64, z[i]);
        }
        bar_arrive<BAR_PUB1>(160);
        TS(2, 9);
        return;
      }
    } else {
      if (grp == 0) {
        reinterpret_cast<float*>(smem + BIAS_OFF)[t] = __bfloat162float(bsp[rb * 128 + t]);
        float acc[2][96];
        zero(acc);
        bar_sync<BAR_ORD1>(256);
        mainloop<192, 1, false, BAR_ORD2>(acc, sbase, STAGE_A, 10, 10, KB_A, 0);
        drain(acc, sbase, 19, KB_A);
        TS(3, 2);
        bar_sync<BAR_BUF>(160);
        #pragma unroll
        for (int mi = 0; mi < 2; mi++)
          #pragma unroll
          for (int jj = 0; jj < 12; jj++) {
            const float* a = &acc[mi][8 * jj];
            stsm4(st_base + mi * 24576 + (jj >> 2) * 8192 + (st_x ^ ((jj & 3) << 5)),
                  pack_bf16(a[0], a[1]), pack_bf16(a[2], a[3]), pack_bf16(a[4], a[5]), pack_bf16(a[6], a[7]));
          }
        __syncwarp();
        TS(3, 3);
        const uint32_t rbase = buf + (l >> 4) * 24576 + gr * 128;
        #pragma unroll 1
        for (int c2 = 0; c2 < 12; c2++) {
          const uint32_t ab = rbase + (c2 >> 2) * 8192;
          uint4 v[2];
          #pragma unroll
          for (int i = 0; i < 2; i++) v[i] = lds128(ab + (((((c2 & 3) * 2 + i) ^ l) & 7) << 4));
          #pragma unroll
          for (int i = 0; i < 2; i++)
            sts128(ab + (((((c2 & 3) * 2 + i) ^ l) & 7) << 4),
                   pack_bf16(gelu_tanh(bf_lo(v[i].x)), gelu_tanh(bf_hi(v[i].x))), pack_bf16(gelu_tanh(bf_lo(v[i].y)), gelu_tanh(bf_hi(v[i].y))),
                   pack_bf16(gelu_tanh(bf_lo(v[i].z)), gelu_tanh(bf_hi(v[i].z))), pack_bf16(gelu_tanh(bf_lo(v[i].w)), gelu_tanh(bf_hi(v[i].w))));
        }
        TS(3, 4);
        bar_arrive<BAR_Z1>(256);
      }
    }
    float acc[2][80];
    if (grp == 1) {
      zero(acc);
      if (wg == 2) {
        bar_sync<BAR_ORD1>(256);
        mainloop<160, 0, false, BAR_ORD2>(acc, sbase, STAGE_B, 10, 10, KB_B, 0);
      } else {
        bar_sync<BAR_ORD2>(256);
        mainloop<160, 0, false, BAR_ORD1>(acc, sbase, STAGE_B, 20, 10, KB_B, 0);
      }
      drain(acc, sbase, wg == 2 ? 19 : 29, KB_B);
      TS(wg + 1, wg == 1 ? 7 : 2);
      if (wg == 1) bar_sync<BAR_BUF>(256);
      const uint32_t sg = wg == 1 ? 0x80008000u : 0u;
      const uint32_t tb = buf + 24576 + ((l >> 4) * 8 + (l & 7)) * 128 + (((w * 2 + ((l >> 3) & 1)) ^ (l & 7)) << 4);
      #pragma unroll
      for (int mi = 0; mi < 2; mi++)
        #pragma unroll
        for (int jj = 0; jj < 10; jj++) {
          const float* a = &acc[mi][8 * jj];
          stsm4_t(tb + mi * 20480 + jj * 2048, pack_bf16(a[0], a[1]) ^ sg, pack_bf16(a[2], a[3]) ^ sg, pack_bf16(a[4], a[5]) ^ sg, pack_bf16(a[6], a[7]) ^ sg);
        }
      if (wg == 1) bar_sync<BAR_WG1>(128); else bar_sync<BAR_WG2>(128);
      TS(wg + 1, wg == 1 ? 8 : 6);
      {
        uint4 z[20];
        const int e0 = t >> 3;
        #pragma unroll
        for (int i = 0; i < 20; i++) z[i] = lds128(buf + 24576 + (e0 + i * 16) * 128 + (((l ^ e0) & 7) << 4));
        bf16* p = g_abT + (size_t)((2 - wg) * DM + ct * 160 + e0) * SEQ + rb * 128 + (l & 7) * 8;
        #pragma unroll
        for (int i = 0; i < 20; i++) stg128(p + (size_t)(i % 10) * 16 * SEQ + (i / 10) * 64, z[i]);
      }
      TS(wg + 1, wg == 1 ? 9 : 10);
      if (wg == 1) { bar_arrive<BAR_PUB1>(160); return; }
      bar_arrive<BAR_PUB2>(160);
      bar_arrive<BAR_BUF>(256);
    }
    zero(acc);
    bar_sync<BAR_ORD1>(256);
    mainloop<160, 0, false, 0>(acc, sbase, stage_bytes, grp == 0 ? 52 : 30, grp == 0 ? NX : 64 - NX, total, grp);
    if (grp == 0) mainloop<160, 2, true, 0>(acc, sbase, STAGE_A, 52 + NX, 12, KB_A, 0);
    drain(acc, sbase, total - 1, total);
    TS(3, 12);
    uint4* dst = g_part + (size_t)blockIdx.x * 27 * 128 + t;
    const uint4* src = g_part + (size_t)(blockIdx.x ^ 2) * 27 * 128 + t;
    #pragma unroll
    for (int i = 0; i < 27; i++)
      st_vol4(dst + i * 128, __float_as_uint(acc[1][3 * i]), __float_as_uint(acc[1][3 * i + 1]),
              __float_as_uint(i < 26 ? acc[1][3 * i + 2] : 0.f), epoch);
    TS(3, 13);
    const uint32_t slab = ring + (total & (STAGES - 1)) * stage_bytes + w * (16 * 320);
    const uint32_t addr = slab + (((l >> 3) & 1) * 8 + (l & 7)) * 320 + (l >> 4) * 16;
    mbar_wait(full0 + 8 * (total & (STAGES - 1)), (total / STAGES) & 1);
    #pragma unroll
    for (int jj = 0; jj < 10; jj++) {
      uint32_t z0, z1, z2, z3;
      ldsm4(addr + jj * 32, z0, z1, z2, z3);
      float* a = &acc[0][8 * jj];
      a[0] += bf_lo(z0); a[1] += bf_hi(z0); a[2] += bf_lo(z1); a[3] += bf_hi(z1);
      a[4] += bf_lo(z2); a[5] += bf_hi(z2); a[6] += bf_lo(z3); a[7] += bf_hi(z3);
    }
    {
      unsigned n = 0;
      while (ld_vol4(src + 26 * 128).w != epoch && ++n < POLL_LIMIT) __nanosleep(POLL_NS);
      uint4 v[27];
      while (true) {
        bool ok = true;
        #pragma unroll
        for (int i = 0; i < 27; i++) v[i] = ld_vol4(src + i * 128);
        #pragma unroll
        for (int i = 0; i < 27; i++) ok = ok && (v[i].w == epoch);
        if (ok || ++n > POLL_LIMIT) break;
      }
      #pragma unroll
      for (int i = 0; i < 27; i++) {
        acc[0][3 * i] += __uint_as_float(v[i].x);
        acc[0][3 * i + 1] += __uint_as_float(v[i].y);
        if (i < 26) acc[0][3 * i + 2] += __uint_as_float(v[i].z);
      }
    }
    TS(3, 14);
    #pragma unroll
    for (int jj = 0; jj < 10; jj++) {
      const float* a = &acc[0][8 * jj];
      stsm4(addr + jj * 32, pack_bf16(a[0], a[1]), pack_bf16(a[2], a[3]), pack_bf16(a[4], a[5]), pack_bf16(a[6], a[7]));
    }
    fence_async_smem();
    __syncwarp();
    if (l == 0) {
      tma_store_2d(&maps.m[M_OUT], slab, ct * 160, rb * 128 + grp * 64 + w * 16);
      bulk_commit();
      bulk_wait_read();
      if (w == 0) atomicAdd(&g_done, 1u);
    }
    TS(3, 15);
  }
}

typedef CUresult (*EncodeFn)(CUtensorMap*, CUtensorMapDataType, cuuint32_t, void*, const cuuint64_t*, const cuuint64_t*,
                             const cuuint32_t*, const cuuint32_t*, CUtensorMapInterleave, CUtensorMapSwizzle,
                             CUtensorMapL2promotion, CUtensorMapFloatOOBfill);

void make2d(EncodeFn enc, CUtensorMap* m, const void* p, uint64_t cols, uint64_t rows, uint32_t bc, uint32_t br, bool swz = true) {
  cuuint64_t gd[2] = {cols, rows}, gs[1] = {cols * 2};
  cuuint32_t bd[2] = {bc, br}, es[2] = {1, 1};
  enc(m, CU_TENSOR_MAP_DATA_TYPE_BFLOAT16, 2, const_cast<void*>(p), gd, gs, bd, es, CU_TENSOR_MAP_INTERLEAVE_NONE,
      swz ? CU_TENSOR_MAP_SWIZZLE_128B : CU_TENSOR_MAP_SWIZZLE_NONE, CU_TENSOR_MAP_L2_PROMOTION_L2_256B, CU_TENSOR_MAP_FLOAT_OOB_FILL_NONE);
}
void make3d(EncodeFn enc, CUtensorMap* m, const void* p, uint64_t cols, uint64_t rows, uint32_t cw, uint32_t nc, uint32_t br = 64) {
  cuuint64_t gd[3] = {cw, rows, cols / cw}, gs[2] = {cols * 2, cw * 2};
  cuuint32_t bd[3] = {cw, br, nc}, es[3] = {1, 1, 1};
  enc(m, CU_TENSOR_MAP_DATA_TYPE_BFLOAT16, 3, const_cast<void*>(p), gd, gs, bd, es, CU_TENSOR_MAP_INTERLEAVE_NONE,
      cw == 64 ? CU_TENSOR_MAP_SWIZZLE_128B : CU_TENSOR_MAP_SWIZZLE_64B, CU_TENSOR_MAP_L2_PROMOTION_L2_256B, CU_TENSOR_MAP_FLOAT_OOB_FILL_NONE);
}

}

extern "C" void kernel_launch(void* const* d_in, const int* in_sizes, int n_in, void* d_out, int out_size) {
  const bf16* x = (const bf16*)d_in[0];
  const bf16* wsre = (const bf16*)d_in[1];
  const bf16* wsim = (const bf16*)d_in[2];
  const bf16* wdre = (const bf16*)d_in[3];
  const bf16* wdim = (const bf16*)d_in[4];
  const bf16* win = (const bf16*)d_in[6];
  const bf16* wsp = (const bf16*)d_in[7];
  const bf16* bsp = (const bf16*)d_in[8];
  const bf16* wout = (const bf16*)d_in[9];

  void* fn = nullptr;
  cudaDriverEntryPointQueryResult qr;
  cudaGetDriverEntryPoint("cuTensorMapEncodeTiled", &fn, cudaEnableDefault, &qr);
  EncodeFn enc = (EncodeFn)fn;
  void *abT, *z2, *h, *xn;
  cudaGetSymbolAddress(&xn, g_xn);
  cudaGetSymbolAddress(&abT, g_abT);
  cudaGetSymbolAddress(&z2, g_z2);
  cudaGetSymbolAddress(&h, g_h);

  Maps maps;
  make2d(enc, &maps.m[M_XN], xn, DM, SEQ, 64, 64);
  make3d(enc, &maps.m[M_Z232], z2, FH, SEQ, 32, 3, 128);
  make2d(enc, &maps.m[M_XR], x, DM, SEQ, 160, 64, false);
  make3d(enc, &maps.m[M_WIN32], win, FF, DM, 32, 3);
  make2d(enc, &maps.m[M_WSRE], wsre, SEQ, SEQ, 64, 64);
  make2d(enc, &maps.m[M_WSIM], wsim, SEQ, SEQ, 64, 64);
  make2d(enc, &maps.m[M_WSP], wsp, SEQ, SEQ, 64, 64);
  make2d(enc, &maps.m[M_H], h, FH, SEQ, 64, 64);
  make3d(enc, &maps.m[M_WIN3], win, FF, DM, 64, 3);
  make3d(enc, &maps.m[M_Z23], z2, FH, SEQ, 64, 3);
  make2d(enc, &maps.m[M_WDRE], wdre, DM, DM, 64, 160);
  make2d(enc, &maps.m[M_WDIM], wdim, DM, DM, 64, 160);
  make2d(enc, &maps.m[M_AB], abT, SEQ, 2 * DM, 64, 160);
  make3d(enc, &maps.m[M_WOUT], wout, DM, FH, 32, 5);
  make2d(enc, &maps.m[M_OUT], d_out, DM, SEQ, 160, 16, false);

  cudaFuncSetAttribute(fused_kernel, cudaFuncAttributeMaxDynamicSharedMemorySize, SMEM_BYTES);
  fused_kernel<<<128, 384, SMEM_BYTES>>>(maps, x, bsp);
}
```

```cpp
#include <cuda_runtime.h>
#include <cuda_bf16.h>
#include <cuda.h>
#include <stdint.h>

namespace {

typedef __nv_bfloat16 bf16;

constexpr int SEQ = 2048, DM = 640, FF = 1536, FH = 768;
#define NXV 11
constexpr int NX = NXV;
constexpr int STAGES = 4;
constexpr int A_BYTES = 16384;
constexpr int BIAS_OFF = 0;
constexpr int BAR_OFF = 512;
constexpr int RING_OFF = 1024;
constexpr int STAGE_A = 40960, STAGE_B = 36864;
constexpr int SMEM_BYTES = RING_OFF + 4 * STAGE_A + 49152;
constexpr int KB_A = 20 + 32 + NX + 12;
constexpr int KB_B = 30 + 64 - NX;
constexpr float LN_EPS = 1e-5f;
constexpr unsigned POLL_LIMIT = 100000;
#define POLL_NS 100
#define PF_D 10
#define Z1_NS 0
#define INFL 2
#define LIM_G 1000
#define PF_NS 150

constexpr int BAR_ORD1 = 1, BAR_ORD2 = 2, BAR_WG1 = 3, BAR_WG2 = 4, BAR_LN = 5, BAR_BUF = 6, BAR_Z1 = 7, BAR_PUB1 = 8, BAR_PUB2 = 9;

enum { M_XN, M_XR, M_WIN32, M_Z232, M_WSRE, M_WSIM, M_WSP, M_H, M_WIN3, M_Z23, M_WDRE, M_WDIM, M_AB, M_WOUT, M_OUT, M_HS, M_ABS, M_COUNT };
struct Maps { CUtensorMap m[M_COUNT]; };

__device__ __align__(1024) bf16 g_abT[2 * DM * SEQ];
__device__ __align__(1024) bf16 g_z2[SEQ * FH];
__device__ __align__(1024) bf16 g_h[SEQ * FH];
__device__ __align__(1024) bf16 g_xn[SEQ * DM];
__device__ __align__(16) uint2 g_zstat[128 * 128];
__device__ __align__(16) uint4 g_part[128 * 27 * 128];
__device__ unsigned g_flags[5 * 128];
constexpr int F_A = 0, F_B = 128, F_H = 256, F_Z = 384, F_XN = 512;
__device__ unsigned g_done;
#define TS(role, ev)
#define TC(i)

extern __shared__ __align__(1024) uint8_t smem[];

__device__ __forceinline__ uint32_t smem_u32(const void* p) { return (uint32_t)__cvta_generic_to_shared(p); }
__device__ __forceinline__ void mbar_init(uint32_t bar, uint32_t cnt) { asm volatile("mbarrier.init.shared::cta.b64 [%0], %1;" :: "r"(bar), "r"(cnt)); }
__device__ __forceinline__ void mbar_expect_tx(uint32_t bar, uint32_t bytes) { asm volatile("mbarrier.arrive.expect_tx.shared::cta.b64 _, [%0], %1;" :: "r"(bar), "r"(bytes) : "memory"); }
__device__ __forceinline__ void mbar_arrive(uint32_t bar) { asm volatile("mbarrier.arrive.shared::cta.b64 _, [%0];" :: "r"(bar) : "memory"); }
__device__ __forceinline__ void mbar_arrive_cluster(uint32_t bar, uint32_t cta) {
  asm volatile("{\n.reg .b32 ra;\nmapa.shared::cluster.u32 ra, %0, %1;\nmbarrier.arrive.shared::cluster.b64 _, [ra];\n}" :: "r"(bar), "r"(cta) : "memory");
}
__device__ __forceinline__ void mbar_wait(uint32_t bar, uint32_t parity) {
  asm volatile("{\n.reg .pred p;\n.reg .u32 n;\nmov.u32 n, 0;\n"
               "LW: mbarrier.try_wait.parity.shared::cta.b64 p, [%0], %1, 2000;\n@p bra LD;\n"
               "add.u32 n, n, 1;\nsetp.lt.u32 p, n, 20000;\n@p bra LW;\nLD:\n}" :: "r"(bar), "r"(parity) : "memory");
}
__device__ __forceinline__ void tma_load_2d(uint32_t dst, const CUtensorMap* map, uint32_t bar, int c0, int c1) {
  asm volatile("cp.async.bulk.tensor.2d.shared::cluster.global.mbarrier::complete_tx::bytes [%0], [%1, {%3, %4}], [%2];"
    :: "r"(dst), "l"((uint64_t)map), "r"(bar), "r"(c0), "r"(c1) : "memory");
}
__device__ __forceinline__ void tma_load_3d(uint32_t dst, const CUtensorMap* map, uint32_t bar, int c0, int c1, int c2) {
  asm volatile("cp.async.bulk.tensor.3d.shared::cluster.global.mbarrier::complete_tx::bytes [%0], [%1, {%3, %4, %5}], [%2];"
    :: "r"(dst), "l"((uint64_t)map), "r"(bar), "r"(c0), "r"(c1), "r"(c2) : "memory");
}
__device__ __forceinline__ void tma_load_2d_mc(uint32_t dst, const CUtensorMap* map, uint32_t bar, int c0, int c1, uint16_t mask) {
  asm volatile("cp.async.bulk.tensor.2d.shared::cluster.global.mbarrier::complete_tx::bytes.multicast::cluster [%0], [%1, {%3, %4}], [%2], %5;"
    :: "r"(dst), "l"((uint64_t)map), "r"(bar), "r"(c0), "r"(c1), "h"(mask) : "memory");
}
__device__ __forceinline__ void tma_store_2d(const CUtensorMap* map, uint32_t src, int c0, int c1) {
  asm volatile("cp.async.bulk.tensor.2d.global.shared::cta.bulk_group [%0, {%2, %3}], [%1];"
    :: "l"((uint64_t)map), "r"(src), "r"(c0), "r"(c1) : "memory");
}
__device__ __forceinline__ void tma_store_3d(const CUtensorMap* map, uint32_t src, int c0, int c1, int c2) {
  asm volatile("cp.async.bulk.tensor.3d.global.shared::cta.bulk_group [%0, {%2, %3, %4}], [%1];"
    :: "l"((uint64_t)map), "r"(src), "r"(c0), "r"(c1), "r"(c2) : "memory");
}
__device__ __forceinline__ void bulk_wait_all() { asm volatile("cp.async.bulk.wait_group 0;" ::: "memory"); }
__device__ __forceinline__ void bulk_commit() { asm volatile("cp.async.bulk.commit_group;" ::: "memory"); }
__device__ __forceinline__ void bulk_wait_read() { asm volatile("cp.async.bulk.wait_group.read 0;" ::: "memory"); }
__device__ __forceinline__ void fence_async_smem() { asm volatile("fence.proxy.async.shared::cta;" ::: "memory"); }
__device__ __forceinline__ void fence_async_global() { asm volatile("fence.proxy.async.global;" ::: "memory"); }
__device__ __forceinline__ void wgmma_fence() { asm volatile("wgmma.fence.sync.aligned;" ::: "memory"); }
__device__ __forceinline__ void wgmma_commit() { asm volatile("wgmma.commit_group.sync.aligned;" ::: "memory"); }
template<int N> __device__ __forceinline__ void wgmma_wait() { asm volatile("wgmma.wait_group.sync.aligned %0;" :: "n"(N) : "memory"); }
template<int ID> __device__ __forceinline__ void bar_sync(int n) { asm volatile("bar.sync %0, %1;" :: "n"(ID), "r"(n) : "memory"); }
template<int ID> __device__ __forceinline__ void bar_arrive(int n) { asm volatile("bar.arrive %0, %1;" :: "n"(ID), "r"(n) : "memory"); }
__device__ __forceinline__ void cluster_wait() { asm volatile("barrier.cluster.wait.aligned;" ::: "memory"); }
__device__ __forceinline__ uint64_t desc64(uint32_t lo, uint32_t hi) { return (uint64_t)lo | ((uint64_t)hi << 32); }
__device__ __forceinline__ uint4 ld_vol4(const uint4* p) {
  uint4 v; asm volatile("ld.relaxed.gpu.global.v4.u32 {%0,%1,%2,%3}, [%4];" : "=r"(v.x), "=r"(v.y), "=r"(v.z), "=r"(v.w) : "l"(p) : "memory"); return v;
}
__device__ __forceinline__ uint2 ld_vol2(const uint2* p) {
  uint2 v; asm volatile("ld.relaxed.gpu.global.v2.u32 {%0,%1}, [%2];" : "=r"(v.x), "=r"(v.y) : "l"(p) : "memory"); return v;
}
__device__ __forceinline__ void st_vol4(uint4* p, uint32_t a, uint32_t b, uint32_t c, uint32_t d) {
  asm volatile("st.relaxed.gpu.global.v4.u32 [%0], {%1,%2,%3,%4};" :: "l"(p), "r"(a), "r"(b), "r"(c), "r"(d) : "memory");
}
__device__ __forceinline__ void st_vol2(uint2* p, uint32_t a, uint32_t b) {
  asm volatile("st.relaxed.gpu.global.v2.u32 [%0], {%1,%2};" :: "l"(p), "r"(a), "r"(b) : "memory");
}
__device__ __forceinline__ void stg128(void* p, uint4 v) {
  asm volatile("st.global.v4.u32 [%0], {%1,%2,%3,%4};" :: "l"(p), "r"(v.x), "r"(v.y), "r"(v.z), "r"(v.w));
}
__device__ __forceinline__ unsigned ld_relaxed(const unsigned* p) {
  unsigned v; asm volatile("ld.relaxed.gpu.global.u32 %0, [%1];" : "=r"(v) : "l"(p) : "memory"); return v;
}
__device__ __forceinline__ uint32_t pack_bf16(float lo, float hi) {
  uint32_t r; asm("cvt.rn.bf16x2.f32 %0, %1, %2;" : "=r"(r) : "f"(hi), "f"(lo)); return r;
}
__device__ __forceinline__ float bf_lo(uint32_t v) { return __uint_as_float(v << 16); }
__device__ __forceinline__ float bf_hi(uint32_t v) { return __uint_as_float(v & 0xFFFF0000u); }
__device__ __forceinline__ void stsm4(uint32_t addr, uint32_t a, uint32_t b, uint32_t c, uint32_t d) {
  asm volatile("stmatrix.sync.aligned.m8n8.x4.shared.b16 [%0], {%1,%2,%3,%4};" :: "r"(addr), "r"(a), "r"(b), "r"(c), "r"(d));
}
__device__ __forceinline__ void stsm4_t(uint32_t addr, uint32_t a, uint32_t b, uint32_t c, uint32_t d) {
  asm volatile("stmatrix.sync.aligned.m8n8.x4.trans.shared.b16 [%0], {%1,%2,%3,%4};" :: "r"(addr), "r"(a), "r"(b), "r"(c), "r"(d));
}
__device__ __forceinline__ void ldsm4(uint32_t addr, uint32_t& a, uint32_t& b, uint32_t& c, uint32_t& d) {
  asm volatile("ldmatrix.sync.aligned.m8n8.x4.shared.b16 {%0,%1,%2,%3}, [%4];" : "=r"(a), "=r"(b), "=r"(c), "=r"(d) : "r"(addr));
}
__device__ __forceinline__ uint4 lds128(uint32_t a) {
  uint4 v; asm volatile("ld.shared.v4.u32 {%0,%1,%2,%3}, [%4];" : "=r"(v.x), "=r"(v.y), "=r"(v.z), "=r"(v.w) : "r"(a)); return v;
}
__device__ __forceinline__ void sts128(uint32_t a, uint32_t x, uint32_t y, uint32_t z, uint32_t w) {
  asm volatile("st.shared.v4.u32 [%0], {%1,%2,%3,%4};" :: "r"(a), "r"(x), "r"(y), "r"(z), "r"(w));
}
__device__ __forceinline__ uint32_t hmul2_bf16(uint32_t a, uint32_t b) {
  uint32_t r; asm("mul.rn.bf16x2 %0, %1, %2;" : "=r"(r) : "r"(a), "r"(b)); return r;
}
__device__ __forceinline__ float gelu_tanh(float v) {
  float u = v * fmaf(0.0356774081f, v * v, 0.7978845608f);
  float t; asm("tanh.approx.f32 %0, %1;" : "=f"(t) : "f"(u));
  float hv = 0.5f * v;
  return fmaf(hv, t, hv);
}

template<int TB>
__device__ __forceinline__ void wgmma_n192(float (&d)[96], uint64_t da, uint64_t db, int scale_d) {
  asm volatile("{\n.reg .pred p;\nsetp.ne.b32 p, %98, 0;\n"
   "wgmma.mma_async.sync.aligned.m64n192k16.f32.bf16.bf16 {%0,%1,%2,%3,%4,%5,%6,%7,%8,%9,%10,%11,%12,%13,%14,%15,%16,%17,%18,%19,%20,%21,%22,%23,%24,%25,%26,%27,%28,%29,%30,%31,%32,%33,%34,%35,%36,%37,%38,%39,%40,%41,%42,%43,%44,%45,%46,%47,%48,%49,%50,%51,%52,%53,%54,%55,%56,%57,%58,%59,%60,%61,%62,%63,%64,%65,%66,%67,%68,%69,%70,%71,%72,%73,%74,%75,%76,%77,%78,%79,%80,%81,%82,%83,%84,%85,%86,%87,%88,%89,%90,%91,%92,%93,%94,%95}, %96, %97, p, 1, 1, 0, %99;\n}"
   : "+f"(d[0]),"+f"(d[1]),"+f"(d[2]),"+f"(d[3]),"+f"(d[4]),"+f"(d[5]),"+f"(d[6]),"+f"(d[7]),"+f"(d[8]),"+f"(d[9]),"+f"(d[10]),"+f"(d[11]),"+f"(d[12]),"+f"(d[13]),"+f"(d[14]),"+f"(d[15]),"+f"(d[16]),"+f"(d[17]),"+f"(d[18]),"+f"(d[19]),"+f"(d[20]),"+f"(d[21]),"+f"(d[22]),"+f"(d[23]),"+f"(d[24]),"+f"(d[25]),"+f"(d[26]),"+f"(d[27]),"+f"(d[28]),"+f"(d[29]),"+f"(d[30]),"+f"(d[31]),"+f"(d[32]),"+f"(d[33]),"+f"(d[34]),"+f"(d[35]),"+f"(d[36]),"+f"(d[37]),"+f"(d[38]),"+f"(d[39]),"+f"(d[40]),"+f"(d[41]),"+f"(d[42]),"+f"(d[43]),"+f"(d[44]),"+f"(d[45]),"+f"(d[46]),"+f"(d[47]),"+f"(d[48]),"+f"(d[49]),"+f"(d[50]),"+f"(d[51]),"+f"(d[52]),"+f"(d[53]),"+f"(d[54]),"+f"(d[55]),"+f"(d[56]),"+f"(d[57]),"+f"(d[58]),"+f"(d[59]),"+f"(d[60]),"+f"(d[61]),"+f"(d[62]),"+f"(d[63]),"+f"(d[64]),"+f"(d[65]),"+f"(d[66]),"+f"(d[67]),"+f"(d[68]),"+f"(d[69]),"+f"(d[70]),"+f"(d[71]),"+f"(d[72]),"+f"(d[73]),"+f"(d[74]),"+f"(d[75]),"+f"(d[76]),"+f"(d[77]),"+f"(d[78]),"+f"(d[79]),"+f"(d[80]),"+f"(d[81]),"+f"(d[82]),"+f"(d[83]),"+f"(d[84]),"+f"(d[85]),"+f"(d[86]),"+f"(d[87]),"+f"(d[88]),"+f"(d[89]),"+f"(d[90]),"+f"(d[91]),"+f"(d[92]),"+f"(d[93]),"+f"(d[94]),"+f"(d[95])
   : "l"(da), "l"(db), "r"(scale_d), "n"(TB));
}
template<int TB>
__device__ __forceinline__ void wgmma_n160(float (&d)[80], uint64_t da, uint64_t db, int scale_d) {
  asm volatile("{\n.reg .pred p;\nsetp.ne.b32 p, %82, 0;\n"
   "wgmma.mma_async.sync.aligned.m64n160k16.f32.bf16.bf16 {%0,%1,%2,%3,%4,%5,%6,%7,%8,%9,%10,%11,%12,%13,%14,%15,%16,%17,%18,%19,%20,%21,%22,%23,%24,%25,%26,%27,%28,%29,%30,%31,%32,%33,%34,%35,%36,%37,%38,%39,%40,%41,%42,%43,%44,%45,%46,%47,%48,%49,%50,%51,%52,%53,%54,%55,%56,%57,%58,%59,%60,%61,%62,%63,%64,%65,%66,%67,%68,%69,%70,%71,%72,%73,%74,%75,%76,%77,%78,%79}, %80, %81, p, 1, 1, 0, %83;\n}"
   : "+f"(d[0]),"+f"(d[1]),"+f"(d[2]),"+f"(d[3]),"+f"(d[4]),"+f"(d[5]),"+f"(d[6]),"+f"(d[7]),"+f"(d[8]),"+f"(d[9]),"+f"(d[10]),"+f"(d[11]),"+f"(d[12]),"+f"(d[13]),"+f"(d[14]),"+f"(d[15]),"+f"(d[16]),"+f"(d[17]),"+f"(d[18]),"+f"(d[19]),"+f"(d[20]),"+f"(d[21]),"+f"(d[22]),"+f"(d[23]),"+f"(d[24]),"+f"(d[25]),"+f"(d[26]),"+f"(d[27]),"+f"(d[28]),"+f"(d[29]),"+f"(d[30]),"+f"(d[31]),"+f"(d[32]),"+f"(d[33]),"+f"(d[34]),"+f"(d[35]),"+f"(d[36]),"+f"(d[37]),"+f"(d[38]),"+f"(d[39]),"+f"(d[40]),"+f"(d[41]),"+f"(d[42]),"+f"(d[43]),"+f"(d[44]),"+f"(d[45]),"+f"(d[46]),"+f"(d[47]),"+f"(d[48]),"+f"(d[49]),"+f"(d[50]),"+f"(d[51]),"+f"(d[52]),"+f"(d[53]),"+f"(d[54]),"+f"(d[55]),"+f"(d[56]),"+f"(d[57]),"+f"(d[58]),"+f"(d[59]),"+f"(d[60]),"+f"(d[61]),"+f"(d[62]),"+f"(d[63]),"+f"(d[64]),"+f"(d[65]),"+f"(d[66]),"+f"(d[67]),"+f"(d[68]),"+f"(d[69]),"+f"(d[70]),"+f"(d[71]),"+f"(d[72]),"+f"(d[73]),"+f"(d[74]),"+f"(d[75]),"+f"(d[76]),"+f"(d[77]),"+f"(d[78]),"+f"(d[79])
   : "l"(da), "l"(db), "r"(scale_d), "n"(TB));
}
template<int TB>
__device__ __forceinline__ void wgmma_n96(float (&d)[48], uint64_t da, uint64_t db, int scale_d) {
  asm volatile("{\n.reg .pred p;\nsetp.ne.b32 p, %50, 0;\n"
   "wgmma.mma_async.sync.aligned.m64n96k16.f32.bf16.bf16 {%0,%1,%2,%3,%4,%5,%6,%7,%8,%9,%10,%11,%12,%13,%14,%15,%16,%17,%18,%19,%20,%21,%22,%23,%24,%25,%26,%27,%28,%29,%30,%31,%32,%33,%34,%35,%36,%37,%38,%39,%40,%41,%42,%43,%44,%45,%46,%47}, %48, %49, p, 1, 1, 0, %51;\n}"
   : "+f"(d[0]),"+f"(d[1]),"+f"(d[2]),"+f"(d[3]),"+f"(d[4]),"+f"(d[5]),"+f"(d[6]),"+f"(d[7]),"+f"(d[8]),"+f"(d[9]),"+f"(d[10]),"+f"(d[11]),"+f"(d[12]),"+f"(d[13]),"+f"(d[14]),"+f"(d[15]),"+f"(d[16]),"+f"(d[17]),"+f"(d[18]),"+f"(d[19]),"+f"(d[20]),"+f"(d[21]),"+f"(d[22]),"+f"(d[23]),"+f"(d[24]),"+f"(d[25]),"+f"(d[26]),"+f"(d[27]),"+f"(d[28]),"+f"(d[29]),"+f"(d[30]),"+f"(d[31]),"+f"(d[32]),"+f"(d[33]),"+f"(d[34]),"+f"(d[35]),"+f"(d[36]),"+f"(d[37]),"+f"(d[38]),"+f"(d[39]),"+f"(d[40]),"+f"(d[41]),"+f"(d[42]),"+f"(d[43]),"+f"(d[44]),"+f"(d[45]),"+f"(d[46]),"+f"(d[47])
   : "l"(da), "l"(db), "r"(scale_d), "n"(TB));
}

template<int N, int TB>
__device__ __forceinline__ void wgmma_n(float (&d)[N / 2], uint64_t da, uint64_t db) {
  if constexpr (N == 192) wgmma_n192<TB>(d, da, db, 1);
  else if constexpr (N == 160) wgmma_n160<TB>(d, da, db, 1);
  else wgmma_n96<TB>(d, da, db, 1);
}

template<int R>
__device__ __forceinline__ void pin(float (&acc)[2][R]) {
  #pragma unroll
  for (int mi = 0; mi < 2; mi++)
    #pragma unroll
    for (int i = 0; i < R; i++) asm volatile("" : "+f"(acc[mi][i]) :: "memory");
}
template<int R>
__device__ __forceinline__ void zero(float (&acc)[2][R]) {
  #pragma unroll
  for (int i = 0; i < R; i++) { acc[0][i] = 0.f; acc[1][i] = 0.f; }
  pin(acc);
}

template<int N, int TB, bool CONT, int ORD_BAR>
__device__ __forceinline__ void mainloop(float (&acc)[2][N / 2], uint32_t sbase, uint32_t stage_bytes, int g0, int nk, int total, int mswap) {
  const uint32_t full0 = sbase + BAR_OFF, empty0 = full0 + 8 * STAGES, ring = sbase + RING_OFF;
  const int t = threadIdx.x & 127;
  const uint32_t da0 = (((ring + mswap * 8192) & 0x3FFFF) >> 4) | 0x10000u, da1 = (((ring + (mswap ^ 1) * 8192) & 0x3FFFF) >> 4) | 0x10000u;
  const uint32_t db0 = (((ring + A_BYTES) & 0x3FFFF) >> 4) | ((TB == 2 ? 256u : TB ? 512u : 1u) << 16);
  constexpr uint32_t HI_A = 0x40000040u, HI_B = TB == 2 ? 0x80000020u : 0x40000040u;
  #pragma unroll 1
  for (int g = g0; g < g0 + nk; g++) {
    const int s = g & (STAGES - 1);
    const uint32_t so = s * (stage_bytes >> 4);
    mbar_wait(full0 + 8 * s, (g / STAGES) & 1);
    wgmma_fence();
    #pragma unroll
    for (int k = 0; k < 4; k++) {
      const uint64_t db = desc64(db0 + so + (TB == 2 ? k * 64 : TB ? k * 128 : k * 2), HI_B);
      wgmma_n<N, TB != 0>(acc[0], desc64(da0 + so + k * 2, HI_A), db);
      wgmma_n<N, TB != 0>(acc[1], desc64(da1 + so + k * 2, HI_A), db);
    }
    wgmma_commit();
    if (ORD_BAR != 0 && g == g0 + nk - 1) bar_arrive<ORD_BAR>(256);
    wgmma_wait<1>();
    if (t < 2 && (CONT || g > g0) && g - 1 + STAGES <= total) mbar_arrive_cluster(empty0 + 8 * ((g - 1) & (STAGES - 1)), t);
  }
}
template<int R>
__device__ __forceinline__ void drain(float (&acc)[2][R], uint32_t sbase, int glast, int total) {
  wgmma_wait<0>();
  pin(acc);
  const int t = threadIdx.x & 127;
  if (t < 2 && glast + STAGES <= total) mbar_arrive_cluster(sbase + BAR_OFF + 8 * STAGES + 8 * (glast & (STAGES - 1)), t);
}

__device__ __forceinline__ void set_flag(unsigned* flag, unsigned epoch) {
  asm volatile("st.relaxed.gpu.global.u32 [%0], %1;" :: "l"(flag), "r"(epoch) : "memory");
}
__device__ __forceinline__ void publish(unsigned* flag, unsigned epoch) {
  asm volatile("fence.acq_rel.gpu;" ::: "memory");
  asm volatile("st.relaxed.gpu.global.u32 [%0], %1;" :: "l"(flag), "r"(epoch) : "memory");
}

__device__ __forceinline__ float sum8(uint4 v) {
  return ((bf_lo(v.x) + bf_hi(v.x)) + (bf_lo(v.y) + bf_hi(v.y))) + ((bf_lo(v.z) + bf_hi(v.z)) + (bf_lo(v.w) + bf_hi(v.w)));
}
__device__ __forceinline__ void ln_rows(const bf16* __restrict__ x) {
  const int t = threadIdx.x - 128, row = blockIdx.x * 16 + (t >> 4), c = t & 15;
  uint4 rv[5];
  #pragma unroll
  for (int j = 0; j < 5; j++) rv[j] = __ldg(reinterpret_cast<const uint4*>(x + (size_t)row * DM) + c + 16 * j);
  float s = 0.f;
  #pragma unroll
  for (int j = 0; j < 5; j++) s += sum8(rv[j]);
  #pragma unroll
  for (int o = 1; o < 16; o <<= 1) s += __shfl_xor_sync(0xffffffffu, s, o);
  const float mean = s * (1.f / DM);
  float q = 0.f;
  #pragma unroll
  for (int j = 0; j < 5; j++) {
    const uint32_t u[4] = {rv[j].x, rv[j].y, rv[j].z, rv[j].w};
    #pragma unroll
    for (int e = 0; e < 4; e++) { const float d0 = bf_lo(u[e]) - mean, d1 = bf_hi(u[e]) - mean; q = fmaf(d0, d0, q); q = fmaf(d1, d1, q); }
  }
  #pragma unroll
  for (int o = 1; o < 16; o <<= 1) q += __shfl_xor_sync(0xffffffffu, q, o);
  const float r = rsqrtf(fmaf(q, 1.f / DM, LN_EPS)), o = -mean * r;
  #pragma unroll
  for (int j = 0; j < 5; j++)
    stg128(reinterpret_cast<uint4*>(g_xn + (size_t)row * DM) + c + 16 * j, make_uint4(
           pack_bf16(fmaf(bf_lo(rv[j].x), r, o), fmaf(bf_hi(rv[j].x), r, o)), pack_bf16(fmaf(bf_lo(rv[j].y), r, o), fmaf(bf_hi(rv[j].y), r, o)),
           pack_bf16(fmaf(bf_lo(rv[j].z), r, o), fmaf(bf_hi(rv[j].z), r, o)), pack_bf16(fmaf(bf_lo(rv[j].w), r, o), fmaf(bf_hi(rv[j].w), r, o))));
}

__global__ void __cluster_dims__(2, 1, 1) __launch_bounds__(384, 1)
fused_kernel(const __grid_constant__ Maps maps, const bf16* __restrict__ x, const bf16* __restrict__ bsp) {
  const uint32_t sbase = smem_u32(smem);
  const uint32_t full0 = sbase + BAR_OFF, empty0 = full0 + 8 * STAGES, dep0 = empty0 + 8 * STAGES, ring = sbase + RING_OFF;
  const int tid = threadIdx.x, wg = __shfl_sync(0xffffffffu, tid >> 7, 0);
  const int rank = blockIdx.x & 1, grp = (blockIdx.x >> 1) & 1, q = blockIdx.x >> 2;
  const int rb = q >> 1, ct = (q & 1) * 2 + rank, c8 = grp * 4 + ct;
  const int total = grp == 0 ? KB_A : KB_B;
  const uint32_t stage_bytes = grp == 0 ? STAGE_A : STAGE_B;

  if (tid == 0) {
    TS(0, 0);
    for (int s = 0; s < STAGES; s++) { mbar_init(full0 + 8 * s, 2); mbar_init(empty0 + 8 * s, 2); mbar_init(dep0 + 8 * s, 1); }
    asm volatile("fence.mbarrier_init.release.cluster;" ::: "memory");
  }
  __syncthreads();
  asm volatile("barrier.cluster.arrive.relaxed.aligned;" ::: "memory");

  if (wg == 0) {
    asm volatile("setmaxnreg.dec.sync.aligned.u32 40;");
    const int warp = tid >> 5, lane = tid & 31;
    if (warp == 0) {
      const int row = rb * 128;
      cluster_wait();
      if (lane == 0) {
        #pragma unroll 1
        for (int g = 0; g < total; g++) {
          int mi, kb;
          if (g < 20) { mi = M_XN; kb = g < 10 ? g : g - 10; }
          else if (grp == 0) {
            if (g < 52) { mi = M_WSP; kb = g - 20; }
            else if (g < 52 + NX) { mi = M_WSIM; kb = g - 52 + 32 - NX; }
            else { mi = M_H; kb = g - 52 - NX; }
          } else {
            if (g < 30) { mi = M_XN; kb = g - 20; }
            else if (g < 62) { mi = M_WSRE; kb = g - 30; }
            else { mi = M_WSIM; kb = g - 62; }
          }
          if (g == 0 || (mi == M_H && kb == 0)) { TS(0, g ? 3 : 1); mbar_wait(dep0 + (g ? 24 : 0), 0); fence_async_global(); TS(0, g ? 4 : 2); }
          const int s = g & (STAGES - 1);
          mbar_wait(empty0 + 8 * s, ((g / STAGES) & 1) ^ 1);
          mbar_expect_tx(full0 + 8 * s, A_BYTES);
          tma_load_2d_mc(ring + s * stage_bytes + rank * 8192, &maps.m[mi], full0 + 8 * s, kb * 64, row + rank * 64, 3);
        }
        const int s = total & (STAGES - 1);
        mbar_wait(empty0 + 8 * s, ((total / STAGES) & 1) ^ 1);
        mbar_expect_tx(full0 + 8 * s, 20480);
        mbar_arrive(full0 + 8 * s);
        tma_load_2d(ring + s * stage_bytes, &maps.m[M_XR], full0 + 8 * s, ct * 160, row + grp * 64);
        TS(0, 5);
      }
    } else if (warp == 1) {
      if (lane == 0) {
        #pragma unroll 1
        for (int g = 0; g < total; g++) {
          int kind = 1, mi, kb, c, dep = 0;
          uint32_t bytes = 20480;
          if (g < 10) { kind = 0; mi = M_WIN32; kb = g; c = 24 + 3 * c8; bytes = 12288; }
          else if (grp == 0) {
            if (g < 20) { kind = 0; mi = M_WIN3; kb = g - 10; c = 3 * ct; bytes = 24576; }
            else if (g < 52) { kind = 0; mi = M_Z23; kb = g - 20; c = 3 * ct; bytes = 24576; dep = g == 20 ? 1 : 0; }
            else if (g < 52 + NX) { mi = M_AB; kb = g - 52 + 32 - NX; c = DM + ct * 160; dep = g == 52 ? 2 : 0; }
            else { kind = 0; mi = M_WOUT; kb = g - 52 - NX; c = ct * 5; }
          } else {
            if (g < 30) { mi = g < 20 ? M_WDRE : M_WDIM; kb = g < 20 ? g - 10 : g - 20; c = ct * 160; }
            else { mi = M_AB; kb = g < 62 ? g - 30 : g - 62; c = ct * 160 + (g < 62 ? 0 : DM); dep = g == 30 ? 1 : g == 62 ? 2 : 0; }
          }
          if (dep) { TS(1, dep * 2 - 2); mbar_wait(dep0 + 8 * dep, 0); fence_async_global(); TS(1, dep * 2 - 1); TC(dep); }
          const int s = g & (STAGES - 1);
          const uint32_t dst = ring + s * stage_bytes + A_BYTES, fb = full0 + 8 * s;
          mbar_wait(empty0 + 8 * s, ((g / STAGES) & 1) ^ 1);
          mbar_expect_tx(fb, bytes);
          if (kind == 0) tma_load_3d(dst, &maps.m[mi], fb, 0, kb * 64, c);
          else tma_load_2d(dst, &maps.m[mi], fb, kb * 64, c);
        }
      }
      __syncwarp();
      cluster_wait();
    } else if (warp == 2) {
      cluster_wait();
      const unsigned epoch = (*reinterpret_cast<volatile unsigned*>(&g_done) >> 7) + 1u;
      #pragma unroll 1
      for (int d = 0; d < 4 - grp; d++) {
        const int fi = d == 0 ? F_XN + rb * 8 + (lane & 7)
                     : d == 3 ? F_H + rb * 4 + (lane & 3)
                     : (d == 1 && grp == 0) ? F_Z + (lane >> 1) * 8 + ct * 2 + (lane & 1)
                     : (d == 1 ? F_A : F_B) + (lane & 15) * 4 + ct;
        unsigned it = 0;
        while (!__all_sync(0xffffffffu, ld_relaxed(g_flags + fi) == epoch) && ++it < POLL_LIMIT) __nanosleep(20);
        TS(0, 8 + d * 2);
        fence_async_global();
        __syncwarp();
        TS(0, 9 + d * 2);
        if (lane == 0) mbar_arrive(dep0 + 8 * d);
      }
    } else {
      const unsigned epoch = (*reinterpret_cast<volatile unsigned*>(&g_done) >> 7) + 1u;
      cluster_wait();
      bar_sync<BAR_LN>(288);
      if (lane == 0) { TS(1, 5); publish(g_flags + F_XN + blockIdx.x, epoch); TS(1, 6); }
      __syncwarp();
      bar_sync<BAR_PUB1>(160);
      if (lane == 0) {
        TS(1, 7);
        tma_store_3d(&maps.m[M_Z232], ring + 4 * stage_bytes, 0, rb * 128, 3 * c8);
        bulk_commit();
        bulk_wait_all();
        set_flag(g_flags + F_Z + rb * 8 + c8, epoch);
        TS(1, 8);
      }
      __syncwarp();
      if (grp == 0) {
        bar_arrive<BAR_BUF>(160);
      } else {
        bar_sync<BAR_PUB2>(160);
        if (lane == 0) set_flag(g_flags + F_A + rb * 4 + ct, epoch);
        TS(1, 9);
        __syncwarp();
      }
      bar_sync<BAR_PUB1>(160);
      if (lane == 0) set_flag(g_flags + (grp == 0 ? F_H : F_B) + rb * 4 + ct, epoch);
      TS(1, 10);
    }
  } else {
    asm volatile("setmaxnreg.inc.sync.aligned.u32 232;");
    const int t = tid & 127, w = t >> 5, l = t & 31;
    const uint32_t buf = ring + 4 * stage_bytes;
    const unsigned epoch = (*reinterpret_cast<volatile unsigned*>(&g_done) >> 7) + 1u;
    ln_rows(x);
    bar_arrive<BAR_LN>(288);
    TS(wg + 1, 0);
    cluster_wait();
    const int rl = w * 16 + ((l >> 3) & 1) * 8 + (l & 7);
    const int gr = w * 16 + (l & 15);
    const uint32_t st_base = buf + rl * 128;
    const uint32_t st_x = ((l >> 4) ^ (l & 7)) << 4;
    if (wg == 1) {
      float acc[2][48];
      zero(acc);
      mainloop<96, 2, false, BAR_ORD1>(acc, sbase, stage_bytes, 0, 10, total, 0);
      drain(acc, sbase, 9, total);
      TS(2, 2);
      float sum[4], sq[4];
      #pragma unroll
      for (int r = 0; r < 4; r++) {
        float s0 = 0.f, q0 = 0.f;
        #pragma unroll
        for (int j = 0; j < 12; j++) {
          float* a = &acc[r >> 1][4 * j + (r & 1) * 2];
          a[0] = gelu_tanh(a[0]);
          a[1] = gelu_tanh(a[1]);
          s0 += a[0] + a[1]; q0 = fmaf(a[0], a[0], q0); q0 = fmaf(a[1], a[1], q0);
        }
        s0 += __shfl_xor_sync(0xffffffffu, s0, 1); q0 += __shfl_xor_sync(0xffffffffu, q0, 1);
        s0 += __shfl_xor_sync(0xffffffffu, s0, 2); q0 += __shfl_xor_sync(0xffffffffu, q0, 2);
        sum[r] = s0; sq[r] = q0;
      }
      TS(2, 4);
      float rstd, off;
      {
        const int qd = l & 3;
        const float sm = qd == 0 ? sum[0] : qd == 1 ? sum[1] : qd == 2 ? sum[2] : sum[3];
        const float sv = qd == 0 ? sq[0] : qd == 1 ? sq[1] : qd == 2 ? sq[2] : sq[3];
        const int row = (qd >> 1) * 64 + w * 16 + (qd & 1) * 8 + (l >> 2);
        const float mu = sm * (1.f / 96), m2 = fmaxf(sv - sm * mu, 0.f);
        st_vol2(&g_zstat[(rb * 8 + c8) * 128 + row], __float_as_uint(mu), (__float_as_uint(m2) & ~255u) | (epoch & 255u));
        uint2 v[7];
        unsigned n = 0;
        while (true) {
          bool ok = true;
          #pragma unroll
          for (int j = 0; j < 7; j++) v[j] = ld_vol2(&g_zstat[(rb * 8 + ((c8 + 1 + j) & 7)) * 128 + row]);
          #pragma unroll
          for (int j = 0; j < 7; j++) ok = ok && ((v[j].y ^ epoch) & 255u) == 0;
          if (ok || ++n > POLL_LIMIT) break;
          __nanosleep(POLL_NS);
        }
        float mean = mu, var = m2;
        #pragma unroll
        for (int j = 0; j < 7; j++) { mean += __uint_as_float(v[j].x); var += __uint_as_float(v[j].y & ~255u); }
        mean *= 0.125f;
        float d = (mu - mean) * (mu - mean);
        #pragma unroll
        for (int j = 0; j < 7; j++) d = fmaf(__uint_as_float(v[j].x) - mean, __uint_as_float(v[j].x) - mean, d);
        rstd = rsqrtf(fmaf(96.f, d, var) * (1.f / FH) + LN_EPS); off = -mean * rstd;
        __syncwarp();
      }
      TS(2, 5);
      #pragma unroll
      for (int mi = 0; mi < 2; mi++) {
        const float r0 = __shfl_sync(0xffffffffu, rstd, (l & 28) + mi * 2), o0 = __shfl_sync(0xffffffffu, off, (l & 28) + mi * 2);
        const float r1 = __shfl_sync(0xffffffffu, rstd, (l & 28) + mi * 2 + 1), o1 = __shfl_sync(0xffffffffu, off, (l & 28) + mi * 2 + 1);
        #pragma unroll
        for (int jj = 0; jj < 6; jj++) {
          const float* a = &acc[mi][8 * jj];
          stsm4(buf + (jj >> 1) * 8192 + mi * 4096 + rl * 64 + ((((jj & 1) * 2 + (l >> 4)) ^ ((l >> 1) & 3)) << 4),
                pack_bf16(fmaf(a[0], r0, o0), fmaf(a[1], r0, o0)), pack_bf16(fmaf(a[2], r1, o1), fmaf(a[3], r1, o1)),
                pack_bf16(fmaf(a[4], r0, o0), fmaf(a[5], r0, o0)), pack_bf16(fmaf(a[6], r1, o1), fmaf(a[7], r1, o1)));
        }
      }
      fence_async_smem();
      bar_arrive<BAR_PUB1>(160);
      TS(2, 6);
      if (grp == 0) {
        float acc[2][96];
        zero(acc);
        bar_sync<BAR_ORD2>(256);
        mainloop<192, 1, false, BAR_ORD1>(acc, sbase, STAGE_A, 20, 32, KB_A, 0);
        const float* bias = reinterpret_cast<const float*>(smem + BIAS_OFF) + w * 16 + (l >> 2);
        bar_sync<BAR_Z1>(256);
        drain(acc, sbase, 51, KB_A);
        TS(2, 7);
        {
          const float bb[4] = {bias[0], bias[8], bias[64], bias[72]};
          uint32_t z[2][4][4];
          #pragma unroll
          for (int i = 0; i < 4; i++) ldsm4(st_base + (st_x ^ (i << 5)), z[0][i][0], z[0][i][1], z[0][i][2], z[0][i][3]);
          #pragma unroll
          for (int bx = 0; bx < 6; bx++) {
            if (bx < 5) {
              #pragma unroll
              for (int i = 0; i < 4; i++)
                ldsm4(st_base + (bx + 1) * 8192 + (st_x ^ (i << 5)), z[(bx + 1) & 1][i][0], z[(bx + 1) & 1][i][1], z[(bx + 1) & 1][i][2], z[(bx + 1) & 1][i][3]);
            }
            const float b0 = bb[(bx / 3) * 2], b1 = bb[(bx / 3) * 2 + 1];
            #pragma unroll
            for (int i = 0; i < 4; i++) {
              const float* a = &acc[bx / 3][8 * ((bx % 3) * 4 + i)];
              const uint32_t* zz = z[bx & 1][i];
              stsm4(st_base + bx * 8192 + (st_x ^ (i << 5)),
                    hmul2_bf16(zz[0], pack_bf16(a[0] + b0, a[1] + b0)), hmul2_bf16(zz[1], pack_bf16(a[2] + b1, a[3] + b1)),
                    hmul2_bf16(zz[2], pack_bf16(a[4] + b0, a[5] + b0)), hmul2_bf16(zz[3], pack_bf16(a[6] + b1, a[7] + b1)));
            }
            fence_async_smem();
            __syncwarp();
            if (l == 0) {
              tma_store_2d(&maps.m[M_HS], buf + bx * 8192 + w * 2048, ct * 192 + (bx % 3) * 64, rb * 128 + (bx / 3) * 64 + w * 16);
              bulk_commit();
            }
          }
        }
        TS(2, 8);
        if (l == 0) bulk_wait_all();
        __syncwarp();
        bar_arrive<BAR_PUB1>(160);
        TS(2, 9);
        return;
      }
    } else {
      if (grp == 0) {
        reinterpret_cast<float*>(smem + BIAS_OFF)[t] = __bfloat162float(bsp[rb * 128 + t]);
        float acc[2][96];
        zero(acc);
        bar_sync<BAR_ORD1>(256);
        mainloop<192, 1, false, BAR_ORD2>(acc, sbase, STAGE_A, 10, 10, KB_A, 0);
        drain(acc, sbase, 19, KB_A);
        TS(3, 2);
        bar_sync<BAR_BUF>(160);
        #pragma unroll
        for (int mi = 0; mi < 2; mi++)
          #pragma unroll
          for (int jj = 0; jj < 12; jj++) {
            const float* a = &acc[mi][8 * jj];
            stsm4(st_base + mi * 24576 + (jj >> 2) * 8192 + (st_x ^ ((jj & 3) << 5)),
                  pack_bf16(a[0], a[1]), pack_bf16(a[2], a[3]), pack_bf16(a[4], a[5]), pack_bf16(a[6], a[7]));
          }
        __syncwarp();
        TS(3, 3);
        const uint32_t rbase = buf + (l >> 4) * 24576 + gr * 128;
        #pragma unroll 1
        for (int c2 = 0; c2 < 12; c2++) {
          const uint32_t ab = rbase + (c2 >> 2) * 8192;
          uint4 v[2];
          #pragma unroll
          for (int i = 0; i < 2; i++) v[i] = lds128(ab + (((((c2 & 3) * 2 + i) ^ l) & 7) << 4));
          #pragma unroll
          for (int i = 0; i < 2; i++)
            sts128(ab + (((((c2 & 3) * 2 + i) ^ l) & 7) << 4),
                   pack_bf16(gelu_tanh(bf_lo(v[i].x)), gelu_tanh(bf_hi(v[i].x))), pack_bf16(gelu_tanh(bf_lo(v[i].y)), gelu_tanh(bf_hi(v[i].y))),
                   pack_bf16(gelu_tanh(bf_lo(v[i].z)), gelu_tanh(bf_hi(v[i].z))), pack_bf16(gelu_tanh(bf_lo(v[i].w)), gelu_tanh(bf_hi(v[i].w))));
        }
        TS(3, 4);
        bar_arrive<BAR_Z1>(256);
      }
    }
    float acc[2][80];
    if (grp == 1) {
      zero(acc);
      if (wg == 2) {
        bar_sync<BAR_ORD1>(256);
        mainloop<160, 0, false, BAR_ORD2>(acc, sbase, STAGE_B, 10, 10, KB_B, 0);
      } else {
        bar_sync<BAR_ORD2>(256);
        mainloop<160, 0, false, BAR_ORD1>(acc, sbase, STAGE_B, 20, 10, KB_B, 0);
      }
      drain(acc, sbase, wg == 2 ? 19 : 29, KB_B);
      TS(wg + 1, wg == 1 ? 7 : 2);
      if (wg == 1) bar_sync<BAR_BUF>(256);
      const uint32_t sg = wg == 1 ? 0x80008000u : 0u;
      const uint32_t tb = buf + 24576 + ((l >> 4) * 8 + (l & 7)) * 128 + (((w * 2 + ((l >> 3) & 1)) ^ (l & 7)) << 4);
      #pragma unroll
      for (int mi = 0; mi < 2; mi++)
        #pragma unroll
        for (int jj = 0; jj < 10; jj++) {
          const float* a = &acc[mi][8 * jj];
          stsm4_t(tb + mi * 20480 + jj * 2048, pack_bf16(a[0], a[1]) ^ sg, pack_bf16(a[2], a[3]) ^ sg, pack_bf16(a[4], a[5]) ^ sg, pack_bf16(a[6], a[7]) ^ sg);
        }
      fence_async_smem();
      if (wg == 1) bar_sync<BAR_WG1>(128); else bar_sync<BAR_WG2>(128);
      TS(wg + 1, wg == 1 ? 8 : 6);
      if (l == 0) {
        #pragma unroll 1
        for (int i = 0; i < 2; i++) {
          tma_store_2d(&maps.m[M_ABS], buf + 24576 + i * 20480 + w * 5120, rb * 128 + i * 64, (2 - wg) * DM + ct * 160 + w * 40);
          bulk_commit();
        }
        bulk_wait_all();
      }
      __syncwarp();
      TS(wg + 1, wg == 1 ? 9 : 10);
      if (wg == 1) { bar_arrive<BAR_PUB1>(160); return; }
      bar_arrive<BAR_PUB2>(160);
      bar_arrive<BAR_BUF>(256);
    }
    zero(acc);
    bar_sync<BAR_ORD1>(256);
    mainloop<160, 0, false, 0>(acc, sbase, stage_bytes, grp == 0 ? 52 : 30, grp == 0 ? NX : 64 - NX, total, grp);
    if (grp == 0) mainloop<160, 2, true, 0>(acc, sbase, STAGE_A, 52 + NX, 12, KB_A, 0);
    drain(acc, sbase, total - 1, total);
    TS(3, 12);
    uint4* dst = g_part + (size_t)blockIdx.x * 27 * 128 + t;
    const uint4* src = g_part + (size_t)(blockIdx.x ^ 2) * 27 * 128 + t;
    #pragma unroll
    for (int i = 0; i < 27; i++)
      st_vol4(dst + i * 128, __float_as_uint(acc[1][3 * i]), __float_as_uint(acc[1][3 * i + 1]),
              __float_as_uint(i < 26 ? acc[1][3 * i + 2] : 0.f), epoch);
    TS(3, 13);
    const uint32_t slab = ring + (total & (STAGES - 1)) * stage_bytes + w * (16 * 320);
    const uint32_t addr = slab + (((l >> 3) & 1) * 8 + (l & 7)) * 320 + (l >> 4) * 16;
    mbar_wait(full0 + 8 * (total & (STAGES - 1)), (total / STAGES) & 1);
    #pragma unroll
    for (int jj = 0; jj < 10; jj++) {
      uint32_t z0, z1, z2, z3;
      ldsm4(addr + jj * 32, z0, z1, z2, z3);
      float* a = &acc[0][8 * jj];
      a[0] += bf_lo(z0); a[1] += bf_hi(z0); a[2] += bf_lo(z1); a[3] += bf_hi(z1);
      a[4] += bf_lo(z2); a[5] += bf_hi(z2); a[6] += bf_lo(z3); a[7] += bf_hi(z3);
    }
    {
      unsigned n = 0;
      while (ld_vol4(src + 26 * 128).w != epoch && ++n < POLL_LIMIT) __nanosleep(POLL_NS);
      uint4 v[27];
      while (true) {
        bool ok = true;
        #pragma unroll
        for (int i = 0; i < 27; i++) v[i] = ld_vol4(src + i * 128);
        #pragma unroll
        for (int i = 0; i < 27; i++) ok = ok && (v[i].w == epoch);
        if (ok || ++n > POLL_LIMIT) break;
      }
      #pragma unroll
      for (int i = 0; i < 27; i++) {
        acc[0][3 * i] += __uint_as_float(v[i].x);
        acc[0][3 * i + 1] += __uint_as_float(v[i].y);
        if (i < 26) acc[0][3 * i + 2] += __uint_as_float(v[i].z);
      }
    }
    TS(3, 14);
    #pragma unroll
    for (int jj = 0; jj < 10; jj++) {
      const float* a = &acc[0][8 * jj];
      stsm4(addr + jj * 32, pack_bf16(a[0], a[1]), pack_bf16(a[2], a[3]), pack_bf16(a[4], a[5]), pack_bf16(a[6], a[7]));
    }
    fence_async_smem();
    __syncwarp();
    if (l == 0) {
      tma_store_2d(&maps.m[M_OUT], slab, ct * 160, rb * 128 + grp * 64 + w * 16);
      bulk_commit();
      bulk_wait_read();
      if (w == 0) atomicAdd(&g_done, 1u);
    }
    TS(3, 15);
  }
}

typedef CUresult (*EncodeFn)(CUtensorMap*, CUtensorMapDataType, cuuint32_t, void*, const cuuint64_t*, const cuuint64_t*,
                             const cuuint32_t*, const cuuint32_t*, CUtensorMapInterleave, CUtensorMapSwizzle,
                             CUtensorMapL2promotion, CUtensorMapFloatOOBfill);

void make2d(EncodeFn enc, CUtensorMap* m, const void* p, uint64_t cols, uint64_t rows, uint32_t bc, uint32_t br, bool swz = true) {
  cuuint64_t gd[2] = {cols, rows}, gs[1] = {cols * 2};
  cuuint32_t bd[2] = {bc, br}, es[2] = {1, 1};
  enc(m, CU_TENSOR_MAP_DATA_TYPE_BFLOAT16, 2, const_cast<void*>(p), gd, gs, bd, es, CU_TENSOR_MAP_INTERLEAVE_NONE,
      swz ? CU_TENSOR_MAP_SWIZZLE_128B : CU_TENSOR_MAP_SWIZZLE_NONE, CU_TENSOR_MAP_L2_PROMOTION_L2_256B, CU_TENSOR_MAP_FLOAT_OOB_FILL_NONE);
}
void make3d(EncodeFn enc, CUtensorMap* m, const void* p, uint64_t cols, uint64_t rows, uint32_t cw, uint32_t nc, uint32_t br = 64) {
  cuuint64_t gd[3] = {cw, rows, cols / cw}, gs[2] = {cols * 2, cw * 2};
  cuuint32_t bd[3] = {cw, br, nc}, es[3] = {1, 1, 1};
  enc(m, CU_TENSOR_MAP_DATA_TYPE_BFLOAT16, 3, const_cast<void*>(p), gd, gs, bd, es, CU_TENSOR_MAP_INTERLEAVE_NONE,
      cw == 64 ? CU_TENSOR_MAP_SWIZZLE_128B : CU_TENSOR_MAP_SWIZZLE_64B, CU_TENSOR_MAP_L2_PROMOTION_L2_256B, CU_TENSOR_MAP_FLOAT_OOB_FILL_NONE);
}

}

extern "C" void kernel_launch(void* const* d_in, const int* in_sizes, int n_in, void* d_out, int out_size) {
  const bf16* x = (const bf16*)d_in[0];
  const bf16* wsre = (const bf16*)d_in[1];
  const bf16* wsim = (const bf16*)d_in[2];
  const bf16* wdre = (const bf16*)d_in[3];
  const bf16* wdim = (const bf16*)d_in[4];
  const bf16* win = (const bf16*)d_in[6];
  const bf16* wsp = (const bf16*)d_in[7];
  const bf16* bsp = (const bf16*)d_in[8];
  const bf16* wout = (const bf16*)d_in[9];

  void* fn = nullptr;
  cudaDriverEntryPointQueryResult qr;
  cudaGetDriverEntryPoint("cuTensorMapEncodeTiled", &fn, cudaEnableDefault, &qr);
  EncodeFn enc = (EncodeFn)fn;
  void *abT, *z2, *h, *xn;
  cudaGetSymbolAddress(&xn, g_xn);
  cudaGetSymbolAddress(&abT, g_abT);
  cudaGetSymbolAddress(&z2, g_z2);
  cudaGetSymbolAddress(&h, g_h);

  Maps maps;
  make2d(enc, &maps.m[M_XN], xn, DM, SEQ, 64, 64);
  make3d(enc, &maps.m[M_Z232], z2, FH, SEQ, 32, 3, 128);
  make2d(enc, &maps.m[M_XR], x, DM, SEQ, 160, 64, false);
  make3d(enc, &maps.m[M_WIN32], win, FF, DM, 32, 3);
  make2d(enc, &maps.m[M_WSRE], wsre, SEQ, SEQ, 64, 64);
  make2d(enc, &maps.m[M_WSIM], wsim, SEQ, SEQ, 64, 64);
  make2d(enc, &maps.m[M_WSP], wsp, SEQ, SEQ, 64, 64);
  make2d(enc, &maps.m[M_H], h, FH, SEQ, 64, 64);
  make3d(enc, &maps.m[M_WIN3], win, FF, DM, 64, 3);
  make3d(enc, &maps.m[M_Z23], z2, FH, SEQ, 64, 3);
  make2d(enc, &maps.m[M_WDRE], wdre, DM, DM, 64, 160);
  make2d(enc, &maps.m[M_WDIM], wdim, DM, DM, 64, 160);
  make2d(enc, &maps.m[M_AB], abT, SEQ, 2 * DM, 64, 160);
  make3d(enc, &maps.m[M_WOUT], wout, DM, FH, 32, 5);
  make2d(enc, &maps.m[M_HS], h, FH, SEQ, 64, 16);
  make2d(enc, &maps.m[M_ABS], abT, SEQ, 2 * DM, 64, 40);
  make2d(enc, &maps.m[M_OUT], d_out, DM, SEQ, 160, 16, false);

  cudaFuncSetAttribute(fused_kernel, cudaFuncAttributeMaxDynamicSharedMemorySize, SMEM_BYTES);
  fused_kernel<<<128, 384, SMEM_BYTES>>>(maps, x, bsp);
}
```

```cpp
#include <cuda_runtime.h>
#include <cuda_bf16.h>
#include <cuda.h>
#include <stdint.h>

namespace {

typedef __nv_bfloat16 bf16;

constexpr int SEQ = 2048, DM = 640, FF = 1536, FH = 768;
#define NXV 11
constexpr int NX = NXV;
constexpr int STAGES = 4;
constexpr int A_BYTES = 16384;
constexpr int BIAS_OFF = 0;
constexpr int BAR_OFF = 512;
constexpr int READY_OFF = 640;
constexpr int RING_OFF = 1024;
constexpr int STAGE_A = 40960, STAGE_B = 36864;
constexpr int SMEM_BYTES = RING_OFF + 4 * STAGE_A + 49152;
constexpr int KB_A = 20 + 32 + NX + 12;
constexpr int KB_B = 30 + 64 - NX;
constexpr float LN_EPS = 1e-5f;
constexpr unsigned POLL_LIMIT = 100000;
#define POLL_NS 100
#define PF_D 8
#define ROT 2
#define Z1_NS 0
#define INFL 2
#define LIM_G 1000
#define PF_NS 150

constexpr int BAR_ORD1 = 1, BAR_ORD2 = 2, BAR_WG1 = 3, BAR_WG2 = 4, BAR_LN = 5, BAR_BUF = 6, BAR_Z1 = 7, BAR_PUB1 = 8, BAR_PUB2 = 9;

enum { M_XN, M_XR, M_WIN32, M_Z232, M_WSRE, M_WSIM, M_WSP, M_H, M_WIN3, M_Z23, M_WDRE, M_WDIM, M_AB, M_WOUT, M_OUT, M_HS, M_ABS, M_COUNT };
struct Maps { CUtensorMap m[M_COUNT]; };

__device__ __align__(1024) bf16 g_abT[2 * DM * SEQ];
__device__ __align__(1024) bf16 g_z2[SEQ * FH];
__device__ __align__(1024) bf16 g_h[SEQ * FH];
__device__ __align__(1024) bf16 g_xn[SEQ * DM];
__device__ __align__(16) uint2 g_zstat[128 * 128];
__device__ __align__(16) uint4 g_part[128 * 27 * 128];
__device__ unsigned g_flags[5 * 128];
constexpr int F_A = 0, F_B = 128, F_H = 256, F_Z = 384, F_XN = 512;
__device__ unsigned g_done;
#define TS(role, ev)
#define TC(i)

extern __shared__ __align__(1024) uint8_t smem[];

__device__ __forceinline__ uint32_t smem_u32(const void* p) { return (uint32_t)__cvta_generic_to_shared(p); }
__device__ __forceinline__ void mbar_init(uint32_t bar, uint32_t cnt) { asm volatile("mbarrier.init.shared::cta.b64 [%0], %1;" :: "r"(bar), "r"(cnt)); }
__device__ __forceinline__ void mbar_expect_tx(uint32_t bar, uint32_t bytes) { asm volatile("mbarrier.arrive.expect_tx.shared::cta.b64 _, [%0], %1;" :: "r"(bar), "r"(bytes) : "memory"); }
__device__ __forceinline__ void mbar_arrive(uint32_t bar) { asm volatile("mbarrier.arrive.shared::cta.b64 _, [%0];" :: "r"(bar) : "memory"); }
__device__ __forceinline__ void mbar_arrive_cluster(uint32_t bar, uint32_t cta) {
  asm volatile("{\n.reg .b32 ra;\nmapa.shared::cluster.u32 ra, %0, %1;\nmbarrier.arrive.shared::cluster.b64 _, [ra];\n}" :: "r"(bar), "r"(cta) : "memory");
}
__device__ __forceinline__ void mbar_wait(uint32_t bar, uint32_t parity) {
  asm volatile("{\n.reg .pred p;\n.reg .u32 n;\nmov.u32 n, 0;\n"
               "LW: mbarrier.try_wait.parity.shared::cta.b64 p, [%0], %1, 2000;\n@p bra LD;\n"
               "add.u32 n, n, 1;\nsetp.lt.u32 p, n, 20000;\n@p bra LW;\nLD:\n}" :: "r"(bar), "r"(parity) : "memory");
}
__device__ __forceinline__ void tma_load_2d(uint32_t dst, const CUtensorMap* map, uint32_t bar, int c0, int c1) {
  asm volatile("cp.async.bulk.tensor.2d.shared::cluster.global.mbarrier::complete_tx::bytes [%0], [%1, {%3, %4}], [%2];"
    :: "r"(dst), "l"((uint64_t)map), "r"(bar), "r"(c0), "r"(c1) : "memory");
}
__device__ __forceinline__ void tma_load_3d(uint32_t dst, const CUtensorMap* map, uint32_t bar, int c0, int c1, int c2) {
  asm volatile("cp.async.bulk.tensor.3d.shared::cluster.global.mbarrier::complete_tx::bytes [%0], [%1, {%3, %4, %5}], [%2];"
    :: "r"(dst), "l"((uint64_t)map), "r"(bar), "r"(c0), "r"(c1), "r"(c2) : "memory");
}
__device__ __forceinline__ void tma_load_2d_mc(uint32_t dst, const CUtensorMap* map, uint32_t bar, int c0, int c1, uint16_t mask) {
  asm volatile("cp.async.bulk.tensor.2d.shared::cluster.global.mbarrier::complete_tx::bytes.multicast::cluster [%0], [%1, {%3, %4}], [%2], %5;"
    :: "r"(dst), "l"((uint64_t)map), "r"(bar), "r"(c0), "r"(c1), "h"(mask) : "memory");
}
__device__ __forceinline__ void tma_store_2d(const CUtensorMap* map, uint32_t src, int c0, int c1) {
  asm volatile("cp.async.bulk.tensor.2d.global.shared::cta.bulk_group [%0, {%2, %3}], [%1];"
    :: "l"((uint64_t)map), "r"(src), "r"(c0), "r"(c1) : "memory");
}
__device__ __forceinline__ void tma_store_3d(const CUtensorMap* map, uint32_t src, int c0, int c1, int c2) {
  asm volatile("cp.async.bulk.tensor.3d.global.shared::cta.bulk_group [%0, {%2, %3, %4}], [%1];"
    :: "l"((uint64_t)map), "r"(src), "r"(c0), "r"(c1), "r"(c2) : "memory");
}
__device__ __forceinline__ void bulk_wait_all() { asm volatile("cp.async.bulk.wait_group 0;" ::: "memory"); }
__device__ __forceinline__ void bulk_commit() { asm volatile("cp.async.bulk.commit_group;" ::: "memory"); }
__device__ __forceinline__ void bulk_wait_read() { asm volatile("cp.async.bulk.wait_group.read 0;" ::: "memory"); }
__device__ __forceinline__ void fence_async_smem() { asm volatile("fence.proxy.async.shared::cta;" ::: "memory"); }
__device__ __forceinline__ void fence_async_global() { asm volatile("fence.proxy.async.global;" ::: "memory"); }
__device__ __forceinline__ void wgmma_fence() { asm volatile("wgmma.fence.sync.aligned;" ::: "memory"); }
__device__ __forceinline__ void wgmma_commit() { asm volatile("wgmma.commit_group.sync.aligned;" ::: "memory"); }
template<int N> __device__ __forceinline__ void wgmma_wait() { asm volatile("wgmma.wait_group.sync.aligned %0;" :: "n"(N) : "memory"); }
template<int ID> __device__ __forceinline__ void bar_sync(int n) { asm volatile("bar.sync %0, %1;" :: "n"(ID), "r"(n) : "memory"); }
template<int ID> __device__ __forceinline__ void bar_arrive(int n) { asm volatile("bar.arrive %0, %1;" :: "n"(ID), "r"(n) : "memory"); }
__device__ __forceinline__ void cluster_wait() { asm volatile("barrier.cluster.wait.aligned;" ::: "memory"); }
__device__ __forceinline__ uint64_t desc64(uint32_t lo, uint32_t hi) { return (uint64_t)lo | ((uint64_t)hi << 32); }
__device__ __forceinline__ uint4 ld_vol4(const uint4* p) {
  uint4 v; asm volatile("ld.relaxed.gpu.global.v4.u32 {%0,%1,%2,%3}, [%4];" : "=r"(v.x), "=r"(v.y), "=r"(v.z), "=r"(v.w) : "l"(p) : "memory"); return v;
}
__device__ __forceinline__ uint2 ld_vol2(const uint2* p) {
  uint2 v; asm volatile("ld.relaxed.gpu.global.v2.u32 {%0,%1}, [%2];" : "=r"(v.x), "=r"(v.y) : "l"(p) : "memory"); return v;
}
__device__ __forceinline__ void st_vol4(uint4* p, uint32_t a, uint32_t b, uint32_t c, uint32_t d) {
  asm volatile("st.relaxed.gpu.global.v4.u32 [%0], {%1,%2,%3,%4};" :: "l"(p), "r"(a), "r"(b), "r"(c), "r"(d) : "memory");
}
__device__ __forceinline__ void st_vol2(uint2* p, uint32_t a, uint32_t b) {
  asm volatile("st.relaxed.gpu.global.v2.u32 [%0], {%1,%2};" :: "l"(p), "r"(a), "r"(b) : "memory");
}
__device__ __forceinline__ void stg128(void* p, uint4 v) {
  asm volatile("st.global.v4.u32 [%0], {%1,%2,%3,%4};" :: "l"(p), "r"(v.x), "r"(v.y), "r"(v.z), "r"(v.w));
}
__device__ __forceinline__ unsigned ld_relaxed(const unsigned* p) {
  unsigned v; asm volatile("ld.relaxed.gpu.global.u32 %0, [%1];" : "=r"(v) : "l"(p) : "memory"); return v;
}
__device__ __forceinline__ uint32_t pack_bf16(float lo, float hi) {
  uint32_t r; asm("cvt.rn.bf16x2.f32 %0, %1, %2;" : "=r"(r) : "f"(hi), "f"(lo)); return r;
}
__device__ __forceinline__ float bf_lo(uint32_t v) { return __uint_as_float(v << 16); }
__device__ __forceinline__ float bf_hi(uint32_t v) { return __uint_as_float(v & 0xFFFF0000u); }
__device__ __forceinline__ void stsm4(uint32_t addr, uint32_t a, uint32_t b, uint32_t c, uint32_t d) {
  asm volatile("stmatrix.sync.aligned.m8n8.x4.shared.b16 [%0], {%1,%2,%3,%4};" :: "r"(addr), "r"(a), "r"(b), "r"(c), "r"(d));
}
__device__ __forceinline__ void stsm4_t(uint32_t addr, uint32_t a, uint32_t b, uint32_t c, uint32_t d) {
  asm volatile("stmatrix.sync.aligned.m8n8.x4.trans.shared.b16 [%0], {%1,%2,%3,%4};" :: "r"(addr), "r"(a), "r"(b), "r"(c), "r"(d));
}
__device__ __forceinline__ void ldsm4(uint32_t addr, uint32_t& a, uint32_t& b, uint32_t& c, uint32_t& d) {
  asm volatile("ldmatrix.sync.aligned.m8n8.x4.shared.b16 {%0,%1,%2,%3}, [%4];" : "=r"(a), "=r"(b), "=r"(c), "=r"(d) : "r"(addr));
}
__device__ __forceinline__ uint4 lds128(uint32_t a) {
  uint4 v; asm volatile("ld.shared.v4.u32 {%0,%1,%2,%3}, [%4];" : "=r"(v.x), "=r"(v.y), "=r"(v.z), "=r"(v.w) : "r"(a)); return v;
}
__device__ __forceinline__ void sts128(uint32_t a, uint32_t x, uint32_t y, uint32_t z, uint32_t w) {
  asm volatile("st.shared.v4.u32 [%0], {%1,%2,%3,%4};" :: "r"(a), "r"(x), "r"(y), "r"(z), "r"(w));
}
__device__ __forceinline__ uint32_t hmul2_bf16(uint32_t a, uint32_t b) {
  uint32_t r; asm("mul.rn.bf16x2 %0, %1, %2;" : "=r"(r) : "r"(a), "r"(b)); return r;
}
__device__ __forceinline__ float gelu_tanh(float v) {
  float u = v * fmaf(0.0356774081f, v * v, 0.7978845608f);
  float t; asm("tanh.approx.f32 %0, %1;" : "=f"(t) : "f"(u));
  float hv = 0.5f * v;
  return fmaf(hv, t, hv);
}

template<int TB>
__device__ __forceinline__ void wgmma_n192(float (&d)[96], uint64_t da, uint64_t db, int scale_d) {
  asm volatile("{\n.reg .pred p;\nsetp.ne.b32 p, %98, 0;\n"
   "wgmma.mma_async.sync.aligned.m64n192k16.f32.bf16.bf16 {%0,%1,%2,%3,%4,%5,%6,%7,%8,%9,%10,%11,%12,%13,%14,%15,%16,%17,%18,%19,%20,%21,%22,%23,%24,%25,%26,%27,%28,%29,%30,%31,%32,%33,%34,%35,%36,%37,%38,%39,%40,%41,%42,%43,%44,%45,%46,%47,%48,%49,%50,%51,%52,%53,%54,%55,%56,%57,%58,%59,%60,%61,%62,%63,%64,%65,%66,%67,%68,%69,%70,%71,%72,%73,%74,%75,%76,%77,%78,%79,%80,%81,%82,%83,%84,%85,%86,%87,%88,%89,%90,%91,%92,%93,%94,%95}, %96, %97, p, 1, 1, 0, %99;\n}"
   : "+f"(d[0]),"+f"(d[1]),"+f"(d[2]),"+f"(d[3]),"+f"(d[4]),"+f"(d[5]),"+f"(d[6]),"+f"(d[7]),"+f"(d[8]),"+f"(d[9]),"+f"(d[10]),"+f"(d[11]),"+f"(d[12]),"+f"(d[13]),"+f"(d[14]),"+f"(d[15]),"+f"(d[16]),"+f"(d[17]),"+f"(d[18]),"+f"(d[19]),"+f"(d[20]),"+f"(d[21]),"+f"(d[22]),"+f"(d[23]),"+f"(d[24]),"+f"(d[25]),"+f"(d[26]),"+f"(d[27]),"+f"(d[28]),"+f"(d[29]),"+f"(d[30]),"+f"(d[31]),"+f"(d[32]),"+f"(d[33]),"+f"(d[34]),"+f"(d[35]),"+f"(d[36]),"+f"(d[37]),"+f"(d[38]),"+f"(d[39]),"+f"(d[40]),"+f"(d[41]),"+f"(d[42]),"+f"(d[43]),"+f"(d[44]),"+f"(d[45]),"+f"(d[46]),"+f"(d[47]),"+f"(d[48]),"+f"(d[49]),"+f"(d[50]),"+f"(d[51]),"+f"(d[52]),"+f"(d[53]),"+f"(d[54]),"+f"(d[55]),"+f"(d[56]),"+f"(d[57]),"+f"(d[58]),"+f"(d[59]),"+f"(d[60]),"+f"(d[61]),"+f"(d[62]),"+f"(d[63]),"+f"(d[64]),"+f"(d[65]),"+f"(d[66]),"+f"(d[67]),"+f"(d[68]),"+f"(d[69]),"+f"(d[70]),"+f"(d[71]),"+f"(d[72]),"+f"(d[73]),"+f"(d[74]),"+f"(d[75]),"+f"(d[76]),"+f"(d[77]),"+f"(d[78]),"+f"(d[79]),"+f"(d[80]),"+f"(d[81]),"+f"(d[82]),"+f"(d[83]),"+f"(d[84]),"+f"(d[85]),"+f"(d[86]),"+f"(d[87]),"+f"(d[88]),"+f"(d[89]),"+f"(d[90]),"+f"(d[91]),"+f"(d[92]),"+f"(d[93]),"+f"(d[94]),"+f"(d[95])
   : "l"(da), "l"(db), "r"(scale_d), "n"(TB));
}
template<int TB>
__device__ __forceinline__ void wgmma_n160(float (&d)[80], uint64_t da, uint64_t db, int scale_d) {
  asm volatile("{\n.reg .pred p;\nsetp.ne.b32 p, %82, 0;\n"
   "wgmma.mma_async.sync.aligned.m64n160k16.f32.bf16.bf16 {%0,%1,%2,%3,%4,%5,%6,%7,%8,%9,%10,%11,%12,%13,%14,%15,%16,%17,%18,%19,%20,%21,%22,%23,%24,%25,%26,%27,%28,%29,%30,%31,%32,%33,%34,%35,%36,%37,%38,%39,%40,%41,%42,%43,%44,%45,%46,%47,%48,%49,%50,%51,%52,%53,%54,%55,%56,%57,%58,%59,%60,%61,%62,%63,%64,%65,%66,%67,%68,%69,%70,%71,%72,%73,%74,%75,%76,%77,%78,%79}, %80, %81, p, 1, 1, 0, %83;\n}"
   : "+f"(d[0]),"+f"(d[1]),"+f"(d[2]),"+f"(d[3]),"+f"(d[4]),"+f"(d[5]),"+f"(d[6]),"+f"(d[7]),"+f"(d[8]),"+f"(d[9]),"+f"(d[10]),"+f"(d[11]),"+f"(d[12]),"+f"(d[13]),"+f"(d[14]),"+f"(d[15]),"+f"(d[16]),"+f"(d[17]),"+f"(d[18]),"+f"(d[19]),"+f"(d[20]),"+f"(d[21]),"+f"(d[22]),"+f"(d[23]),"+f"(d[24]),"+f"(d[25]),"+f"(d[26]),"+f"(d[27]),"+f"(d[28]),"+f"(d[29]),"+f"(d[30]),"+f"(d[31]),"+f"(d[32]),"+f"(d[33]),"+f"(d[34]),"+f"(d[35]),"+f"(d[36]),"+f"(d[37]),"+f"(d[38]),"+f"(d[39]),"+f"(d[40]),"+f"(d[41]),"+f"(d[42]),"+f"(d[43]),"+f"(d[44]),"+f"(d[45]),"+f"(d[46]),"+f"(d[47]),"+f"(d[48]),"+f"(d[49]),"+f"(d[50]),"+f"(d[51]),"+f"(d[52]),"+f"(d[53]),"+f"(d[54]),"+f"(d[55]),"+f"(d[56]),"+f"(d[57]),"+f"(d[58]),"+f"(d[59]),"+f"(d[60]),"+f"(d[61]),"+f"(d[62]),"+f"(d[63]),"+f"(d[64]),"+f"(d[65]),"+f"(d[66]),"+f"(d[67]),"+f"(d[68]),"+f"(d[69]),"+f"(d[70]),"+f"(d[71]),"+f"(d[72]),"+f"(d[73]),"+f"(d[74]),"+f"(d[75]),"+f"(d[76]),"+f"(d[77]),"+f"(d[78]),"+f"(d[79])
   : "l"(da), "l"(db), "r"(scale_d), "n"(TB));
}
template<int TB>
__device__ __forceinline__ void wgmma_n96(float (&d)[48], uint64_t da, uint64_t db, int scale_d) {
  asm volatile("{\n.reg .pred p;\nsetp.ne.b32 p, %50, 0;\n"
   "wgmma.mma_async.sync.aligned.m64n96k16.f32.bf16.bf16 {%0,%1,%2,%3,%4,%5,%6,%7,%8,%9,%10,%11,%12,%13,%14,%15,%16,%17,%18,%19,%20,%21,%22,%23,%24,%25,%26,%27,%28,%29,%30,%31,%32,%33,%34,%35,%36,%37,%38,%39,%40,%41,%42,%43,%44,%45,%46,%47}, %48, %49, p, 1, 1, 0, %51;\n}"
   : "+f"(d[0]),"+f"(d[1]),"+f"(d[2]),"+f"(d[3]),"+f"(d[4]),"+f"(d[5]),"+f"(d[6]),"+f"(d[7]),"+f"(d[8]),"+f"(d[9]),"+f"(d[10]),"+f"(d[11]),"+f"(d[12]),"+f"(d[13]),"+f"(d[14]),"+f"(d[15]),"+f"(d[16]),"+f"(d[17]),"+f"(d[18]),"+f"(d[19]),"+f"(d[20]),"+f"(d[21]),"+f"(d[22]),"+f"(d[23]),"+f"(d[24]),"+f"(d[25]),"+f"(d[26]),"+f"(d[27]),"+f"(d[28]),"+f"(d[29]),"+f"(d[30]),"+f"(d[31]),"+f"(d[32]),"+f"(d[33]),"+f"(d[34]),"+f"(d[35]),"+f"(d[36]),"+f"(d[37]),"+f"(d[38]),"+f"(d[39]),"+f"(d[40]),"+f"(d[41]),"+f"(d[42]),"+f"(d[43]),"+f"(d[44]),"+f"(d[45]),"+f"(d[46]),"+f"(d[47])
   : "l"(da), "l"(db), "r"(scale_d), "n"(TB));
}

template<int N, int TB>
__device__ __forceinline__ void wgmma_n(float (&d)[N / 2], uint64_t da, uint64_t db) {
  if constexpr (N == 192) wgmma_n192<TB>(d, da, db, 1);
  else if constexpr (N == 160) wgmma_n160<TB>(d, da, db, 1);
  else wgmma_n96<TB>(d, da, db, 1);
}

template<int R>
__device__ __forceinline__ void pin(float (&acc)[2][R]) {
  #pragma unroll
  for (int mi = 0; mi < 2; mi++)
    #pragma unroll
    for (int i = 0; i < R; i++) asm volatile("" : "+f"(acc[mi][i]) :: "memory");
}
template<int R>
__device__ __forceinline__ void zero(float (&acc)[2][R]) {
  #pragma unroll
  for (int i = 0; i < R; i++) { acc[0][i] = 0.f; acc[1][i] = 0.f; }
  pin(acc);
}

template<int N, int TB, bool CONT, int ORD_BAR>
__device__ __forceinline__ void mainloop(float (&acc)[2][N / 2], uint32_t sbase, uint32_t stage_bytes, int g0, int nk, int total, int mswap) {
  const uint32_t full0 = sbase + BAR_OFF, empty0 = full0 + 8 * STAGES, ring = sbase + RING_OFF;
  const int t = threadIdx.x & 127;
  const uint32_t da0 = (((ring + mswap * 8192) & 0x3FFFF) >> 4) | 0x10000u, da1 = (((ring + (mswap ^ 1) * 8192) & 0x3FFFF) >> 4) | 0x10000u;
  const uint32_t db0 = (((ring + A_BYTES) & 0x3FFFF) >> 4) | ((TB == 2 ? 256u : TB ? 512u : 1u) << 16);
  constexpr uint32_t HI_A = 0x40000040u, HI_B = TB == 2 ? 0x80000020u : 0x40000040u;
  #pragma unroll 1
  for (int g = g0; g < g0 + nk; g++) {
    const int s = g & (STAGES - 1);
    const uint32_t so = s * (stage_bytes >> 4);
    mbar_wait(full0 + 8 * s, (g / STAGES) & 1);
    wgmma_fence();
    #pragma unroll
    for (int k = 0; k < 4; k++) {
      const uint64_t db = desc64(db0 + so + (TB == 2 ? k * 64 : TB ? k * 128 : k * 2), HI_B);
      wgmma_n<N, TB != 0>(acc[0], desc64(da0 + so + k * 2, HI_A), db);
      wgmma_n<N, TB != 0>(acc[1], desc64(da1 + so + k * 2, HI_A), db);
    }
    wgmma_commit();
    if (ORD_BAR != 0 && g == g0 + nk - 1) bar_arrive<ORD_BAR>(256);
    wgmma_wait<1>();
    if (t < 2 && (CONT || g > g0) && g - 1 + STAGES <= total) mbar_arrive_cluster(empty0 + 8 * ((g - 1) & (STAGES - 1)), t);
  }
}
template<int R>
__device__ __forceinline__ void drain(float (&acc)[2][R], uint32_t sbase, int glast, int total) {
  wgmma_wait<0>();
  pin(acc);
  const int t = threadIdx.x & 127;
  if (t < 2 && glast + STAGES <= total) mbar_arrive_cluster(sbase + BAR_OFF + 8 * STAGES + 8 * (glast & (STAGES - 1)), t);
}

__device__ __forceinline__ void set_flag(unsigned* flag, unsigned epoch) {
  asm volatile("st.relaxed.gpu.global.u32 [%0], %1;" :: "l"(flag), "r"(epoch) : "memory");
}
__device__ __forceinline__ void publish(unsigned* flag, unsigned epoch) {
  asm volatile("fence.acq_rel.gpu;" ::: "memory");
  asm volatile("st.relaxed.gpu.global.u32 [%0], %1;" :: "l"(flag), "r"(epoch) : "memory");
}

__device__ __forceinline__ float sum8(uint4 v) {
  return ((bf_lo(v.x) + bf_hi(v.x)) + (bf_lo(v.y) + bf_hi(v.y))) + ((bf_lo(v.z) + bf_hi(v.z)) + (bf_lo(v.w) + bf_hi(v.w)));
}
__device__ __forceinline__ void ln_rows(const bf16* __restrict__ x) {
  const int t = threadIdx.x - 128, row = blockIdx.x * 16 + (t >> 4), c = t & 15;
  uint4 rv[5];
  #pragma unroll
  for (int j = 0; j < 5; j++) rv[j] = __ldg(reinterpret_cast<const uint4*>(x + (size_t)row * DM) + c + 16 * j);
  float s = 0.f;
  #pragma unroll
  for (int j = 0; j < 5; j++) s += sum8(rv[j]);
  #pragma unroll
  for (int o = 1; o < 16; o <<= 1) s += __shfl_xor_sync(0xffffffffu, s, o);
  const float mean = s * (1.f / DM);
  float q = 0.f;
  #pragma unroll
  for (int j = 0; j < 5; j++) {
    const uint32_t u[4] = {rv[j].x, rv[j].y, rv[j].z, rv[j].w};
    #pragma unroll
    for (int e = 0; e < 4; e++) { const float d0 = bf_lo(u[e]) - mean, d1 = bf_hi(u[e]) - mean; q = fmaf(d0, d0, q); q = fmaf(d1, d1, q); }
  }
  #pragma unroll
  for (int o = 1; o < 16; o <<= 1) q += __shfl_xor_sync(0xffffffffu, q, o);
  const float r = rsqrtf(fmaf(q, 1.f / DM, LN_EPS)), o = -mean * r;
  #pragma unroll
  for (int j = 0; j < 5; j++)
    stg128(reinterpret_cast<uint4*>(g_xn + (size_t)row * DM) + c + 16 * j, make_uint4(
           pack_bf16(fmaf(bf_lo(rv[j].x), r, o), fmaf(bf_hi(rv[j].x), r, o)), pack_bf16(fmaf(bf_lo(rv[j].y), r, o), fmaf(bf_hi(rv[j].y), r, o)),
           pack_bf16(fmaf(bf_lo(rv[j].z), r, o), fmaf(bf_hi(rv[j].z), r, o)), pack_bf16(fmaf(bf_lo(rv[j].w), r, o), fmaf(bf_hi(rv[j].w), r, o))));
}

__device__ __forceinline__ void a_entry(int g, int grp, int rb, int& mi, int& kb) {
  if (g < 20) { mi = M_XN; kb = g < 10 ? g : g - 10; }
  else if (grp == 0) {
    if (g < 52) { mi = M_WSP; kb = (g - 20 + ROT * rb) & 31; }
    else if (g < 52 + NX) { mi = M_WSIM; kb = g - 52 + 32 - NX; }
    else { mi = M_H; kb = g - 52 - NX; }
  } else {
    if (g < 30) { mi = M_XN; kb = g - 20; }
    else if (g < 62) { mi = M_WSRE; kb = (g - 30 + ROT * rb) & 31; }
    else { mi = M_WSIM; kb = g - 62; }
  }
}

__global__ void __cluster_dims__(2, 1, 1) __launch_bounds__(384, 1)
fused_kernel(const __grid_constant__ Maps maps, const bf16* __restrict__ x, const bf16* __restrict__ bsp) {
  const uint32_t sbase = smem_u32(smem);
  const uint32_t full0 = sbase + BAR_OFF, empty0 = full0 + 8 * STAGES, dep0 = empty0 + 8 * STAGES, ring = sbase + RING_OFF;
  const int tid = threadIdx.x, wg = __shfl_sync(0xffffffffu, tid >> 7, 0);
  const int rank = blockIdx.x & 1, grp = (blockIdx.x >> 1) & 1, q = blockIdx.x >> 2;
  const int rb = q >> 1, ct = (q & 1) * 2 + rank, c8 = grp * 4 + ct;
  const int total = grp == 0 ? KB_A : KB_B;
  const uint32_t stage_bytes = grp == 0 ? STAGE_A : STAGE_B;

  if (tid == 0) {
    TS(0, 0);
    for (int s = 0; s < STAGES; s++) { mbar_init(full0 + 8 * s, 2); mbar_init(empty0 + 8 * s, 2); mbar_init(dep0 + 8 * s, 1); }
    *reinterpret_cast<volatile int*>(smem + READY_OFF) = 0;
    asm volatile("fence.mbarrier_init.release.cluster;" ::: "memory");
  }
  __syncthreads();
  asm volatile("barrier.cluster.arrive.relaxed.aligned;" ::: "memory");

  if (wg == 0) {
    asm volatile("setmaxnreg.dec.sync.aligned.u32 40;");
    const int warp = tid >> 5, lane = tid & 31;
    if (warp == 0) {
      const int row = rb * 128;
      cluster_wait();
      if (lane == 0) {
        #pragma unroll 1
        for (int g = 0; g < total; g++) {
          int mi, kb;
          a_entry(g, grp, rb, mi, kb);
          if (g == 0 || (mi == M_H && kb == 0)) { TS(0, g ? 3 : 1); mbar_wait(dep0 + (g ? 24 : 0), 0); fence_async_global(); TS(0, g ? 4 : 2); }
          const int s = g & (STAGES - 1);
          mbar_wait(empty0 + 8 * s, ((g / STAGES) & 1) ^ 1);
          mbar_expect_tx(full0 + 8 * s, A_BYTES);
          tma_load_2d_mc(ring + s * stage_bytes + rank * 8192, &maps.m[mi], full0 + 8 * s, kb * 64, row + rank * 64, 3);
          if (g + PF_D < total) {
            a_entry(g + PF_D, grp, rb, mi, kb);
            if (mi >= M_WSRE && mi <= M_WSP && (kb & 1) == 0 && ((kb >> 1) & 1) == (ct >> 1))
              asm volatile("cp.async.bulk.prefetch.tensor.2d.L2.global.tile [%0, {%1, %2}];" :: "l"((uint64_t)&maps.m[mi]), "r"(kb * 64), "r"(row + rank * 64) : "memory");
          }
        }
        const int s = total & (STAGES - 1);
        mbar_wait(empty0 + 8 * s, ((total / STAGES) & 1) ^ 1);
        mbar_expect_tx(full0 + 8 * s, 20480);
        mbar_arrive(full0 + 8 * s);
        tma_load_2d(ring + s * stage_bytes, &maps.m[M_XR], full0 + 8 * s, ct * 160, row + grp * 64);
        TS(0, 5);
      }
    } else if (warp == 1) {
      if (lane == 0) {
        int have = 0;
        #pragma unroll 1
        for (int g = 0; g < total; g++) {
          int kind = 1, mi, kb, c, dep = 0, need = 0;
          uint32_t bytes = 20480;
          if (g < 10) { kind = 0; mi = M_WIN32; kb = g; c = 24 + 3 * c8; bytes = 12288; }
          else if (grp == 0) {
            if (g < 20) { kind = 0; mi = M_WIN3; kb = g - 10; c = 3 * ct; bytes = 24576; }
            else if (g < 52) { kind = 0; mi = M_Z23; kb = (g - 20 + ROT * rb) & 31; c = 3 * ct; bytes = 24576; need = ((g - 20) >> 1) + 1; }
            else if (g < 52 + NX) { mi = M_AB; kb = g - 52 + 32 - NX; c = DM + ct * 160; dep = g == 52 ? 2 : 0; }
            else { kind = 0; mi = M_WOUT; kb = g - 52 - NX; c = ct * 5; }
          } else {
            if (g < 30) { mi = g < 20 ? M_WDRE : M_WDIM; kb = g < 20 ? g - 10 : g - 20; c = ct * 160; }
            else if (g < 62) { mi = M_AB; kb = (g - 30 + ROT * rb) & 31; c = ct * 160; need = ((g - 30) >> 1) + 1; }
            else { mi = M_AB; kb = g - 62; c = ct * 160 + DM; dep = g == 62 ? 2 : 0; }
          }
          if (need > have) {
            if (need == 1) TS(1, 0);
            unsigned it = 0;
            while ((have = *reinterpret_cast<volatile int*>(smem + READY_OFF)) < need && ++it < 50 * POLL_LIMIT) {}
            fence_async_global();
            if (need == 1) { TS(1, 1); TC(1); }
          }
          if (dep) { TS(1, dep * 2 - 2); mbar_wait(dep0 + 8 * dep, 0); fence_async_global(); TS(1, dep * 2 - 1); TC(dep); }
          const int s = g & (STAGES - 1);
          const uint32_t dst = ring + s * stage_bytes + A_BYTES, fb = full0 + 8 * s;
          mbar_wait(empty0 + 8 * s, ((g / STAGES) & 1) ^ 1);
          mbar_expect_tx(fb, bytes);
          if (kind == 0) tma_load_3d(dst, &maps.m[mi], fb, 0, kb * 64, c);
          else tma_load_2d(dst, &maps.m[mi], fb, kb * 64, c);
        }
      }
      __syncwarp();
      cluster_wait();
    } else if (warp == 2) {
      cluster_wait();
      const unsigned epoch = (*reinterpret_cast<volatile unsigned*>(&g_done) >> 7) + 1u;
      #pragma unroll 1
      for (int d = 0; d < 4 - grp; d++) {
        const int rr = ((lane >> 1) + (ROT / 2) * rb) & 15;
        const int fi = d == 0 ? F_XN + rb * 8 + (lane & 7)
                     : d == 3 ? F_H + rb * 4 + (lane & 3)
                     : d == 2 ? F_B + (lane & 15) * 4 + ct
                     : grp == 0 ? F_Z + rr * 8 + ct * 2 + (lane & 1) : F_A + rr * 4 + ct;
        unsigned it = 0, m;
        while ((m = __ballot_sync(0xffffffffu, ld_relaxed(g_flags + fi) != epoch)) != 0 && ++it < POLL_LIMIT) {
          if (d == 1 && lane == 0) *reinterpret_cast<volatile int*>(smem + READY_OFF) = (__ffs(m) - 1) >> 1;
          __nanosleep(20);
        }
        if (d == 1 && lane == 0) *reinterpret_cast<volatile int*>(smem + READY_OFF) = 16;
        TS(0, 8 + d * 2);
        fence_async_global();
        __syncwarp();
        TS(0, 9 + d * 2);
        if (lane == 0) mbar_arrive(dep0 + 8 * d);
      }
    } else {
      const unsigned epoch = (*reinterpret_cast<volatile unsigned*>(&g_done) >> 7) + 1u;
      cluster_wait();
      bar_sync<BAR_LN>(288);
      if (lane == 0) { TS(1, 5); publish(g_flags + F_XN + blockIdx.x, epoch); TS(1, 6); }
      __syncwarp();
      bar_sync<BAR_PUB1>(160);
      if (lane == 0) {
        TS(1, 7);
        tma_store_3d(&maps.m[M_Z232], ring + 4 * stage_bytes, 0, rb * 128, 3 * c8);
        bulk_commit();
        bulk_wait_all();
        set_flag(g_flags + F_Z + rb * 8 + c8, epoch);
        TS(1, 8);
      }
      __syncwarp();
      if (grp == 0) {
        bar_arrive<BAR_BUF>(160);
      } else {
        bar_sync<BAR_PUB2>(160);
        if (lane == 0) set_flag(g_flags + F_A + rb * 4 + ct, epoch);
        TS(1, 9);
        __syncwarp();
      }
      bar_sync<BAR_PUB1>(160);
      if (lane == 0) set_flag(g_flags + (grp == 0 ? F_H : F_B) + rb * 4 + ct, epoch);
      TS(1, 10);
    }
  } else {
    asm volatile("setmaxnreg.inc.sync.aligned.u32 232;");
    const int t = tid & 127, w = t >> 5, l = t & 31;
    const uint32_t buf = ring + 4 * stage_bytes;
    const unsigned epoch = (*reinterpret_cast<volatile unsigned*>(&g_done) >> 7) + 1u;
    ln_rows(x);
    bar_arrive<BAR_LN>(288);
    TS(wg + 1, 0);
    cluster_wait();
    const int rl = w * 16 + ((l >> 3) & 1) * 8 + (l & 7);
    const int gr = w * 16 + (l & 15);
    const uint32_t st_base = buf + rl * 128;
    const uint32_t st_x = ((l >> 4) ^ (l & 7)) << 4;
    if (wg == 1) {
      float acc[2][48];
      zero(acc);
      mainloop<96, 2, false, BAR_ORD1>(acc, sbase, stage_bytes, 0, 10, total, 0);
      drain(acc, sbase, 9, total);
      TS(2, 2);
      float sum[4], sq[4];
      #pragma unroll
      for (int r = 0; r < 4; r++) {
        float s0 = 0.f, q0 = 0.f;
        #pragma unroll
        for (int j = 0; j < 12; j++) {
          float* a = &acc[r >> 1][4 * j + (r & 1) * 2];
          a[0] = gelu_tanh(a[0]);
          a[1] = gelu_tanh(a[1]);
          s0 += a[0] + a[1]; q0 = fmaf(a[0], a[0], q0); q0 = fmaf(a[1], a[1], q0);
        }
        s0 += __shfl_xor_sync(0xffffffffu, s0, 1); q0 += __shfl_xor_sync(0xffffffffu, q0, 1);
        s0 += __shfl_xor_sync(0xffffffffu, s0, 2); q0 += __shfl_xor_sync(0xffffffffu, q0, 2);
        sum[r] = s0; sq[r] = q0;
      }
      TS(2, 4);
      float rstd, off;
      {
        const int qd = l & 3;
        const float sm = qd == 0 ? sum[0] : qd == 1 ? sum[1] : qd == 2 ? sum[2] : sum[3];
        const float sv = qd == 0 ? sq[0] : qd == 1 ? sq[1] : qd == 2 ? sq[2] : sq[3];
        const int row = (qd >> 1) * 64 + w * 16 + (qd & 1) * 8 + (l >> 2);
        const float mu = sm * (1.f / 96), m2 = fmaxf(sv - sm * mu, 0.f);
        st_vol2(&g_zstat[(rb * 8 + c8) * 128 + row], __float_as_uint(mu), (__float_as_uint(m2) & ~255u) | (epoch & 255u));
        uint2 v[7];
        unsigned n = 0;
        while (true) {
          bool ok = true;
          #pragma unroll
          for (int j = 0; j < 7; j++) v[j] = ld_vol2(&g_zstat[(rb * 8 + ((c8 + 1 + j) & 7)) * 128 + row]);
          #pragma unroll
          for (int j = 0; j < 7; j++) ok = ok && ((v[j].y ^ epoch) & 255u) == 0;
          if (ok || ++n > POLL_LIMIT) break;
          __nanosleep(POLL_NS);
        }
        float mean = mu, var = m2;
        #pragma unroll
        for (int j = 0; j < 7; j++) { mean += __uint_as_float(v[j].x); var += __uint_as_float(v[j].y & ~255u); }
        mean *= 0.125f;
        float d = (mu - mean) * (mu - mean);
        #pragma unroll
        for (int j = 0; j < 7; j++) d = fmaf(__uint_as_float(v[j].x) - mean, __uint_as_float(v[j].x) - mean, d);
        rstd = rsqrtf(fmaf(96.f, d, var) * (1.f / FH) + LN_EPS); off = -mean * rstd;
        __syncwarp();
      }
      TS(2, 5);
      #pragma unroll
      for (int mi = 0; mi < 2; mi++) {
        const float r0 = __shfl_sync(0xffffffffu, rstd, (l & 28) + mi * 2), o0 = __shfl_sync(0xffffffffu, off, (l & 28) + mi * 2);
        const float r1 = __shfl_sync(0xffffffffu, rstd, (l & 28) + mi * 2 + 1), o1 = __shfl_sync(0xffffffffu, off, (l & 28) + mi * 2 + 1);
        #pragma unroll
        for (int jj = 0; jj < 6; jj++) {
          const float* a = &acc[mi][8 * jj];
          stsm4(buf + (jj >> 1) * 8192 + mi * 4096 + rl * 64 + ((((jj & 1) * 2 + (l >> 4)) ^ ((l >> 1) & 3)) << 4),
                pack_bf16(fmaf(a[0], r0, o0), fmaf(a[1], r0, o0)), pack_bf16(fmaf(a[2], r1, o1), fmaf(a[3], r1, o1)),
                pack_bf16(fmaf(a[4], r0, o0), fmaf(a[5], r0, o0)), pack_bf16(fmaf(a[6], r1, o1), fmaf(a[7], r1, o1)));
        }
      }
      fence_async_smem();
      bar_arrive<BAR_PUB1>(160);
      TS(2, 6);
      if (grp == 0) {
        float acc[2][96];
        zero(acc);
        bar_sync<BAR_ORD2>(256);
        mainloop<192, 1, false, BAR_ORD1>(acc, sbase, STAGE_A, 20, 32, KB_A, 0);
        const float* bias = reinterpret_cast<const float*>(smem + BIAS_OFF) + w * 16 + (l >> 2);
        bar_sync<BAR_Z1>(256);
        drain(acc, sbase, 51, KB_A);
        TS(2, 7);
        {
          const float bb[4] = {bias[0], bias[8], bias[64], bias[72]};
          uint32_t z[2][4][4];
          #pragma unroll
          for (int i = 0; i < 4; i++) ldsm4(st_base + (st_x ^ (i << 5)), z[0][i][0], z[0][i][1], z[0][i][2], z[0][i][3]);
          #pragma unroll
          for (int bx = 0; bx < 6; bx++) {
            if (bx < 5) {
              #pragma unroll
              for (int i = 0; i < 4; i++)
                ldsm4(st_base + (bx + 1) * 8192 + (st_x ^ (i << 5)), z[(bx + 1) & 1][i][0], z[(bx + 1) & 1][i][1], z[(bx + 1) & 1][i][2], z[(bx + 1) & 1][i][3]);
            }
            const float b0 = bb[(bx / 3) * 2], b1 = bb[(bx / 3) * 2 + 1];
            #pragma unroll
            for (int i = 0; i < 4; i++) {
              const float* a = &acc[bx / 3][8 * ((bx % 3) * 4 + i)];
              const uint32_t* zz = z[bx & 1][i];
              stsm4(st_base + bx * 8192 + (st_x ^ (i << 5)),
                    hmul2_bf16(zz[0], pack_bf16(a[0] + b0, a[1] + b0)), hmul2_bf16(zz[1], pack_bf16(a[2] + b1, a[3] + b1)),
                    hmul2_bf16(zz[2], pack_bf16(a[4] + b0, a[5] + b0)), hmul2_bf16(zz[3], pack_bf16(a[6] + b1, a[7] + b1)));
            }
            fence_async_smem();
            __syncwarp();
            if (l == 0) {
              tma_store_2d(&maps.m[M_HS], buf + bx * 8192 + w * 2048, ct * 192 + (bx % 3) * 64, rb * 128 + (bx / 3) * 64 + w * 16);
              bulk_commit();
            }
          }
        }
        TS(2, 8);
        if (l == 0) bulk_wait_all();
        __syncwarp();
        bar_arrive<BAR_PUB1>(160);
        TS(2, 9);
        return;
      }
    } else {
      if (grp == 0) {
        reinterpret_cast<float*>(smem + BIAS_OFF)[t] = __bfloat162float(bsp[rb * 128 + t]);
        float acc[2][96];
        zero(acc);
        bar_sync<BAR_ORD1>(256);
        mainloop<192, 1, false, BAR_ORD2>(acc, sbase, STAGE_A, 10, 10, KB_A, 0);
        drain(acc, sbase, 19, KB_A);
        TS(3, 2);
        bar_sync<BAR_BUF>(160);
        #pragma unroll
        for (int mi = 0; mi < 2; mi++)
          #pragma unroll
          for (int jj = 0; jj < 12; jj++) {
            const float* a = &acc[mi][8 * jj];
            stsm4(st_base + mi * 24576 + (jj >> 2) * 8192 + (st_x ^ ((jj & 3) << 5)),
                  pack_bf16(a[0], a[1]), pack_bf16(a[2], a[3]), pack_bf16(a[4], a[5]), pack_bf16(a[6], a[7]));
          }
        __syncwarp();
        TS(3, 3);
        const uint32_t rbase = buf + (l >> 4) * 24576 + gr * 128;
        #pragma unroll 1
        for (int c2 = 0; c2 < 12; c2++) {
          const uint32_t ab = rbase + (c2 >> 2) * 8192;
          uint4 v[2];
          #pragma unroll
          for (int i = 0; i < 2; i++) v[i] = lds128(ab + (((((c2 & 3) * 2 + i) ^ l) & 7) << 4));
          #pragma unroll
          for (int i = 0; i < 2; i++)
            sts128(ab + (((((c2 & 3) * 2 + i) ^ l) & 7) << 4),
                   pack_bf16(gelu_tanh(bf_lo(v[i].x)), gelu_tanh(bf_hi(v[i].x))), pack_bf16(gelu_tanh(bf_lo(v[i].y)), gelu_tanh(bf_hi(v[i].y))),
                   pack_bf16(gelu_tanh(bf_lo(v[i].z)), gelu_tanh(bf_hi(v[i].z))), pack_bf16(gelu_tanh(bf_lo(v[i].w)), gelu_tanh(bf_hi(v[i].w))));
        }
        TS(3, 4);
        bar_arrive<BAR_Z1>(256);
      }
    }
    float acc[2][80];
    if (grp == 1) {
      zero(acc);
      if (wg == 2) {
        bar_sync<BAR_ORD1>(256);
        mainloop<160, 0, false, BAR_ORD2>(acc, sbase, STAGE_B, 10, 10, KB_B, 0);
      } else {
        bar_sync<BAR_ORD2>(256);
        mainloop<160, 0, false, BAR_ORD1>(acc, sbase, STAGE_B, 20, 10, KB_B, 0);
      }
      drain(acc, sbase, wg == 2 ? 19 : 29, KB_B);
      TS(wg + 1, wg == 1 ? 7 : 2);
      if (wg == 1) bar_sync<BAR_BUF>(256);
      const uint32_t sg = wg == 1 ? 0x80008000u : 0u;
      const uint32_t tb = buf + 24576 + ((l >> 4) * 8 + (l & 7)) * 128 + (((w * 2 + ((l >> 3) & 1)) ^ (l & 7)) << 4);
      #pragma unroll
      for (int mi = 0; mi < 2; mi++)
        #pragma unroll
        for (int jj = 0; jj < 10; jj++) {
          const float* a = &acc[mi][8 * jj];
          stsm4_t(tb + mi * 20480 + jj * 2048, pack_bf16(a[0], a[1]) ^ sg, pack_bf16(a[2], a[3]) ^ sg, pack_bf16(a[4], a[5]) ^ sg, pack_bf16(a[6], a[7]) ^ sg);
        }
      fence_async_smem();
      if (wg == 1) bar_sync<BAR_WG1>(128); else bar_sync<BAR_WG2>(128);
      TS(wg + 1, wg == 1 ? 8 : 6);
      if (l == 0) {
        #pragma unroll 1
        for (int i = 0; i < 2; i++) {
          tma_store_2d(&maps.m[M_ABS], buf + 24576 + i * 20480 + w * 5120, rb * 128 + i * 64, (2 - wg) * DM + ct * 160 + w * 40);
          bulk_commit();
        }
        bulk_wait_all();
      }
      __syncwarp();
      TS(wg + 1, wg == 1 ? 9 : 10);
      if (wg == 1) { bar_arrive<BAR_PUB1>(160); return; }
      bar_arrive<BAR_PUB2>(160);
      bar_arrive<BAR_BUF>(256);
    }
    zero(acc);
    bar_sync<BAR_ORD1>(256);
    mainloop<160, 0, false, 0>(acc, sbase, stage_bytes, grp == 0 ? 52 : 30, grp == 0 ? NX : 64 - NX, total, grp);
    if (grp == 0) mainloop<160, 2, true, 0>(acc, sbase, STAGE_A, 52 + NX, 12, KB_A, 0);
    drain(acc, sbase, total - 1, total);
    TS(3, 12);
    uint4* dst = g_part + (size_t)blockIdx.x * 27 * 128 + t;
    const uint4* src = g_part + (size_t)(blockIdx.x ^ 2) * 27 * 128 + t;
    #pragma unroll
    for (int i = 0; i < 27; i++)
      st_vol4(dst + i * 128, __float_as_uint(acc[1][3 * i]), __float_as_uint(acc[1][3 * i + 1]),
              __float_as_uint(i < 26 ? acc[1][3 * i + 2] : 0.f), epoch);
    TS(3, 13);
    const uint32_t slab = ring + (total & (STAGES - 1)) * stage_bytes + w * (16 * 320);
    const uint32_t addr = slab + (((l >> 3) & 1) * 8 + (l & 7)) * 320 + (l >> 4) * 16;
    mbar_wait(full0 + 8 * (total & (STAGES - 1)), (total / STAGES) & 1);
    #pragma unroll
    for (int jj = 0; jj < 10; jj++) {
      uint32_t z0, z1, z2, z3;
      ldsm4(addr + jj * 32, z0, z1, z2, z3);
      float* a = &acc[0][8 * jj];
      a[0] += bf_lo(z0); a[1] += bf_hi(z0); a[2] += bf_lo(z1); a[3] += bf_hi(z1);
      a[4] += bf_lo(z2); a[5] += bf_hi(z2); a[6] += bf_lo(z3); a[7] += bf_hi(z3);
    }
    {
      unsigned n = 0;
      while (ld_vol4(src + 26 * 128).w != epoch && ++n < POLL_LIMIT) __nanosleep(POLL_NS);
      uint4 v[27];
      while (true) {
        bool ok = true;
        #pragma unroll
        for (int i = 0; i < 27; i++) v[i] = ld_vol4(src + i * 128);
        #pragma unroll
        for (int i = 0; i < 27; i++) ok = ok && (v[i].w == epoch);
        if (ok || ++n > POLL_LIMIT) break;
      }
      #pragma unroll
      for (int i = 0; i < 27; i++) {
        acc[0][3 * i] += __uint_as_float(v[i].x);
        acc[0][3 * i + 1] += __uint_as_float(v[i].y);
        if (i < 26) acc[0][3 * i + 2] += __uint_as_float(v[i].z);
      }
    }
    TS(3, 14);
    #pragma unroll
    for (int jj = 0; jj < 10; jj++) {
      const float* a = &acc[0][8 * jj];
      stsm4(addr + jj * 32, pack_bf16(a[0], a[1]), pack_bf16(a[2], a[3]), pack_bf16(a[4], a[5]), pack_bf16(a[6], a[7]));
    }
    fence_async_smem();
    __syncwarp();
    if (l == 0) {
      tma_store_2d(&maps.m[M_OUT], slab, ct * 160, rb * 128 + grp * 64 + w * 16);
      bulk_commit();
      bulk_wait_read();
      if (w == 0) atomicAdd(&g_done, 1u);
    }
    TS(3, 15);
  }
}

typedef CUresult (*EncodeFn)(CUtensorMap*, CUtensorMapDataType, cuuint32_t, void*, const cuuint64_t*, const cuuint64_t*,
                             const cuuint32_t*, const cuuint32_t*, CUtensorMapInterleave, CUtensorMapSwizzle,
                             CUtensorMapL2promotion, CUtensorMapFloatOOBfill);

void make2d(EncodeFn enc, CUtensorMap* m, const void* p, uint64_t cols, uint64_t rows, uint32_t bc, uint32_t br, bool swz = true) {
  cuuint64_t gd[2] = {cols, rows}, gs[1] = {cols * 2};
  cuuint32_t bd[2] = {bc, br}, es[2] = {1, 1};
  enc(m, CU_TENSOR_MAP_DATA_TYPE_BFLOAT16, 2, const_cast<void*>(p), gd, gs, bd, es, CU_TENSOR_MAP_INTERLEAVE_NONE,
      swz ? CU_TENSOR_MAP_SWIZZLE_128B : CU_TENSOR_MAP_SWIZZLE_NONE, CU_TENSOR_MAP_L2_PROMOTION_L2_256B, CU_TENSOR_MAP_FLOAT_OOB_FILL_NONE);
}
void make3d(EncodeFn enc, CUtensorMap* m, const void* p, uint64_t cols, uint64_t rows, uint32_t cw, uint32_t nc, uint32_t br = 64) {
  cuuint64_t gd[3] = {cw, rows, cols / cw}, gs[2] = {cols * 2, cw * 2};
  cuuint32_t bd[3] = {cw, br, nc}, es[3] = {1, 1, 1};
  enc(m, CU_TENSOR_MAP_DATA_TYPE_BFLOAT16, 3, const_cast<void*>(p), gd, gs, bd, es, CU_TENSOR_MAP_INTERLEAVE_NONE,
      cw == 64 ? CU_TENSOR_MAP_SWIZZLE_128B : CU_TENSOR_MAP_SWIZZLE_64B, CU_TENSOR_MAP_L2_PROMOTION_L2_256B, CU_TENSOR_MAP_FLOAT_OOB_FILL_NONE);
}

}

extern "C" void kernel_launch(void* const* d_in, const int* in_sizes, int n_in, void* d_out, int out_size) {
  const bf16* x = (const bf16*)d_in[0];
  const bf16* wsre = (const bf16*)d_in[1];
  const bf16* wsim = (const bf16*)d_in[2];
  const bf16* wdre = (const bf16*)d_in[3];
  const bf16* wdim = (const bf16*)d_in[4];
  const bf16* win = (const bf16*)d_in[6];
  const bf16* wsp = (const bf16*)d_in[7];
  const bf16* bsp = (const bf16*)d_in[8];
  const bf16* wout = (const bf16*)d_in[9];

  void* fn = nullptr;
  cudaDriverEntryPointQueryResult qr;
  cudaGetDriverEntryPoint("cuTensorMapEncodeTiled", &fn, cudaEnableDefault, &qr);
  EncodeFn enc = (EncodeFn)fn;
  void *abT, *z2, *h, *xn;
  cudaGetSymbolAddress(&xn, g_xn);
  cudaGetSymbolAddress(&abT, g_abT);
  cudaGetSymbolAddress(&z2, g_z2);
  cudaGetSymbolAddress(&h, g_h);

  Maps maps;
  make2d(enc, &maps.m[M_XN], xn, DM, SEQ, 64, 64);
  make3d(enc, &maps.m[M_Z232], z2, FH, SEQ, 32, 3, 128);
  make2d(enc, &maps.m[M_XR], x, DM, SEQ, 160, 64, false);
  make3d(enc, &maps.m[M_WIN32], win, FF, DM, 32, 3);
  make2d(enc, &maps.m[M_WSRE], wsre, SEQ, SEQ, 64, 64);
  make2d(enc, &maps.m[M_WSIM], wsim, SEQ, SEQ, 64, 64);
  make2d(enc, &maps.m[M_WSP], wsp, SEQ, SEQ, 64, 64);
  make2d(enc, &maps.m[M_H], h, FH, SEQ, 64, 64);
  make3d(enc, &maps.m[M_WIN3], win, FF, DM, 64, 3);
  make3d(enc, &maps.m[M_Z23], z2, FH, SEQ, 64, 3);
  make2d(enc, &maps.m[M_WDRE], wdre, DM, DM, 64, 160);
  make2d(enc, &maps.m[M_WDIM], wdim, DM, DM, 64, 160);
  make2d(enc, &maps.m[M_AB], abT, SEQ, 2 * DM, 64, 160);
  make3d(enc, &maps.m[M_WOUT], wout, DM, FH, 32, 5);
  make2d(enc, &maps.m[M_HS], h, FH, SEQ, 64, 16);
  make2d(enc, &maps.m[M_ABS], abT, SEQ, 2 * DM, 64, 40);
  make2d(enc, &maps.m[M_OUT], d_out, DM, SEQ, 160, 16, false);

  cudaFuncSetAttribute(fused_kernel, cudaFuncAttributeMaxDynamicSharedMemorySize, SMEM_BYTES);
  fused_kernel<<<128, 384, SMEM_BYTES>>>(maps, x, bsp);
}
```

```cpp
#include <cuda_runtime.h>
#include <cuda_bf16.h>
#include <cuda.h>
#include <stdint.h>

namespace {

typedef __nv_bfloat16 bf16;

constexpr int SEQ = 2048, DM = 640, FF = 1536, FH = 768;
#define NXV 11
constexpr int NX = NXV;
constexpr int STAGES = 4;
constexpr int A_BYTES = 16384;
constexpr int BIAS_OFF = 0;
constexpr int BAR_OFF = 512;
constexpr int READY_OFF = 640;
constexpr int ROWSTAT_OFF = 1024;
constexpr int COLSUM_OFF = 2048;
constexpr int RED_OFF = 2560;
constexpr int RING_OFF = 3072;
constexpr int STAGE_A = 40960, STAGE_B = 36864;
constexpr int SMEM_BYTES = RING_OFF + 4 * STAGE_A + 49152;
constexpr int KB_A = 20 + 32 + NX + 12;
constexpr int KB_B = 30 + 64 - NX;
constexpr float LN_EPS = 1e-5f;
constexpr unsigned POLL_LIMIT = 100000;
#define POLL_NS 100
#define PF_D 0
#define ROT 0
#define Z1_NS 0
#define INFL 2
#define LIM_G 1000
#define MAPV 0
#define PROMO CU_TENSOR_MAP_L2_PROMOTION_L2_128B
#define PF_NS 150

constexpr int BAR_ORD1 = 1, BAR_ORD2 = 2, BAR_WG1 = 3, BAR_WG2 = 4, BAR_LN = 5, BAR_BUF = 6, BAR_Z1 = 7, BAR_PUB1 = 8, BAR_PUB2 = 9, BAR_STATS = 10;

enum { M_X, M_XN, M_XR, M_WIN32, M_Z232, M_WSRE, M_WSIM, M_WSP, M_H, M_WIN3, M_Z23, M_WDRE, M_WDIM, M_AB, M_WOUT, M_OUT, M_HS, M_ABS, M_COUNT };
struct Maps { CUtensorMap m[M_COUNT]; };

__device__ __align__(1024) bf16 g_abT[2 * DM * SEQ];
__device__ __align__(1024) bf16 g_z2[SEQ * FH];
__device__ __align__(1024) bf16 g_h[SEQ * FH];
__device__ __align__(1024) bf16 g_xn[SEQ * DM];
__device__ __align__(16) uint2 g_xstat[SEQ];
__device__ __align__(16) uint2 g_csum[5 * FH];
__device__ __align__(16) uint2 g_zstat[128 * 128];
__device__ __align__(16) uint4 g_part[128 * 27 * 128];
__device__ unsigned g_flags[5 * 128];
constexpr int F_A = 0, F_B = 128, F_H = 256, F_Z = 384, F_XN = 512;
__device__ unsigned g_done;
#define TS(role, ev)
#define TC(i)

extern __shared__ __align__(1024) uint8_t smem[];

__device__ __forceinline__ uint32_t smem_u32(const void* p) { return (uint32_t)__cvta_generic_to_shared(p); }
__device__ __forceinline__ void mbar_init(uint32_t bar, uint32_t cnt) { asm volatile("mbarrier.init.shared::cta.b64 [%0], %1;" :: "r"(bar), "r"(cnt)); }
__device__ __forceinline__ void mbar_expect_tx(uint32_t bar, uint32_t bytes) { asm volatile("mbarrier.arrive.expect_tx.shared::cta.b64 _, [%0], %1;" :: "r"(bar), "r"(bytes) : "memory"); }
__device__ __forceinline__ void mbar_arrive(uint32_t bar) { asm volatile("mbarrier.arrive.shared::cta.b64 _, [%0];" :: "r"(bar) : "memory"); }
__device__ __forceinline__ void mbar_arrive_cluster(uint32_t bar, uint32_t cta) {
  asm volatile("{\n.reg .b32 ra;\nmapa.shared::cluster.u32 ra, %0, %1;\nmbarrier.arrive.shared::cluster.b64 _, [ra];\n}" :: "r"(bar), "r"(cta) : "memory");
}
__device__ __forceinline__ void mbar_wait(uint32_t bar, uint32_t parity) {
  asm volatile("{\n.reg .pred p;\n.reg .u32 n;\nmov.u32 n, 0;\n"
               "LW: mbarrier.try_wait.parity.shared::cta.b64 p, [%0], %1, 2000;\n@p bra LD;\n"
               "add.u32 n, n, 1;\nsetp.lt.u32 p, n, 20000;\n@p bra LW;\nLD:\n}" :: "r"(bar), "r"(parity) : "memory");
}
__device__ __forceinline__ void tma_load_2d(uint32_t dst, const CUtensorMap* map, uint32_t bar, int c0, int c1) {
  asm volatile("cp.async.bulk.tensor.2d.shared::cluster.global.mbarrier::complete_tx::bytes [%0], [%1, {%3, %4}], [%2];"
    :: "r"(dst), "l"((uint64_t)map), "r"(bar), "r"(c0), "r"(c1) : "memory");
}
__device__ __forceinline__ void tma_load_3d(uint32_t dst, const CUtensorMap* map, uint32_t bar, int c0, int c1, int c2) {
  asm volatile("cp.async.bulk.tensor.3d.shared::cluster.global.mbarrier::complete_tx::bytes [%0], [%1, {%3, %4, %5}], [%2];"
    :: "r"(dst), "l"((uint64_t)map), "r"(bar), "r"(c0), "r"(c1), "r"(c2) : "memory");
}
__device__ __forceinline__ void tma_load_2d_mc(uint32_t dst, const CUtensorMap* map, uint32_t bar, int c0, int c1, uint16_t mask) {
  asm volatile("cp.async.bulk.tensor.2d.shared::cluster.global.mbarrier::complete_tx::bytes.multicast::cluster [%0], [%1, {%3, %4}], [%2], %5;"
    :: "r"(dst), "l"((uint64_t)map), "r"(bar), "r"(c0), "r"(c1), "h"(mask) : "memory");
}
__device__ __forceinline__ void tma_store_2d(const CUtensorMap* map, uint32_t src, int c0, int c1) {
  asm volatile("cp.async.bulk.tensor.2d.global.shared::cta.bulk_group [%0, {%2, %3}], [%1];"
    :: "l"((uint64_t)map), "r"(src), "r"(c0), "r"(c1) : "memory");
}
__device__ __forceinline__ void tma_store_3d(const CUtensorMap* map, uint32_t src, int c0, int c1, int c2) {
  asm volatile("cp.async.bulk.tensor.3d.global.shared::cta.bulk_group [%0, {%2, %3, %4}], [%1];"
    :: "l"((uint64_t)map), "r"(src), "r"(c0), "r"(c1), "r"(c2) : "memory");
}
__device__ __forceinline__ void bulk_wait_all() { asm volatile("cp.async.bulk.wait_group 0;" ::: "memory"); }
__device__ __forceinline__ void bulk_commit() { asm volatile("cp.async.bulk.commit_group;" ::: "memory"); }
__device__ __forceinline__ void bulk_wait_read() { asm volatile("cp.async.bulk.wait_group.read 0;" ::: "memory"); }
__device__ __forceinline__ void fence_async_smem() { asm volatile("fence.proxy.async.shared::cta;" ::: "memory"); }
__device__ __forceinline__ void fence_async_global() { asm volatile("fence.proxy.async.global;" ::: "memory"); }
__device__ __forceinline__ void wgmma_fence() { asm volatile("wgmma.fence.sync.aligned;" ::: "memory"); }
__device__ __forceinline__ void wgmma_commit() { asm volatile("wgmma.commit_group.sync.aligned;" ::: "memory"); }
template<int N> __device__ __forceinline__ void wgmma_wait() { asm volatile("wgmma.wait_group.sync.aligned %0;" :: "n"(N) : "memory"); }
template<int ID> __device__ __forceinline__ void bar_sync(int n) { asm volatile("bar.sync %0, %1;" :: "n"(ID), "r"(n) : "memory"); }
template<int ID> __device__ __forceinline__ void bar_arrive(int n) { asm volatile("bar.arrive %0, %1;" :: "n"(ID), "r"(n) : "memory"); }
__device__ __forceinline__ void cluster_wait() { asm volatile("barrier.cluster.wait.aligned;" ::: "memory"); }
__device__ __forceinline__ uint64_t desc64(uint32_t lo, uint32_t hi) { return (uint64_t)lo | ((uint64_t)hi << 32); }
__device__ __forceinline__ uint4 ld_vol4(const uint4* p) {
  uint4 v; asm volatile("ld.relaxed.gpu.global.v4.u32 {%0,%1,%2,%3}, [%4];" : "=r"(v.x), "=r"(v.y), "=r"(v.z), "=r"(v.w) : "l"(p) : "memory"); return v;
}
__device__ __forceinline__ uint2 ld_vol2(const uint2* p) {
  uint2 v; asm volatile("ld.relaxed.gpu.global.v2.u32 {%0,%1}, [%2];" : "=r"(v.x), "=r"(v.y) : "l"(p) : "memory"); return v;
}
__device__ __forceinline__ void st_vol4(uint4* p, uint32_t a, uint32_t b, uint32_t c, uint32_t d) {
  asm volatile("st.relaxed.gpu.global.v4.u32 [%0], {%1,%2,%3,%4};" :: "l"(p), "r"(a), "r"(b), "r"(c), "r"(d) : "memory");
}
__device__ __forceinline__ void st_vol2(uint2* p, uint32_t a, uint32_t b) {
  asm volatile("st.relaxed.gpu.global.v2.u32 [%0], {%1,%2};" :: "l"(p), "r"(a), "r"(b) : "memory");
}
__device__ __forceinline__ void stg128(void* p, uint4 v) {
  asm volatile("st.global.v4.u32 [%0], {%1,%2,%3,%4};" :: "l"(p), "r"(v.x), "r"(v.y), "r"(v.z), "r"(v.w));
}
__device__ __forceinline__ unsigned ld_relaxed(const unsigned* p) {
  unsigned v; asm volatile("ld.relaxed.gpu.global.u32 %0, [%1];" : "=r"(v) : "l"(p) : "memory"); return v;
}
__device__ __forceinline__ uint32_t pack_bf16(float lo, float hi) {
  uint32_t r; asm("cvt.rn.bf16x2.f32 %0, %1, %2;" : "=r"(r) : "f"(hi), "f"(lo)); return r;
}
__device__ __forceinline__ float bf_lo(uint32_t v) { return __uint_as_float(v << 16); }
__device__ __forceinline__ float bf_hi(uint32_t v) { return __uint_as_float(v & 0xFFFF0000u); }
__device__ __forceinline__ void stsm4(uint32_t addr, uint32_t a, uint32_t b, uint32_t c, uint32_t d) {
  asm volatile("stmatrix.sync.aligned.m8n8.x4.shared.b16 [%0], {%1,%2,%3,%4};" :: "r"(addr), "r"(a), "r"(b), "r"(c), "r"(d));
}
__device__ __forceinline__ void stsm4_t(uint32_t addr, uint32_t a, uint32_t b, uint32_t c, uint32_t d) {
  asm volatile("stmatrix.sync.aligned.m8n8.x4.trans.shared.b16 [%0], {%1,%2,%3,%4};" :: "r"(addr), "r"(a), "r"(b), "r"(c), "r"(d));
}
__device__ __forceinline__ void ldsm4(uint32_t addr, uint32_t& a, uint32_t& b, uint32_t& c, uint32_t& d) {
  asm volatile("ldmatrix.sync.aligned.m8n8.x4.shared.b16 {%0,%1,%2,%3}, [%4];" : "=r"(a), "=r"(b), "=r"(c), "=r"(d) : "r"(addr));
}
__device__ __forceinline__ uint4 lds128(uint32_t a) {
  uint4 v; asm volatile("ld.shared.v4.u32 {%0,%1,%2,%3}, [%4];" : "=r"(v.x), "=r"(v.y), "=r"(v.z), "=r"(v.w) : "r"(a)); return v;
}
__device__ __forceinline__ void sts128(uint32_t a, uint32_t x, uint32_t y, uint32_t z, uint32_t w) {
  asm volatile("st.shared.v4.u32 [%0], {%1,%2,%3,%4};" :: "r"(a), "r"(x), "r"(y), "r"(z), "r"(w));
}
__device__ __forceinline__ uint32_t hmul2_bf16(uint32_t a, uint32_t b) {
  uint32_t r; asm("mul.rn.bf16x2 %0, %1, %2;" : "=r"(r) : "r"(a), "r"(b)); return r;
}
__device__ __forceinline__ float gelu_tanh(float v) {
  float u = v * fmaf(0.0356774081f, v * v, 0.7978845608f);
  float t; asm("tanh.approx.f32 %0, %1;" : "=f"(t) : "f"(u));
  float hv = 0.5f * v;
  return fmaf(hv, t, hv);
}

template<int TB>
__device__ __forceinline__ void wgmma_n192(float (&d)[96], uint64_t da, uint64_t db, int scale_d) {
  asm volatile("{\n.reg .pred p;\nsetp.ne.b32 p, %98, 0;\n"
   "wgmma.mma_async.sync.aligned.m64n192k16.f32.bf16.bf16 {%0,%1,%2,%3,%4,%5,%6,%7,%8,%9,%10,%11,%12,%13,%14,%15,%16,%17,%18,%19,%20,%21,%22,%23,%24,%25,%26,%27,%28,%29,%30,%31,%32,%33,%34,%35,%36,%37,%38,%39,%40,%41,%42,%43,%44,%45,%46,%47,%48,%49,%50,%51,%52,%53,%54,%55,%56,%57,%58,%59,%60,%61,%62,%63,%64,%65,%66,%67,%68,%69,%70,%71,%72,%73,%74,%75,%76,%77,%78,%79,%80,%81,%82,%83,%84,%85,%86,%87,%88,%89,%90,%91,%92,%93,%94,%95}, %96, %97, p, 1, 1, 0, %99;\n}"
   : "+f"(d[0]),"+f"(d[1]),"+f"(d[2]),"+f"(d[3]),"+f"(d[4]),"+f"(d[5]),"+f"(d[6]),"+f"(d[7]),"+f"(d[8]),"+f"(d[9]),"+f"(d[10]),"+f"(d[11]),"+f"(d[12]),"+f"(d[13]),"+f"(d[14]),"+f"(d[15]),"+f"(d[16]),"+f"(d[17]),"+f"(d[18]),"+f"(d[19]),"+f"(d[20]),"+f"(d[21]),"+f"(d[22]),"+f"(d[23]),"+f"(d[24]),"+f"(d[25]),"+f"(d[26]),"+f"(d[27]),"+f"(d[28]),"+f"(d[29]),"+f"(d[30]),"+f"(d[31]),"+f"(d[32]),"+f"(d[33]),"+f"(d[34]),"+f"(d[35]),"+f"(d[36]),"+f"(d[37]),"+f"(d[38]),"+f"(d[39]),"+f"(d[40]),"+f"(d[41]),"+f"(d[42]),"+f"(d[43]),"+f"(d[44]),"+f"(d[45]),"+f"(d[46]),"+f"(d[47]),"+f"(d[48]),"+f"(d[49]),"+f"(d[50]),"+f"(d[51]),"+f"(d[52]),"+f"(d[53]),"+f"(d[54]),"+f"(d[55]),"+f"(d[56]),"+f"(d[57]),"+f"(d[58]),"+f"(d[59]),"+f"(d[60]),"+f"(d[61]),"+f"(d[62]),"+f"(d[63]),"+f"(d[64]),"+f"(d[65]),"+f"(d[66]),"+f"(d[67]),"+f"(d[68]),"+f"(d[69]),"+f"(d[70]),"+f"(d[71]),"+f"(d[72]),"+f"(d[73]),"+f"(d[74]),"+f"(d[75]),"+f"(d[76]),"+f"(d[77]),"+f"(d[78]),"+f"(d[79]),"+f"(d[80]),"+f"(d[81]),"+f"(d[82]),"+f"(d[83]),"+f"(d[84]),"+f"(d[85]),"+f"(d[86]),"+f"(d[87]),"+f"(d[88]),"+f"(d[89]),"+f"(d[90]),"+f"(d[91]),"+f"(d[92]),"+f"(d[93]),"+f"(d[94]),"+f"(d[95])
   : "l"(da), "l"(db), "r"(scale_d), "n"(TB));
}
template<int TB>
__device__ __forceinline__ void wgmma_n160(float (&d)[80], uint64_t da, uint64_t db, int scale_d) {
  asm volatile("{\n.reg .pred p;\nsetp.ne.b32 p, %82, 0;\n"
   "wgmma.mma_async.sync.aligned.m64n160k16.f32.bf16.bf16 {%0,%1,%2,%3,%4,%5,%6,%7,%8,%9,%10,%11,%12,%13,%14,%15,%16,%17,%18,%19,%20,%21,%22,%23,%24,%25,%26,%27,%28,%29,%30,%31,%32,%33,%34,%35,%36,%37,%38,%39,%40,%41,%42,%43,%44,%45,%46,%47,%48,%49,%50,%51,%52,%53,%54,%55,%56,%57,%58,%59,%60,%61,%62,%63,%64,%65,%66,%67,%68,%69,%70,%71,%72,%73,%74,%75,%76,%77,%78,%79}, %80, %81, p, 1, 1, 0, %83;\n}"
   : "+f"(d[0]),"+f"(d[1]),"+f"(d[2]),"+f"(d[3]),"+f"(d[4]),"+f"(d[5]),"+f"(d[6]),"+f"(d[7]),"+f"(d[8]),"+f"(d[9]),"+f"(d[10]),"+f"(d[11]),"+f"(d[12]),"+f"(d[13]),"+f"(d[14]),"+f"(d[15]),"+f"(d[16]),"+f"(d[17]),"+f"(d[18]),"+f"(d[19]),"+f"(d[20]),"+f"(d[21]),"+f"(d[22]),"+f"(d[23]),"+f"(d[24]),"+f"(d[25]),"+f"(d[26]),"+f"(d[27]),"+f"(d[28]),"+f"(d[29]),"+f"(d[30]),"+f"(d[31]),"+f"(d[32]),"+f"(d[33]),"+f"(d[34]),"+f"(d[35]),"+f"(d[36]),"+f"(d[37]),"+f"(d[38]),"+f"(d[39]),"+f"(d[40]),"+f"(d[41]),"+f"(d[42]),"+f"(d[43]),"+f"(d[44]),"+f"(d[45]),"+f"(d[46]),"+f"(d[47]),"+f"(d[48]),"+f"(d[49]),"+f"(d[50]),"+f"(d[51]),"+f"(d[52]),"+f"(d[53]),"+f"(d[54]),"+f"(d[55]),"+f"(d[56]),"+f"(d[57]),"+f"(d[58]),"+f"(d[59]),"+f"(d[60]),"+f"(d[61]),"+f"(d[62]),"+f"(d[63]),"+f"(d[64]),"+f"(d[65]),"+f"(d[66]),"+f"(d[67]),"+f"(d[68]),"+f"(d[69]),"+f"(d[70]),"+f"(d[71]),"+f"(d[72]),"+f"(d[73]),"+f"(d[74]),"+f"(d[75]),"+f"(d[76]),"+f"(d[77]),"+f"(d[78]),"+f"(d[79])
   : "l"(da), "l"(db), "r"(scale_d), "n"(TB));
}
template<int TB>
__device__ __forceinline__ void wgmma_n96(float (&d)[48], uint64_t da, uint64_t db, int scale_d) {
  asm volatile("{\n.reg .pred p;\nsetp.ne.b32 p, %50, 0;\n"
   "wgmma.mma_async.sync.aligned.m64n96k16.f32.bf16.bf16 {%0,%1,%2,%3,%4,%5,%6,%7,%8,%9,%10,%11,%12,%13,%14,%15,%16,%17,%18,%19,%20,%21,%22,%23,%24,%25,%26,%27,%28,%29,%30,%31,%32,%33,%34,%35,%36,%37,%38,%39,%40,%41,%42,%43,%44,%45,%46,%47}, %48, %49, p, 1, 1, 0, %51;\n}"
   : "+f"(d[0]),"+f"(d[1]),"+f"(d[2]),"+f"(d[3]),"+f"(d[4]),"+f"(d[5]),"+f"(d[6]),"+f"(d[7]),"+f"(d[8]),"+f"(d[9]),"+f"(d[10]),"+f"(d[11]),"+f"(d[12]),"+f"(d[13]),"+f"(d[14]),"+f"(d[15]),"+f"(d[16]),"+f"(d[17]),"+f"(d[18]),"+f"(d[19]),"+f"(d[20]),"+f"(d[21]),"+f"(d[22]),"+f"(d[23]),"+f"(d[24]),"+f"(d[25]),"+f"(d[26]),"+f"(d[27]),"+f"(d[28]),"+f"(d[29]),"+f"(d[30]),"+f"(d[31]),"+f"(d[32]),"+f"(d[33]),"+f"(d[34]),"+f"(d[35]),"+f"(d[36]),"+f"(d[37]),"+f"(d[38]),"+f"(d[39]),"+f"(d[40]),"+f"(d[41]),"+f"(d[42]),"+f"(d[43]),"+f"(d[44]),"+f"(d[45]),"+f"(d[46]),"+f"(d[47])
   : "l"(da), "l"(db), "r"(scale_d), "n"(TB));
}

template<int N, int TB>
__device__ __forceinline__ void wgmma_n(float (&d)[N / 2], uint64_t da, uint64_t db) {
  if constexpr (N == 192) wgmma_n192<TB>(d, da, db, 1);
  else if constexpr (N == 160) wgmma_n160<TB>(d, da, db, 1);
  else wgmma_n96<TB>(d, da, db, 1);
}

template<int R>
__device__ __forceinline__ void pin(float (&acc)[2][R]) {
  #pragma unroll
  for (int mi = 0; mi < 2; mi++)
    #pragma unroll
    for (int i = 0; i < R; i++) asm volatile("" : "+f"(acc[mi][i]) :: "memory");
}
template<int R>
__device__ __forceinline__ void zero(float (&acc)[2][R]) {
  #pragma unroll
  for (int i = 0; i < R; i++) { acc[0][i] = 0.f; acc[1][i] = 0.f; }
  pin(acc);
}

template<int N, int TB, bool CONT, int ORD_BAR>
__device__ __forceinline__ void mainloop(float (&acc)[2][N / 2], uint32_t sbase, uint32_t stage_bytes, int g0, int nk, int total, int mswap) {
  const uint32_t full0 = sbase + BAR_OFF, empty0 = full0 + 8 * STAGES, ring = sbase + RING_OFF;
  const int t = threadIdx.x & 127;
  const uint32_t da0 = (((ring + mswap * 8192) & 0x3FFFF) >> 4) | 0x10000u, da1 = (((ring + (mswap ^ 1) * 8192) & 0x3FFFF) >> 4) | 0x10000u;
  const uint32_t db0 = (((ring + A_BYTES) & 0x3FFFF) >> 4) | ((TB == 2 ? 256u : TB ? 512u : 1u) << 16);
  constexpr uint32_t HI_A = 0x40000040u, HI_B = TB == 2 ? 0x80000020u : 0x40000040u;
  #pragma unroll 1
  for (int g = g0; g < g0 + nk; g++) {
    const int s = g & (STAGES - 1);
    const uint32_t so = s * (stage_bytes >> 4);
    mbar_wait(full0 + 8 * s, (g / STAGES) & 1);
    wgmma_fence();
    #pragma unroll
    for (int k = 0; k < 4; k++) {
      const uint64_t db = desc64(db0 + so + (TB == 2 ? k * 64 : TB ? k * 128 : k * 2), HI_B);
      wgmma_n<N, TB != 0>(acc[0], desc64(da0 + so + k * 2, HI_A), db);
      wgmma_n<N, TB != 0>(acc[1], desc64(da1 + so + k * 2, HI_A), db);
    }
    wgmma_commit();
    if (ORD_BAR != 0 && g == g0 + nk - 1) bar_arrive<ORD_BAR>(256);
    wgmma_wait<1>();
    if (t < 2 && (CONT || g > g0) && g - 1 + STAGES <= total) mbar_arrive_cluster(empty0 + 8 * ((g - 1) & (STAGES - 1)), t);
  }
}
template<int R>
__device__ __forceinline__ void drain(float (&acc)[2][R], uint32_t sbase, int glast, int total) {
  wgmma_wait<0>();
  pin(acc);
  const int t = threadIdx.x & 127;
  if (t < 2 && glast + STAGES <= total) mbar_arrive_cluster(sbase + BAR_OFF + 8 * STAGES + 8 * (glast & (STAGES - 1)), t);
}

__device__ __forceinline__ void set_flag(unsigned* flag, unsigned epoch) {
  asm volatile("st.relaxed.gpu.global.u32 [%0], %1;" :: "l"(flag), "r"(epoch) : "memory");
}
__device__ __forceinline__ void publish(unsigned* flag, unsigned epoch) {
  asm volatile("fence.acq_rel.gpu;" ::: "memory");
  asm volatile("st.relaxed.gpu.global.u32 [%0], %1;" :: "l"(flag), "r"(epoch) : "memory");
}

__device__ __forceinline__ float sum8(uint4 v) {
  return ((bf_lo(v.x) + bf_hi(v.x)) + (bf_lo(v.y) + bf_hi(v.y))) + ((bf_lo(v.z) + bf_hi(v.z)) + (bf_lo(v.w) + bf_hi(v.w)));
}
__device__ __forceinline__ void ln_rows(const bf16* __restrict__ x, const bf16* __restrict__ win, int cta, unsigned epoch) {
  const int t = threadIdx.x & 127, w = t >> 5, l = t & 31, row = cta * 16 + (t >> 3), c = t & 7;
  const int cj = min(cta, 119), cg = cj % 24, rg = cj / 24;
  uint4 rv[10], cv[4];
  #pragma unroll
  for (int j = 0; j < 10; j++) rv[j] = __ldg(reinterpret_cast<const uint4*>(x + (size_t)row * DM) + c + 8 * j);
  #pragma unroll
  for (int j = 0; j < 4; j++) cv[j] = __ldg(reinterpret_cast<const uint4*>(win + (size_t)(rg * 128 + w * 32 + j * 8 + (l >> 2)) * FF + FH + cg * 32) + (l & 3));
  float s = 0.f;
  #pragma unroll
  for (int j = 0; j < 10; j++) s += sum8(rv[j]);
  #pragma unroll
  for (int o = 1; o < 8; o <<= 1) s += __shfl_xor_sync(0xffffffffu, s, o);
  const float mean = s * (1.f / DM);
  float q = 0.f;
  #pragma unroll
  for (int j = 0; j < 10; j++) {
    const uint32_t u[4] = {rv[j].x, rv[j].y, rv[j].z, rv[j].w};
    #pragma unroll
    for (int e = 0; e < 4; e++) { const float d0 = bf_lo(u[e]) - mean, d1 = bf_hi(u[e]) - mean; q = fmaf(d0, d0, q); q = fmaf(d1, d1, q); }
  }
  #pragma unroll
  for (int o = 1; o < 8; o <<= 1) q += __shfl_xor_sync(0xffffffffu, q, o);
  const float r = rsqrtf(fmaf(q, 1.f / DM, LN_EPS)), o = -mean * r;
  if (c == 0) st_vol2(&g_xstat[row], __float_as_uint(r), (__float_as_uint(o) & ~255u) | (epoch & 255u));
  #pragma unroll
  for (int j = 0; j < 10; j++)
    stg128(reinterpret_cast<uint4*>(g_xn + (size_t)row * DM) + c + 8 * j, make_uint4(
           pack_bf16(fmaf(bf_lo(rv[j].x), r, o), fmaf(bf_hi(rv[j].x), r, o)), pack_bf16(fmaf(bf_lo(rv[j].y), r, o), fmaf(bf_hi(rv[j].y), r, o)),
           pack_bf16(fmaf(bf_lo(rv[j].z), r, o), fmaf(bf_hi(rv[j].z), r, o)), pack_bf16(fmaf(bf_lo(rv[j].w), r, o), fmaf(bf_hi(rv[j].w), r, o))));
  bar_arrive<BAR_LN>(160);
  float v[8];
  v[0] = (bf_lo(cv[0].x) + bf_lo(cv[1].x)) + (bf_lo(cv[2].x) + bf_lo(cv[3].x)); v[1] = (bf_hi(cv[0].x) + bf_hi(cv[1].x)) + (bf_hi(cv[2].x) + bf_hi(cv[3].x));
  v[2] = (bf_lo(cv[0].y) + bf_lo(cv[1].y)) + (bf_lo(cv[2].y) + bf_lo(cv[3].y)); v[3] = (bf_hi(cv[0].y) + bf_hi(cv[1].y)) + (bf_hi(cv[2].y) + bf_hi(cv[3].y));
  v[4] = (bf_lo(cv[0].z) + bf_lo(cv[1].z)) + (bf_lo(cv[2].z) + bf_lo(cv[3].z)); v[5] = (bf_hi(cv[0].z) + bf_hi(cv[1].z)) + (bf_hi(cv[2].z) + bf_hi(cv[3].z));
  v[6] = (bf_lo(cv[0].w) + bf_lo(cv[1].w)) + (bf_lo(cv[2].w) + bf_lo(cv[3].w)); v[7] = (bf_hi(cv[0].w) + bf_hi(cv[1].w)) + (bf_hi(cv[2].w) + bf_hi(cv[3].w));
  #pragma unroll
  for (int st = 0; st < 3; st++) {
    const int n = 4 >> st;
    const bool up = (l & (4 * n)) != 0;
    #pragma unroll
    for (int e = 0; e < 4; e++)
      if (e < n) { const float keep = up ? v[e + n] : v[e], send = up ? v[e] : v[e + n]; v[e] = keep + __shfl_xor_sync(0xffffffffu, send, 4 * n); }
  }
  float* red = reinterpret_cast<float*>(smem + RED_OFF);
  red[w * 32 + (l & 3) * 8 + (l >> 2)] = v[0];
  bar_sync<BAR_WG2>(128);
  if (t < 32) st_vol2(&g_csum[rg * FH + cg * 32 + t], __float_as_uint((red[t] + red[32 + t]) + (red[64 + t] + red[96 + t])), epoch);
}

__device__ __forceinline__ void a_entry(int g, int grp, int rb, int& mi, int& kb) {
  if (g < 10) { mi = M_X; kb = g; }
  else if (g < 20) { mi = M_XN; kb = g - 10; }
  else if (grp == 0) {
    if (g < 52) { mi = M_WSP; kb = (g - 20 + ROT * rb) & 31; }
    else if (g < 52 + NX) { mi = M_WSIM; kb = g - 52 + 32 - NX; }
    else { mi = M_H; kb = g - 52 - NX; }
  } else {
    if (g < 30) { mi = M_XN; kb = g - 20; }
    else if (g < 62) { mi = M_WSRE; kb = (g - 30 + ROT * rb) & 31; }
    else { mi = M_WSIM; kb = g - 62; }
  }
}

__global__ void __cluster_dims__(2, 1, 1) __launch_bounds__(384, 1)
fused_kernel(const __grid_constant__ Maps maps, const bf16* __restrict__ x, const bf16* __restrict__ win, const bf16* __restrict__ bsp) {
  const uint32_t sbase = smem_u32(smem);
  const uint32_t full0 = sbase + BAR_OFF, empty0 = full0 + 8 * STAGES, dep0 = empty0 + 8 * STAGES, ring = sbase + RING_OFF;
  const int tid = threadIdx.x, wg = __shfl_sync(0xffffffffu, tid >> 7, 0);
  const int rank = blockIdx.x & 1;
  const int grp = (blockIdx.x >> 1) & 1, half = (blockIdx.x >> 2) & 1, rb = blockIdx.x >> 3;
  const int ct = half * 2 + rank, c8 = grp * 4 + ct;
  const int cta = rb * 8 + half * 4 + grp * 2 + rank;
  const int total = grp == 0 ? KB_A : KB_B;
  const uint32_t stage_bytes = grp == 0 ? STAGE_A : STAGE_B;

  if (tid == 0) {
    TS(0, 0);
    for (int s = 0; s < STAGES; s++) { mbar_init(full0 + 8 * s, 2); mbar_init(empty0 + 8 * s, 2); mbar_init(dep0 + 8 * s, 1); }
    *reinterpret_cast<volatile int*>(smem + READY_OFF) = 0;
    asm volatile("fence.mbarrier_init.release.cluster;" ::: "memory");
  }
  __syncthreads();
  asm volatile("barrier.cluster.arrive.relaxed.aligned;" ::: "memory");

  if (wg == 0) {
    asm volatile("setmaxnreg.dec.sync.aligned.u32 40;");
    const int warp = tid >> 5, lane = tid & 31;
    if (warp == 0) {
      const int row = rb * 128;
      if (lane == 0) {
        for (int g = 0; g < STAGES; g++) {
          mbar_expect_tx(full0 + 8 * g, A_BYTES);
          tma_load_2d(ring + g * stage_bytes, &maps.m[M_X], full0 + 8 * g, g * 64, row);
          tma_load_2d(ring + g * stage_bytes + 8192, &maps.m[M_X], full0 + 8 * g, g * 64, row + 64);
        }
      }
      __syncwarp();
      cluster_wait();
      if (lane == 0) {
        #pragma unroll 1
        for (int g = STAGES; g < total; g++) {
          int mi, kb;
          a_entry(g, grp, rb, mi, kb);
          if (g == 10 || (mi == M_H && kb == 0)) { TS(0, g > 10 ? 3 : 1); mbar_wait(dep0 + (g > 10 ? 24 : 0), 0); fence_async_global(); TS(0, g > 10 ? 4 : 2); }
          const int s = g & (STAGES - 1);
          mbar_wait(empty0 + 8 * s, ((g / STAGES) & 1) ^ 1);
          mbar_expect_tx(full0 + 8 * s, A_BYTES);
          tma_load_2d_mc(ring + s * stage_bytes + rank * 8192, &maps.m[mi], full0 + 8 * s, kb * 64, row + rank * 64, 3);
        }
        const int s = total & (STAGES - 1);
        mbar_wait(empty0 + 8 * s, ((total / STAGES) & 1) ^ 1);
        mbar_expect_tx(full0 + 8 * s, 20480);
        mbar_arrive(full0 + 8 * s);
        tma_load_2d(ring + s * stage_bytes, &maps.m[M_XR], full0 + 8 * s, ct * 160, row + grp * 64);
        TS(0, 5);
      }
    } else if (warp == 1) {
      if (lane == 0) {
        int have = 0;
        #pragma unroll 1
        for (int g = 0; g < total; g++) {
          int kind = 1, mi, kb, c, dep = 0, need = 0;
          uint32_t bytes = 20480;
          if (g < 10) { kind = 0; mi = M_WIN32; kb = g; c = 24 + 3 * c8; bytes = 12288; }
          else if (grp == 0) {
            if (g < 20) { kind = 0; mi = M_WIN3; kb = g - 10; c = 3 * ct; bytes = 24576; }
            else if (g < 52) { kind = 0; mi = M_Z23; kb = (g - 20 + ROT * rb) & 31; c = 3 * ct; bytes = 24576; need = ((g - 20) >> 1) + 1; }
            else if (g < 52 + NX) { mi = M_AB; kb = g - 52 + 32 - NX; c = DM + ct * 160; dep = g == 52 ? 2 : 0; }
            else { kind = 0; mi = M_WOUT; kb = g - 52 - NX; c = ct * 5; }
          } else {
            if (g < 30) { mi = g < 20 ? M_WDRE : M_WDIM; kb = g < 20 ? g - 10 : g - 20; c = ct * 160; }
            else if (g < 62) { mi = M_AB; kb = (g - 30 + ROT * rb) & 31; c = ct * 160; need = ((g - 30) >> 1) + 1; }
            else { mi = M_AB; kb = g - 62; c = ct * 160 + DM; dep = g == 62 ? 2 : 0; }
          }
          if (need > have) {
            if (need == 1) TS(1, 0);
            unsigned it = 0;
            while ((have = *reinterpret_cast<volatile int*>(smem + READY_OFF)) < need && ++it < 50 * POLL_LIMIT) {}
            fence_async_global();
            if (need == 1) { TS(1, 1); TC(1); }
          }
          if (dep) { TS(1, dep * 2 - 2); mbar_wait(dep0 + 8 * dep, 0); fence_async_global(); TS(1, dep * 2 - 1); TC(dep); }
          const int s = g & (STAGES - 1);
          const uint32_t dst = ring + s * stage_bytes + A_BYTES, fb = full0 + 8 * s;
          mbar_wait(empty0 + 8 * s, ((g / STAGES) & 1) ^ 1);
          mbar_expect_tx(fb, bytes);
          if (kind == 0) tma_load_3d(dst, &maps.m[mi], fb, 0, kb * 64, c);
          else tma_load_2d(dst, &maps.m[mi], fb, kb * 64, c);
        }
      }
      __syncwarp();
      cluster_wait();
    } else if (warp == 2) {
      cluster_wait();
      const unsigned epoch = (*reinterpret_cast<volatile unsigned*>(&g_done) >> 7) + 1u;
      {
        unsigned it = 0;
        uint2 v[4];
        while (true) {
          bool ok = true;
          #pragma unroll
          for (int i = 0; i < 4; i++) { v[i] = ld_vol2(&g_xstat[rb * 128 + i * 32 + lane]); ok = ok && ((v[i].y ^ epoch) & 255u) == 0; }
          if (ok || ++it > POLL_LIMIT) break;
          __nanosleep(POLL_NS);
        }
        #pragma unroll
        for (int i = 0; i < 4; i++) reinterpret_cast<uint2*>(smem + ROWSTAT_OFF)[i * 32 + lane] = make_uint2(v[i].x, v[i].y & ~255u);
        __syncwarp();
        TS(0, 6);
        bar_arrive<BAR_STATS>(192);
      }
      #pragma unroll 1
      for (int d = 0; d < 4 - grp; d++) {
        const int rr = ((lane >> 1) + (ROT / 2) * rb) & 15;
        const int fi = d == 0 ? F_XN + rb * 8 + (lane & 7)
                     : d == 3 ? F_H + rb * 4 + (lane & 3)
                     : d == 2 ? F_B + (lane & 15) * 4 + ct
                     : grp == 0 ? F_Z + rr * 8 + ct * 2 + (lane & 1) : F_A + rr * 4 + ct;
        unsigned it = 0, m;
        while ((m = __ballot_sync(0xffffffffu, ld_relaxed(g_flags + fi) != epoch)) != 0 && ++it < POLL_LIMIT) {
          if (d == 1 && lane == 0) *reinterpret_cast<volatile int*>(smem + READY_OFF) = (__ffs(m) - 1) >> 1;
          __nanosleep(20);
        }
        if (d == 1 && lane == 0) *reinterpret_cast<volatile int*>(smem + READY_OFF) = 16;
        TS(0, 8 + d * 2);
        fence_async_global();
        __syncwarp();
        TS(0, 9 + d * 2);
        if (lane == 0) mbar_arrive(dep0 + 8 * d);
      }
    } else {
      const unsigned epoch = (*reinterpret_cast<volatile unsigned*>(&g_done) >> 7) + 1u;
      cluster_wait();
      bar_sync<BAR_LN>(160);
      if (lane == 0) { TS(1, 5); publish(g_flags + F_XN + cta, epoch); TS(1, 6); }
      __syncwarp();
      #pragma unroll 1
      for (int i = 0; i < 3; i++) {
        unsigned it = 0;
        while (true) {
          bool ok = true;
          float a = 0.f;
          #pragma unroll
          for (int p = 0; p < 5; p++) { const uint2 u = ld_vol2(&g_csum[p * FH + c8 * 96 + i * 32 + lane]); ok = ok && u.y == epoch; a += __uint_as_float(u.x); }
          reinterpret_cast<float*>(smem + COLSUM_OFF)[i * 32 + lane] = a;
          if (ok || ++it > POLL_LIMIT) break;
          __nanosleep(POLL_NS);
        }
      }
      __syncwarp();
      TS(1, 4);
      bar_arrive<BAR_STATS>(192);
      bar_sync<BAR_PUB1>(160);
      if (lane == 0) {
        TS(1, 7);
        tma_store_3d(&maps.m[M_Z232], ring + 4 * stage_bytes, 0, rb * 128, 3 * c8);
        bulk_commit();
        bulk_wait_all();
        set_flag(g_flags + F_Z + rb * 8 + c8, epoch);
        TS(1, 8);
      }
      __syncwarp();
      if (grp == 0) {
        bar_arrive<BAR_BUF>(160);
      } else {
        bar_sync<BAR_PUB2>(160);
        if (lane == 0) set_flag(g_flags + F_A + rb * 4 + ct, epoch);
        TS(1, 9);
        __syncwarp();
      }
      bar_sync<BAR_PUB1>(160);
      if (lane == 0) set_flag(g_flags + (grp == 0 ? F_H : F_B) + rb * 4 + ct, epoch);
      TS(1, 10);
    }
  } else {
    asm volatile("setmaxnreg.inc.sync.aligned.u32 232;");
    const int t = tid & 127, w = t >> 5, l = t & 31;
    const uint32_t buf = ring + 4 * stage_bytes;
    const unsigned epoch = (*reinterpret_cast<volatile unsigned*>(&g_done) >> 7) + 1u;
    if (wg == 2) ln_rows(x, win, cta, epoch);
    TS(wg + 1, 0);
    cluster_wait();
    const int rl = w * 16 + ((l >> 3) & 1) * 8 + (l & 7);
    const int gr = w * 16 + (l & 15);
    const uint32_t st_base = buf + rl * 128;
    const uint32_t st_x = ((l >> 4) ^ (l & 7)) << 4;
    if (wg == 1) {
      float acc[2][48];
      zero(acc);
      mainloop<96, 2, false, BAR_ORD1>(acc, sbase, stage_bytes, 0, 10, total, 0);
      drain(acc, sbase, 9, total);
      TS(2, 2);
      bar_sync<BAR_STATS>(192);
      const float2* rs = reinterpret_cast<const float2*>(smem + ROWSTAT_OFF) + w * 16 + (l >> 2);
      const float2* cs = reinterpret_cast<const float2*>(smem + COLSUM_OFF) + (l & 3);
      float sum[4], sq[4];
      #pragma unroll
      for (int r = 0; r < 4; r++) {
        const float2 st = rs[(r >> 1) * 64 + (r & 1) * 8];
        float s0 = 0.f, q0 = 0.f;
        #pragma unroll
        for (int j = 0; j < 12; j++) {
          const float2 c = cs[j * 4];
          float* a = &acc[r >> 1][4 * j + (r & 1) * 2];
          a[0] = gelu_tanh(fmaf(a[0], st.x, st.y * c.x));
          a[1] = gelu_tanh(fmaf(a[1], st.x, st.y * c.y));
          s0 += a[0] + a[1]; q0 = fmaf(a[0], a[0], q0); q0 = fmaf(a[1], a[1], q0);
        }
        s0 += __shfl_xor_sync(0xffffffffu, s0, 1); q0 += __shfl_xor_sync(0xffffffffu, q0, 1);
        s0 += __shfl_xor_sync(0xffffffffu, s0, 2); q0 += __shfl_xor_sync(0xffffffffu, q0, 2);
        sum[r] = s0; sq[r] = q0;
      }
      TS(2, 4);
      float rstd, off;
      {
        const int qd = l & 3;
        const float sm = qd == 0 ? sum[0] : qd == 1 ? sum[1] : qd == 2 ? sum[2] : sum[3];
        const float sv = qd == 0 ? sq[0] : qd == 1 ? sq[1] : qd == 2 ? sq[2] : sq[3];
        const int row = (qd >> 1) * 64 + w * 16 + (qd & 1) * 8 + (l >> 2);
        const float mu = sm * (1.f / 96), m2 = fmaxf(sv - sm * mu, 0.f);
        st_vol2(&g_zstat[(rb * 8 + c8) * 128 + row], __float_as_uint(mu), (__float_as_uint(m2) & ~255u) | (epoch & 255u));
        uint2 v[7];
        unsigned n = 0;
        while (true) {
          bool ok = true;
          #pragma unroll
          for (int j = 0; j < 7; j++) v[j] = ld_vol2(&g_zstat[(rb * 8 + ((c8 + 1 + j) & 7)) * 128 + row]);
          #pragma unroll
          for (int j = 0; j < 7; j++) ok = ok && ((v[j].y ^ epoch) & 255u) == 0;
          if (ok || ++n > POLL_LIMIT) break;
          __nanosleep(POLL_NS);
        }
        float mean = mu, var = m2;
        #pragma unroll
        for (int j = 0; j < 7; j++) { mean += __uint_as_float(v[j].x); var += __uint_as_float(v[j].y & ~255u); }
        mean *= 0.125f;
        float d = (mu - mean) * (mu - mean);
        #pragma unroll
        for (int j = 0; j < 7; j++) d = fmaf(__uint_as_float(v[j].x) - mean, __uint_as_float(v[j].x) - mean, d);
        rstd = rsqrtf(fmaf(96.f, d, var) * (1.f / FH) + LN_EPS); off = -mean * rstd;
        __syncwarp();
      }
      TS(2, 5);
      #pragma unroll
      for (int mi = 0; mi < 2; mi++) {
        const float r0 = __shfl_sync(0xffffffffu, rstd, (l & 28) + mi * 2), o0 = __shfl_sync(0xffffffffu, off, (l & 28) + mi * 2);
        const float r1 = __shfl_sync(0xffffffffu, rstd, (l & 28) + mi * 2 + 1), o1 = __shfl_sync(0xffffffffu, off, (l & 28) + mi * 2 + 1);
        #pragma unroll
        for (int jj = 0; jj < 6; jj++) {
          const float* a = &acc[mi][8 * jj];
          stsm4(buf + (jj >> 1) * 8192 + mi * 4096 + rl * 64 + ((((jj & 1) * 2 + (l >> 4)) ^ ((l >> 1) & 3)) << 4),
                pack_bf16(fmaf(a[0], r0, o0), fmaf(a[1], r0, o0)), pack_bf16(fmaf(a[2], r1, o1), fmaf(a[3], r1, o1)),
                pack_bf16(fmaf(a[4], r0, o0), fmaf(a[5], r0, o0)), pack_bf16(fmaf(a[6], r1, o1), fmaf(a[7], r1, o1)));
        }
      }
      fence_async_smem();
      bar_arrive<BAR_PUB1>(160);
      TS(2, 6);
      if (grp == 0) {
        float acc[2][96];
        zero(acc);
        bar_sync<BAR_ORD2>(256);
        mainloop<192, 1, false, BAR_ORD1>(acc, sbase, STAGE_A, 20, 32, KB_A, 0);
        const float* bias = reinterpret_cast<const float*>(smem + BIAS_OFF) + w * 16 + (l >> 2);
        bar_sync<BAR_Z1>(256);
        drain(acc, sbase, 51, KB_A);
        TS(2, 7);
        {
          const float bb[4] = {bias[0], bias[8], bias[64], bias[72]};
          uint32_t z[2][4][4];
          #pragma unroll
          for (int i = 0; i < 4; i++) ldsm4(st_base + (st_x ^ (i << 5)), z[0][i][0], z[0][i][1], z[0][i][2], z[0][i][3]);
          #pragma unroll
          for (int bx = 0; bx < 6; bx++) {
            if (bx < 5) {
              #pragma unroll
              for (int i = 0; i < 4; i++)
                ldsm4(st_base + (bx + 1) * 8192 + (st_x ^ (i << 5)), z[(bx + 1) & 1][i][0], z[(bx + 1) & 1][i][1], z[(bx + 1) & 1][i][2], z[(bx + 1) & 1][i][3]);
            }
            const float b0 = bb[(bx / 3) * 2], b1 = bb[(bx / 3) * 2 + 1];
            #pragma unroll
            for (int i = 0; i < 4; i++) {
              const float* a = &acc[bx / 3][8 * ((bx % 3) * 4 + i)];
              const uint32_t* zz = z[bx & 1][i];
              stsm4(st_base + bx * 8192 + (st_x ^ (i << 5)),
                    hmul2_bf16(zz[0], pack_bf16(a[0] + b0, a[1] + b0)), hmul2_bf16(zz[1], pack_bf16(a[2] + b1, a[3] + b1)),
                    hmul2_bf16(zz[2], pack_bf16(a[4] + b0, a[5] + b0)), hmul2_bf16(zz[3], pack_bf16(a[6] + b1, a[7] + b1)));
            }
            fence_async_smem();
            __syncwarp();
            if (l == 0) {
              tma_store_2d(&maps.m[M_HS], buf + bx * 8192 + w * 2048, ct * 192 + (bx % 3) * 64, rb * 128 + (bx / 3) * 64 + w * 16);
              bulk_commit();
            }
          }
        }
        TS(2, 8);
        if (l == 0) bulk_wait_all();
        __syncwarp();
        bar_arrive<BAR_PUB1>(160);
        TS(2, 9);
        return;
      }
    } else {
      if (grp == 0) {
        reinterpret_cast<float*>(smem + BIAS_OFF)[t] = __bfloat162float(bsp[rb * 128 + t]);
        float acc[2][96];
        zero(acc);
        bar_sync<BAR_ORD1>(256);
        mainloop<192, 1, false, BAR_ORD2>(acc, sbase, STAGE_A, 10, 10, KB_A, 0);
        drain(acc, sbase, 19, KB_A);
        TS(3, 2);
        bar_sync<BAR_BUF>(160);
        #pragma unroll
        for (int mi = 0; mi < 2; mi++)
          #pragma unroll
          for (int jj = 0; jj < 12; jj++) {
            const float* a = &acc[mi][8 * jj];
            stsm4(st_base + mi * 24576 + (jj >> 2) * 8192 + (st_x ^ ((jj & 3) << 5)),
                  pack_bf16(a[0], a[1]), pack_bf16(a[2], a[3]), pack_bf16(a[4], a[5]), pack_bf16(a[6], a[7]));
          }
        __syncwarp();
        TS(3, 3);
        const uint32_t rbase = buf + (l >> 4) * 24576 + gr * 128;
        #pragma unroll 1
        for (int c2 = 0; c2 < 12; c2++) {
          const uint32_t ab = rbase + (c2 >> 2) * 8192;
          uint4 v[2];
          #pragma unroll
          for (int i = 0; i < 2; i++) v[i] = lds128(ab + (((((c2 & 3) * 2 + i) ^ l) & 7) << 4));
          #pragma unroll
          for (int i = 0; i < 2; i++)
            sts128(ab + (((((c2 & 3) * 2 + i) ^ l) & 7) << 4),
                   pack_bf16(gelu_tanh(bf_lo(v[i].x)), gelu_tanh(bf_hi(v[i].x))), pack_bf16(gelu_tanh(bf_lo(v[i].y)), gelu_tanh(bf_hi(v[i].y))),
                   pack_bf16(gelu_tanh(bf_lo(v[i].z)), gelu_tanh(bf_hi(v[i].z))), pack_bf16(gelu_tanh(bf_lo(v[i].w)), gelu_tanh(bf_hi(v[i].w))));
        }
        TS(3, 4);
        bar_arrive<BAR_Z1>(256);
      }
    }
    float acc[2][80];
    if (grp == 1) {
      zero(acc);
      if (wg == 2) {
        bar_sync<BAR_ORD1>(256);
        mainloop<160, 0, false, BAR_ORD2>(acc, sbase, STAGE_B, 10, 10, KB_B, 0);
      } else {
        bar_sync<BAR_ORD2>(256);
        mainloop<160, 0, false, BAR_ORD1>(acc, sbase, STAGE_B, 20, 10, KB_B, 0);
      }
      drain(acc, sbase, wg == 2 ? 19 : 29, KB_B);
      TS(wg + 1, wg == 1 ? 7 : 2);
      if (wg == 1) bar_sync<BAR_BUF>(256);
      const uint32_t sg = wg == 1 ? 0x80008000u : 0u;
      const uint32_t tb = buf + 24576 + ((l >> 4) * 8 + (l & 7)) * 128 + (((w * 2 + ((l >> 3) & 1)) ^ (l & 7)) << 4);
      #pragma unroll
      for (int mi = 0; mi < 2; mi++)
        #pragma unroll
        for (int jj = 0; jj < 10; jj++) {
          const float* a = &acc[mi][8 * jj];
          stsm4_t(tb + mi * 20480 + jj * 2048, pack_bf16(a[0], a[1]) ^ sg, pack_bf16(a[2], a[3]) ^ sg, pack_bf16(a[4], a[5]) ^ sg, pack_bf16(a[6], a[7]) ^ sg);
        }
      fence_async_smem();
      if (wg == 1) bar_sync<BAR_WG1>(128); else bar_sync<BAR_WG2>(128);
      TS(wg + 1, wg == 1 ? 8 : 6);
      if (l == 0) {
        #pragma unroll 1
        for (int i = 0; i < 2; i++) {
          tma_store_2d(&maps.m[M_ABS], buf + 24576 + i * 20480 + w * 5120, rb * 128 + i * 64, (2 - wg) * DM + ct * 160 + w * 40);
          bulk_commit();
        }
        bulk_wait_all();
      }
      __syncwarp();
      TS(wg + 1, wg == 1 ? 9 : 10);
      if (wg == 1) { bar_arrive<BAR_PUB1>(160); return; }
      bar_arrive<BAR_PUB2>(160);
      bar_arrive<BAR_BUF>(256);
    }
    zero(acc);
    bar_sync<BAR_ORD1>(256);
    mainloop<160, 0, false, 0>(acc, sbase, stage_bytes, grp == 0 ? 52 : 30, grp == 0 ? NX : 64 - NX, total, grp);
    if (grp == 0) mainloop<160, 2, true, 0>(acc, sbase, STAGE_A, 52 + NX, 12, KB_A, 0);
    drain(acc, sbase, total - 1, total);
    TS(3, 12);
    uint4* dst = g_part + (size_t)cta * 27 * 128 + t;
    const uint4* src = g_part + (size_t)(cta ^ 2) * 27 * 128 + t;
    #pragma unroll
    for (int i = 0; i < 27; i++)
      st_vol4(dst + i * 128, __float_as_uint(acc[1][3 * i]), __float_as_uint(acc[1][3 * i + 1]),
              __float_as_uint(i < 26 ? acc[1][3 * i + 2] : 0.f), epoch);
    TS(3, 13);
    const uint32_t slab = ring + (total & (STAGES - 1)) * stage_bytes + w * (16 * 320);
    const uint32_t addr = slab + (((l >> 3) & 1) * 8 + (l & 7)) * 320 + (l >> 4) * 16;
    mbar_wait(full0 + 8 * (total & (STAGES - 1)), (total / STAGES) & 1);
    #pragma unroll
    for (int jj = 0; jj < 10; jj++) {
      uint32_t z0, z1, z2, z3;
      ldsm4(addr + jj * 32, z0, z1, z2, z3);
      float* a = &acc[0][8 * jj];
      a[0] += bf_lo(z0); a[1] += bf_hi(z0); a[2] += bf_lo(z1); a[3] += bf_hi(z1);
      a[4] += bf_lo(z2); a[5] += bf_hi(z2); a[6] += bf_lo(z3); a[7] += bf_hi(z3);
    }
    {
      unsigned n = 0;
      while (ld_vol4(src + 26 * 128).w != epoch && ++n < POLL_LIMIT) __nanosleep(POLL_NS);
      uint4 v[27];
      while (true) {
        bool ok = true;
        #pragma unroll
        for (int i = 0; i < 27; i++) v[i] = ld_vol4(src + i * 128);
        #pragma unroll
        for (int i = 0; i < 27; i++) ok = ok && (v[i].w == epoch);
        if (ok || ++n > POLL_LIMIT) break;
      }
      #pragma unroll
      for (int i = 0; i < 27; i++) {
        acc[0][3 * i] += __uint_as_float(v[i].x);
        acc[0][3 * i + 1] += __uint_as_float(v[i].y);
        if (i < 26) acc[0][3 * i + 2] += __uint_as_float(v[i].z);
      }
    }
    TS(3, 14);
    #pragma unroll
    for (int jj = 0; jj < 10; jj++) {
      const float* a = &acc[0][8 * jj];
      stsm4(addr + jj * 32, pack_bf16(a[0], a[1]), pack_bf16(a[2], a[3]), pack_bf16(a[4], a[5]), pack_bf16(a[6], a[7]));
    }
    fence_async_smem();
    __syncwarp();
    if (l == 0) {
      tma_store_2d(&maps.m[M_OUT], slab, ct * 160, rb * 128 + grp * 64 + w * 16);
      bulk_commit();
      bulk_wait_read();
      if (w == 0) atomicAdd(&g_done, 1u);
    }
    TS(3, 15);
  }
}

typedef CUresult (*EncodeFn)(CUtensorMap*, CUtensorMapDataType, cuuint32_t, void*, const cuuint64_t*, const cuuint64_t*,
                             const cuuint32_t*, const cuuint32_t*, CUtensorMapInterleave, CUtensorMapSwizzle,
                             CUtensorMapL2promotion, CUtensorMapFloatOOBfill);

void make2d(EncodeFn enc, CUtensorMap* m, const void* p, uint64_t cols, uint64_t rows, uint32_t bc, uint32_t br, bool swz = true) {
  cuuint64_t gd[2] = {cols, rows}, gs[1] = {cols * 2};
  cuuint32_t bd[2] = {bc, br}, es[2] = {1, 1};
  enc(m, CU_TENSOR_MAP_DATA_TYPE_BFLOAT16, 2, const_cast<void*>(p), gd, gs, bd, es, CU_TENSOR_MAP_INTERLEAVE_NONE,
      swz ? CU_TENSOR_MAP_SWIZZLE_128B : CU_TENSOR_MAP_SWIZZLE_NONE, PROMO, CU_TENSOR_MAP_FLOAT_OOB_FILL_NONE);
}
void make3d(EncodeFn enc, CUtensorMap* m, const void* p, uint64_t cols, uint64_t rows, uint32_t cw, uint32_t nc, uint32_t br = 64) {
  cuuint64_t gd[3] = {cw, rows, cols / cw}, gs[2] = {cols * 2, cw * 2};
  cuuint32_t bd[3] = {cw, br, nc}, es[3] = {1, 1, 1};
  enc(m, CU_TENSOR_MAP_DATA_TYPE_BFLOAT16, 3, const_cast<void*>(p), gd, gs, bd, es, CU_TENSOR_MAP_INTERLEAVE_NONE,
      cw == 64 ? CU_TENSOR_MAP_SWIZZLE_128B : CU_TENSOR_MAP_SWIZZLE_64B, PROMO, CU_TENSOR_MAP_FLOAT_OOB_FILL_NONE);
}

}

extern "C" void kernel_launch(void* const* d_in, const int* in_sizes, int n_in, void* d_out, int out_size) {
  const bf16* x = (const bf16*)d_in[0];
  const bf16* wsre = (const bf16*)d_in[1];
  const bf16* wsim = (const bf16*)d_in[2];
  const bf16* wdre = (const bf16*)d_in[3];
  const bf16* wdim = (const bf16*)d_in[4];
  const bf16* win = (const bf16*)d_in[6];
  const bf16* wsp = (const bf16*)d_in[7];
  const bf16* bsp = (const bf16*)d_in[8];
  const bf16* wout = (const bf16*)d_in[9];

  void* fn = nullptr;
  cudaDriverEntryPointQueryResult qr;
  cudaGetDriverEntryPoint("cuTensorMapEncodeTiled", &fn, cudaEnableDefault, &qr);
  EncodeFn enc = (EncodeFn)fn;
  void *abT, *z2, *h, *xn;
  cudaGetSymbolAddress(&xn, g_xn);
  cudaGetSymbolAddress(&abT, g_abT);
  cudaGetSymbolAddress(&z2, g_z2);
  cudaGetSymbolAddress(&h, g_h);

  Maps maps;
  make2d(enc, &maps.m[M_X], x, DM, SEQ, 64, 64);
  make2d(enc, &maps.m[M_XN], xn, DM, SEQ, 64, 64);
  make3d(enc, &maps.m[M_Z232], z2, FH, SEQ, 32, 3, 128);
  make2d(enc, &maps.m[M_XR], x, DM, SEQ, 160, 64, false);
  make3d(enc, &maps.m[M_WIN32], win, FF, DM, 32, 3);
  make2d(enc, &maps.m[M_WSRE], wsre, SEQ, SEQ, 64, 64);
  make2d(enc, &maps.m[M_WSIM], wsim, SEQ, SEQ, 64, 64);
  make2d(enc, &maps.m[M_WSP], wsp, SEQ, SEQ, 64, 64);
  make2d(enc, &maps.m[M_H], h, FH, SEQ, 64, 64);
  make3d(enc, &maps.m[M_WIN3], win, FF, DM, 64, 3);
  make3d(enc, &maps.m[M_Z23], z2, FH, SEQ, 64, 3);
  make2d(enc, &maps.m[M_WDRE], wdre, DM, DM, 64, 160);
  make2d(enc, &maps.m[M_WDIM], wdim, DM, DM, 64, 160);
  make2d(enc, &maps.m[M_AB], abT, SEQ, 2 * DM, 64, 160);
  make3d(enc, &maps.m[M_WOUT], wout, DM, FH, 32, 5);
  make2d(enc, &maps.m[M_HS], h, FH, SEQ, 64, 16);
  make2d(enc, &maps.m[M_ABS], abT, SEQ, 2 * DM, 64, 40);
  make2d(enc, &maps.m[M_OUT], d_out, DM, SEQ, 160, 16, false);

  cudaFuncSetAttribute(fused_kernel, cudaFuncAttributeMaxDynamicSharedMemorySize, SMEM_BYTES);
  fused_kernel<<<128, 384, SMEM_BYTES>>>(maps, x, win, bsp);
}
```

```cpp
#include <cuda_runtime.h>
#include <cuda_bf16.h>
#include <cuda.h>
#include <stdint.h>

namespace {

typedef __nv_bfloat16 bf16;

constexpr int SEQ = 2048, DM = 640, FF = 1536, FH = 768;
#define NXV 11
constexpr int NX = NXV;
constexpr int STAGES = 4;
constexpr int A_BYTES = 16384;
constexpr int BIAS_OFF = 0;
constexpr int BAR_OFF = 512;
constexpr int READY_OFF = 640;
constexpr int ROWSTAT_OFF = 1024;
constexpr int COLSUM_OFF = 2048;
constexpr int RED_OFF = 2560;
constexpr int RING_OFF = 3072;
constexpr int STAGE_A = 40960, STAGE_B = 36864;
constexpr int SMEM_BYTES = RING_OFF + 4 * STAGE_A + 49152;
constexpr int KB_A = 20 + 32 + NX + 12;
constexpr int KB_B = 30 + 64 - NX;
constexpr float LN_EPS = 1e-5f;
constexpr unsigned POLL_LIMIT = 100000;
#define POLL_NS 100
#define PF_D 0
#define ROT 0
#define Z1_NS 0
#define INFL 2
#define LIM_G 1000
#define MAPV 0
#define PROMO CU_TENSOR_MAP_L2_PROMOTION_L2_128B
#define WATCH_NS 40
#define PF_NS 150

constexpr int BAR_ORD1 = 1, BAR_ORD2 = 2, BAR_WG1 = 3, BAR_WG2 = 4, BAR_LN = 5, BAR_BUF = 6, BAR_Z1 = 7, BAR_PUB1 = 8, BAR_PUB2 = 9, BAR_STATS = 10;

enum { M_X, M_XN, M_XR, M_WIN32, M_Z232, M_WSRE, M_WSIM, M_WSP, M_H, M_WIN3, M_Z23, M_WDRE, M_WDIM, M_AB, M_WOUT, M_OUT, M_HS, M_ABS, M_COUNT };
struct Maps { CUtensorMap m[M_COUNT]; };

__device__ __align__(1024) bf16 g_abT[2 * DM * SEQ];
__device__ __align__(1024) bf16 g_z2[SEQ * FH];
__device__ __align__(1024) bf16 g_h[SEQ * FH];
__device__ __align__(1024) bf16 g_xn[SEQ * DM];
__device__ __align__(16) uint2 g_xstat[SEQ];
__device__ __align__(16) uint2 g_csum[5 * FH];
__device__ __align__(16) uint2 g_zstat[128 * 128];
__device__ __align__(16) uint4 g_part[128 * 27 * 128];
__device__ __align__(256) unsigned char g_flags[44 * 256];
constexpr int F_A = 0, F_B = 4, F_Z = 8, F_H = 12, F_XN = 28;
__device__ unsigned g_done;
#define TS(role, ev)
#define TC(i)

extern __shared__ __align__(1024) uint8_t smem[];

__device__ __forceinline__ uint32_t smem_u32(const void* p) { return (uint32_t)__cvta_generic_to_shared(p); }
__device__ __forceinline__ void mbar_init(uint32_t bar, uint32_t cnt) { asm volatile("mbarrier.init.shared::cta.b64 [%0], %1;" :: "r"(bar), "r"(cnt)); }
__device__ __forceinline__ void mbar_expect_tx(uint32_t bar, uint32_t bytes) { asm volatile("mbarrier.arrive.expect_tx.shared::cta.b64 _, [%0], %1;" :: "r"(bar), "r"(bytes) : "memory"); }
__device__ __forceinline__ void mbar_arrive(uint32_t bar) { asm volatile("mbarrier.arrive.shared::cta.b64 _, [%0];" :: "r"(bar) : "memory"); }
__device__ __forceinline__ void mbar_arrive_cluster(uint32_t bar, uint32_t cta) {
  asm volatile("{\n.reg .b32 ra;\nmapa.shared::cluster.u32 ra, %0, %1;\nmbarrier.arrive.shared::cluster.b64 _, [ra];\n}" :: "r"(bar), "r"(cta) : "memory");
}
__device__ __forceinline__ void mbar_wait(uint32_t bar, uint32_t parity) {
  asm volatile("{\n.reg .pred p;\n.reg .u32 n;\nmov.u32 n, 0;\n"
               "LW: mbarrier.try_wait.parity.shared::cta.b64 p, [%0], %1, 2000;\n@p bra LD;\n"
               "add.u32 n, n, 1;\nsetp.lt.u32 p, n, 20000;\n@p bra LW;\nLD:\n}" :: "r"(bar), "r"(parity) : "memory");
}
__device__ __forceinline__ void tma_load_2d(uint32_t dst, const CUtensorMap* map, uint32_t bar, int c0, int c1) {
  asm volatile("cp.async.bulk.tensor.2d.shared::cluster.global.mbarrier::complete_tx::bytes [%0], [%1, {%3, %4}], [%2];"
    :: "r"(dst), "l"((uint64_t)map), "r"(bar), "r"(c0), "r"(c1) : "memory");
}
__device__ __forceinline__ void tma_load_3d(uint32_t dst, const CUtensorMap* map, uint32_t bar, int c0, int c1, int c2) {
  asm volatile("cp.async.bulk.tensor.3d.shared::cluster.global.mbarrier::complete_tx::bytes [%0], [%1, {%3, %4, %5}], [%2];"
    :: "r"(dst), "l"((uint64_t)map), "r"(bar), "r"(c0), "r"(c1), "r"(c2) : "memory");
}
__device__ __forceinline__ void tma_load_2d_mc(uint32_t dst, const CUtensorMap* map, uint32_t bar, int c0, int c1, uint16_t mask) {
  asm volatile("cp.async.bulk.tensor.2d.shared::cluster.global.mbarrier::complete_tx::bytes.multicast::cluster [%0], [%1, {%3, %4}], [%2], %5;"
    :: "r"(dst), "l"((uint64_t)map), "r"(bar), "r"(c0), "r"(c1), "h"(mask) : "memory");
}
__device__ __forceinline__ void tma_store_2d(const CUtensorMap* map, uint32_t src, int c0, int c1) {
  asm volatile("cp.async.bulk.tensor.2d.global.shared::cta.bulk_group [%0, {%2, %3}], [%1];"
    :: "l"((uint64_t)map), "r"(src), "r"(c0), "r"(c1) : "memory");
}
__device__ __forceinline__ void tma_store_3d(const CUtensorMap* map, uint32_t src, int c0, int c1, int c2) {
  asm volatile("cp.async.bulk.tensor.3d.global.shared::cta.bulk_group [%0, {%2, %3, %4}], [%1];"
    :: "l"((uint64_t)map), "r"(src), "r"(c0), "r"(c1), "r"(c2) : "memory");
}
__device__ __forceinline__ void bulk_wait_all() { asm volatile("cp.async.bulk.wait_group 0;" ::: "memory"); }
__device__ __forceinline__ void bulk_commit() { asm volatile("cp.async.bulk.commit_group;" ::: "memory"); }
__device__ __forceinline__ void bulk_wait_read() { asm volatile("cp.async.bulk.wait_group.read 0;" ::: "memory"); }
__device__ __forceinline__ void fence_async_smem() { asm volatile("fence.proxy.async.shared::cta;" ::: "memory"); }
__device__ __forceinline__ void fence_async_global() { asm volatile("fence.proxy.async.global;" ::: "memory"); }
__device__ __forceinline__ void wgmma_fence() { asm volatile("wgmma.fence.sync.aligned;" ::: "memory"); }
__device__ __forceinline__ void wgmma_commit() { asm volatile("wgmma.commit_group.sync.aligned;" ::: "memory"); }
template<int N> __device__ __forceinline__ void wgmma_wait() { asm volatile("wgmma.wait_group.sync.aligned %0;" :: "n"(N) : "memory"); }
template<int ID> __device__ __forceinline__ void bar_sync(int n) { asm volatile("bar.sync %0, %1;" :: "n"(ID), "r"(n) : "memory"); }
template<int ID> __device__ __forceinline__ void bar_arrive(int n) { asm volatile("bar.arrive %0, %1;" :: "n"(ID), "r"(n) : "memory"); }
__device__ __forceinline__ void cluster_wait() { asm volatile("barrier.cluster.wait.aligned;" ::: "memory"); }
__device__ __forceinline__ uint64_t desc64(uint32_t lo, uint32_t hi) { return (uint64_t)lo | ((uint64_t)hi << 32); }
__device__ __forceinline__ uint4 ld_vol4(const uint4* p) {
  uint4 v; asm volatile("ld.relaxed.gpu.global.v4.u32 {%0,%1,%2,%3}, [%4];" : "=r"(v.x), "=r"(v.y), "=r"(v.z), "=r"(v.w) : "l"(p) : "memory"); return v;
}
__device__ __forceinline__ uint2 ld_vol2(const uint2* p) {
  uint2 v; asm volatile("ld.relaxed.gpu.global.v2.u32 {%0,%1}, [%2];" : "=r"(v.x), "=r"(v.y) : "l"(p) : "memory"); return v;
}
__device__ __forceinline__ void st_vol4(uint4* p, uint32_t a, uint32_t b, uint32_t c, uint32_t d) {
  asm volatile("st.relaxed.gpu.global.v4.u32 [%0], {%1,%2,%3,%4};" :: "l"(p), "r"(a), "r"(b), "r"(c), "r"(d) : "memory");
}
__device__ __forceinline__ void st_vol2(uint2* p, uint32_t a, uint32_t b) {
  asm volatile("st.relaxed.gpu.global.v2.u32 [%0], {%1,%2};" :: "l"(p), "r"(a), "r"(b) : "memory");
}
__device__ __forceinline__ void stg128(void* p, uint4 v) {
  asm volatile("st.global.v4.u32 [%0], {%1,%2,%3,%4};" :: "l"(p), "r"(v.x), "r"(v.y), "r"(v.z), "r"(v.w));
}
__device__ __forceinline__ unsigned ld_relaxed(const unsigned* p) {
  unsigned v; asm volatile("ld.relaxed.gpu.global.u32 %0, [%1];" : "=r"(v) : "l"(p) : "memory"); return v;
}
__device__ __forceinline__ uint32_t pack_bf16(float lo, float hi) {
  uint32_t r; asm("cvt.rn.bf16x2.f32 %0, %1, %2;" : "=r"(r) : "f"(hi), "f"(lo)); return r;
}
__device__ __forceinline__ float bf_lo(uint32_t v) { return __uint_as_float(v << 16); }
__device__ __forceinline__ float bf_hi(uint32_t v) { return __uint_as_float(v & 0xFFFF0000u); }
__device__ __forceinline__ void stsm4(uint32_t addr, uint32_t a, uint32_t b, uint32_t c, uint32_t d) {
  asm volatile("stmatrix.sync.aligned.m8n8.x4.shared.b16 [%0], {%1,%2,%3,%4};" :: "r"(addr), "r"(a), "r"(b), "r"(c), "r"(d));
}
__device__ __forceinline__ void stsm4_t(uint32_t addr, uint32_t a, uint32_t b, uint32_t c, uint32_t d) {
  asm volatile("stmatrix.sync.aligned.m8n8.x4.trans.shared.b16 [%0], {%1,%2,%3,%4};" :: "r"(addr), "r"(a), "r"(b), "r"(c), "r"(d));
}
__device__ __forceinline__ void ldsm4(uint32_t addr, uint32_t& a, uint32_t& b, uint32_t& c, uint32_t& d) {
  asm volatile("ldmatrix.sync.aligned.m8n8.x4.shared.b16 {%0,%1,%2,%3}, [%4];" : "=r"(a), "=r"(b), "=r"(c), "=r"(d) : "r"(addr));
}
__device__ __forceinline__ uint4 lds128(uint32_t a) {
  uint4 v; asm volatile("ld.shared.v4.u32 {%0,%1,%2,%3}, [%4];" : "=r"(v.x), "=r"(v.y), "=r"(v.z), "=r"(v.w) : "r"(a)); return v;
}
__device__ __forceinline__ void sts128(uint32_t a, uint32_t x, uint32_t y, uint32_t z, uint32_t w) {
  asm volatile("st.shared.v4.u32 [%0], {%1,%2,%3,%4};" :: "r"(a), "r"(x), "r"(y), "r"(z), "r"(w));
}
__device__ __forceinline__ uint32_t hmul2_bf16(uint32_t a, uint32_t b) {
  uint32_t r; asm("mul.rn.bf16x2 %0, %1, %2;" : "=r"(r) : "r"(a), "r"(b)); return r;
}
__device__ __forceinline__ float gelu_tanh(float v) {
  float u = v * fmaf(0.0356774081f, v * v, 0.7978845608f);
  float t; asm("tanh.approx.f32 %0, %1;" : "=f"(t) : "f"(u));
  float hv = 0.5f * v;
  return fmaf(hv, t, hv);
}

template<int TB>
__device__ __forceinline__ void wgmma_n192(float (&d)[96], uint64_t da, uint64_t db, int scale_d) {
  asm volatile("{\n.reg .pred p;\nsetp.ne.b32 p, %98, 0;\n"
   "wgmma.mma_async.sync.aligned.m64n192k16.f32.bf16.bf16 {%0,%1,%2,%3,%4,%5,%6,%7,%8,%9,%10,%11,%12,%13,%14,%15,%16,%17,%18,%19,%20,%21,%22,%23,%24,%25,%26,%27,%28,%29,%30,%31,%32,%33,%34,%35,%36,%37,%38,%39,%40,%41,%42,%43,%44,%45,%46,%47,%48,%49,%50,%51,%52,%53,%54,%55,%56,%57,%58,%59,%60,%61,%62,%63,%64,%65,%66,%67,%68,%69,%70,%71,%72,%73,%74,%75,%76,%77,%78,%79,%80,%81,%82,%83,%84,%85,%86,%87,%88,%89,%90,%91,%92,%93,%94,%95}, %96, %97, p, 1, 1, 0, %99;\n}"
   : "+f"(d[0]),"+f"(d[1]),"+f"(d[2]),"+f"(d[3]),"+f"(d[4]),"+f"(d[5]),"+f"(d[6]),"+f"(d[7]),"+f"(d[8]),"+f"(d[9]),"+f"(d[10]),"+f"(d[11]),"+f"(d[12]),"+f"(d[13]),"+f"(d[14]),"+f"(d[15]),"+f"(d[16]),"+f"(d[17]),"+f"(d[18]),"+f"(d[19]),"+f"(d[20]),"+f"(d[21]),"+f"(d[22]),"+f"(d[23]),"+f"(d[24]),"+f"(d[25]),"+f"(d[26]),"+f"(d[27]),"+f"(d[28]),"+f"(d[29]),"+f"(d[30]),"+f"(d[31]),"+f"(d[32]),"+f"(d[33]),"+f"(d[34]),"+f"(d[35]),"+f"(d[36]),"+f"(d[37]),"+f"(d[38]),"+f"(d[39]),"+f"(d[40]),"+f"(d[41]),"+f"(d[42]),"+f"(d[43]),"+f"(d[44]),"+f"(d[45]),"+f"(d[46]),"+f"(d[47]),"+f"(d[48]),"+f"(d[49]),"+f"(d[50]),"+f"(d[51]),"+f"(d[52]),"+f"(d[53]),"+f"(d[54]),"+f"(d[55]),"+f"(d[56]),"+f"(d[57]),"+f"(d[58]),"+f"(d[59]),"+f"(d[60]),"+f"(d[61]),"+f"(d[62]),"+f"(d[63]),"+f"(d[64]),"+f"(d[65]),"+f"(d[66]),"+f"(d[67]),"+f"(d[68]),"+f"(d[69]),"+f"(d[70]),"+f"(d[71]),"+f"(d[72]),"+f"(d[73]),"+f"(d[74]),"+f"(d[75]),"+f"(d[76]),"+f"(d[77]),"+f"(d[78]),"+f"(d[79]),"+f"(d[80]),"+f"(d[81]),"+f"(d[82]),"+f"(d[83]),"+f"(d[84]),"+f"(d[85]),"+f"(d[86]),"+f"(d[87]),"+f"(d[88]),"+f"(d[89]),"+f"(d[90]),"+f"(d[91]),"+f"(d[92]),"+f"(d[93]),"+f"(d[94]),"+f"(d[95])
   : "l"(da), "l"(db), "r"(scale_d), "n"(TB));
}
template<int TB>
__device__ __forceinline__ void wgmma_n160(float (&d)[80], uint64_t da, uint64_t db, int scale_d) {
  asm volatile("{\n.reg .pred p;\nsetp.ne.b32 p, %82, 0;\n"
   "wgmma.mma_async.sync.aligned.m64n160k16.f32.bf16.bf16 {%0,%1,%2,%3,%4,%5,%6,%7,%8,%9,%10,%11,%12,%13,%14,%15,%16,%17,%18,%19,%20,%21,%22,%23,%24,%25,%26,%27,%28,%29,%30,%31,%32,%33,%34,%35,%36,%37,%38,%39,%40,%41,%42,%43,%44,%45,%46,%47,%48,%49,%50,%51,%52,%53,%54,%55,%56,%57,%58,%59,%60,%61,%62,%63,%64,%65,%66,%67,%68,%69,%70,%71,%72,%73,%74,%75,%76,%77,%78,%79}, %80, %81, p, 1, 1, 0, %83;\n}"
   : "+f"(d[0]),"+f"(d[1]),"+f"(d[2]),"+f"(d[3]),"+f"(d[4]),"+f"(d[5]),"+f"(d[6]),"+f"(d[7]),"+f"(d[8]),"+f"(d[9]),"+f"(d[10]),"+f"(d[11]),"+f"(d[12]),"+f"(d[13]),"+f"(d[14]),"+f"(d[15]),"+f"(d[16]),"+f"(d[17]),"+f"(d[18]),"+f"(d[19]),"+f"(d[20]),"+f"(d[21]),"+f"(d[22]),"+f"(d[23]),"+f"(d[24]),"+f"(d[25]),"+f"(d[26]),"+f"(d[27]),"+f"(d[28]),"+f"(d[29]),"+f"(d[30]),"+f"(d[31]),"+f"(d[32]),"+f"(d[33]),"+f"(d[34]),"+f"(d[35]),"+f"(d[36]),"+f"(d[37]),"+f"(d[38]),"+f"(d[39]),"+f"(d[40]),"+f"(d[41]),"+f"(d[42]),"+f"(d[43]),"+f"(d[44]),"+f"(d[45]),"+f"(d[46]),"+f"(d[47]),"+f"(d[48]),"+f"(d[49]),"+f"(d[50]),"+f"(d[51]),"+f"(d[52]),"+f"(d[53]),"+f"(d[54]),"+f"(d[55]),"+f"(d[56]),"+f"(d[57]),"+f"(d[58]),"+f"(d[59]),"+f"(d[60]),"+f"(d[61]),"+f"(d[62]),"+f"(d[63]),"+f"(d[64]),"+f"(d[65]),"+f"(d[66]),"+f"(d[67]),"+f"(d[68]),"+f"(d[69]),"+f"(d[70]),"+f"(d[71]),"+f"(d[72]),"+f"(d[73]),"+f"(d[74]),"+f"(d[75]),"+f"(d[76]),"+f"(d[77]),"+f"(d[78]),"+f"(d[79])
   : "l"(da), "l"(db), "r"(scale_d), "n"(TB));
}
template<int TB>
__device__ __forceinline__ void wgmma_n96(float (&d)[48], uint64_t da, uint64_t db, int scale_d) {
  asm volatile("{\n.reg .pred p;\nsetp.ne.b32 p, %50, 0;\n"
   "wgmma.mma_async.sync.aligned.m64n96k16.f32.bf16.bf16 {%0,%1,%2,%3,%4,%5,%6,%7,%8,%9,%10,%11,%12,%13,%14,%15,%16,%17,%18,%19,%20,%21,%22,%23,%24,%25,%26,%27,%28,%29,%30,%31,%32,%33,%34,%35,%36,%37,%38,%39,%40,%41,%42,%43,%44,%45,%46,%47}, %48, %49, p, 1, 1, 0, %51;\n}"
   : "+f"(d[0]),"+f"(d[1]),"+f"(d[2]),"+f"(d[3]),"+f"(d[4]),"+f"(d[5]),"+f"(d[6]),"+f"(d[7]),"+f"(d[8]),"+f"(d[9]),"+f"(d[10]),"+f"(d[11]),"+f"(d[12]),"+f"(d[13]),"+f"(d[14]),"+f"(d[15]),"+f"(d[16]),"+f"(d[17]),"+f"(d[18]),"+f"(d[19]),"+f"(d[20]),"+f"(d[21]),"+f"(d[22]),"+f"(d[23]),"+f"(d[24]),"+f"(d[25]),"+f"(d[26]),"+f"(d[27]),"+f"(d[28]),"+f"(d[29]),"+f"(d[30]),"+f"(d[31]),"+f"(d[32]),"+f"(d[33]),"+f"(d[34]),"+f"(d[35]),"+f"(d[36]),"+f"(d[37]),"+f"(d[38]),"+f"(d[39]),"+f"(d[40]),"+f"(d[41]),"+f"(d[42]),"+f"(d[43]),"+f"(d[44]),"+f"(d[45]),"+f"(d[46]),"+f"(d[47])
   : "l"(da), "l"(db), "r"(scale_d), "n"(TB));
}

template<int N, int TB>
__device__ __forceinline__ void wgmma_n(float (&d)[N / 2], uint64_t da, uint64_t db) {
  if constexpr (N == 192) wgmma_n192<TB>(d, da, db, 1);
  else if constexpr (N == 160) wgmma_n160<TB>(d, da, db, 1);
  else wgmma_n96<TB>(d, da, db, 1);
}

template<int R>
__device__ __forceinline__ void pin(float (&acc)[2][R]) {
  #pragma unroll
  for (int mi = 0; mi < 2; mi++)
    #pragma unroll
    for (int i = 0; i < R; i++) asm volatile("" : "+f"(acc[mi][i]) :: "memory");
}
template<int R>
__device__ __forceinline__ void zero(float (&acc)[2][R]) {
  #pragma unroll
  for (int i = 0; i < R; i++) { acc[0][i] = 0.f; acc[1][i] = 0.f; }
  pin(acc);
}

template<int N, int TB, bool CONT, int ORD_BAR>
__device__ __forceinline__ void mainloop(float (&acc)[2][N / 2], uint32_t sbase, uint32_t stage_bytes, int g0, int nk, int total, int mswap) {
  const uint32_t full0 = sbase + BAR_OFF, empty0 = full0 + 8 * STAGES, ring = sbase + RING_OFF;
  const int t = threadIdx.x & 127;
  const uint32_t da0 = (((ring + mswap * 8192) & 0x3FFFF) >> 4) | 0x10000u, da1 = (((ring + (mswap ^ 1) * 8192) & 0x3FFFF) >> 4) | 0x10000u;
  const uint32_t db0 = (((ring + A_BYTES) & 0x3FFFF) >> 4) | ((TB == 2 ? 256u : TB ? 512u : 1u) << 16);
  constexpr uint32_t HI_A = 0x40000040u, HI_B = TB == 2 ? 0x80000020u : 0x40000040u;
  #pragma unroll 1
  for (int g = g0; g < g0 + nk; g++) {
    const int s = g & (STAGES - 1);
    const uint32_t so = s * (stage_bytes >> 4);
    mbar_wait(full0 + 8 * s, (g / STAGES) & 1);
    wgmma_fence();
    #pragma unroll
    for (int k = 0; k < 4; k++) {
      const uint64_t db = desc64(db0 + so + (TB == 2 ? k * 64 : TB ? k * 128 : k * 2), HI_B);
      wgmma_n<N, TB != 0>(acc[0], desc64(da0 + so + k * 2, HI_A), db);
      wgmma_n<N, TB != 0>(acc[1], desc64(da1 + so + k * 2, HI_A), db);
    }
    wgmma_commit();
    if (ORD_BAR != 0 && g == g0 + nk - 1) bar_arrive<ORD_BAR>(256);
    wgmma_wait<1>();
    if (t < 2 && (CONT || g > g0) && g - 1 + STAGES <= total) mbar_arrive_cluster(empty0 + 8 * ((g - 1) & (STAGES - 1)), t);
  }
}
template<int R>
__device__ __forceinline__ void drain(float (&acc)[2][R], uint32_t sbase, int glast, int total) {
  wgmma_wait<0>();
  pin(acc);
  const int t = threadIdx.x & 127;
  if (t < 2 && glast + STAGES <= total) mbar_arrive_cluster(sbase + BAR_OFF + 8 * STAGES + 8 * (glast & (STAGES - 1)), t);
}

__device__ __forceinline__ void set_flag(int slot, int byte, unsigned epoch) {
  asm volatile("st.relaxed.gpu.global.u8 [%0], %1;" :: "l"(g_flags + slot * 256 + byte), "r"(epoch & 255u) : "memory");
}
__device__ __forceinline__ unsigned get_flag(int slot, int byte) {
  unsigned v; asm volatile("ld.relaxed.gpu.global.u8 %0, [%1];" : "=r"(v) : "l"(g_flags + slot * 256 + byte) : "memory"); return v;
}
__device__ __forceinline__ void publish(int slot, int byte, unsigned epoch) {
  asm volatile("fence.acq_rel.gpu;" ::: "memory");
  set_flag(slot, byte, epoch);
}

__device__ __forceinline__ float sum8(uint4 v) {
  return ((bf_lo(v.x) + bf_hi(v.x)) + (bf_lo(v.y) + bf_hi(v.y))) + ((bf_lo(v.z) + bf_hi(v.z)) + (bf_lo(v.w) + bf_hi(v.w)));
}
__device__ __forceinline__ uint4 ldg128(const void* p) {
  uint4 v; asm volatile("ld.global.nc.v4.u32 {%0,%1,%2,%3}, [%4];" : "=r"(v.x), "=r"(v.y), "=r"(v.z), "=r"(v.w) : "l"(p)); return v;
}
__device__ __forceinline__ void ln_load(const bf16* __restrict__ x, int cta, uint4 (&rv)[5]) {
  const int t = threadIdx.x - 128, row = cta * 16 + (t >> 4), c = t & 15;
  #pragma unroll
  for (int j = 0; j < 5; j++) rv[j] = ldg128(reinterpret_cast<const uint4*>(x + (size_t)row * DM) + c + 16 * j);
}
__device__ __forceinline__ void ln_rows(const uint4 (&rv)[5], int cta, unsigned epoch) {
  const int t = threadIdx.x - 128, row = cta * 16 + (t >> 4), c = t & 15;
  const float sh = __shfl_sync(0xffffffffu, bf_lo(rv[0].x), t & 16);
  float d[40], s = 0.f, q = 0.f;
  #pragma unroll
  for (int j = 0; j < 5; j++) {
    const uint32_t u[4] = {rv[j].x, rv[j].y, rv[j].z, rv[j].w};
    #pragma unroll
    for (int e = 0; e < 4; e++) {
      const float d0 = bf_lo(u[e]) - sh, d1 = bf_hi(u[e]) - sh;
      d[j * 8 + e * 2] = d0; d[j * 8 + e * 2 + 1] = d1;
      s += d0 + d1; q = fmaf(d0, d0, q); q = fmaf(d1, d1, q);
    }
  }
  #pragma unroll
  for (int o = 1; o < 16; o <<= 1) { s += __shfl_xor_sync(0xffffffffu, s, o); q += __shfl_xor_sync(0xffffffffu, q, o); }
  const float md = s * (1.f / DM);
  const float r = rsqrtf(fmaxf(fmaf(q, 1.f / DM, -md * md), 0.f) + LN_EPS), o = -md * r;
  if (c == 0) st_vol2(&g_xstat[row], __float_as_uint(r), (__float_as_uint(-(md + sh) * r) & ~255u) | (epoch & 255u));
  #pragma unroll
  for (int j = 0; j < 5; j++) {
    const float* a = &d[j * 8];
    stg128(reinterpret_cast<uint4*>(g_xn + (size_t)row * DM) + c + 16 * j, make_uint4(
           pack_bf16(fmaf(a[0], r, o), fmaf(a[1], r, o)), pack_bf16(fmaf(a[2], r, o), fmaf(a[3], r, o)),
           pack_bf16(fmaf(a[4], r, o), fmaf(a[5], r, o)), pack_bf16(fmaf(a[6], r, o), fmaf(a[7], r, o))));
  }
  bar_arrive<BAR_LN>(288);
}
__device__ __forceinline__ void colsum_part(const bf16* __restrict__ win, int cta, unsigned epoch) {
  const int t = threadIdx.x & 127, w = t >> 5, l = t & 31;
  const int cj = min(cta, 119), cg = cj % 24, rg = cj / 24;
  uint4 cv[4];
  #pragma unroll
  for (int j = 0; j < 4; j++) cv[j] = ldg128(reinterpret_cast<const uint4*>(win + (size_t)(rg * 128 + w * 32 + j * 8 + (l >> 2)) * FF + FH + cg * 32) + (l & 3));
  float v[8];
  v[0] = (bf_lo(cv[0].x) + bf_lo(cv[1].x)) + (bf_lo(cv[2].x) + bf_lo(cv[3].x)); v[1] = (bf_hi(cv[0].x) + bf_hi(cv[1].x)) + (bf_hi(cv[2].x) + bf_hi(cv[3].x));
  v[2] = (bf_lo(cv[0].y) + bf_lo(cv[1].y)) + (bf_lo(cv[2].y) + bf_lo(cv[3].y)); v[3] = (bf_hi(cv[0].y) + bf_hi(cv[1].y)) + (bf_hi(cv[2].y) + bf_hi(cv[3].y));
  v[4] = (bf_lo(cv[0].z) + bf_lo(cv[1].z)) + (bf_lo(cv[2].z) + bf_lo(cv[3].z)); v[5] = (bf_hi(cv[0].z) + bf_hi(cv[1].z)) + (bf_hi(cv[2].z) + bf_hi(cv[3].z));
  v[6] = (bf_lo(cv[0].w) + bf_lo(cv[1].w)) + (bf_lo(cv[2].w) + bf_lo(cv[3].w)); v[7] = (bf_hi(cv[0].w) + bf_hi(cv[1].w)) + (bf_hi(cv[2].w) + bf_hi(cv[3].w));
  #pragma unroll
  for (int st = 0; st < 3; st++) {
    const int n = 4 >> st;
    const bool up = (l & (4 * n)) != 0;
    #pragma unroll
    for (int e = 0; e < 4; e++)
      if (e < n) { const float keep = up ? v[e + n] : v[e], send = up ? v[e] : v[e + n]; v[e] = keep + __shfl_xor_sync(0xffffffffu, send, 4 * n); }
  }
  float* red = reinterpret_cast<float*>(smem + RED_OFF);
  red[w * 32 + (l & 3) * 8 + (l >> 2)] = v[0];
  bar_sync<BAR_WG2>(128);
  if (t < 32) st_vol2(&g_csum[rg * FH + cg * 32 + t], __float_as_uint((red[t] + red[32 + t]) + (red[64 + t] + red[96 + t])), epoch);
}

__device__ __forceinline__ void a_entry(int g, int grp, int rb, int& mi, int& kb) {
  if (g < 10) { mi = M_X; kb = g; }
  else if (g < 20) { mi = M_XN; kb = g - 10; }
  else if (grp == 0) {
    if (g < 52) { mi = M_WSP; kb = (g - 20); }
    else if (g < 52 + NX) { mi = M_WSIM; kb = g - 52 + 32 - NX; }
    else { mi = M_H; kb = g - 52 - NX; }
  } else {
    if (g < 30) { mi = M_XN; kb = g - 20; }
    else if (g < 62) { mi = M_WSRE; kb = (g - 30); }
    else { mi = M_WSIM; kb = g - 62; }
  }
}

__global__ void __cluster_dims__(2, 1, 1) __launch_bounds__(384, 1)
fused_kernel(const __grid_constant__ Maps maps, const bf16* __restrict__ x, const bf16* __restrict__ win, const bf16* __restrict__ bsp) {
  const uint32_t sbase = smem_u32(smem);
  const uint32_t full0 = sbase + BAR_OFF, empty0 = full0 + 8 * STAGES, dep0 = empty0 + 8 * STAGES, ring = sbase + RING_OFF;
  const int tid = threadIdx.x, wg = __shfl_sync(0xffffffffu, tid >> 7, 0);
  const int rank = blockIdx.x & 1;
  const int grp = (blockIdx.x >> 1) & 1, half = (blockIdx.x >> 2) & 1, rb = blockIdx.x >> 3;
  const int ct = half * 2 + rank, c8 = grp * 4 + ct;
  const int cta = rb * 8 + half * 4 + grp * 2 + rank;
  const int total = grp == 0 ? KB_A : KB_B;
  const uint32_t stage_bytes = grp == 0 ? STAGE_A : STAGE_B;

  uint4 rv[5];
  if (wg != 0) ln_load(x, cta, rv);
  const unsigned epoch = (ld_relaxed(&g_done) >> 7) + 1u;
  if (tid == 0) {
    TS(0, 0);
    for (int s = 0; s < STAGES; s++) { mbar_init(full0 + 8 * s, 2); mbar_init(empty0 + 8 * s, 2); mbar_init(dep0 + 8 * s, 1); }
    *reinterpret_cast<volatile int*>(smem + READY_OFF) = 0;
    asm volatile("fence.mbarrier_init.release.cluster;" ::: "memory");
  }
  __syncthreads();
  asm volatile("barrier.cluster.arrive.relaxed.aligned;" ::: "memory");

  if (wg == 0) {
    asm volatile("setmaxnreg.dec.sync.aligned.u32 40;");
    const int warp = tid >> 5, lane = tid & 31;
    if (warp == 0) {
      const int row = rb * 128;
      if (lane == 0) {
        for (int g = 0; g < STAGES; g++) {
          mbar_expect_tx(full0 + 8 * g, A_BYTES);
          tma_load_2d(ring + g * stage_bytes, &maps.m[M_X], full0 + 8 * g, g * 64, row);
          tma_load_2d(ring + g * stage_bytes + 8192, &maps.m[M_X], full0 + 8 * g, g * 64, row + 64);
        }
      }
      __syncwarp();
      cluster_wait();
      if (lane == 0) {
        #pragma unroll 1
        for (int g = STAGES; g < total; g++) {
          int mi, kb;
          a_entry(g, grp, rb, mi, kb);
          if (g == 10 || (mi == M_H && kb == 0)) { TS(0, g > 10 ? 3 : 1); mbar_wait(dep0 + (g > 10 ? 24 : 0), 0); fence_async_global(); TS(0, g > 10 ? 4 : 2); }
          const int s = g & (STAGES - 1);
          mbar_wait(empty0 + 8 * s, ((g / STAGES) & 1) ^ 1);
          mbar_expect_tx(full0 + 8 * s, A_BYTES);
          tma_load_2d_mc(ring + s * stage_bytes + rank * 8192, &maps.m[mi], full0 + 8 * s, kb * 64, row + rank * 64, 3);
        }
        const int s = total & (STAGES - 1);
        mbar_wait(empty0 + 8 * s, ((total / STAGES) & 1) ^ 1);
        mbar_expect_tx(full0 + 8 * s, 20480);
        mbar_arrive(full0 + 8 * s);
        tma_load_2d(ring + s * stage_bytes, &maps.m[M_XR], full0 + 8 * s, ct * 160, row + grp * 64);
        TS(0, 5);
      }
    } else if (warp == 1) {
      if (lane == 0) {
        int have = 0;
        #pragma unroll 1
        for (int g = 0; g < total; g++) {
          int kind = 1, mi, kb, c, dep = 0, need = 0;
          uint32_t bytes = 20480;
          if (g < 10) { kind = 0; mi = M_WIN32; kb = g; c = 24 + 3 * c8; bytes = 12288; }
          else if (grp == 0) {
            if (g < 20) { kind = 0; mi = M_WIN3; kb = g - 10; c = 3 * ct; bytes = 24576; }
            else if (g < 52) { kind = 0; mi = M_Z23; kb = (g - 20); c = 3 * ct; bytes = 24576; need = ((g - 20) >> 1) + 1; }
            else if (g < 52 + NX) { mi = M_AB; kb = g - 52 + 32 - NX; c = DM + ct * 160; dep = g == 52 ? 2 : 0; }
            else { kind = 0; mi = M_WOUT; kb = g - 52 - NX; c = ct * 5; }
          } else {
            if (g < 30) { mi = g < 20 ? M_WDRE : M_WDIM; kb = g < 20 ? g - 10 : g - 20; c = ct * 160; }
            else if (g < 62) { mi = M_AB; kb = (g - 30); c = ct * 160; need = ((g - 30) >> 1) + 1; }
            else { mi = M_AB; kb = g - 62; c = ct * 160 + DM; dep = g == 62 ? 2 : 0; }
          }
          if (need > have) {
            if (need == 1) TS(1, 0);
            unsigned it = 0;
            while ((have = *reinterpret_cast<volatile int*>(smem + READY_OFF)) < need && ++it < 50 * POLL_LIMIT) {}
            fence_async_global();
            if (need == 1) { TS(1, 1); TC(1); }
          }
          if (dep) { TS(1, dep * 2 - 2); mbar_wait(dep0 + 8 * dep, 0); fence_async_global(); TS(1, dep * 2 - 1); TC(dep); }
          const int s = g & (STAGES - 1);
          const uint32_t dst = ring + s * stage_bytes + A_BYTES, fb = full0 + 8 * s;
          mbar_wait(empty0 + 8 * s, ((g / STAGES) & 1) ^ 1);
          mbar_expect_tx(fb, bytes);
          if (kind == 0) tma_load_3d(dst, &maps.m[mi], fb, 0, kb * 64, c);
          else tma_load_2d(dst, &maps.m[mi], fb, kb * 64, c);
        }
      }
      __syncwarp();
      cluster_wait();
    } else if (warp == 2) {
      cluster_wait();
      {
        unsigned it = 0;
        uint2 v[4];
        while (true) {
          bool ok = true;
          #pragma unroll
          for (int i = 0; i < 4; i++) { v[i] = ld_vol2(&g_xstat[rb * 128 + i * 32 + lane]); ok = ok && ((v[i].y ^ epoch) & 255u) == 0; }
          if (ok || ++it > POLL_LIMIT) break;
          __nanosleep(POLL_NS);
        }
        #pragma unroll
        for (int i = 0; i < 4; i++) reinterpret_cast<uint2*>(smem + ROWSTAT_OFF)[i * 32 + lane] = make_uint2(v[i].x, v[i].y & ~255u);
        __syncwarp();
        TS(0, 6);
        bar_arrive<BAR_STATS>(192);
      }
      #pragma unroll 1
      for (int d = 0; d < 4 - grp; d++) {
        const int slot = d == 0 ? F_XN + rb : d == 3 ? F_H + rb : d == 2 ? F_B + ct : grp == 0 ? F_Z + ct : F_A + ct;
        const int byte = d == 0 ? lane & 7 : d == 3 ? lane & 3 : (d == 1 && grp == 0) ? lane : lane >> 1;
        unsigned it = 0, m;
        while ((m = __ballot_sync(0xffffffffu, get_flag(slot, byte) != (epoch & 255u))) != 0 && ++it < POLL_LIMIT) {
          if (d == 1 && lane == 0) *reinterpret_cast<volatile int*>(smem + READY_OFF) = (__ffs(m) - 1) >> 1;
          __nanosleep(WATCH_NS);
        }
        if (d == 1 && lane == 0) *reinterpret_cast<volatile int*>(smem + READY_OFF) = 16;
        TS(0, 8 + d * 2);
        fence_async_global();
        __syncwarp();
        TS(0, 9 + d * 2);
        if (lane == 0) mbar_arrive(dep0 + 8 * d);
      }
    } else {
      cluster_wait();
      bar_sync<BAR_LN>(288);
      if (lane == 0) { TS(1, 5); publish(F_XN + rb, cta & 7, epoch); TS(1, 6); }
      __syncwarp();
      #pragma unroll 1
      for (int i = 0; i < 3; i++) {
        unsigned it = 0;
        while (true) {
          bool ok = true;
          float a = 0.f;
          #pragma unroll
          for (int p = 0; p < 5; p++) { const uint2 u = ld_vol2(&g_csum[p * FH + c8 * 96 + i * 32 + lane]); ok = ok && u.y == epoch; a += __uint_as_float(u.x); }
          reinterpret_cast<float*>(smem + COLSUM_OFF)[i * 32 + lane] = a;
          if (ok || ++it > POLL_LIMIT) break;
          __nanosleep(POLL_NS);
        }
      }
      __syncwarp();
      TS(1, 4);
      bar_arrive<BAR_STATS>(192);
      bar_sync<BAR_PUB1>(160);
      if (lane == 0) {
        TS(1, 7);
        tma_store_3d(&maps.m[M_Z232], ring + 4 * stage_bytes, 0, rb * 128, 3 * c8);
        bulk_commit();
        bulk_wait_all();
        set_flag(F_Z + (c8 >> 1), rb * 2 + (c8 & 1), epoch);
        TS(1, 8);
      }
      __syncwarp();
      if (grp == 0) {
        bar_arrive<BAR_BUF>(160);
      } else {
        bar_sync<BAR_PUB2>(160);
        if (lane == 0) set_flag(F_A + ct, rb, epoch);
        TS(1, 9);
        __syncwarp();
      }
      bar_sync<BAR_PUB1>(160);
      if (lane == 0) set_flag(grp == 0 ? F_H + rb : F_B + ct, grp == 0 ? ct : rb, epoch);
      TS(1, 10);
    }
  } else {
    asm volatile("setmaxnreg.inc.sync.aligned.u32 232;");
    const int t = tid & 127, w = t >> 5, l = t & 31;
    const uint32_t buf = ring + 4 * stage_bytes;
    ln_rows(rv, cta, epoch);
    if (wg == 2) colsum_part(win, cta, epoch);
    TS(wg + 1, 0);
    cluster_wait();
    const int rl = w * 16 + ((l >> 3) & 1) * 8 + (l & 7);
    const int gr = w * 16 + (l & 15);
    const uint32_t st_base = buf + rl * 128;
    const uint32_t st_x = ((l >> 4) ^ (l & 7)) << 4;
    if (wg == 1) {
      float acc[2][48];
      zero(acc);
      mainloop<96, 2, false, BAR_ORD1>(acc, sbase, stage_bytes, 0, 10, total, 0);
      drain(acc, sbase, 9, total);
      TS(2, 2);
      bar_sync<BAR_STATS>(192);
      const float2* rs = reinterpret_cast<const float2*>(smem + ROWSTAT_OFF) + w * 16 + (l >> 2);
      const float2* cs = reinterpret_cast<const float2*>(smem + COLSUM_OFF) + (l & 3);
      float sum[4], sq[4];
      #pragma unroll
      for (int r = 0; r < 4; r++) {
        const float2 st = rs[(r >> 1) * 64 + (r & 1) * 8];
        float s0 = 0.f, q0 = 0.f;
        #pragma unroll
        for (int j = 0; j < 12; j++) {
          const float2 c = cs[j * 4];
          float* a = &acc[r >> 1][4 * j + (r & 1) * 2];
          a[0] = gelu_tanh(fmaf(a[0], st.x, st.y * c.x));
          a[1] = gelu_tanh(fmaf(a[1], st.x, st.y * c.y));
          s0 += a[0] + a[1]; q0 = fmaf(a[0], a[0], q0); q0 = fmaf(a[1], a[1], q0);
        }
        s0 += __shfl_xor_sync(0xffffffffu, s0, 1); q0 += __shfl_xor_sync(0xffffffffu, q0, 1);
        s0 += __shfl_xor_sync(0xffffffffu, s0, 2); q0 += __shfl_xor_sync(0xffffffffu, q0, 2);
        sum[r] = s0; sq[r] = q0;
      }
      TS(2, 4);
      float rstd, off;
      {
        const int qd = l & 3;
        const float sm = qd == 0 ? sum[0] : qd == 1 ? sum[1] : qd == 2 ? sum[2] : sum[3];
        const float sv = qd == 0 ? sq[0] : qd == 1 ? sq[1] : qd == 2 ? sq[2] : sq[3];
        const int row = (qd >> 1) * 64 + w * 16 + (qd & 1) * 8 + (l >> 2);
        const float mu = sm * (1.f / 96), m2 = fmaxf(sv - sm * mu, 0.f);
        st_vol2(&g_zstat[(rb * 8 + c8) * 128 + row], __float_as_uint(mu), (__float_as_uint(m2) & ~255u) | (epoch & 255u));
        uint2 v[7];
        unsigned n = 0;
        while (true) {
          bool ok = true;
          #pragma unroll
          for (int j = 0; j < 7; j++) v[j] = ld_vol2(&g_zstat[(rb * 8 + ((c8 + 1 + j) & 7)) * 128 + row]);
          #pragma unroll
          for (int j = 0; j < 7; j++) ok = ok && ((v[j].y ^ epoch) & 255u) == 0;
          if (ok || ++n > POLL_LIMIT) break;
          __nanosleep(POLL_NS);
        }
        float mean = mu, var = m2;
        #pragma unroll
        for (int j = 0; j < 7; j++) { mean += __uint_as_float(v[j].x); var += __uint_as_float(v[j].y & ~255u); }
        mean *= 0.125f;
        float d = (mu - mean) * (mu - mean);
        #pragma unroll
        for (int j = 0; j < 7; j++) d = fmaf(__uint_as_float(v[j].x) - mean, __uint_as_float(v[j].x) - mean, d);
        rstd = rsqrtf(fmaf(96.f, d, var) * (1.f / FH) + LN_EPS); off = -mean * rstd;
        __syncwarp();
      }
      TS(2, 5);
      #pragma unroll
      for (int mi = 0; mi < 2; mi++) {
        const float r0 = __shfl_sync(0xffffffffu, rstd, (l & 28) + mi * 2), o0 = __shfl_sync(0xffffffffu, off, (l & 28) + mi * 2);
        const float r1 = __shfl_sync(0xffffffffu, rstd, (l & 28) + mi * 2 + 1), o1 = __shfl_sync(0xffffffffu, off, (l & 28) + mi * 2 + 1);
        #pragma unroll
        for (int jj = 0; jj < 6; jj++) {
          const float* a = &acc[mi][8 * jj];
          stsm4(buf + (jj >> 1) * 8192 + mi * 4096 + rl * 64 + ((((jj & 1) * 2 + (l >> 4)) ^ ((l >> 1) & 3)) << 4),
                pack_bf16(fmaf(a[0], r0, o0), fmaf(a[1], r0, o0)), pack_bf16(fmaf(a[2], r1, o1), fmaf(a[3], r1, o1)),
                pack_bf16(fmaf(a[4], r0, o0), fmaf(a[5], r0, o0)), pack_bf16(fmaf(a[6], r1, o1), fmaf(a[7], r1, o1)));
        }
      }
      fence_async_smem();
      bar_arrive<BAR_PUB1>(160);
      TS(2, 6);
      if (grp == 0) {
        float acc[2][96];
        zero(acc);
        bar_sync<BAR_ORD2>(256);
        mainloop<192, 1, false, BAR_ORD1>(acc, sbase, STAGE_A, 20, 32, KB_A, 0);
        const float* bias = reinterpret_cast<const float*>(smem + BIAS_OFF) + w * 16 + (l >> 2);
        bar_sync<BAR_Z1>(256);
        drain(acc, sbase, 51, KB_A);
        TS(2, 7);
        {
          const float bb[4] = {bias[0], bias[8], bias[64], bias[72]};
          uint32_t z[2][4][4];
          #pragma unroll
          for (int i = 0; i < 4; i++) ldsm4(st_base + (st_x ^ (i << 5)), z[0][i][0], z[0][i][1], z[0][i][2], z[0][i][3]);
          #pragma unroll
          for (int bx = 0; bx < 6; bx++) {
            if (bx < 5) {
              #pragma unroll
              for (int i = 0; i < 4; i++)
                ldsm4(st_base + (bx + 1) * 8192 + (st_x ^ (i << 5)), z[(bx + 1) & 1][i][0], z[(bx + 1) & 1][i][1], z[(bx + 1) & 1][i][2], z[(bx + 1) & 1][i][3]);
            }
            const float b0 = bb[(bx / 3) * 2], b1 = bb[(bx / 3) * 2 + 1];
            #pragma unroll
            for (int i = 0; i < 4; i++) {
              const float* a = &acc[bx / 3][8 * ((bx % 3) * 4 + i)];
              const uint32_t* zz = z[bx & 1][i];
              stsm4(st_base + bx * 8192 + (st_x ^ (i << 5)),
                    hmul2_bf16(zz[0], pack_bf16(a[0] + b0, a[1] + b0)), hmul2_bf16(zz[1], pack_bf16(a[2] + b1, a[3] + b1)),
                    hmul2_bf16(zz[2], pack_bf16(a[4] + b0, a[5] + b0)), hmul2_bf16(zz[3], pack_bf16(a[6] + b1, a[7] + b1)));
            }
            fence_async_smem();
            __syncwarp();
            if (l == 0) {
              tma_store_2d(&maps.m[M_HS], buf + bx * 8192 + w * 2048, ct * 192 + (bx % 3) * 64, rb * 128 + (bx / 3) * 64 + w * 16);
              bulk_commit();
            }
          }
        }
        TS(2, 8);
        if (l == 0) bulk_wait_all();
        __syncwarp();
        bar_arrive<BAR_PUB1>(160);
        TS(2, 9);
        return;
      }
    } else {
      if (grp == 0) {
        reinterpret_cast<float*>(smem + BIAS_OFF)[t] = __bfloat162float(bsp[rb * 128 + t]);
        float acc[2][96];
        zero(acc);
        bar_sync<BAR_ORD1>(256);
        mainloop<192, 1, false, BAR_ORD2>(acc, sbase, STAGE_A, 10, 10, KB_A, 0);
        drain(acc, sbase, 19, KB_A);
        TS(3, 2);
        bar_sync<BAR_BUF>(160);
        #pragma unroll
        for (int mi = 0; mi < 2; mi++)
          #pragma unroll
          for (int jj = 0; jj < 12; jj++) {
            const float* a = &acc[mi][8 * jj];
            stsm4(st_base + mi * 24576 + (jj >> 2) * 8192 + (st_x ^ ((jj & 3) << 5)),
                  pack_bf16(a[0], a[1]), pack_bf16(a[2], a[3]), pack_bf16(a[4], a[5]), pack_bf16(a[6], a[7]));
          }
        __syncwarp();
        TS(3, 3);
        const uint32_t rbase = buf + (l >> 4) * 24576 + gr * 128;
        #pragma unroll 1
        for (int c2 = 0; c2 < 12; c2++) {
          const uint32_t ab = rbase + (c2 >> 2) * 8192;
          uint4 v[2];
          #pragma unroll
          for (int i = 0; i < 2; i++) v[i] = lds128(ab + (((((c2 & 3) * 2 + i) ^ l) & 7) << 4));
          #pragma unroll
          for (int i = 0; i < 2; i++)
            sts128(ab + (((((c2 & 3) * 2 + i) ^ l) & 7) << 4),
                   pack_bf16(gelu_tanh(bf_lo(v[i].x)), gelu_tanh(bf_hi(v[i].x))), pack_bf16(gelu_tanh(bf_lo(v[i].y)), gelu_tanh(bf_hi(v[i].y))),
                   pack_bf16(gelu_tanh(bf_lo(v[i].z)), gelu_tanh(bf_hi(v[i].z))), pack_bf16(gelu_tanh(bf_lo(v[i].w)), gelu_tanh(bf_hi(v[i].w))));
        }
        TS(3, 4);
        bar_arrive<BAR_Z1>(256);
      }
    }
    float acc[2][80];
    if (grp == 1) {
      zero(acc);
      if (wg == 2) {
        bar_sync<BAR_ORD1>(256);
        mainloop<160, 0, false, BAR_ORD2>(acc, sbase, STAGE_B, 10, 10, KB_B, 0);
      } else {
        bar_sync<BAR_ORD2>(256);
        mainloop<160, 0, false, BAR_ORD1>(acc, sbase, STAGE_B, 20, 10, KB_B, 0);
      }
      drain(acc, sbase, wg == 2 ? 19 : 29, KB_B);
      TS(wg + 1, wg == 1 ? 7 : 2);
      if (wg == 1) bar_sync<BAR_BUF>(256);
      const uint32_t sg = wg == 1 ? 0x80008000u : 0u;
      const uint32_t tb = buf + 24576 + ((l >> 4) * 8 + (l & 7)) * 128 + (((w * 2 + ((l >> 3) & 1)) ^ (l & 7)) << 4);
      #pragma unroll
      for (int mi = 0; mi < 2; mi++)
        #pragma unroll
        for (int jj = 0; jj < 10; jj++) {
          const float* a = &acc[mi][8 * jj];
          stsm4_t(tb + mi * 20480 + jj * 2048, pack_bf16(a[0], a[1]) ^ sg, pack_bf16(a[2], a[3]) ^ sg, pack_bf16(a[4], a[5]) ^ sg, pack_bf16(a[6], a[7]) ^ sg);
        }
      fence_async_smem();
      if (wg == 1) bar_sync<BAR_WG1>(128); else bar_sync<BAR_WG2>(128);
      TS(wg + 1, wg == 1 ? 8 : 6);
      if (l == 0) {
        #pragma unroll 1
        for (int i = 0; i < 2; i++) {
          tma_store_2d(&maps.m[M_ABS], buf + 24576 + i * 20480 + w * 5120, rb * 128 + i * 64, (2 - wg) * DM + ct * 160 + w * 40);
          bulk_commit();
        }
        bulk_wait_all();
      }
      __syncwarp();
      TS(wg + 1, wg == 1 ? 9 : 10);
      if (wg == 1) { bar_arrive<BAR_PUB1>(160); return; }
      bar_arrive<BAR_PUB2>(160);
      bar_arrive<BAR_BUF>(256);
    }
    zero(acc);
    bar_sync<BAR_ORD1>(256);
    mainloop<160, 0, false, 0>(acc, sbase, stage_bytes, grp == 0 ? 52 : 30, grp == 0 ? NX : 64 - NX, total, grp);
    if (grp == 0) mainloop<160, 2, true, 0>(acc, sbase, STAGE_A, 52 + NX, 12, KB_A, 0);
    drain(acc, sbase, total - 1, total);
    TS(3, 12);
    uint4* dst = g_part + (size_t)cta * 27 * 128 + t;
    const uint4* src = g_part + (size_t)(cta ^ 2) * 27 * 128 + t;
    #pragma unroll
    for (int i = 0; i < 27; i++)
      st_vol4(dst + i * 128, __float_as_uint(acc[1][3 * i]), __float_as_uint(acc[1][3 * i + 1]),
              __float_as_uint(i < 26 ? acc[1][3 * i + 2] : 0.f), epoch);
    TS(3, 13);
    const uint32_t slab = ring + (total & (STAGES - 1)) * stage_bytes + w * (16 * 320);
    const uint32_t addr = slab + (((l >> 3) & 1) * 8 + (l & 7)) * 320 + (l >> 4) * 16;
    mbar_wait(full0 + 8 * (total & (STAGES - 1)), (total / STAGES) & 1);
    #pragma unroll
    for (int jj = 0; jj < 10; jj++) {
      uint32_t z0, z1, z2, z3;
      ldsm4(addr + jj * 32, z0, z1, z2, z3);
      float* a = &acc[0][8 * jj];
      a[0] += bf_lo(z0); a[1] += bf_hi(z0); a[2] += bf_lo(z1); a[3] += bf_hi(z1);
      a[4] += bf_lo(z2); a[5] += bf_hi(z2); a[6] += bf_lo(z3); a[7] += bf_hi(z3);
    }
    {
      unsigned n = 0;
      while (ld_vol4(src + 26 * 128).w != epoch && ++n < POLL_LIMIT) __nanosleep(POLL_NS);
      uint4 v[27];
      while (true) {
        bool ok = true;
        #pragma unroll
        for (int i = 0; i < 27; i++) v[i] = ld_vol4(src + i * 128);
        #pragma unroll
        for (int i = 0; i < 27; i++) ok = ok && (v[i].w == epoch);
        if (ok || ++n > POLL_LIMIT) break;
      }
      #pragma unroll
      for (int i = 0; i < 27; i++) {
        acc[0][3 * i] += __uint_as_float(v[i].x);
        acc[0][3 * i + 1] += __uint_as_float(v[i].y);
        if (i < 26) acc[0][3 * i + 2] += __uint_as_float(v[i].z);
      }
    }
    TS(3, 14);
    #pragma unroll
    for (int jj = 0; jj < 10; jj++) {
      const float* a = &acc[0][8 * jj];
      stsm4(addr + jj * 32, pack_bf16(a[0], a[1]), pack_bf16(a[2], a[3]), pack_bf16(a[4], a[5]), pack_bf16(a[6], a[7]));
    }
    fence_async_smem();
    __syncwarp();
    if (l == 0) {
      tma_store_2d(&maps.m[M_OUT], slab, ct * 160, rb * 128 + grp * 64 + w * 16);
      bulk_commit();
      bulk_wait_read();
      if (w == 0) atomicAdd(&g_done, 1u);
    }
    TS(3, 15);
  }
}

typedef CUresult (*EncodeFn)(CUtensorMap*, CUtensorMapDataType, cuuint32_t, void*, const cuuint64_t*, const cuuint64_t*,
                             const cuuint32_t*, const cuuint32_t*, CUtensorMapInterleave, CUtensorMapSwizzle,
                             CUtensorMapL2promotion, CUtensorMapFloatOOBfill);

void make2d(EncodeFn enc, CUtensorMap* m, const void* p, uint64_t cols, uint64_t rows, uint32_t bc, uint32_t br, bool swz = true) {
  cuuint64_t gd[2] = {cols, rows}, gs[1] = {cols * 2};
  cuuint32_t bd[2] = {bc, br}, es[2] = {1, 1};
  enc(m, CU_TENSOR_MAP_DATA_TYPE_BFLOAT16, 2, const_cast<void*>(p), gd, gs, bd, es, CU_TENSOR_MAP_INTERLEAVE_NONE,
      swz ? CU_TENSOR_MAP_SWIZZLE_128B : CU_TENSOR_MAP_SWIZZLE_NONE, PROMO, CU_TENSOR_MAP_FLOAT_OOB_FILL_NONE);
}
void make3d(EncodeFn enc, CUtensorMap* m, const void* p, uint64_t cols, uint64_t rows, uint32_t cw, uint32_t nc, uint32_t br = 64) {
  cuuint64_t gd[3] = {cw, rows, cols / cw}, gs[2] = {cols * 2, cw * 2};
  cuuint32_t bd[3] = {cw, br, nc}, es[3] = {1, 1, 1};
  enc(m, CU_TENSOR_MAP_DATA_TYPE_BFLOAT16, 3, const_cast<void*>(p), gd, gs, bd, es, CU_TENSOR_MAP_INTERLEAVE_NONE,
      cw == 64 ? CU_TENSOR_MAP_SWIZZLE_128B : CU_TENSOR_MAP_SWIZZLE_64B, PROMO, CU_TENSOR_MAP_FLOAT_OOB_FILL_NONE);
}

}

extern "C" void kernel_launch(void* const* d_in, const int* in_sizes, int n_in, void* d_out, int out_size) {
  const bf16* x = (const bf16*)d_in[0];
  const bf16* wsre = (const bf16*)d_in[1];
  const bf16* wsim = (const bf16*)d_in[2];
  const bf16* wdre = (const bf16*)d_in[3];
  const bf16* wdim = (const bf16*)d_in[4];
  const bf16* win = (const bf16*)d_in[6];
  const bf16* wsp = (const bf16*)d_in[7];
  const bf16* bsp = (const bf16*)d_in[8];
  const bf16* wout = (const bf16*)d_in[9];

  void* fn = nullptr;
  cudaDriverEntryPointQueryResult qr;
  cudaGetDriverEntryPoint("cuTensorMapEncodeTiled", &fn, cudaEnableDefault, &qr);
  EncodeFn enc = (EncodeFn)fn;
  void *abT, *z2, *h, *xn;
  cudaGetSymbolAddress(&xn, g_xn);
  cudaGetSymbolAddress(&abT, g_abT);
  cudaGetSymbolAddress(&z2, g_z2);
  cudaGetSymbolAddress(&h, g_h);

  Maps maps;
  make2d(enc, &maps.m[M_X], x, DM, SEQ, 64, 64);
  make2d(enc, &maps.m[M_XN], xn, DM, SEQ, 64, 64);
  make3d(enc, &maps.m[M_Z232], z2, FH, SEQ, 32, 3, 128);
  make2d(enc, &maps.m[M_XR], x, DM, SEQ, 160, 64, false);
  make3d(enc, &maps.m[M_WIN32], win, FF, DM, 32, 3);
  make2d(enc, &maps.m[M_WSRE], wsre, SEQ, SEQ, 64, 64);
  make2d(enc, &maps.m[M_WSIM], wsim, SEQ, SEQ, 64, 64);
  make2d(enc, &maps.m[M_WSP], wsp, SEQ, SEQ, 64, 64);
  make2d(enc, &maps.m[M_H], h, FH, SEQ, 64, 64);
  make3d(enc, &maps.m[M_WIN3], win, FF, DM, 64, 3);
  make3d(enc, &maps.m[M_Z23], z2, FH, SEQ, 64, 3);
  make2d(enc, &maps.m[M_WDRE], wdre, DM, DM, 64, 160);
  make2d(enc, &maps.m[M_WDIM], wdim, DM, DM, 64, 160);
  make2d(enc, &maps.m[M_AB], abT, SEQ, 2 * DM, 64, 160);
  make3d(enc, &maps.m[M_WOUT], wout, DM, FH, 32, 5);
  make2d(enc, &maps.m[M_HS], h, FH, SEQ, 64, 16);
  make2d(enc, &maps.m[M_ABS], abT, SEQ, 2 * DM, 64, 40);
  make2d(enc, &maps.m[M_OUT], d_out, DM, SEQ, 160, 16, false);

  cudaFuncSetAttribute(fused_kernel, cudaFuncAttributeMaxDynamicSharedMemorySize, SMEM_BYTES);
  fused_kernel<<<128, 384, SMEM_BYTES>>>(maps, x, win, bsp);
}
```

```cpp
#include <cuda_runtime.h>
#include <cuda_bf16.h>
#include <cuda.h>
#include <stdint.h>

namespace {

typedef __nv_bfloat16 bf16;

constexpr int SEQ = 2048, DM = 640, FF = 1536, FH = 768;
#define NXV 11
constexpr int NX = NXV;
constexpr int STAGES = 4;
constexpr int A_BYTES = 16384;
constexpr int BIAS_OFF = 0;
constexpr int BAR_OFF = 512;
constexpr int READY_OFF = 640;
constexpr int ROWSTAT_OFF = 1024;
constexpr int COLSUM_OFF = 2048;
constexpr int RED_OFF = 2560;
constexpr int RING_OFF = 3072;
constexpr int STAGE_A = 40960, STAGE_B = 36864;
constexpr int SMEM_BYTES = RING_OFF + 4 * STAGE_A + 49152;
constexpr int KB_A = 20 + 32 + NX + 12;
constexpr int KB_B = 30 + 64 - NX;
constexpr float LN_EPS = 1e-5f;
constexpr unsigned POLL_LIMIT = 100000;
#define POLL_NS 100
#define PF_D 0
#define ROT 0
#define Z1_NS 0
#define INFL 2
#define LIM_G 1000
#define MAPV 0
#define PROMO CU_TENSOR_MAP_L2_PROMOTION_L2_128B
#define WATCH_NS 40
#define FIN_NS 50
#define PF_NS 150

constexpr int BAR_ORD1 = 1, BAR_ORD2 = 2, BAR_WG1 = 3, BAR_WG2 = 4, BAR_LN = 5, BAR_BUF = 6, BAR_Z1 = 7, BAR_PUB1 = 8, BAR_PUB2 = 9, BAR_STATS = 10;

enum { M_X, M_XN, M_XR, M_WIN32, M_Z232, M_WSRE, M_WSIM, M_WSP, M_H, M_WIN3, M_Z23, M_WDRE, M_WDIM, M_AB, M_WOUT, M_OUT, M_HS, M_ABS, M_COUNT };
struct Maps { CUtensorMap m[M_COUNT]; };

__device__ __align__(1024) bf16 g_abT[2 * DM * SEQ];
__device__ __align__(1024) bf16 g_z2[SEQ * FH];
__device__ __align__(1024) bf16 g_h[SEQ * FH];
__device__ __align__(1024) bf16 g_xn[SEQ * DM];
__device__ __align__(16) uint2 g_xstat[SEQ];
__device__ __align__(16) uint2 g_csum[5 * FH];
__device__ __align__(16) uint2 g_zstat[128 * 128];
__device__ __align__(16) uint4 g_part[128 * 27 * 128];
__device__ __align__(256) unsigned char g_flags[44 * 256];
constexpr int F_A = 0, F_B = 4, F_Z = 8, F_H = 12, F_XN = 28;
__device__ unsigned g_done;
#define TS(role, ev)
#define TC(i)

extern __shared__ __align__(1024) uint8_t smem[];

__device__ __forceinline__ uint32_t smem_u32(const void* p) { return (uint32_t)__cvta_generic_to_shared(p); }
__device__ __forceinline__ void mbar_init(uint32_t bar, uint32_t cnt) { asm volatile("mbarrier.init.shared::cta.b64 [%0], %1;" :: "r"(bar), "r"(cnt)); }
__device__ __forceinline__ void mbar_expect_tx(uint32_t bar, uint32_t bytes) { asm volatile("mbarrier.arrive.expect_tx.shared::cta.b64 _, [%0], %1;" :: "r"(bar), "r"(bytes) : "memory"); }
__device__ __forceinline__ void mbar_arrive(uint32_t bar) { asm volatile("mbarrier.arrive.shared::cta.b64 _, [%0];" :: "r"(bar) : "memory"); }
__device__ __forceinline__ void mbar_arrive_cluster(uint32_t bar, uint32_t cta) {
  asm volatile("{\n.reg .b32 ra;\nmapa.shared::cluster.u32 ra, %0, %1;\nmbarrier.arrive.shared::cluster.b64 _, [ra];\n}" :: "r"(bar), "r"(cta) : "memory");
}
__device__ __forceinline__ void mbar_wait(uint32_t bar, uint32_t parity) {
  asm volatile("{\n.reg .pred p;\n.reg .u32 n;\nmov.u32 n, 0;\n"
               "LW: mbarrier.try_wait.parity.shared::cta.b64 p, [%0], %1, 2000;\n@p bra LD;\n"
               "add.u32 n, n, 1;\nsetp.lt.u32 p, n, 20000;\n@p bra LW;\nLD:\n}" :: "r"(bar), "r"(parity) : "memory");
}
__device__ __forceinline__ void tma_load_2d(uint32_t dst, const CUtensorMap* map, uint32_t bar, int c0, int c1) {
  asm volatile("cp.async.bulk.tensor.2d.shared::cluster.global.mbarrier::complete_tx::bytes [%0], [%1, {%3, %4}], [%2];"
    :: "r"(dst), "l"((uint64_t)map), "r"(bar), "r"(c0), "r"(c1) : "memory");
}
__device__ __forceinline__ void tma_load_3d(uint32_t dst, const CUtensorMap* map, uint32_t bar, int c0, int c1, int c2) {
  asm volatile("cp.async.bulk.tensor.3d.shared::cluster.global.mbarrier::complete_tx::bytes [%0], [%1, {%3, %4, %5}], [%2];"
    :: "r"(dst), "l"((uint64_t)map), "r"(bar), "r"(c0), "r"(c1), "r"(c2) : "memory");
}
__device__ __forceinline__ void tma_load_2d_mc(uint32_t dst, const CUtensorMap* map, uint32_t bar, int c0, int c1, uint16_t mask) {
  asm volatile("cp.async.bulk.tensor.2d.shared::cluster.global.mbarrier::complete_tx::bytes.multicast::cluster [%0], [%1, {%3, %4}], [%2], %5;"
    :: "r"(dst), "l"((uint64_t)map), "r"(bar), "r"(c0), "r"(c1), "h"(mask) : "memory");
}
__device__ __forceinline__ void tma_store_2d(const CUtensorMap* map, uint32_t src, int c0, int c1) {
  asm volatile("cp.async.bulk.tensor.2d.global.shared::cta.bulk_group [%0, {%2, %3}], [%1];"
    :: "l"((uint64_t)map), "r"(src), "r"(c0), "r"(c1) : "memory");
}
__device__ __forceinline__ void tma_store_3d(const CUtensorMap* map, uint32_t src, int c0, int c1, int c2) {
  asm volatile("cp.async.bulk.tensor.3d.global.shared::cta.bulk_group [%0, {%2, %3, %4}], [%1];"
    :: "l"((uint64_t)map), "r"(src), "r"(c0), "r"(c1), "r"(c2) : "memory");
}
__device__ __forceinline__ void bulk_wait_all() { asm volatile("cp.async.bulk.wait_group 0;" ::: "memory"); }
__device__ __forceinline__ void bulk_commit() { asm volatile("cp.async.bulk.commit_group;" ::: "memory"); }
__device__ __forceinline__ void bulk_wait_read() { asm volatile("cp.async.bulk.wait_group.read 0;" ::: "memory"); }
__device__ __forceinline__ void fence_async_smem() { asm volatile("fence.proxy.async.shared::cta;" ::: "memory"); }
__device__ __forceinline__ void fence_async_global() { asm volatile("fence.proxy.async.global;" ::: "memory"); }
__device__ __forceinline__ void wgmma_fence() { asm volatile("wgmma.fence.sync.aligned;" ::: "memory"); }
__device__ __forceinline__ void wgmma_commit() { asm volatile("wgmma.commit_group.sync.aligned;" ::: "memory"); }
template<int N> __device__ __forceinline__ void wgmma_wait() { asm volatile("wgmma.wait_group.sync.aligned %0;" :: "n"(N) : "memory"); }
template<int ID> __device__ __forceinline__ void bar_sync(int n) { asm volatile("bar.sync %0, %1;" :: "n"(ID), "r"(n) : "memory"); }
template<int ID> __device__ __forceinline__ void bar_arrive(int n) { asm volatile("bar.arrive %0, %1;" :: "n"(ID), "r"(n) : "memory"); }
__device__ __forceinline__ void cluster_wait() { asm volatile("barrier.cluster.wait.aligned;" ::: "memory"); }
__device__ __forceinline__ uint64_t desc64(uint32_t lo, uint32_t hi) { return (uint64_t)lo | ((uint64_t)hi << 32); }
__device__ __forceinline__ uint4 ld_vol4(const uint4* p) {
  uint4 v; asm volatile("ld.relaxed.gpu.global.v4.u32 {%0,%1,%2,%3}, [%4];" : "=r"(v.x), "=r"(v.y), "=r"(v.z), "=r"(v.w) : "l"(p) : "memory"); return v;
}
__device__ __forceinline__ uint2 ld_vol2(const uint2* p) {
  uint2 v; asm volatile("ld.relaxed.gpu.global.v2.u32 {%0,%1}, [%2];" : "=r"(v.x), "=r"(v.y) : "l"(p) : "memory"); return v;
}
__device__ __forceinline__ void st_vol4(uint4* p, uint32_t a, uint32_t b, uint32_t c, uint32_t d) {
  asm volatile("st.relaxed.gpu.global.v4.u32 [%0], {%1,%2,%3,%4};" :: "l"(p), "r"(a), "r"(b), "r"(c), "r"(d) : "memory");
}
__device__ __forceinline__ void st_vol2(uint2* p, uint32_t a, uint32_t b) {
  asm volatile("st.relaxed.gpu.global.v2.u32 [%0], {%1,%2};" :: "l"(p), "r"(a), "r"(b) : "memory");
}
__device__ __forceinline__ void stg128(void* p, uint4 v) {
  asm volatile("st.global.v4.u32 [%0], {%1,%2,%3,%4};" :: "l"(p), "r"(v.x), "r"(v.y), "r"(v.z), "r"(v.w));
}
__device__ __forceinline__ unsigned ld_relaxed(const unsigned* p) {
  unsigned v; asm volatile("ld.relaxed.gpu.global.u32 %0, [%1];" : "=r"(v) : "l"(p) : "memory"); return v;
}
__device__ __forceinline__ uint32_t pack_bf16(float lo, float hi) {
  uint32_t r; asm("cvt.rn.bf16x2.f32 %0, %1, %2;" : "=r"(r) : "f"(hi), "f"(lo)); return r;
}
__device__ __forceinline__ float bf_lo(uint32_t v) { return __uint_as_float(v << 16); }
__device__ __forceinline__ float bf_hi(uint32_t v) { return __uint_as_float(v & 0xFFFF0000u); }
__device__ __forceinline__ void stsm4(uint32_t addr, uint32_t a, uint32_t b, uint32_t c, uint32_t d) {
  asm volatile("stmatrix.sync.aligned.m8n8.x4.shared.b16 [%0], {%1,%2,%3,%4};" :: "r"(addr), "r"(a), "r"(b), "r"(c), "r"(d));
}
__device__ __forceinline__ void stsm4_t(uint32_t addr, uint32_t a, uint32_t b, uint32_t c, uint32_t d) {
  asm volatile("stmatrix.sync.aligned.m8n8.x4.trans.shared.b16 [%0], {%1,%2,%3,%4};" :: "r"(addr), "r"(a), "r"(b), "r"(c), "r"(d));
}
__device__ __forceinline__ void ldsm4(uint32_t addr, uint32_t& a, uint32_t& b, uint32_t& c, uint32_t& d) {
  asm volatile("ldmatrix.sync.aligned.m8n8.x4.shared.b16 {%0,%1,%2,%3}, [%4];" : "=r"(a), "=r"(b), "=r"(c), "=r"(d) : "r"(addr));
}
__device__ __forceinline__ uint4 lds128(uint32_t a) {
  uint4 v; asm volatile("ld.shared.v4.u32 {%0,%1,%2,%3}, [%4];" : "=r"(v.x), "=r"(v.y), "=r"(v.z), "=r"(v.w) : "r"(a)); return v;
}
__device__ __forceinline__ void sts128(uint32_t a, uint32_t x, uint32_t y, uint32_t z, uint32_t w) {
  asm volatile("st.shared.v4.u32 [%0], {%1,%2,%3,%4};" :: "r"(a), "r"(x), "r"(y), "r"(z), "r"(w));
}
__device__ __forceinline__ uint32_t hmul2_bf16(uint32_t a, uint32_t b) {
  uint32_t r; asm("mul.rn.bf16x2 %0, %1, %2;" : "=r"(r) : "r"(a), "r"(b)); return r;
}
__device__ __forceinline__ float gelu_tanh(float v) {
  float u = v * fmaf(0.0356774081f, v * v, 0.7978845608f);
  float t; asm("tanh.approx.f32 %0, %1;" : "=f"(t) : "f"(u));
  float hv = 0.5f * v;
  return fmaf(hv, t, hv);
}

template<int TB>
__device__ __forceinline__ void wgmma_n192(float (&d)[96], uint64_t da, uint64_t db, int scale_d) {
  asm volatile("{\n.reg .pred p;\nsetp.ne.b32 p, %98, 0;\n"
   "wgmma.mma_async.sync.aligned.m64n192k16.f32.bf16.bf16 {%0,%1,%2,%3,%4,%5,%6,%7,%8,%9,%10,%11,%12,%13,%14,%15,%16,%17,%18,%19,%20,%21,%22,%23,%24,%25,%26,%27,%28,%29,%30,%31,%32,%33,%34,%35,%36,%37,%38,%39,%40,%41,%42,%43,%44,%45,%46,%47,%48,%49,%50,%51,%52,%53,%54,%55,%56,%57,%58,%59,%60,%61,%62,%63,%64,%65,%66,%67,%68,%69,%70,%71,%72,%73,%74,%75,%76,%77,%78,%79,%80,%81,%82,%83,%84,%85,%86,%87,%88,%89,%90,%91,%92,%93,%94,%95}, %96, %97, p, 1, 1, 0, %99;\n}"
   : "+f"(d[0]),"+f"(d[1]),"+f"(d[2]),"+f"(d[3]),"+f"(d[4]),"+f"(d[5]),"+f"(d[6]),"+f"(d[7]),"+f"(d[8]),"+f"(d[9]),"+f"(d[10]),"+f"(d[11]),"+f"(d[12]),"+f"(d[13]),"+f"(d[14]),"+f"(d[15]),"+f"(d[16]),"+f"(d[17]),"+f"(d[18]),"+f"(d[19]),"+f"(d[20]),"+f"(d[21]),"+f"(d[22]),"+f"(d[23]),"+f"(d[24]),"+f"(d[25]),"+f"(d[26]),"+f"(d[27]),"+f"(d[28]),"+f"(d[29]),"+f"(d[30]),"+f"(d[31]),"+f"(d[32]),"+f"(d[33]),"+f"(d[34]),"+f"(d[35]),"+f"(d[36]),"+f"(d[37]),"+f"(d[38]),"+f"(d[39]),"+f"(d[40]),"+f"(d[41]),"+f"(d[42]),"+f"(d[43]),"+f"(d[44]),"+f"(d[45]),"+f"(d[46]),"+f"(d[47]),"+f"(d[48]),"+f"(d[49]),"+f"(d[50]),"+f"(d[51]),"+f"(d[52]),"+f"(d[53]),"+f"(d[54]),"+f"(d[55]),"+f"(d[56]),"+f"(d[57]),"+f"(d[58]),"+f"(d[59]),"+f"(d[60]),"+f"(d[61]),"+f"(d[62]),"+f"(d[63]),"+f"(d[64]),"+f"(d[65]),"+f"(d[66]),"+f"(d[67]),"+f"(d[68]),"+f"(d[69]),"+f"(d[70]),"+f"(d[71]),"+f"(d[72]),"+f"(d[73]),"+f"(d[74]),"+f"(d[75]),"+f"(d[76]),"+f"(d[77]),"+f"(d[78]),"+f"(d[79]),"+f"(d[80]),"+f"(d[81]),"+f"(d[82]),"+f"(d[83]),"+f"(d[84]),"+f"(d[85]),"+f"(d[86]),"+f"(d[87]),"+f"(d[88]),"+f"(d[89]),"+f"(d[90]),"+f"(d[91]),"+f"(d[92]),"+f"(d[93]),"+f"(d[94]),"+f"(d[95])
   : "l"(da), "l"(db), "r"(scale_d), "n"(TB));
}
template<int TB>
__device__ __forceinline__ void wgmma_n160(float (&d)[80], uint64_t da, uint64_t db, int scale_d) {
  asm volatile("{\n.reg .pred p;\nsetp.ne.b32 p, %82, 0;\n"
   "wgmma.mma_async.sync.aligned.m64n160k16.f32.bf16.bf16 {%0,%1,%2,%3,%4,%5,%6,%7,%8,%9,%10,%11,%12,%13,%14,%15,%16,%17,%18,%19,%20,%21,%22,%23,%24,%25,%26,%27,%28,%29,%30,%31,%32,%33,%34,%35,%36,%37,%38,%39,%40,%41,%42,%43,%44,%45,%46,%47,%48,%49,%50,%51,%52,%53,%54,%55,%56,%57,%58,%59,%60,%61,%62,%63,%64,%65,%66,%67,%68,%69,%70,%71,%72,%73,%74,%75,%76,%77,%78,%79}, %80, %81, p, 1, 1, 0, %83;\n}"
   : "+f"(d[0]),"+f"(d[1]),"+f"(d[2]),"+f"(d[3]),"+f"(d[4]),"+f"(d[5]),"+f"(d[6]),"+f"(d[7]),"+f"(d[8]),"+f"(d[9]),"+f"(d[10]),"+f"(d[11]),"+f"(d[12]),"+f"(d[13]),"+f"(d[14]),"+f"(d[15]),"+f"(d[16]),"+f"(d[17]),"+f"(d[18]),"+f"(d[19]),"+f"(d[20]),"+f"(d[21]),"+f"(d[22]),"+f"(d[23]),"+f"(d[24]),"+f"(d[25]),"+f"(d[26]),"+f"(d[27]),"+f"(d[28]),"+f"(d[29]),"+f"(d[30]),"+f"(d[31]),"+f"(d[32]),"+f"(d[33]),"+f"(d[34]),"+f"(d[35]),"+f"(d[36]),"+f"(d[37]),"+f"(d[38]),"+f"(d[39]),"+f"(d[40]),"+f"(d[41]),"+f"(d[42]),"+f"(d[43]),"+f"(d[44]),"+f"(d[45]),"+f"(d[46]),"+f"(d[47]),"+f"(d[48]),"+f"(d[49]),"+f"(d[50]),"+f"(d[51]),"+f"(d[52]),"+f"(d[53]),"+f"(d[54]),"+f"(d[55]),"+f"(d[56]),"+f"(d[57]),"+f"(d[58]),"+f"(d[59]),"+f"(d[60]),"+f"(d[61]),"+f"(d[62]),"+f"(d[63]),"+f"(d[64]),"+f"(d[65]),"+f"(d[66]),"+f"(d[67]),"+f"(d[68]),"+f"(d[69]),"+f"(d[70]),"+f"(d[71]),"+f"(d[72]),"+f"(d[73]),"+f"(d[74]),"+f"(d[75]),"+f"(d[76]),"+f"(d[77]),"+f"(d[78]),"+f"(d[79])
   : "l"(da), "l"(db), "r"(scale_d), "n"(TB));
}
template<int TB>
__device__ __forceinline__ void wgmma_n96(float (&d)[48], uint64_t da, uint64_t db, int scale_d) {
  asm volatile("{\n.reg .pred p;\nsetp.ne.b32 p, %50, 0;\n"
   "wgmma.mma_async.sync.aligned.m64n96k16.f32.bf16.bf16 {%0,%1,%2,%3,%4,%5,%6,%7,%8,%9,%10,%11,%12,%13,%14,%15,%16,%17,%18,%19,%20,%21,%22,%23,%24,%25,%26,%27,%28,%29,%30,%31,%32,%33,%34,%35,%36,%37,%38,%39,%40,%41,%42,%43,%44,%45,%46,%47}, %48, %49, p, 1, 1, 0, %51;\n}"
   : "+f"(d[0]),"+f"(d[1]),"+f"(d[2]),"+f"(d[3]),"+f"(d[4]),"+f"(d[5]),"+f"(d[6]),"+f"(d[7]),"+f"(d[8]),"+f"(d[9]),"+f"(d[10]),"+f"(d[11]),"+f"(d[12]),"+f"(d[13]),"+f"(d[14]),"+f"(d[15]),"+f"(d[16]),"+f"(d[17]),"+f"(d[18]),"+f"(d[19]),"+f"(d[20]),"+f"(d[21]),"+f"(d[22]),"+f"(d[23]),"+f"(d[24]),"+f"(d[25]),"+f"(d[26]),"+f"(d[27]),"+f"(d[28]),"+f"(d[29]),"+f"(d[30]),"+f"(d[31]),"+f"(d[32]),"+f"(d[33]),"+f"(d[34]),"+f"(d[35]),"+f"(d[36]),"+f"(d[37]),"+f"(d[38]),"+f"(d[39]),"+f"(d[40]),"+f"(d[41]),"+f"(d[42]),"+f"(d[43]),"+f"(d[44]),"+f"(d[45]),"+f"(d[46]),"+f"(d[47])
   : "l"(da), "l"(db), "r"(scale_d), "n"(TB));
}

template<int N, int TB>
__device__ __forceinline__ void wgmma_n(float (&d)[N / 2], uint64_t da, uint64_t db) {
  if constexpr (N == 192) wgmma_n192<TB>(d, da, db, 1);
  else if constexpr (N == 160) wgmma_n160<TB>(d, da, db, 1);
  else wgmma_n96<TB>(d, da, db, 1);
}

template<int R>
__device__ __forceinline__ void pin(float (&acc)[2][R]) {
  #pragma unroll
  for (int mi = 0; mi < 2; mi++)
    #pragma unroll
    for (int i = 0; i < R; i++) asm volatile("" : "+f"(acc[mi][i]) :: "memory");
}
template<int R>
__device__ __forceinline__ void zero(float (&acc)[2][R]) {
  #pragma unroll
  for (int i = 0; i < R; i++) { acc[0][i] = 0.f; acc[1][i] = 0.f; }
  pin(acc);
}

template<int N, int TB, bool CONT, int ORD_BAR>
__device__ __forceinline__ void mainloop(float (&acc)[2][N / 2], uint32_t sbase, uint32_t stage_bytes, int g0, int nk, int total, int mswap) {
  const uint32_t full0 = sbase + BAR_OFF, empty0 = full0 + 8 * STAGES, ring = sbase + RING_OFF;
  const int t = threadIdx.x & 127;
  const uint32_t da0 = (((ring + mswap * 8192) & 0x3FFFF) >> 4) | 0x10000u, da1 = (((ring + (mswap ^ 1) * 8192) & 0x3FFFF) >> 4) | 0x10000u;
  const uint32_t db0 = (((ring + A_BYTES) & 0x3FFFF) >> 4) | ((TB == 2 ? 256u : TB ? 512u : 1u) << 16);
  constexpr uint32_t HI_A = 0x40000040u, HI_B = TB == 2 ? 0x80000020u : 0x40000040u;
  #pragma unroll 1
  for (int g = g0; g < g0 + nk; g++) {
    const int s = g & (STAGES - 1);
    const uint32_t so = s * (stage_bytes >> 4);
    mbar_wait(full0 + 8 * s, (g / STAGES) & 1);
    wgmma_fence();
    #pragma unroll
    for (int k = 0; k < 4; k++) {
      const uint64_t db = desc64(db0 + so + (TB == 2 ? k * 64 : TB ? k * 128 : k * 2), HI_B);
      wgmma_n<N, TB != 0>(acc[0], desc64(da0 + so + k * 2, HI_A), db);
      wgmma_n<N, TB != 0>(acc[1], desc64(da1 + so + k * 2, HI_A), db);
    }
    wgmma_commit();
    if (ORD_BAR != 0 && g == g0 + nk - 1) bar_arrive<ORD_BAR>(256);
    wgmma_wait<1>();
    if (t < 2 && (CONT || g > g0) && g - 1 + STAGES <= total) mbar_arrive_cluster(empty0 + 8 * ((g - 1) & (STAGES - 1)), t);
  }
}
template<int TB>
__device__ __forceinline__ void tail3(float (&acc)[2][80], uint32_t sbase, uint32_t stage_bytes, int total, int mswap) {
  const uint32_t full0 = sbase + BAR_OFF, empty0 = full0 + 8 * STAGES, ring = sbase + RING_OFF;
  const int t = threadIdx.x & 127;
  const uint32_t da0 = (((ring + mswap * 8192) & 0x3FFFF) >> 4) | 0x10000u, da1 = (((ring + (mswap ^ 1) * 8192) & 0x3FFFF) >> 4) | 0x10000u;
  const uint32_t db0 = (((ring + A_BYTES) & 0x3FFFF) >> 4) | ((TB == 2 ? 256u : 1u) << 16);
  constexpr uint32_t HI_A = 0x40000040u, HI_B = TB == 2 ? 0x80000020u : 0x40000040u;
  #pragma unroll 1
  for (int g = total - 3; g < total; g++) {
    const int s = g & (STAGES - 1);
    const uint32_t so = s * (stage_bytes >> 4);
    mbar_wait(full0 + 8 * s, (g / STAGES) & 1);
    wgmma_fence();
    #pragma unroll
    for (int k = 0; k < 4; k++) wgmma_n<160, TB != 0>(acc[1], desc64(da1 + so + k * 2, HI_A), desc64(db0 + so + (TB == 2 ? k * 64 : k * 2), HI_B));
    wgmma_commit();
    wgmma_wait<1>();
    if (t < 2 && g == total - 3) mbar_arrive_cluster(empty0 + 8 * ((g - 1) & (STAGES - 1)), t);
  }
  wgmma_fence();
  #pragma unroll
  for (int i = 0; i < 3; i++) {
    const uint32_t so = ((total - 3 + i) & (STAGES - 1)) * (stage_bytes >> 4);
    #pragma unroll
    for (int k = 0; k < 4; k++) wgmma_n<160, TB != 0>(acc[0], desc64(da0 + so + k * 2, HI_A), desc64(db0 + so + (TB == 2 ? k * 64 : k * 2), HI_B));
  }
  wgmma_commit();
}
template<int R>
__device__ __forceinline__ void drain(float (&acc)[2][R], uint32_t sbase, int glast, int total) {
  wgmma_wait<0>();
  pin(acc);
  const int t = threadIdx.x & 127;
  if (t < 2 && glast + STAGES <= total) mbar_arrive_cluster(sbase + BAR_OFF + 8 * STAGES + 8 * (glast & (STAGES - 1)), t);
}

__device__ __forceinline__ void set_flag(int slot, int byte, unsigned epoch) {
  asm volatile("st.relaxed.gpu.global.u8 [%0], %1;" :: "l"(g_flags + slot * 256 + byte), "r"(epoch & 255u) : "memory");
}
__device__ __forceinline__ unsigned get_flag(int slot, int byte) {
  unsigned v; asm volatile("ld.relaxed.gpu.global.u8 %0, [%1];" : "=r"(v) : "l"(g_flags + slot * 256 + byte) : "memory"); return v;
}
__device__ __forceinline__ void publish(int slot, int byte, unsigned epoch) {
  asm volatile("fence.acq_rel.gpu;" ::: "memory");
  set_flag(slot, byte, epoch);
}

__device__ __forceinline__ float sum8(uint4 v) {
  return ((bf_lo(v.x) + bf_hi(v.x)) + (bf_lo(v.y) + bf_hi(v.y))) + ((bf_lo(v.z) + bf_hi(v.z)) + (bf_lo(v.w) + bf_hi(v.w)));
}
__device__ __forceinline__ uint4 ldg128(const void* p) {
  uint4 v; asm volatile("ld.global.nc.v4.u32 {%0,%1,%2,%3}, [%4];" : "=r"(v.x), "=r"(v.y), "=r"(v.z), "=r"(v.w) : "l"(p)); return v;
}
__device__ __forceinline__ void ln_load(const bf16* __restrict__ x, int cta, uint4 (&rv)[5]) {
  const int t = threadIdx.x - 128, row = cta * 16 + (t >> 4), c = t & 15;
  #pragma unroll
  for (int j = 0; j < 5; j++) rv[j] = ldg128(reinterpret_cast<const uint4*>(x + (size_t)row * DM) + c + 16 * j);
}
__device__ __forceinline__ void ln_rows(const uint4 (&rv)[5], int cta, unsigned epoch) {
  const int t = threadIdx.x - 128, row = cta * 16 + (t >> 4), c = t & 15;
  const float sh = __shfl_sync(0xffffffffu, bf_lo(rv[0].x), t & 16);
  float d[40], s = 0.f, q = 0.f;
  #pragma unroll
  for (int j = 0; j < 5; j++) {
    const uint32_t u[4] = {rv[j].x, rv[j].y, rv[j].z, rv[j].w};
    #pragma unroll
    for (int e = 0; e < 4; e++) {
      const float d0 = bf_lo(u[e]) - sh, d1 = bf_hi(u[e]) - sh;
      d[j * 8 + e * 2] = d0; d[j * 8 + e * 2 + 1] = d1;
      s += d0 + d1; q = fmaf(d0, d0, q); q = fmaf(d1, d1, q);
    }
  }
  #pragma unroll
  for (int o = 1; o < 16; o <<= 1) { s += __shfl_xor_sync(0xffffffffu, s, o); q += __shfl_xor_sync(0xffffffffu, q, o); }
  const float md = s * (1.f / DM);
  const float r = rsqrtf(fmaxf(fmaf(q, 1.f / DM, -md * md), 0.f) + LN_EPS), o = -md * r;
  if (c == 0) st_vol2(&g_xstat[row], __float_as_uint(r), (__float_as_uint(-(md + sh) * r) & ~255u) | (epoch & 255u));
  #pragma unroll
  for (int j = 0; j < 5; j++) {
    const float* a = &d[j * 8];
    stg128(reinterpret_cast<uint4*>(g_xn + (size_t)row * DM) + c + 16 * j, make_uint4(
           pack_bf16(fmaf(a[0], r, o), fmaf(a[1], r, o)), pack_bf16(fmaf(a[2], r, o), fmaf(a[3], r, o)),
           pack_bf16(fmaf(a[4], r, o), fmaf(a[5], r, o)), pack_bf16(fmaf(a[6], r, o), fmaf(a[7], r, o))));
  }
  bar_arrive<BAR_LN>(288);
}
__device__ __forceinline__ void colsum_part(const bf16* __restrict__ win, int cta, unsigned epoch) {
  const int t = threadIdx.x & 127, w = t >> 5, l = t & 31;
  const int cj = min(cta, 119), cg = cj % 24, rg = cj / 24;
  uint4 cv[4];
  #pragma unroll
  for (int j = 0; j < 4; j++) cv[j] = ldg128(reinterpret_cast<const uint4*>(win + (size_t)(rg * 128 + w * 32 + j * 8 + (l >> 2)) * FF + FH + cg * 32) + (l & 3));
  float v[8];
  v[0] = (bf_lo(cv[0].x) + bf_lo(cv[1].x)) + (bf_lo(cv[2].x) + bf_lo(cv[3].x)); v[1] = (bf_hi(cv[0].x) + bf_hi(cv[1].x)) + (bf_hi(cv[2].x) + bf_hi(cv[3].x));
  v[2] = (bf_lo(cv[0].y) + bf_lo(cv[1].y)) + (bf_lo(cv[2].y) + bf_lo(cv[3].y)); v[3] = (bf_hi(cv[0].y) + bf_hi(cv[1].y)) + (bf_hi(cv[2].y) + bf_hi(cv[3].y));
  v[4] = (bf_lo(cv[0].z) + bf_lo(cv[1].z)) + (bf_lo(cv[2].z) + bf_lo(cv[3].z)); v[5] = (bf_hi(cv[0].z) + bf_hi(cv[1].z)) + (bf_hi(cv[2].z) + bf_hi(cv[3].z));
  v[6] = (bf_lo(cv[0].w) + bf_lo(cv[1].w)) + (bf_lo(cv[2].w) + bf_lo(cv[3].w)); v[7] = (bf_hi(cv[0].w) + bf_hi(cv[1].w)) + (bf_hi(cv[2].w) + bf_hi(cv[3].w));
  #pragma unroll
  for (int st = 0; st < 3; st++) {
    const int n = 4 >> st;
    const bool up = (l & (4 * n)) != 0;
    #pragma unroll
    for (int e = 0; e < 4; e++)
      if (e < n) { const float keep = up ? v[e + n] : v[e], send = up ? v[e] : v[e + n]; v[e] = keep + __shfl_xor_sync(0xffffffffu, send, 4 * n); }
  }
  float* red = reinterpret_cast<float*>(smem + RED_OFF);
  red[w * 32 + (l & 3) * 8 + (l >> 2)] = v[0];
  bar_sync<BAR_WG2>(128);
  if (t < 32) st_vol2(&g_csum[rg * FH + cg * 32 + t], __float_as_uint((red[t] + red[32 + t]) + (red[64 + t] + red[96 + t])), epoch);
}

__device__ __forceinline__ void a_entry(int g, int grp, int rb, int& mi, int& kb) {
  if (g < 10) { mi = M_X; kb = g; }
  else if (g < 20) { mi = M_XN; kb = g - 10; }
  else if (grp == 0) {
    if (g < 52) { mi = M_WSP; kb = (g - 20); }
    else if (g < 52 + NX) { mi = M_WSIM; kb = g - 52 + 32 - NX; }
    else { mi = M_H; kb = g - 52 - NX; }
  } else {
    if (g < 30) { mi = M_XN; kb = g - 20; }
    else if (g < 62) { mi = M_WSRE; kb = (g - 30); }
    else { mi = M_WSIM; kb = g - 62; }
  }
}

__global__ void __cluster_dims__(2, 1, 1) __launch_bounds__(384, 1)
fused_kernel(const __grid_constant__ Maps maps, const bf16* __restrict__ x, const bf16* __restrict__ win, const bf16* __restrict__ bsp) {
  const uint32_t sbase = smem_u32(smem);
  const uint32_t full0 = sbase + BAR_OFF, empty0 = full0 + 8 * STAGES, dep0 = empty0 + 8 * STAGES, ring = sbase + RING_OFF;
  const int tid = threadIdx.x, wg = __shfl_sync(0xffffffffu, tid >> 7, 0);
  const int rank = blockIdx.x & 1;
  const int grp = (blockIdx.x >> 1) & 1, half = (blockIdx.x >> 2) & 1, rb = blockIdx.x >> 3;
  const int ct = half * 2 + rank, c8 = grp * 4 + ct;
  const int cta = rb * 8 + half * 4 + grp * 2 + rank;
  const int total = grp == 0 ? KB_A : KB_B;
  const uint32_t stage_bytes = grp == 0 ? STAGE_A : STAGE_B;

  uint4 rv[5];
  if (wg != 0) ln_load(x, cta, rv);
  const unsigned epoch = (ld_relaxed(&g_done) >> 7) + 1u;
  if (tid == 0) {
    TS(0, 0);
    for (int s = 0; s < STAGES; s++) { mbar_init(full0 + 8 * s, 2); mbar_init(empty0 + 8 * s, 2); mbar_init(dep0 + 8 * s, 1); }
    *reinterpret_cast<volatile int*>(smem + READY_OFF) = 0;
    asm volatile("fence.mbarrier_init.release.cluster;" ::: "memory");
  }
  __syncthreads();
  asm volatile("barrier.cluster.arrive.relaxed.aligned;" ::: "memory");

  if (wg == 0) {
    asm volatile("setmaxnreg.dec.sync.aligned.u32 40;");
    const int warp = tid >> 5, lane = tid & 31;
    if (warp == 0) {
      const int row = rb * 128;
      if (lane == 0) {
        for (int g = 0; g < STAGES; g++) {
          mbar_expect_tx(full0 + 8 * g, A_BYTES);
          tma_load_2d(ring + g * stage_bytes, &maps.m[M_X], full0 + 8 * g, g * 64, row);
          tma_load_2d(ring + g * stage_bytes + 8192, &maps.m[M_X], full0 + 8 * g, g * 64, row + 64);
        }
      }
      __syncwarp();
      cluster_wait();
      if (lane == 0) {
        #pragma unroll 1
        for (int g = STAGES; g < total; g++) {
          int mi, kb;
          a_entry(g, grp, rb, mi, kb);
          if (g == 10 || (mi == M_H && kb == 0)) { TS(0, g > 10 ? 3 : 1); mbar_wait(dep0 + (g > 10 ? 24 : 0), 0); fence_async_global(); TS(0, g > 10 ? 4 : 2); }
          const int s = g & (STAGES - 1);
          mbar_wait(empty0 + 8 * s, ((g / STAGES) & 1) ^ 1);
          mbar_expect_tx(full0 + 8 * s, A_BYTES);
          tma_load_2d_mc(ring + s * stage_bytes + rank * 8192, &maps.m[mi], full0 + 8 * s, kb * 64, row + rank * 64, 3);
        }
        const int s = total & (STAGES - 1);
        mbar_wait(empty0 + 8 * s, ((total / STAGES) & 1) ^ 1);
        mbar_expect_tx(full0 + 8 * s, 20480);
        mbar_arrive(full0 + 8 * s);
        tma_load_2d(ring + s * stage_bytes, &maps.m[M_XR], full0 + 8 * s, ct * 160, row + grp * 64);
        TS(0, 5);
      }
    } else if (warp == 1) {
      if (lane == 0) {
        int have = 0;
        #pragma unroll 1
        for (int g = 0; g < total; g++) {
          int kind = 1, mi, kb, c, dep = 0, need = 0;
          uint32_t bytes = 20480;
          if (g < 10) { kind = 0; mi = M_WIN32; kb = g; c = 24 + 3 * c8; bytes = 12288; }
          else if (grp == 0) {
            if (g < 20) { kind = 0; mi = M_WIN3; kb = g - 10; c = 3 * ct; bytes = 24576; }
            else if (g < 52) { kind = 0; mi = M_Z23; kb = (g - 20); c = 3 * ct; bytes = 24576; need = ((g - 20) >> 1) + 1; }
            else if (g < 52 + NX) { mi = M_AB; kb = g - 52 + 32 - NX; c = DM + ct * 160; dep = g == 52 ? 2 : 0; }
            else { kind = 0; mi = M_WOUT; kb = g - 52 - NX; c = ct * 5; }
          } else {
            if (g < 30) { mi = g < 20 ? M_WDRE : M_WDIM; kb = g < 20 ? g - 10 : g - 20; c = ct * 160; }
            else if (g < 62) { mi = M_AB; kb = (g - 30); c = ct * 160; need = ((g - 30) >> 1) + 1; }
            else { mi = M_AB; kb = g - 62; c = ct * 160 + DM; dep = g == 62 ? 2 : 0; }
          }
          if (need > have) {
            if (need == 1) TS(1, 0);
            unsigned it = 0;
            while ((have = *reinterpret_cast<volatile int*>(smem + READY_OFF)) < need && ++it < 50 * POLL_LIMIT) {}
            fence_async_global();
            if (need == 1) { TS(1, 1); TC(1); }
          }
          if (dep) { TS(1, dep * 2 - 2); mbar_wait(dep0 + 8 * dep, 0); fence_async_global(); TS(1, dep * 2 - 1); TC(dep); }
          const int s = g & (STAGES - 1);
          const uint32_t dst = ring + s * stage_bytes + A_BYTES, fb = full0 + 8 * s;
          mbar_wait(empty0 + 8 * s, ((g / STAGES) & 1) ^ 1);
          mbar_expect_tx(fb, bytes);
          if (kind == 0) tma_load_3d(dst, &maps.m[mi], fb, 0, kb * 64, c);
          else tma_load_2d(dst, &maps.m[mi], fb, kb * 64, c);
        }
      }
      __syncwarp();
      cluster_wait();
    } else if (warp == 2) {
      cluster_wait();
      {
        unsigned it = 0;
        uint2 v[4];
        while (true) {
          bool ok = true;
          #pragma unroll
          for (int i = 0; i < 4; i++) { v[i] = ld_vol2(&g_xstat[rb * 128 + i * 32 + lane]); ok = ok && ((v[i].y ^ epoch) & 255u) == 0; }
          if (ok || ++it > POLL_LIMIT) break;
          __nanosleep(POLL_NS);
        }
        #pragma unroll
        for (int i = 0; i < 4; i++) reinterpret_cast<uint2*>(smem + ROWSTAT_OFF)[i * 32 + lane] = make_uint2(v[i].x, v[i].y & ~255u);
        __syncwarp();
        TS(0, 6);
        bar_arrive<BAR_STATS>(192);
      }
      #pragma unroll 1
      for (int d = 0; d < 4 - grp; d++) {
        const int slot = d == 0 ? F_XN + rb : d == 3 ? F_H + rb : d == 2 ? F_B + ct : grp == 0 ? F_Z + ct : F_A + ct;
        const int byte = d == 0 ? lane & 7 : d == 3 ? lane & 3 : (d == 1 && grp == 0) ? lane : lane >> 1;
        unsigned it = 0, m;
        while ((m = __ballot_sync(0xffffffffu, get_flag(slot, byte) != (epoch & 255u))) != 0 && ++it < POLL_LIMIT) {
          if (d == 1 && lane == 0) *reinterpret_cast<volatile int*>(smem + READY_OFF) = (__ffs(m) - 1) >> 1;
          __nanosleep(WATCH_NS);
        }
        if (d == 1 && lane == 0) *reinterpret_cast<volatile int*>(smem + READY_OFF) = 16;
        TS(0, 8 + d * 2);
        fence_async_global();
        __syncwarp();
        TS(0, 9 + d * 2);
        if (lane == 0) mbar_arrive(dep0 + 8 * d);
      }
    } else {
      cluster_wait();
      bar_sync<BAR_LN>(288);
      if (lane == 0) { TS(1, 5); publish(F_XN + rb, cta & 7, epoch); TS(1, 6); }
      __syncwarp();
      #pragma unroll 1
      for (int i = 0; i < 3; i++) {
        unsigned it = 0;
        while (true) {
          bool ok = true;
          float a = 0.f;
          #pragma unroll
          for (int p = 0; p < 5; p++) { const uint2 u = ld_vol2(&g_csum[p * FH + c8 * 96 + i * 32 + lane]); ok = ok && u.y == epoch; a += __uint_as_float(u.x); }
          reinterpret_cast<float*>(smem + COLSUM_OFF)[i * 32 + lane] = a;
          if (ok || ++it > POLL_LIMIT) break;
          __nanosleep(POLL_NS);
        }
      }
      __syncwarp();
      TS(1, 4);
      bar_arrive<BAR_STATS>(192);
      bar_sync<BAR_PUB1>(160);
      if (lane == 0) {
        TS(1, 7);
        tma_store_3d(&maps.m[M_Z232], ring + 4 * stage_bytes, 0, rb * 128, 3 * c8);
        bulk_commit();
        bulk_wait_all();
        set_flag(F_Z + (c8 >> 1), rb * 2 + (c8 & 1), epoch);
        TS(1, 8);
      }
      __syncwarp();
      if (grp == 0) {
        bar_arrive<BAR_BUF>(160);
      } else {
        bar_sync<BAR_PUB2>(160);
        if (lane == 0) set_flag(F_A + ct, rb, epoch);
        TS(1, 9);
        __syncwarp();
      }
      bar_sync<BAR_PUB1>(160);
      if (lane == 0) set_flag(grp == 0 ? F_H + rb : F_B + ct, grp == 0 ? ct : rb, epoch);
      TS(1, 10);
    }
  } else {
    asm volatile("setmaxnreg.inc.sync.aligned.u32 232;");
    const int t = tid & 127, w = t >> 5, l = t & 31;
    const uint32_t buf = ring + 4 * stage_bytes;
    ln_rows(rv, cta, epoch);
    if (wg == 2) colsum_part(win, cta, epoch);
    TS(wg + 1, 0);
    cluster_wait();
    const int rl = w * 16 + ((l >> 3) & 1) * 8 + (l & 7);
    const int gr = w * 16 + (l & 15);
    const uint32_t st_base = buf + rl * 128;
    const uint32_t st_x = ((l >> 4) ^ (l & 7)) << 4;
    if (wg == 1) {
      float acc[2][48];
      zero(acc);
      mainloop<96, 2, false, BAR_ORD1>(acc, sbase, stage_bytes, 0, 10, total, 0);
      drain(acc, sbase, 9, total);
      TS(2, 2);
      bar_sync<BAR_STATS>(192);
      const float2* rs = reinterpret_cast<const float2*>(smem + ROWSTAT_OFF) + w * 16 + (l >> 2);
      const float2* cs = reinterpret_cast<const float2*>(smem + COLSUM_OFF) + (l & 3);
      float sum[4], sq[4];
      #pragma unroll
      for (int r = 0; r < 4; r++) {
        const float2 st = rs[(r >> 1) * 64 + (r & 1) * 8];
        float s0 = 0.f, q0 = 0.f;
        #pragma unroll
        for (int j = 0; j < 12; j++) {
          const float2 c = cs[j * 4];
          float* a = &acc[r >> 1][4 * j + (r & 1) * 2];
          a[0] = gelu_tanh(fmaf(a[0], st.x, st.y * c.x));
          a[1] = gelu_tanh(fmaf(a[1], st.x, st.y * c.y));
          s0 += a[0] + a[1]; q0 = fmaf(a[0], a[0], q0); q0 = fmaf(a[1], a[1], q0);
        }
        s0 += __shfl_xor_sync(0xffffffffu, s0, 1); q0 += __shfl_xor_sync(0xffffffffu, q0, 1);
        s0 += __shfl_xor_sync(0xffffffffu, s0, 2); q0 += __shfl_xor_sync(0xffffffffu, q0, 2);
        sum[r] = s0; sq[r] = q0;
      }
      TS(2, 4);
      float rstd, off;
      {
        const int qd = l & 3;
        const float sm = qd == 0 ? sum[0] : qd == 1 ? sum[1] : qd == 2 ? sum[2] : sum[3];
        const float sv = qd == 0 ? sq[0] : qd == 1 ? sq[1] : qd == 2 ? sq[2] : sq[3];
        const int row = (qd >> 1) * 64 + w * 16 + (qd & 1) * 8 + (l >> 2);
        const float mu = sm * (1.f / 96), m2 = fmaxf(sv - sm * mu, 0.f);
        st_vol2(&g_zstat[(rb * 8 + c8) * 128 + row], __float_as_uint(mu), (__float_as_uint(m2) & ~255u) | (epoch & 255u));
        uint2 v[7];
        unsigned n = 0;
        while (true) {
          bool ok = true;
          #pragma unroll
          for (int j = 0; j < 7; j++) v[j] = ld_vol2(&g_zstat[(rb * 8 + ((c8 + 1 + j) & 7)) * 128 + row]);
          #pragma unroll
          for (int j = 0; j < 7; j++) ok = ok && ((v[j].y ^ epoch) & 255u) == 0;
          if (ok || ++n > POLL_LIMIT) break;
          __nanosleep(POLL_NS);
        }
        float mean = mu, var = m2;
        #pragma unroll
        for (int j = 0; j < 7; j++) { mean += __uint_as_float(v[j].x); var += __uint_as_float(v[j].y & ~255u); }
        mean *= 0.125f;
        float d = (mu - mean) * (mu - mean);
        #pragma unroll
        for (int j = 0; j < 7; j++) d = fmaf(__uint_as_float(v[j].x) - mean, __uint_as_float(v[j].x) - mean, d);
        rstd = rsqrtf(fmaf(96.f, d, var) * (1.f / FH) + LN_EPS); off = -mean * rstd;
        __syncwarp();
      }
      TS(2, 5);
      #pragma unroll
      for (int mi = 0; mi < 2; mi++) {
        const float r0 = __shfl_sync(0xffffffffu, rstd, (l & 28) + mi * 2), o0 = __shfl_sync(0xffffffffu, off, (l & 28) + mi * 2);
        const float r1 = __shfl_sync(0xffffffffu, rstd, (l & 28) + mi * 2 + 1), o1 = __shfl_sync(0xffffffffu, off, (l & 28) + mi * 2 + 1);
        #pragma unroll
        for (int jj = 0; jj < 6; jj++) {
          const float* a = &acc[mi][8 * jj];
          stsm4(buf + (jj >> 1) * 8192 + mi * 4096 + rl * 64 + ((((jj & 1) * 2 + (l >> 4)) ^ ((l >> 1) & 3)) << 4),
                pack_bf16(fmaf(a[0], r0, o0), fmaf(a[1], r0, o0)), pack_bf16(fmaf(a[2], r1, o1), fmaf(a[3], r1, o1)),
                pack_bf16(fmaf(a[4], r0, o0), fmaf(a[5], r0, o0)), pack_bf16(fmaf(a[6], r1, o1), fmaf(a[7], r1, o1)));
        }
      }
      fence_async_smem();
      bar_arrive<BAR_PUB1>(160);
      TS(2, 6);
      if (grp == 0) {
        float acc[2][96];
        zero(acc);
        bar_sync<BAR_ORD2>(256);
        mainloop<192, 1, false, BAR_ORD1>(acc, sbase, STAGE_A, 20, 32, KB_A, 0);
        const float* bias = reinterpret_cast<const float*>(smem + BIAS_OFF) + w * 16 + (l >> 2);
        bar_sync<BAR_Z1>(256);
        drain(acc, sbase, 51, KB_A);
        TS(2, 7);
        {
          const float bb[4] = {bias[0], bias[8], bias[64], bias[72]};
          uint32_t z[2][4][4];
          #pragma unroll
          for (int i = 0; i < 4; i++) ldsm4(st_base + (st_x ^ (i << 5)), z[0][i][0], z[0][i][1], z[0][i][2], z[0][i][3]);
          #pragma unroll
          for (int bx = 0; bx < 6; bx++) {
            if (bx < 5) {
              #pragma unroll
              for (int i = 0; i < 4; i++)
                ldsm4(st_base + (bx + 1) * 8192 + (st_x ^ (i << 5)), z[(bx + 1) & 1][i][0], z[(bx + 1) & 1][i][1], z[(bx + 1) & 1][i][2], z[(bx + 1) & 1][i][3]);
            }
            const float b0 = bb[(bx / 3) * 2], b1 = bb[(bx / 3) * 2 + 1];
            #pragma unroll
            for (int i = 0; i < 4; i++) {
              const float* a = &acc[bx / 3][8 * ((bx % 3) * 4 + i)];
              const uint32_t* zz = z[bx & 1][i];
              stsm4(st_base + bx * 8192 + (st_x ^ (i << 5)),
                    hmul2_bf16(zz[0], pack_bf16(a[0] + b0, a[1] + b0)), hmul2_bf16(zz[1], pack_bf16(a[2] + b1, a[3] + b1)),
                    hmul2_bf16(zz[2], pack_bf16(a[4] + b0, a[5] + b0)), hmul2_bf16(zz[3], pack_bf16(a[6] + b1, a[7] + b1)));
            }
            fence_async_smem();
            __syncwarp();
            if (l == 0) {
              tma_store_2d(&maps.m[M_HS], buf + bx * 8192 + w * 2048, ct * 192 + (bx % 3) * 64, rb * 128 + (bx / 3) * 64 + w * 16);
              bulk_commit();
            }
          }
        }
        TS(2, 8);
        if (l == 0) bulk_wait_all();
        __syncwarp();
        bar_arrive<BAR_PUB1>(160);
        TS(2, 9);
        return;
      }
    } else {
      if (grp == 0) {
        reinterpret_cast<float*>(smem + BIAS_OFF)[t] = __bfloat162float(bsp[rb * 128 + t]);
        float acc[2][96];
        zero(acc);
        bar_sync<BAR_ORD1>(256);
        mainloop<192, 1, false, BAR_ORD2>(acc, sbase, STAGE_A, 10, 10, KB_A, 0);
        drain(acc, sbase, 19, KB_A);
        TS(3, 2);
        bar_sync<BAR_BUF>(160);
        #pragma unroll
        for (int mi = 0; mi < 2; mi++)
          #pragma unroll
          for (int jj = 0; jj < 12; jj++) {
            const float* a = &acc[mi][8 * jj];
            stsm4(st_base + mi * 24576 + (jj >> 2) * 8192 + (st_x ^ ((jj & 3) << 5)),
                  pack_bf16(a[0], a[1]), pack_bf16(a[2], a[3]), pack_bf16(a[4], a[5]), pack_bf16(a[6], a[7]));
          }
        __syncwarp();
        TS(3, 3);
        const uint32_t rbase = buf + (l >> 4) * 24576 + gr * 128;
        #pragma unroll 1
        for (int c2 = 0; c2 < 12; c2++) {
          const uint32_t ab = rbase + (c2 >> 2) * 8192;
          uint4 v[2];
          #pragma unroll
          for (int i = 0; i < 2; i++) v[i] = lds128(ab + (((((c2 & 3) * 2 + i) ^ l) & 7) << 4));
          #pragma unroll
          for (int i = 0; i < 2; i++)
            sts128(ab + (((((c2 & 3) * 2 + i) ^ l) & 7) << 4),
                   pack_bf16(gelu_tanh(bf_lo(v[i].x)), gelu_tanh(bf_hi(v[i].x))), pack_bf16(gelu_tanh(bf_lo(v[i].y)), gelu_tanh(bf_hi(v[i].y))),
                   pack_bf16(gelu_tanh(bf_lo(v[i].z)), gelu_tanh(bf_hi(v[i].z))), pack_bf16(gelu_tanh(bf_lo(v[i].w)), gelu_tanh(bf_hi(v[i].w))));
        }
        TS(3, 4);
        bar_arrive<BAR_Z1>(256);
      }
    }
    float acc[2][80];
    if (grp == 1) {
      zero(acc);
      if (wg == 2) {
        bar_sync<BAR_ORD1>(256);
        mainloop<160, 0, false, BAR_ORD2>(acc, sbase, STAGE_B, 10, 10, KB_B, 0);
      } else {
        bar_sync<BAR_ORD2>(256);
        mainloop<160, 0, false, BAR_ORD1>(acc, sbase, STAGE_B, 20, 10, KB_B, 0);
      }
      drain(acc, sbase, wg == 2 ? 19 : 29, KB_B);
      TS(wg + 1, wg == 1 ? 7 : 2);
      if (wg == 1) bar_sync<BAR_BUF>(256);
      const uint32_t sg = wg == 1 ? 0x80008000u : 0u;
      const uint32_t tb = buf + 24576 + ((l >> 4) * 8 + (l & 7)) * 128 + (((w * 2 + ((l >> 3) & 1)) ^ (l & 7)) << 4);
      #pragma unroll
      for (int mi = 0; mi < 2; mi++)
        #pragma unroll
        for (int jj = 0; jj < 10; jj++) {
          const float* a = &acc[mi][8 * jj];
          stsm4_t(tb + mi * 20480 + jj * 2048, pack_bf16(a[0], a[1]) ^ sg, pack_bf16(a[2], a[3]) ^ sg, pack_bf16(a[4], a[5]) ^ sg, pack_bf16(a[6], a[7]) ^ sg);
        }
      fence_async_smem();
      if (wg == 1) bar_sync<BAR_WG1>(128); else bar_sync<BAR_WG2>(128);
      TS(wg + 1, wg == 1 ? 8 : 6);
      if (l == 0) {
        #pragma unroll 1
        for (int i = 0; i < 2; i++) {
          tma_store_2d(&maps.m[M_ABS], buf + 24576 + i * 20480 + w * 5120, rb * 128 + i * 64, (2 - wg) * DM + ct * 160 + w * 40);
          bulk_commit();
        }
        bulk_wait_all();
      }
      __syncwarp();
      TS(wg + 1, wg == 1 ? 9 : 10);
      if (wg == 1) { bar_arrive<BAR_PUB1>(160); return; }
      bar_arrive<BAR_PUB2>(160);
      bar_arrive<BAR_BUF>(256);
    }
    zero(acc);
    bar_sync<BAR_ORD1>(256);
    mainloop<160, 0, false, 0>(acc, sbase, stage_bytes, grp == 0 ? 52 : 30, grp == 0 ? NX : 61 - NX, total, grp);
    if (grp == 0) {
      mainloop<160, 2, true, 0>(acc, sbase, STAGE_A, 52 + NX, 9, KB_A, 0);
      tail3<2>(acc, sbase, STAGE_A, KB_A, 0);
    } else {
      tail3<0>(acc, sbase, STAGE_B, KB_B, 1);
    }
    wgmma_wait<1>();
    #pragma unroll
    for (int i = 0; i < 80; i++) asm volatile("" : "+f"(acc[1][i]) :: "memory");
    TS(3, 12);
    uint4* dst = g_part + (size_t)cta * 27 * 128 + t;
    const uint4* src = g_part + (size_t)(cta ^ 2) * 27 * 128 + t;
    #pragma unroll
    for (int i = 0; i < 27; i++)
      st_vol4(dst + i * 128, __float_as_uint(acc[1][3 * i]), __float_as_uint(acc[1][3 * i + 1]),
              __float_as_uint(i < 26 ? acc[1][3 * i + 2] : 0.f), epoch);
    wgmma_wait<0>();
    #pragma unroll
    for (int i = 0; i < 80; i++) asm volatile("" : "+f"(acc[0][i]) :: "memory");
    TS(3, 13);
    const uint32_t slab = ring + (total & (STAGES - 1)) * stage_bytes + w * (16 * 320);
    const uint32_t addr = slab + (((l >> 3) & 1) * 8 + (l & 7)) * 320 + (l >> 4) * 16;
    mbar_wait(full0 + 8 * (total & (STAGES - 1)), (total / STAGES) & 1);
    #pragma unroll
    for (int jj = 0; jj < 10; jj++) {
      uint32_t z0, z1, z2, z3;
      ldsm4(addr + jj * 32, z0, z1, z2, z3);
      float* a = &acc[0][8 * jj];
      a[0] += bf_lo(z0); a[1] += bf_hi(z0); a[2] += bf_lo(z1); a[3] += bf_hi(z1);
      a[4] += bf_lo(z2); a[5] += bf_hi(z2); a[6] += bf_lo(z3); a[7] += bf_hi(z3);
    }
    {
      unsigned n = 0;
      #pragma unroll
      for (int gq = 0; gq < 3; gq++) {
        uint4 v[9];
        while (true) {
          bool ok = true;
          #pragma unroll
          for (int i = 0; i < 9; i++) v[i] = ld_vol4(src + (gq * 9 + i) * 128);
          #pragma unroll
          for (int i = 0; i < 9; i++) ok = ok && (v[i].w == epoch);
          if (ok || ++n > POLL_LIMIT) break;
          __nanosleep(FIN_NS);
        }
        #pragma unroll
        for (int i = 0; i < 9; i++) {
          const int e = (gq * 9 + i) * 3;
          acc[0][e] += __uint_as_float(v[i].x);
          acc[0][e + 1] += __uint_as_float(v[i].y);
          if (e + 2 < 80) acc[0][e + 2] += __uint_as_float(v[i].z);
        }
      }
    }
    TS(3, 14);
    #pragma unroll
    for (int jj = 0; jj < 10; jj++) {
      const float* a = &acc[0][8 * jj];
      stsm4(addr + jj * 32, pack_bf16(a[0], a[1]), pack_bf16(a[2], a[3]), pack_bf16(a[4], a[5]), pack_bf16(a[6], a[7]));
    }
    fence_async_smem();
    __syncwarp();
    if (l == 0) {
      tma_store_2d(&maps.m[M_OUT], slab, ct * 160, rb * 128 + grp * 64 + w * 16);
      bulk_commit();
      bulk_wait_read();
      if (w == 0) atomicAdd(&g_done, 1u);
    }
    TS(3, 15);
  }
}

typedef CUresult (*EncodeFn)(CUtensorMap*, CUtensorMapDataType, cuuint32_t, void*, const cuuint64_t*, const cuuint64_t*,
                             const cuuint32_t*, const cuuint32_t*, CUtensorMapInterleave, CUtensorMapSwizzle,
                             CUtensorMapL2promotion, CUtensorMapFloatOOBfill);

void make2d(EncodeFn enc, CUtensorMap* m, const void* p, uint64_t cols, uint64_t rows, uint32_t bc, uint32_t br, bool swz = true) {
  cuuint64_t gd[2] = {cols, rows}, gs[1] = {cols * 2};
  cuuint32_t bd[2] = {bc, br}, es[2] = {1, 1};
  enc(m, CU_TENSOR_MAP_DATA_TYPE_BFLOAT16, 2, const_cast<void*>(p), gd, gs, bd, es, CU_TENSOR_MAP_INTERLEAVE_NONE,
      swz ? CU_TENSOR_MAP_SWIZZLE_128B : CU_TENSOR_MAP_SWIZZLE_NONE, PROMO, CU_TENSOR_MAP_FLOAT_OOB_FILL_NONE);
}
void make3d(EncodeFn enc, CUtensorMap* m, const void* p, uint64_t cols, uint64_t rows, uint32_t cw, uint32_t nc, uint32_t br = 64) {
  cuuint64_t gd[3] = {cw, rows, cols / cw}, gs[2] = {cols * 2, cw * 2};
  cuuint32_t bd[3] = {cw, br, nc}, es[3] = {1, 1, 1};
  enc(m, CU_TENSOR_MAP_DATA_TYPE_BFLOAT16, 3, const_cast<void*>(p), gd, gs, bd, es, CU_TENSOR_MAP_INTERLEAVE_NONE,
      cw == 64 ? CU_TENSOR_MAP_SWIZZLE_128B : CU_TENSOR_MAP_SWIZZLE_64B, PROMO, CU_TENSOR_MAP_FLOAT_OOB_FILL_NONE);
}

}

extern "C" void kernel_launch(void* const* d_in, const int* in_sizes, int n_in, void* d_out, int out_size) {
  const bf16* x = (const bf16*)d_in[0];
  const bf16* wsre = (const bf16*)d_in[1];
  const bf16* wsim = (const bf16*)d_in[2];
  const bf16* wdre = (const bf16*)d_in[3];
  const bf16* wdim = (const bf16*)d_in[4];
  const bf16* win = (const bf16*)d_in[6];
  const bf16* wsp = (const bf16*)d_in[7];
  const bf16* bsp = (const bf16*)d_in[8];
  const bf16* wout = (const bf16*)d_in[9];

  void* fn = nullptr;
  cudaDriverEntryPointQueryResult qr;
  cudaGetDriverEntryPoint("cuTensorMapEncodeTiled", &fn, cudaEnableDefault, &qr);
  EncodeFn enc = (EncodeFn)fn;
  void *abT, *z2, *h, *xn;
  cudaGetSymbolAddress(&xn, g_xn);
  cudaGetSymbolAddress(&abT, g_abT);
  cudaGetSymbolAddress(&z2, g_z2);
  cudaGetSymbolAddress(&h, g_h);

  Maps maps;
  make2d(enc, &maps.m[M_X], x, DM, SEQ, 64, 64);
  make2d(enc, &maps.m[M_XN], xn, DM, SEQ, 64, 64);
  make3d(enc, &maps.m[M_Z232], z2, FH, SEQ, 32, 3, 128);
  make2d(enc, &maps.m[M_XR], x, DM, SEQ, 160, 64, false);
  make3d(enc, &maps.m[M_WIN32], win, FF, DM, 32, 3);
  make2d(enc, &maps.m[M_WSRE], wsre, SEQ, SEQ, 64, 64);
  make2d(enc, &maps.m[M_WSIM], wsim, SEQ, SEQ, 64, 64);
  make2d(enc, &maps.m[M_WSP], wsp, SEQ, SEQ, 64, 64);
  make2d(enc, &maps.m[M_H], h, FH, SEQ, 64, 64);
  make3d(enc, &maps.m[M_WIN3], win, FF, DM, 64, 3);
  make3d(enc, &maps.m[M_Z23], z2, FH, SEQ, 64, 3);
  make2d(enc, &maps.m[M_WDRE], wdre, DM, DM, 64, 160);
  make2d(enc, &maps.m[M_WDIM], wdim, DM, DM, 64, 160);
  make2d(enc, &maps.m[M_AB], abT, SEQ, 2 * DM, 64, 160);
  make3d(enc, &maps.m[M_WOUT], wout, DM, FH, 32, 5);
  make2d(enc, &maps.m[M_HS], h, FH, SEQ, 64, 16);
  make2d(enc, &maps.m[M_ABS], abT, SEQ, 2 * DM, 64, 40);
  make2d(enc, &maps.m[M_OUT], d_out, DM, SEQ, 160, 16, false);

  cudaFuncSetAttribute(fused_kernel, cudaFuncAttributeMaxDynamicSharedMemorySize, SMEM_BYTES);
  fused_kernel<<<128, 384, SMEM_BYTES>>>(maps, x, win, bsp);
}
```

```cpp
#include <cuda_runtime.h>
#include <cuda_bf16.h>
#include <cuda.h>
#include <stdint.h>

namespace {

typedef __nv_bfloat16 bf16;

constexpr int SEQ = 2048, DM = 640, FF = 1536, FH = 768;
#define NXV 13
constexpr int NX = NXV;
constexpr int STAGES = 4;
constexpr int A_BYTES = 16384;
constexpr int BIAS_OFF = 0;
constexpr int BAR_OFF = 512;
constexpr int READY_OFF = 640;
constexpr int ROWSTAT_OFF = 1024;
constexpr int COLSUM_OFF = 2048;
constexpr int RED_OFF = 2560;
constexpr int RING_OFF = 3072;
constexpr int STAGE_A = 40960, STAGE_B = 36864;
constexpr int SMEM_BYTES = RING_OFF + 4 * STAGE_A + 49152;
constexpr int KB_A = 20 + 32 + NX + 12;
constexpr int KB_B = 30 + 64 - NX;
constexpr float LN_EPS = 1e-5f;
constexpr unsigned POLL_LIMIT = 100000;
#define POLL_NS 100
#define PF_D 0
#define ROT 0
#define Z1_NS 0
#define INFL 2
#define LIM_G 1000
#define MAPV 0
#define PROMO CU_TENSOR_MAP_L2_PROMOTION_L2_128B
#define WATCH_NS 40
#define PF_NS 150

constexpr int BAR_ORD1 = 1, BAR_ORD2 = 2, BAR_WG1 = 3, BAR_WG2 = 4, BAR_LN = 5, BAR_BUF = 6, BAR_Z1 = 7, BAR_PUB1 = 8, BAR_PUB2 = 9, BAR_STATS = 10;

enum { M_X, M_XN, M_XR, M_WIN32, M_Z232, M_WSRE, M_WSIM, M_WSP, M_H, M_WIN3, M_Z23, M_WDRE, M_WDIM, M_AB, M_WOUT, M_OUT, M_HS, M_ABS, M_COUNT };
struct Maps { CUtensorMap m[M_COUNT]; };

__device__ __align__(1024) bf16 g_abT[2 * DM * SEQ];
__device__ __align__(1024) bf16 g_z2[SEQ * FH];
__device__ __align__(1024) bf16 g_h[SEQ * FH];
__device__ __align__(1024) bf16 g_xn[SEQ * DM];
__device__ __align__(16) uint2 g_xstat[SEQ];
__device__ __align__(16) uint2 g_csum[5 * FH];
__device__ __align__(16) uint2 g_zstat[128 * 128];
__device__ __align__(256) unsigned char g_flags[108 * 256];
constexpr int F_A = 0, F_B = 4, F_Z = 8, F_H = 12, F_XN = 28, F_Y = 44;
__device__ unsigned g_done;
#define TS(role, ev)
#define TC(i)

extern __shared__ __align__(1024) uint8_t smem[];

__device__ __forceinline__ uint32_t smem_u32(const void* p) { return (uint32_t)__cvta_generic_to_shared(p); }
__device__ __forceinline__ void mbar_init(uint32_t bar, uint32_t cnt) { asm volatile("mbarrier.init.shared::cta.b64 [%0], %1;" :: "r"(bar), "r"(cnt)); }
__device__ __forceinline__ void mbar_expect_tx(uint32_t bar, uint32_t bytes) { asm volatile("mbarrier.arrive.expect_tx.shared::cta.b64 _, [%0], %1;" :: "r"(bar), "r"(bytes) : "memory"); }
__device__ __forceinline__ void mbar_arrive(uint32_t bar) { asm volatile("mbarrier.arrive.shared::cta.b64 _, [%0];" :: "r"(bar) : "memory"); }
__device__ __forceinline__ void mbar_arrive_cluster(uint32_t bar, uint32_t cta) {
  asm volatile("{\n.reg .b32 ra;\nmapa.shared::cluster.u32 ra, %0, %1;\nmbarrier.arrive.shared::cluster.b64 _, [ra];\n}" :: "r"(bar), "r"(cta) : "memory");
}
__device__ __forceinline__ void mbar_wait(uint32_t bar, uint32_t parity) {
  asm volatile("{\n.reg .pred p;\n.reg .u32 n;\nmov.u32 n, 0;\n"
               "LW: mbarrier.try_wait.parity.shared::cta.b64 p, [%0], %1, 2000;\n@p bra LD;\n"
               "add.u32 n, n, 1;\nsetp.lt.u32 p, n, 20000;\n@p bra LW;\nLD:\n}" :: "r"(bar), "r"(parity) : "memory");
}
__device__ __forceinline__ void tma_load_2d(uint32_t dst, const CUtensorMap* map, uint32_t bar, int c0, int c1) {
  asm volatile("cp.async.bulk.tensor.2d.shared::cluster.global.mbarrier::complete_tx::bytes [%0], [%1, {%3, %4}], [%2];"
    :: "r"(dst), "l"((uint64_t)map), "r"(bar), "r"(c0), "r"(c1) : "memory");
}
__device__ __forceinline__ void tma_load_3d(uint32_t dst, const CUtensorMap* map, uint32_t bar, int c0, int c1, int c2) {
  asm volatile("cp.async.bulk.tensor.3d.shared::cluster.global.mbarrier::complete_tx::bytes [%0], [%1, {%3, %4, %5}], [%2];"
    :: "r"(dst), "l"((uint64_t)map), "r"(bar), "r"(c0), "r"(c1), "r"(c2) : "memory");
}
__device__ __forceinline__ void tma_load_2d_mc(uint32_t dst, const CUtensorMap* map, uint32_t bar, int c0, int c1, uint16_t mask) {
  asm volatile("cp.async.bulk.tensor.2d.shared::cluster.global.mbarrier::complete_tx::bytes.multicast::cluster [%0], [%1, {%3, %4}], [%2], %5;"
    :: "r"(dst), "l"((uint64_t)map), "r"(bar), "r"(c0), "r"(c1), "h"(mask) : "memory");
}
__device__ __forceinline__ void tma_store_2d(const CUtensorMap* map, uint32_t src, int c0, int c1) {
  asm volatile("cp.async.bulk.tensor.2d.global.shared::cta.bulk_group [%0, {%2, %3}], [%1];"
    :: "l"((uint64_t)map), "r"(src), "r"(c0), "r"(c1) : "memory");
}
__device__ __forceinline__ void tma_store_3d(const CUtensorMap* map, uint32_t src, int c0, int c1, int c2) {
  asm volatile("cp.async.bulk.tensor.3d.global.shared::cta.bulk_group [%0, {%2, %3, %4}], [%1];"
    :: "l"((uint64_t)map), "r"(src), "r"(c0), "r"(c1), "r"(c2) : "memory");
}
__device__ __forceinline__ void tma_reduce_2d(const CUtensorMap* map, uint32_t src, int c0, int c1) {
  asm volatile("cp.reduce.async.bulk.tensor.2d.global.shared::cta.add.tile.bulk_group [%0, {%2, %3}], [%1];"
    :: "l"((uint64_t)map), "r"(src), "r"(c0), "r"(c1) : "memory");
}
__device__ __forceinline__ void bulk_wait_all() { asm volatile("cp.async.bulk.wait_group 0;" ::: "memory"); }
__device__ __forceinline__ void bulk_commit() { asm volatile("cp.async.bulk.commit_group;" ::: "memory"); }
__device__ __forceinline__ void bulk_wait_read() { asm volatile("cp.async.bulk.wait_group.read 0;" ::: "memory"); }
__device__ __forceinline__ void fence_async_smem() { asm volatile("fence.proxy.async.shared::cta;" ::: "memory"); }
__device__ __forceinline__ void fence_async_global() { asm volatile("fence.proxy.async.global;" ::: "memory"); }
__device__ __forceinline__ void wgmma_fence() { asm volatile("wgmma.fence.sync.aligned;" ::: "memory"); }
__device__ __forceinline__ void wgmma_commit() { asm volatile("wgmma.commit_group.sync.aligned;" ::: "memory"); }
template<int N> __device__ __forceinline__ void wgmma_wait() { asm volatile("wgmma.wait_group.sync.aligned %0;" :: "n"(N) : "memory"); }
template<int ID> __device__ __forceinline__ void bar_sync(int n) { asm volatile("bar.sync %0, %1;" :: "n"(ID), "r"(n) : "memory"); }
template<int ID> __device__ __forceinline__ void bar_arrive(int n) { asm volatile("bar.arrive %0, %1;" :: "n"(ID), "r"(n) : "memory"); }
__device__ __forceinline__ void cluster_wait() { asm volatile("barrier.cluster.wait.aligned;" ::: "memory"); }
__device__ __forceinline__ uint64_t desc64(uint32_t lo, uint32_t hi) { return (uint64_t)lo | ((uint64_t)hi << 32); }
__device__ __forceinline__ uint4 ld_vol4(const uint4* p) {
  uint4 v; asm volatile("ld.relaxed.gpu.global.v4.u32 {%0,%1,%2,%3}, [%4];" : "=r"(v.x), "=r"(v.y), "=r"(v.z), "=r"(v.w) : "l"(p) : "memory"); return v;
}
__device__ __forceinline__ uint2 ld_vol2(const uint2* p) {
  uint2 v; asm volatile("ld.relaxed.gpu.global.v2.u32 {%0,%1}, [%2];" : "=r"(v.x), "=r"(v.y) : "l"(p) : "memory"); return v;
}
__device__ __forceinline__ void st_vol4(uint4* p, uint32_t a, uint32_t b, uint32_t c, uint32_t d) {
  asm volatile("st.relaxed.gpu.global.v4.u32 [%0], {%1,%2,%3,%4};" :: "l"(p), "r"(a), "r"(b), "r"(c), "r"(d) : "memory");
}
__device__ __forceinline__ void st_vol2(uint2* p, uint32_t a, uint32_t b) {
  asm volatile("st.relaxed.gpu.global.v2.u32 [%0], {%1,%2};" :: "l"(p), "r"(a), "r"(b) : "memory");
}
__device__ __forceinline__ void stg128(void* p, uint4 v) {
  asm volatile("st.global.v4.u32 [%0], {%1,%2,%3,%4};" :: "l"(p), "r"(v.x), "r"(v.y), "r"(v.z), "r"(v.w));
}
__device__ __forceinline__ unsigned ld_relaxed(const unsigned* p) {
  unsigned v; asm volatile("ld.relaxed.gpu.global.u32 %0, [%1];" : "=r"(v) : "l"(p) : "memory"); return v;
}
__device__ __forceinline__ uint32_t pack_bf16(float lo, float hi) {
  uint32_t r; asm("cvt.rn.bf16x2.f32 %0, %1, %2;" : "=r"(r) : "f"(hi), "f"(lo)); return r;
}
__device__ __forceinline__ float bf_lo(uint32_t v) { return __uint_as_float(v << 16); }
__device__ __forceinline__ float bf_hi(uint32_t v) { return __uint_as_float(v & 0xFFFF0000u); }
__device__ __forceinline__ void stsm4(uint32_t addr, uint32_t a, uint32_t b, uint32_t c, uint32_t d) {
  asm volatile("stmatrix.sync.aligned.m8n8.x4.shared.b16 [%0], {%1,%2,%3,%4};" :: "r"(addr), "r"(a), "r"(b), "r"(c), "r"(d));
}
__device__ __forceinline__ void stsm4_t(uint32_t addr, uint32_t a, uint32_t b, uint32_t c, uint32_t d) {
  asm volatile("stmatrix.sync.aligned.m8n8.x4.trans.shared.b16 [%0], {%1,%2,%3,%4};" :: "r"(addr), "r"(a), "r"(b), "r"(c), "r"(d));
}
__device__ __forceinline__ void ldsm4(uint32_t addr, uint32_t& a, uint32_t& b, uint32_t& c, uint32_t& d) {
  asm volatile("ldmatrix.sync.aligned.m8n8.x4.shared.b16 {%0,%1,%2,%3}, [%4];" : "=r"(a), "=r"(b), "=r"(c), "=r"(d) : "r"(addr));
}
__device__ __forceinline__ uint4 lds128(uint32_t a) {
  uint4 v; asm volatile("ld.shared.v4.u32 {%0,%1,%2,%3}, [%4];" : "=r"(v.x), "=r"(v.y), "=r"(v.z), "=r"(v.w) : "r"(a)); return v;
}
__device__ __forceinline__ void sts128(uint32_t a, uint32_t x, uint32_t y, uint32_t z, uint32_t w) {
  asm volatile("st.shared.v4.u32 [%0], {%1,%2,%3,%4};" :: "r"(a), "r"(x), "r"(y), "r"(z), "r"(w));
}
__device__ __forceinline__ uint32_t hmul2_bf16(uint32_t a, uint32_t b) {
  uint32_t r; asm("mul.rn.bf16x2 %0, %1, %2;" : "=r"(r) : "r"(a), "r"(b)); return r;
}
__device__ __forceinline__ float gelu_tanh(float v) {
  float u = v * fmaf(0.0356774081f, v * v, 0.7978845608f);
  float t; asm("tanh.approx.f32 %0, %1;" : "=f"(t) : "f"(u));
  float hv = 0.5f * v;
  return fmaf(hv, t, hv);
}

template<int TB>
__device__ __forceinline__ void wgmma_n192(float (&d)[96], uint64_t da, uint64_t db, int scale_d) {
  asm volatile("{\n.reg .pred p;\nsetp.ne.b32 p, %98, 0;\n"
   "wgmma.mma_async.sync.aligned.m64n192k16.f32.bf16.bf16 {%0,%1,%2,%3,%4,%5,%6,%7,%8,%9,%10,%11,%12,%13,%14,%15,%16,%17,%18,%19,%20,%21,%22,%23,%24,%25,%26,%27,%28,%29,%30,%31,%32,%33,%34,%35,%36,%37,%38,%39,%40,%41,%42,%43,%44,%45,%46,%47,%48,%49,%50,%51,%52,%53,%54,%55,%56,%57,%58,%59,%60,%61,%62,%63,%64,%65,%66,%67,%68,%69,%70,%71,%72,%73,%74,%75,%76,%77,%78,%79,%80,%81,%82,%83,%84,%85,%86,%87,%88,%89,%90,%91,%92,%93,%94,%95}, %96, %97, p, 1, 1, 0, %99;\n}"
   : "+f"(d[0]),"+f"(d[1]),"+f"(d[2]),"+f"(d[3]),"+f"(d[4]),"+f"(d[5]),"+f"(d[6]),"+f"(d[7]),"+f"(d[8]),"+f"(d[9]),"+f"(d[10]),"+f"(d[11]),"+f"(d[12]),"+f"(d[13]),"+f"(d[14]),"+f"(d[15]),"+f"(d[16]),"+f"(d[17]),"+f"(d[18]),"+f"(d[19]),"+f"(d[20]),"+f"(d[21]),"+f"(d[22]),"+f"(d[23]),"+f"(d[24]),"+f"(d[25]),"+f"(d[26]),"+f"(d[27]),"+f"(d[28]),"+f"(d[29]),"+f"(d[30]),"+f"(d[31]),"+f"(d[32]),"+f"(d[33]),"+f"(d[34]),"+f"(d[35]),"+f"(d[36]),"+f"(d[37]),"+f"(d[38]),"+f"(d[39]),"+f"(d[40]),"+f"(d[41]),"+f"(d[42]),"+f"(d[43]),"+f"(d[44]),"+f"(d[45]),"+f"(d[46]),"+f"(d[47]),"+f"(d[48]),"+f"(d[49]),"+f"(d[50]),"+f"(d[51]),"+f"(d[52]),"+f"(d[53]),"+f"(d[54]),"+f"(d[55]),"+f"(d[56]),"+f"(d[57]),"+f"(d[58]),"+f"(d[59]),"+f"(d[60]),"+f"(d[61]),"+f"(d[62]),"+f"(d[63]),"+f"(d[64]),"+f"(d[65]),"+f"(d[66]),"+f"(d[67]),"+f"(d[68]),"+f"(d[69]),"+f"(d[70]),"+f"(d[71]),"+f"(d[72]),"+f"(d[73]),"+f"(d[74]),"+f"(d[75]),"+f"(d[76]),"+f"(d[77]),"+f"(d[78]),"+f"(d[79]),"+f"(d[80]),"+f"(d[81]),"+f"(d[82]),"+f"(d[83]),"+f"(d[84]),"+f"(d[85]),"+f"(d[86]),"+f"(d[87]),"+f"(d[88]),"+f"(d[89]),"+f"(d[90]),"+f"(d[91]),"+f"(d[92]),"+f"(d[93]),"+f"(d[94]),"+f"(d[95])
   : "l"(da), "l"(db), "r"(scale_d), "n"(TB));
}
template<int TB>
__device__ __forceinline__ void wgmma_n160(float (&d)[80], uint64_t da, uint64_t db, int scale_d) {
  asm volatile("{\n.reg .pred p;\nsetp.ne.b32 p, %82, 0;\n"
   "wgmma.mma_async.sync.aligned.m64n160k16.f32.bf16.bf16 {%0,%1,%2,%3,%4,%5,%6,%7,%8,%9,%10,%11,%12,%13,%14,%15,%16,%17,%18,%19,%20,%21,%22,%23,%24,%25,%26,%27,%28,%29,%30,%31,%32,%33,%34,%35,%36,%37,%38,%39,%40,%41,%42,%43,%44,%45,%46,%47,%48,%49,%50,%51,%52,%53,%54,%55,%56,%57,%58,%59,%60,%61,%62,%63,%64,%65,%66,%67,%68,%69,%70,%71,%72,%73,%74,%75,%76,%77,%78,%79}, %80, %81, p, 1, 1, 0, %83;\n}"
   : "+f"(d[0]),"+f"(d[1]),"+f"(d[2]),"+f"(d[3]),"+f"(d[4]),"+f"(d[5]),"+f"(d[6]),"+f"(d[7]),"+f"(d[8]),"+f"(d[9]),"+f"(d[10]),"+f"(d[11]),"+f"(d[12]),"+f"(d[13]),"+f"(d[14]),"+f"(d[15]),"+f"(d[16]),"+f"(d[17]),"+f"(d[18]),"+f"(d[19]),"+f"(d[20]),"+f"(d[21]),"+f"(d[22]),"+f"(d[23]),"+f"(d[24]),"+f"(d[25]),"+f"(d[26]),"+f"(d[27]),"+f"(d[28]),"+f"(d[29]),"+f"(d[30]),"+f"(d[31]),"+f"(d[32]),"+f"(d[33]),"+f"(d[34]),"+f"(d[35]),"+f"(d[36]),"+f"(d[37]),"+f"(d[38]),"+f"(d[39]),"+f"(d[40]),"+f"(d[41]),"+f"(d[42]),"+f"(d[43]),"+f"(d[44]),"+f"(d[45]),"+f"(d[46]),"+f"(d[47]),"+f"(d[48]),"+f"(d[49]),"+f"(d[50]),"+f"(d[51]),"+f"(d[52]),"+f"(d[53]),"+f"(d[54]),"+f"(d[55]),"+f"(d[56]),"+f"(d[57]),"+f"(d[58]),"+f"(d[59]),"+f"(d[60]),"+f"(d[61]),"+f"(d[62]),"+f"(d[63]),"+f"(d[64]),"+f"(d[65]),"+f"(d[66]),"+f"(d[67]),"+f"(d[68]),"+f"(d[69]),"+f"(d[70]),"+f"(d[71]),"+f"(d[72]),"+f"(d[73]),"+f"(d[74]),"+f"(d[75]),"+f"(d[76]),"+f"(d[77]),"+f"(d[78]),"+f"(d[79])
   : "l"(da), "l"(db), "r"(scale_d), "n"(TB));
}
template<int TB>
__device__ __forceinline__ void wgmma_n96(float (&d)[48], uint64_t da, uint64_t db, int scale_d) {
  asm volatile("{\n.reg .pred p;\nsetp.ne.b32 p, %50, 0;\n"
   "wgmma.mma_async.sync.aligned.m64n96k16.f32.bf16.bf16 {%0,%1,%2,%3,%4,%5,%6,%7,%8,%9,%10,%11,%12,%13,%14,%15,%16,%17,%18,%19,%20,%21,%22,%23,%24,%25,%26,%27,%28,%29,%30,%31,%32,%33,%34,%35,%36,%37,%38,%39,%40,%41,%42,%43,%44,%45,%46,%47}, %48, %49, p, 1, 1, 0, %51;\n}"
   : "+f"(d[0]),"+f"(d[1]),"+f"(d[2]),"+f"(d[3]),"+f"(d[4]),"+f"(d[5]),"+f"(d[6]),"+f"(d[7]),"+f"(d[8]),"+f"(d[9]),"+f"(d[10]),"+f"(d[11]),"+f"(d[12]),"+f"(d[13]),"+f"(d[14]),"+f"(d[15]),"+f"(d[16]),"+f"(d[17]),"+f"(d[18]),"+f"(d[19]),"+f"(d[20]),"+f"(d[21]),"+f"(d[22]),"+f"(d[23]),"+f"(d[24]),"+f"(d[25]),"+f"(d[26]),"+f"(d[27]),"+f"(d[28]),"+f"(d[29]),"+f"(d[30]),"+f"(d[31]),"+f"(d[32]),"+f"(d[33]),"+f"(d[34]),"+f"(d[35]),"+f"(d[36]),"+f"(d[37]),"+f"(d[38]),"+f"(d[39]),"+f"(d[40]),"+f"(d[41]),"+f"(d[42]),"+f"(d[43]),"+f"(d[44]),"+f"(d[45]),"+f"(d[46]),"+f"(d[47])
   : "l"(da), "l"(db), "r"(scale_d), "n"(TB));
}

template<int N, int TB>
__device__ __forceinline__ void wgmma_n(float (&d)[N / 2], uint64_t da, uint64_t db) {
  if constexpr (N == 192) wgmma_n192<TB>(d, da, db, 1);
  else if constexpr (N == 160) wgmma_n160<TB>(d, da, db, 1);
  else wgmma_n96<TB>(d, da, db, 1);
}

template<int R>
__device__ __forceinline__ void pin(float (&acc)[2][R]) {
  #pragma unroll
  for (int mi = 0; mi < 2; mi++)
    #pragma unroll
    for (int i = 0; i < R; i++) asm volatile("" : "+f"(acc[mi][i]) :: "memory");
}
template<int R>
__device__ __forceinline__ void zero(float (&acc)[2][R]) {
  #pragma unroll
  for (int i = 0; i < R; i++) { acc[0][i] = 0.f; acc[1][i] = 0.f; }
  pin(acc);
}

template<int N, int TB, bool CONT, int ORD_BAR>
__device__ __forceinline__ void mainloop(float (&acc)[2][N / 2], uint32_t sbase, uint32_t stage_bytes, int g0, int nk, int total, int mswap) {
  const uint32_t full0 = sbase + BAR_OFF, empty0 = full0 + 8 * STAGES, ring = sbase + RING_OFF;
  const int t = threadIdx.x & 127;
  const uint32_t da0 = (((ring + mswap * 8192) & 0x3FFFF) >> 4) | 0x10000u, da1 = (((ring + (mswap ^ 1) * 8192) & 0x3FFFF) >> 4) | 0x10000u;
  const uint32_t db0 = (((ring + A_BYTES) & 0x3FFFF) >> 4) | ((TB == 2 ? 256u : TB ? 512u : 1u) << 16);
  constexpr uint32_t HI_A = 0x40000040u, HI_B = TB == 2 ? 0x80000020u : 0x40000040u;
  #pragma unroll 1
  for (int g = g0; g < g0 + nk; g++) {
    const int s = g & (STAGES - 1);
    const uint32_t so = s * (stage_bytes >> 4);
    mbar_wait(full0 + 8 * s, (g / STAGES) & 1);
    wgmma_fence();
    #pragma unroll
    for (int k = 0; k < 4; k++) {
      const uint64_t db = desc64(db0 + so + (TB == 2 ? k * 64 : TB ? k * 128 : k * 2), HI_B);
      wgmma_n<N, TB != 0>(acc[0], desc64(da0 + so + k * 2, HI_A), db);
      wgmma_n<N, TB != 0>(acc[1], desc64(da1 + so + k * 2, HI_A), db);
    }
    wgmma_commit();
    if (ORD_BAR != 0 && g == g0 + nk - 1) bar_arrive<ORD_BAR>(256);
    wgmma_wait<1>();
    if (t < 2 && (CONT || g > g0) && g - 1 + STAGES < total) mbar_arrive_cluster(empty0 + 8 * ((g - 1) & (STAGES - 1)), t);
  }
}
template<int R>
__device__ __forceinline__ void drain(float (&acc)[2][R], uint32_t sbase, int glast, int total) {
  wgmma_wait<0>();
  pin(acc);
  const int t = threadIdx.x & 127;
  if (t < 2 && glast + STAGES < total) mbar_arrive_cluster(sbase + BAR_OFF + 8 * STAGES + 8 * (glast & (STAGES - 1)), t);
}

__device__ __forceinline__ void set_flag(int slot, int byte, unsigned epoch) {
  asm volatile("st.relaxed.gpu.global.u8 [%0], %1;" :: "l"(g_flags + slot * 256 + byte), "r"(epoch & 255u) : "memory");
}
__device__ __forceinline__ unsigned get_flag(int slot, int byte) {
  unsigned v; asm volatile("ld.relaxed.gpu.global.u8 %0, [%1];" : "=r"(v) : "l"(g_flags + slot * 256 + byte) : "memory"); return v;
}
__device__ __forceinline__ void publish(int slot, int byte, unsigned epoch) {
  asm volatile("fence.acq_rel.gpu;" ::: "memory");
  set_flag(slot, byte, epoch);
}

__device__ __forceinline__ float sum8(uint4 v) {
  return ((bf_lo(v.x) + bf_hi(v.x)) + (bf_lo(v.y) + bf_hi(v.y))) + ((bf_lo(v.z) + bf_hi(v.z)) + (bf_lo(v.w) + bf_hi(v.w)));
}
__device__ __forceinline__ uint4 ldg128(const void* p) {
  uint4 v; asm volatile("ld.global.nc.v4.u32 {%0,%1,%2,%3}, [%4];" : "=r"(v.x), "=r"(v.y), "=r"(v.z), "=r"(v.w) : "l"(p)); return v;
}
__device__ __forceinline__ void ln_load(const bf16* __restrict__ x, int cta, uint4 (&rv)[5]) {
  const int t = threadIdx.x - 128, row = cta * 16 + (t >> 4), c = t & 15;
  #pragma unroll
  for (int j = 0; j < 5; j++) rv[j] = ldg128(reinterpret_cast<const uint4*>(x + (size_t)row * DM) + c + 16 * j);
}
__device__ __forceinline__ void ln_rows(const uint4 (&rv)[5], int cta, unsigned epoch) {
  const int t = threadIdx.x - 128, row = cta * 16 + (t >> 4), c = t & 15;
  const float sh = __shfl_sync(0xffffffffu, bf_lo(rv[0].x), t & 16);
  float d[40], s = 0.f, q = 0.f;
  #pragma unroll
  for (int j = 0; j < 5; j++) {
    const uint32_t u[4] = {rv[j].x, rv[j].y, rv[j].z, rv[j].w};
    #pragma unroll
    for (int e = 0; e < 4; e++) {
      const float d0 = bf_lo(u[e]) - sh, d1 = bf_hi(u[e]) - sh;
      d[j * 8 + e * 2] = d0; d[j * 8 + e * 2 + 1] = d1;
      s += d0 + d1; q = fmaf(d0, d0, q); q = fmaf(d1, d1, q);
    }
  }
  #pragma unroll
  for (int o = 1; o < 16; o <<= 1) { s += __shfl_xor_sync(0xffffffffu, s, o); q += __shfl_xor_sync(0xffffffffu, q, o); }
  const float md = s * (1.f / DM);
  const float r = rsqrtf(fmaxf(fmaf(q, 1.f / DM, -md * md), 0.f) + LN_EPS), o = -md * r;
  if (c == 0) st_vol2(&g_xstat[row], __float_as_uint(r), (__float_as_uint(-(md + sh) * r) & ~255u) | (epoch & 255u));
  #pragma unroll
  for (int j = 0; j < 5; j++) {
    const float* a = &d[j * 8];
    stg128(reinterpret_cast<uint4*>(g_xn + (size_t)row * DM) + c + 16 * j, make_uint4(
           pack_bf16(fmaf(a[0], r, o), fmaf(a[1], r, o)), pack_bf16(fmaf(a[2], r, o), fmaf(a[3], r, o)),
           pack_bf16(fmaf(a[4], r, o), fmaf(a[5], r, o)), pack_bf16(fmaf(a[6], r, o), fmaf(a[7], r, o))));
  }
  bar_arrive<BAR_LN>(288);
}
__device__ __forceinline__ void colsum_part(const bf16* __restrict__ win, int cta, unsigned epoch) {
  const int t = threadIdx.x & 127, w = t >> 5, l = t & 31;
  const int cj = min(cta, 119), cg = cj % 24, rg = cj / 24;
  uint4 cv[4];
  #pragma unroll
  for (int j = 0; j < 4; j++) cv[j] = ldg128(reinterpret_cast<const uint4*>(win + (size_t)(rg * 128 + w * 32 + j * 8 + (l >> 2)) * FF + FH + cg * 32) + (l & 3));
  float v[8];
  v[0] = (bf_lo(cv[0].x) + bf_lo(cv[1].x)) + (bf_lo(cv[2].x) + bf_lo(cv[3].x)); v[1] = (bf_hi(cv[0].x) + bf_hi(cv[1].x)) + (bf_hi(cv[2].x) + bf_hi(cv[3].x));
  v[2] = (bf_lo(cv[0].y) + bf_lo(cv[1].y)) + (bf_lo(cv[2].y) + bf_lo(cv[3].y)); v[3] = (bf_hi(cv[0].y) + bf_hi(cv[1].y)) + (bf_hi(cv[2].y) + bf_hi(cv[3].y));
  v[4] = (bf_lo(cv[0].z) + bf_lo(cv[1].z)) + (bf_lo(cv[2].z) + bf_lo(cv[3].z)); v[5] = (bf_hi(cv[0].z) + bf_hi(cv[1].z)) + (bf_hi(cv[2].z) + bf_hi(cv[3].z));
  v[6] = (bf_lo(cv[0].w) + bf_lo(cv[1].w)) + (bf_lo(cv[2].w) + bf_lo(cv[3].w)); v[7] = (bf_hi(cv[0].w) + bf_hi(cv[1].w)) + (bf_hi(cv[2].w) + bf_hi(cv[3].w));
  #pragma unroll
  for (int st = 0; st < 3; st++) {
    const int n = 4 >> st;
    const bool up = (l & (4 * n)) != 0;
    #pragma unroll
    for (int e = 0; e < 4; e++)
      if (e < n) { const float keep = up ? v[e + n] : v[e], send = up ? v[e] : v[e + n]; v[e] = keep + __shfl_xor_sync(0xffffffffu, send, 4 * n); }
  }
  float* red = reinterpret_cast<float*>(smem + RED_OFF);
  red[w * 32 + (l & 3) * 8 + (l >> 2)] = v[0];
  bar_sync<BAR_WG2>(128);
  if (t < 32) st_vol2(&g_csum[rg * FH + cg * 32 + t], __float_as_uint((red[t] + red[32 + t]) + (red[64 + t] + red[96 + t])), epoch);
}

__device__ __forceinline__ void a_entry(int g, int grp, int rb, int& mi, int& kb) {
  if (g < 10) { mi = M_X; kb = g; }
  else if (g < 20) { mi = M_XN; kb = g - 10; }
  else if (grp == 0) {
    if (g < 52) { mi = M_WSP; kb = (g - 20); }
    else if (g < 52 + NX) { mi = M_WSIM; kb = g - 52 + 32 - NX; }
    else { mi = M_H; kb = g - 52 - NX; }
  } else {
    if (g < 30) { mi = M_XN; kb = g - 20; }
    else if (g < 62) { mi = M_WSRE; kb = (g - 30); }
    else { mi = M_WSIM; kb = g - 62; }
  }
}

__global__ void __cluster_dims__(2, 1, 1) __launch_bounds__(384, 1)
fused_kernel(const __grid_constant__ Maps maps, const bf16* __restrict__ x, const bf16* __restrict__ win, const bf16* __restrict__ bsp) {
  const uint32_t sbase = smem_u32(smem);
  const uint32_t full0 = sbase + BAR_OFF, empty0 = full0 + 8 * STAGES, dep0 = empty0 + 8 * STAGES, ring = sbase + RING_OFF;
  const int tid = threadIdx.x, wg = __shfl_sync(0xffffffffu, tid >> 7, 0);
  const int rank = blockIdx.x & 1;
  const int grp = (blockIdx.x >> 1) & 1, half = (blockIdx.x >> 2) & 1, rb = blockIdx.x >> 3;
  const int ct = half * 2 + rank, c8 = grp * 4 + ct;
  const int cta = rb * 8 + half * 4 + grp * 2 + rank;
  const int total = grp == 0 ? KB_A : KB_B;
  const uint32_t stage_bytes = grp == 0 ? STAGE_A : STAGE_B;

  uint4 rv[5];
  if (wg != 0) ln_load(x, cta, rv);
  const unsigned epoch = (ld_relaxed(&g_done) >> 7) + 1u;
  if (tid == 0) {
    TS(0, 0);
    for (int s = 0; s < STAGES; s++) { mbar_init(full0 + 8 * s, 2); mbar_init(empty0 + 8 * s, 2); mbar_init(dep0 + 8 * s, 1); }
    mbar_init(dep0 + 8 * STAGES, 1);
    *reinterpret_cast<volatile int*>(smem + READY_OFF) = 0;
    asm volatile("fence.mbarrier_init.release.cluster;" ::: "memory");
  }
  __syncthreads();
  asm volatile("barrier.cluster.arrive.relaxed.aligned;" ::: "memory");

  if (wg == 0) {
    asm volatile("setmaxnreg.dec.sync.aligned.u32 40;");
    const int warp = tid >> 5, lane = tid & 31;
    if (warp == 0) {
      const int row = rb * 128;
      if (lane == 0) {
        for (int g = 0; g < STAGES; g++) {
          mbar_expect_tx(full0 + 8 * g, A_BYTES);
          tma_load_2d(ring + g * stage_bytes, &maps.m[M_X], full0 + 8 * g, g * 64, row);
          tma_load_2d(ring + g * stage_bytes + 8192, &maps.m[M_X], full0 + 8 * g, g * 64, row + 64);
        }
      }
      __syncwarp();
      cluster_wait();
      if (lane == 0) {
        #pragma unroll 1
        for (int g = STAGES; g < total; g++) {
          int mi, kb;
          a_entry(g, grp, rb, mi, kb);
          if (g == 10 || (mi == M_H && kb == 0)) { TS(0, g > 10 ? 3 : 1); mbar_wait(dep0 + (g > 10 ? 24 : 0), 0); fence_async_global(); TS(0, g > 10 ? 4 : 2); }
          const int s = g & (STAGES - 1);
          mbar_wait(empty0 + 8 * s, ((g / STAGES) & 1) ^ 1);
          mbar_expect_tx(full0 + 8 * s, A_BYTES);
          tma_load_2d_mc(ring + s * stage_bytes + rank * 8192, &maps.m[mi], full0 + 8 * s, kb * 64, row + rank * 64, 3);
        }
        TS(0, 5);
      }
    } else if (warp == 1) {
      if (lane == 0) {
        int have = 0;
        #pragma unroll 1
        for (int g = 0; g < total; g++) {
          int kind = 1, mi, kb, c, dep = 0, need = 0;
          uint32_t bytes = 20480;
          if (g < 10) { kind = 0; mi = M_WIN32; kb = g; c = 24 + 3 * c8; bytes = 12288; }
          else if (grp == 0) {
            if (g < 20) { kind = 0; mi = M_WIN3; kb = g - 10; c = 3 * ct; bytes = 24576; }
            else if (g < 52) { kind = 0; mi = M_Z23; kb = (g - 20); c = 3 * ct; bytes = 24576; need = ((g - 20) >> 1) + 1; }
            else if (g < 52 + NX) { mi = M_AB; kb = g - 52 + 32 - NX; c = DM + ct * 160; dep = g == 52 ? 2 : 0; }
            else { kind = 0; mi = M_WOUT; kb = g - 52 - NX; c = ct * 5; }
          } else {
            if (g < 30) { mi = g < 20 ? M_WDRE : M_WDIM; kb = g < 20 ? g - 10 : g - 20; c = ct * 160; }
            else if (g < 62) { mi = M_AB; kb = (g - 30); c = ct * 160; need = ((g - 30) >> 1) + 1; }
            else { mi = M_AB; kb = g - 62; c = ct * 160 + DM; dep = g == 62 ? 2 : 0; }
          }
          if (need > have) {
            if (need == 1) TS(1, 0);
            unsigned it = 0;
            while ((have = *reinterpret_cast<volatile int*>(smem + READY_OFF)) < need && ++it < 50 * POLL_LIMIT) {}
            fence_async_global();
            if (need == 1) { TS(1, 1); TC(1); }
          }
          if (dep) { TS(1, dep * 2 - 2); mbar_wait(dep0 + 8 * dep, 0); fence_async_global(); TS(1, dep * 2 - 1); TC(dep); }
          const int s = g & (STAGES - 1);
          const uint32_t dst = ring + s * stage_bytes + A_BYTES, fb = full0 + 8 * s;
          mbar_wait(empty0 + 8 * s, ((g / STAGES) & 1) ^ 1);
          mbar_expect_tx(fb, bytes);
          if (kind == 0) tma_load_3d(dst, &maps.m[mi], fb, 0, kb * 64, c);
          else tma_load_2d(dst, &maps.m[mi], fb, kb * 64, c);
        }
      }
      __syncwarp();
      cluster_wait();
    } else if (warp == 2) {
      cluster_wait();
      {
        unsigned it = 0;
        uint2 v[4];
        while (true) {
          bool ok = true;
          #pragma unroll
          for (int i = 0; i < 4; i++) { v[i] = ld_vol2(&g_xstat[rb * 128 + i * 32 + lane]); ok = ok && ((v[i].y ^ epoch) & 255u) == 0; }
          if (ok || ++it > POLL_LIMIT) break;
          __nanosleep(POLL_NS);
        }
        #pragma unroll
        for (int i = 0; i < 4; i++) reinterpret_cast<uint2*>(smem + ROWSTAT_OFF)[i * 32 + lane] = make_uint2(v[i].x, v[i].y & ~255u);
        __syncwarp();
        TS(0, 6);
        bar_arrive<BAR_STATS>(192);
      }
      #pragma unroll 1
      for (int d = 0; d < 5 - 2 * grp; d++) {
        const int slot = d == 0 ? F_XN + rb : d == 4 ? F_Y + rb * 4 + ct : d == 3 ? F_H + rb : d == 2 ? F_B + ct : grp == 0 ? F_Z + ct : F_A + ct;
        const int byte = d == 0 ? lane & 7 : d == 4 ? 0 : d == 3 ? lane & 3 : (d == 1 && grp == 0) ? lane : lane >> 1;
        unsigned it = 0, m;
        while ((m = __ballot_sync(0xffffffffu, get_flag(slot, byte) != (epoch & 255u))) != 0 && ++it < POLL_LIMIT) {
          if (d == 1 && lane == 0) *reinterpret_cast<volatile int*>(smem + READY_OFF) = (__ffs(m) - 1) >> 1;
          __nanosleep(WATCH_NS);
        }
        if (d == 1 && lane == 0) *reinterpret_cast<volatile int*>(smem + READY_OFF) = 16;
        if (d < 4) TS(0, 8 + d * 2); else TS(0, 7);
        fence_async_global();
        __syncwarp();
        if (lane == 0 && d != 1) mbar_arrive(dep0 + 8 * d);
      }
    } else {
      cluster_wait();
      bar_sync<BAR_LN>(288);
      if (lane == 0) { TS(1, 5); publish(F_XN + rb, cta & 7, epoch); TS(1, 6); }
      __syncwarp();
      #pragma unroll 1
      for (int i = 0; i < 3; i++) {
        unsigned it = 0;
        while (true) {
          bool ok = true;
          float a = 0.f;
          #pragma unroll
          for (int p = 0; p < 5; p++) { const uint2 u = ld_vol2(&g_csum[p * FH + c8 * 96 + i * 32 + lane]); ok = ok && u.y == epoch; a += __uint_as_float(u.x); }
          reinterpret_cast<float*>(smem + COLSUM_OFF)[i * 32 + lane] = a;
          if (ok || ++it > POLL_LIMIT) break;
          __nanosleep(POLL_NS);
        }
      }
      __syncwarp();
      TS(1, 4);
      bar_arrive<BAR_STATS>(192);
      bar_sync<BAR_PUB1>(160);
      if (lane == 0) {
        TS(1, 7);
        tma_store_3d(&maps.m[M_Z232], ring + 4 * stage_bytes, 0, rb * 128, 3 * c8);
        bulk_commit();
        bulk_wait_all();
        set_flag(F_Z + (c8 >> 1), rb * 2 + (c8 & 1), epoch);
        TS(1, 8);
      }
      __syncwarp();
      if (grp == 0) {
        bar_arrive<BAR_BUF>(160);
      } else {
        bar_sync<BAR_PUB2>(160);
        if (lane == 0) set_flag(F_A + ct, rb, epoch);
        TS(1, 9);
        __syncwarp();
      }
      bar_sync<BAR_PUB1>(160);
      if (lane == 0) set_flag(grp == 0 ? F_H + rb : F_B + ct, grp == 0 ? ct : rb, epoch);
      TS(1, 10);
      if (grp == 0) {
        __syncwarp();
        bar_arrive<BAR_BUF>(160);
      } else {
        if (lane == 0) {
          mbar_expect_tx(dep0 + 8, 40960);
          tma_load_2d(ring + 4 * stage_bytes + 24576, &maps.m[M_XR], dep0 + 8, ct * 160, rb * 128);
        }
        __syncwarp();
        bar_sync<BAR_PUB2>(160);
        if (lane == 0) { set_flag(F_Y + rb * 4 + ct, 0, epoch); atomicAdd(&g_done, 1u); }
      }
    }
  } else {
    asm volatile("setmaxnreg.inc.sync.aligned.u32 232;");
    const int t = tid & 127, w = t >> 5, l = t & 31;
    const uint32_t buf = ring + 4 * stage_bytes;
    ln_rows(rv, cta, epoch);
    if (wg == 2) colsum_part(win, cta, epoch);
    TS(wg + 1, 0);
    cluster_wait();
    const int rl = w * 16 + ((l >> 3) & 1) * 8 + (l & 7);
    const int gr = w * 16 + (l & 15);
    const uint32_t st_base = buf + rl * 128;
    const uint32_t st_x = ((l >> 4) ^ (l & 7)) << 4;
    if (wg == 1) {
      float acc[2][48];
      zero(acc);
      mainloop<96, 2, false, BAR_ORD1>(acc, sbase, stage_bytes, 0, 10, total, 0);
      drain(acc, sbase, 9, total);
      TS(2, 2);
      bar_sync<BAR_STATS>(192);
      const float2* rs = reinterpret_cast<const float2*>(smem + ROWSTAT_OFF) + w * 16 + (l >> 2);
      const float2* cs = reinterpret_cast<const float2*>(smem + COLSUM_OFF) + (l & 3);
      float sum[4], sq[4];
      #pragma unroll
      for (int r = 0; r < 4; r++) {
        const float2 st = rs[(r >> 1) * 64 + (r & 1) * 8];
        float s0 = 0.f, q0 = 0.f;
        #pragma unroll
        for (int j = 0; j < 12; j++) {
          const float2 c = cs[j * 4];
          float* a = &acc[r >> 1][4 * j + (r & 1) * 2];
          a[0] = gelu_tanh(fmaf(a[0], st.x, st.y * c.x));
          a[1] = gelu_tanh(fmaf(a[1], st.x, st.y * c.y));
          s0 += a[0] + a[1]; q0 = fmaf(a[0], a[0], q0); q0 = fmaf(a[1], a[1], q0);
        }
        s0 += __shfl_xor_sync(0xffffffffu, s0, 1); q0 += __shfl_xor_sync(0xffffffffu, q0, 1);
        s0 += __shfl_xor_sync(0xffffffffu, s0, 2); q0 += __shfl_xor_sync(0xffffffffu, q0, 2);
        sum[r] = s0; sq[r] = q0;
      }
      TS(2, 4);
      float rstd, off;
      {
        const int qd = l & 3;
        const float sm = qd == 0 ? sum[0] : qd == 1 ? sum[1] : qd == 2 ? sum[2] : sum[3];
        const float sv = qd == 0 ? sq[0] : qd == 1 ? sq[1] : qd == 2 ? sq[2] : sq[3];
        const int row = (qd >> 1) * 64 + w * 16 + (qd & 1) * 8 + (l >> 2);
        const float mu = sm * (1.f / 96), m2 = fmaxf(sv - sm * mu, 0.f);
        st_vol2(&g_zstat[(rb * 8 + c8) * 128 + row], __float_as_uint(mu), (__float_as_uint(m2) & ~255u) | (epoch & 255u));
        uint2 v[7];
        unsigned n = 0;
        while (true) {
          bool ok = true;
          #pragma unroll
          for (int j = 0; j < 7; j++) v[j] = ld_vol2(&g_zstat[(rb * 8 + ((c8 + 1 + j) & 7)) * 128 + row]);
          #pragma unroll
          for (int j = 0; j < 7; j++) ok = ok && ((v[j].y ^ epoch) & 255u) == 0;
          if (ok || ++n > POLL_LIMIT) break;
          __nanosleep(POLL_NS);
        }
        float mean = mu, var = m2;
        #pragma unroll
        for (int j = 0; j < 7; j++) { mean += __uint_as_float(v[j].x); var += __uint_as_float(v[j].y & ~255u); }
        mean *= 0.125f;
        float d = (mu - mean) * (mu - mean);
        #pragma unroll
        for (int j = 0; j < 7; j++) d = fmaf(__uint_as_float(v[j].x) - mean, __uint_as_float(v[j].x) - mean, d);
        rstd = rsqrtf(fmaf(96.f, d, var) * (1.f / FH) + LN_EPS); off = -mean * rstd;
        __syncwarp();
      }
      TS(2, 5);
      #pragma unroll
      for (int mi = 0; mi < 2; mi++) {
        const float r0 = __shfl_sync(0xffffffffu, rstd, (l & 28) + mi * 2), o0 = __shfl_sync(0xffffffffu, off, (l & 28) + mi * 2);
        const float r1 = __shfl_sync(0xffffffffu, rstd, (l & 28) + mi * 2 + 1), o1 = __shfl_sync(0xffffffffu, off, (l & 28) + mi * 2 + 1);
        #pragma unroll
        for (int jj = 0; jj < 6; jj++) {
          const float* a = &acc[mi][8 * jj];
          stsm4(buf + (jj >> 1) * 8192 + mi * 4096 + rl * 64 + ((((jj & 1) * 2 + (l >> 4)) ^ ((l >> 1) & 3)) << 4),
                pack_bf16(fmaf(a[0], r0, o0), fmaf(a[1], r0, o0)), pack_bf16(fmaf(a[2], r1, o1), fmaf(a[3], r1, o1)),
                pack_bf16(fmaf(a[4], r0, o0), fmaf(a[5], r0, o0)), pack_bf16(fmaf(a[6], r1, o1), fmaf(a[7], r1, o1)));
        }
      }
      fence_async_smem();
      bar_arrive<BAR_PUB1>(160);
      TS(2, 6);
      if (grp == 0) {
        float acc[2][96];
        zero(acc);
        bar_sync<BAR_ORD2>(256);
        mainloop<192, 1, false, BAR_ORD1>(acc, sbase, STAGE_A, 20, 32, KB_A, 0);
        const float* bias = reinterpret_cast<const float*>(smem + BIAS_OFF) + w * 16 + (l >> 2);
        bar_sync<BAR_Z1>(256);
        drain(acc, sbase, 51, KB_A);
        TS(2, 7);
        {
          const float bb[4] = {bias[0], bias[8], bias[64], bias[72]};
          uint32_t z[2][4][4];
          #pragma unroll
          for (int i = 0; i < 4; i++) ldsm4(st_base + (st_x ^ (i << 5)), z[0][i][0], z[0][i][1], z[0][i][2], z[0][i][3]);
          #pragma unroll
          for (int bx = 0; bx < 6; bx++) {
            if (bx < 5) {
              #pragma unroll
              for (int i = 0; i < 4; i++)
                ldsm4(st_base + (bx + 1) * 8192 + (st_x ^ (i << 5)), z[(bx + 1) & 1][i][0], z[(bx + 1) & 1][i][1], z[(bx + 1) & 1][i][2], z[(bx + 1) & 1][i][3]);
            }
            const float b0 = bb[(bx / 3) * 2], b1 = bb[(bx / 3) * 2 + 1];
            #pragma unroll
            for (int i = 0; i < 4; i++) {
              const float* a = &acc[bx / 3][8 * ((bx % 3) * 4 + i)];
              const uint32_t* zz = z[bx & 1][i];
              stsm4(st_base + bx * 8192 + (st_x ^ (i << 5)),
                    hmul2_bf16(zz[0], pack_bf16(a[0] + b0, a[1] + b0)), hmul2_bf16(zz[1], pack_bf16(a[2] + b1, a[3] + b1)),
                    hmul2_bf16(zz[2], pack_bf16(a[4] + b0, a[5] + b0)), hmul2_bf16(zz[3], pack_bf16(a[6] + b1, a[7] + b1)));
            }
            fence_async_smem();
            __syncwarp();
            if (l == 0) {
              tma_store_2d(&maps.m[M_HS], buf + bx * 8192 + w * 2048, ct * 192 + (bx % 3) * 64, rb * 128 + (bx / 3) * 64 + w * 16);
              bulk_commit();
            }
          }
        }
        TS(2, 8);
        if (l == 0) bulk_wait_all();
        __syncwarp();
        bar_arrive<BAR_PUB1>(160);
        TS(2, 9);
        return;
      }
    } else {
      if (grp == 0) {
        reinterpret_cast<float*>(smem + BIAS_OFF)[t] = __bfloat162float(bsp[rb * 128 + t]);
        float acc[2][96];
        zero(acc);
        bar_sync<BAR_ORD1>(256);
        mainloop<192, 1, false, BAR_ORD2>(acc, sbase, STAGE_A, 10, 10, KB_A, 0);
        drain(acc, sbase, 19, KB_A);
        TS(3, 2);
        bar_sync<BAR_BUF>(160);
        #pragma unroll
        for (int mi = 0; mi < 2; mi++)
          #pragma unroll
          for (int jj = 0; jj < 12; jj++) {
            const float* a = &acc[mi][8 * jj];
            stsm4(st_base + mi * 24576 + (jj >> 2) * 8192 + (st_x ^ ((jj & 3) << 5)),
                  pack_bf16(a[0], a[1]), pack_bf16(a[2], a[3]), pack_bf16(a[4], a[5]), pack_bf16(a[6], a[7]));
          }
        __syncwarp();
        TS(3, 3);
        const uint32_t rbase = buf + (l >> 4) * 24576 + gr * 128;
        #pragma unroll 1
        for (int c2 = 0; c2 < 12; c2++) {
          const uint32_t ab = rbase + (c2 >> 2) * 8192;
          uint4 v[2];
          #pragma unroll
          for (int i = 0; i < 2; i++) v[i] = lds128(ab + (((((c2 & 3) * 2 + i) ^ l) & 7) << 4));
          #pragma unroll
          for (int i = 0; i < 2; i++)
            sts128(ab + (((((c2 & 3) * 2 + i) ^ l) & 7) << 4),
                   pack_bf16(gelu_tanh(bf_lo(v[i].x)), gelu_tanh(bf_hi(v[i].x))), pack_bf16(gelu_tanh(bf_lo(v[i].y)), gelu_tanh(bf_hi(v[i].y))),
                   pack_bf16(gelu_tanh(bf_lo(v[i].z)), gelu_tanh(bf_hi(v[i].z))), pack_bf16(gelu_tanh(bf_lo(v[i].w)), gelu_tanh(bf_hi(v[i].w))));
        }
        TS(3, 4);
        bar_arrive<BAR_Z1>(256);
      }
    }
    float acc[2][80];
    if (grp == 1) {
      zero(acc);
      if (wg == 2) {
        bar_sync<BAR_ORD1>(256);
        mainloop<160, 0, false, BAR_ORD2>(acc, sbase, STAGE_B, 10, 10, KB_B, 0);
      } else {
        bar_sync<BAR_ORD2>(256);
        mainloop<160, 0, false, BAR_ORD1>(acc, sbase, STAGE_B, 20, 10, KB_B, 0);
      }
      drain(acc, sbase, wg == 2 ? 19 : 29, KB_B);
      TS(wg + 1, wg == 1 ? 7 : 2);
      if (wg == 1) bar_sync<BAR_BUF>(256);
      const uint32_t sg = wg == 1 ? 0x80008000u : 0u;
      const uint32_t tb = buf + 24576 + ((l >> 4) * 8 + (l & 7)) * 128 + (((w * 2 + ((l >> 3) & 1)) ^ (l & 7)) << 4);
      #pragma unroll
      for (int mi = 0; mi < 2; mi++)
        #pragma unroll
        for (int jj = 0; jj < 10; jj++) {
          const float* a = &acc[mi][8 * jj];
          stsm4_t(tb + mi * 20480 + jj * 2048, pack_bf16(a[0], a[1]) ^ sg, pack_bf16(a[2], a[3]) ^ sg, pack_bf16(a[4], a[5]) ^ sg, pack_bf16(a[6], a[7]) ^ sg);
        }
      fence_async_smem();
      if (wg == 1) bar_sync<BAR_WG1>(128); else bar_sync<BAR_WG2>(128);
      TS(wg + 1, wg == 1 ? 8 : 6);
      if (l == 0) {
        #pragma unroll 1
        for (int i = 0; i < 2; i++) {
          tma_store_2d(&maps.m[M_ABS], buf + 24576 + i * 20480 + w * 5120, rb * 128 + i * 64, (2 - wg) * DM + ct * 160 + w * 40);
          bulk_commit();
        }
        bulk_wait_all();
      }
      __syncwarp();
      TS(wg + 1, wg == 1 ? 9 : 10);
      if (wg == 1) { bar_arrive<BAR_PUB1>(160); return; }
      bar_arrive<BAR_PUB2>(160);
      bar_arrive<BAR_BUF>(256);
    }
    zero(acc);
    bar_sync<BAR_ORD1>(256);
    mainloop<160, 0, false, 0>(acc, sbase, stage_bytes, grp == 0 ? 52 : 30, grp == 0 ? NX : 64 - NX, total, 0);
    if (grp == 0) mainloop<160, 2, true, 0>(acc, sbase, STAGE_A, 52 + NX, 12, KB_A, 0);
    const uint32_t slab = buf + grp * 24576 + w * (16 * 320);
    const uint32_t addr = slab + (((l >> 3) & 1) * 8 + (l & 7)) * 320 + (l >> 4) * 16;
    if (grp == 0) bar_sync<BAR_BUF>(160); else mbar_wait(dep0 + 8, 0);
    drain(acc, sbase, total - 1, total);
    TS(3, 12);
    #pragma unroll
    for (int mi = 0; mi < 2; mi++) {
      if (grp == 1) {
        #pragma unroll
        for (int jj = 0; jj < 10; jj++) {
          uint32_t z0, z1, z2, z3;
          ldsm4(addr + mi * 20480 + jj * 32, z0, z1, z2, z3);
          float* a = &acc[mi][8 * jj];
          a[0] += bf_lo(z0); a[1] += bf_hi(z0); a[2] += bf_lo(z1); a[3] += bf_hi(z1);
          a[4] += bf_lo(z2); a[5] += bf_hi(z2); a[6] += bf_lo(z3); a[7] += bf_hi(z3);
        }
      }
      #pragma unroll
      for (int jj = 0; jj < 10; jj++) {
        const float* a = &acc[mi][8 * jj];
        stsm4(addr + mi * 20480 + jj * 32, pack_bf16(a[0], a[1]), pack_bf16(a[2], a[3]), pack_bf16(a[4], a[5]), pack_bf16(a[6], a[7]));
      }
    }
    fence_async_smem();
    __syncwarp();
    TS(3, 13);
    if (l == 0) {
      if (grp == 0) {
        mbar_wait(dep0 + 32, 0);
        fence_async_global();
        TS(3, 14);
        tma_reduce_2d(&maps.m[M_OUT], slab, ct * 160, rb * 128 + w * 16);
        tma_reduce_2d(&maps.m[M_OUT], slab + 20480, ct * 160, rb * 128 + 64 + w * 16);
        bulk_commit();
        bulk_wait_read();
        if (w == 0) atomicAdd(&g_done, 1u);
      } else {
        tma_store_2d(&maps.m[M_OUT], slab, ct * 160, rb * 128 + w * 16);
        tma_store_2d(&maps.m[M_OUT], slab + 20480, ct * 160, rb * 128 + 64 + w * 16);
        bulk_commit();
        bulk_wait_all();
      }
    }
    __syncwarp();
    if (grp == 1) bar_arrive<BAR_PUB2>(160);
    TS(3, 15);
  }
}

typedef CUresult (*EncodeFn)(CUtensorMap*, CUtensorMapDataType, cuuint32_t, void*, const cuuint64_t*, const cuuint64_t*,
                             const cuuint32_t*, const cuuint32_t*, CUtensorMapInterleave, CUtensorMapSwizzle,
                             CUtensorMapL2promotion, CUtensorMapFloatOOBfill);

void make2d(EncodeFn enc, CUtensorMap* m, const void* p, uint64_t cols, uint64_t rows, uint32_t bc, uint32_t br, bool swz = true) {
  cuuint64_t gd[2] = {cols, rows}, gs[1] = {cols * 2};
  cuuint32_t bd[2] = {bc, br}, es[2] = {1, 1};
  enc(m, CU_TENSOR_MAP_DATA_TYPE_BFLOAT16, 2, const_cast<void*>(p), gd, gs, bd, es, CU_TENSOR_MAP_INTERLEAVE_NONE,
      swz ? CU_TENSOR_MAP_SWIZZLE_128B : CU_TENSOR_MAP_SWIZZLE_NONE, PROMO, CU_TENSOR_MAP_FLOAT_OOB_FILL_NONE);
}
void make3d(EncodeFn enc, CUtensorMap* m, const void* p, uint64_t cols, uint64_t rows, uint32_t cw, uint32_t nc, uint32_t br = 64) {
  cuuint64_t gd[3] = {cw, rows, cols / cw}, gs[2] = {cols * 2, cw * 2};
  cuuint32_t bd[3] = {cw, br, nc}, es[3] = {1, 1, 1};
  enc(m, CU_TENSOR_MAP_DATA_TYPE_BFLOAT16, 3, const_cast<void*>(p), gd, gs, bd, es, CU_TENSOR_MAP_INTERLEAVE_NONE,
      cw == 64 ? CU_TENSOR_MAP_SWIZZLE_128B : CU_TENSOR_MAP_SWIZZLE_64B, PROMO, CU_TENSOR_MAP_FLOAT_OOB_FILL_NONE);
}

}

extern "C" void kernel_launch(void* const* d_in, const int* in_sizes, int n_in, void* d_out, int out_size) {
  const bf16* x = (const bf16*)d_in[0];
  const bf16* wsre = (const bf16*)d_in[1];
  const bf16* wsim = (const bf16*)d_in[2];
  const bf16* wdre = (const bf16*)d_in[3];
  const bf16* wdim = (const bf16*)d_in[4];
  const bf16* win = (const bf16*)d_in[6];
  const bf16* wsp = (const bf16*)d_in[7];
  const bf16* bsp = (const bf16*)d_in[8];
  const bf16* wout = (const bf16*)d_in[9];

  void* fn = nullptr;
  cudaDriverEntryPointQueryResult qr;
  cudaGetDriverEntryPoint("cuTensorMapEncodeTiled", &fn, cudaEnableDefault, &qr);
  EncodeFn enc = (EncodeFn)fn;
  void *abT, *z2, *h, *xn;
  cudaGetSymbolAddress(&xn, g_xn);
  cudaGetSymbolAddress(&abT, g_abT);
  cudaGetSymbolAddress(&z2, g_z2);
  cudaGetSymbolAddress(&h, g_h);

  Maps maps;
  make2d(enc, &maps.m[M_X], x, DM, SEQ, 64, 64);
  make2d(enc, &maps.m[M_XN], xn, DM, SEQ, 64, 64);
  make3d(enc, &maps.m[M_Z232], z2, FH, SEQ, 32, 3, 128);
  make2d(enc, &maps.m[M_XR], x, DM, SEQ, 160, 128, false);
  make3d(enc, &maps.m[M_WIN32], win, FF, DM, 32, 3);
  make2d(enc, &maps.m[M_WSRE], wsre, SEQ, SEQ, 64, 64);
  make2d(enc, &maps.m[M_WSIM], wsim, SEQ, SEQ, 64, 64);
  make2d(enc, &maps.m[M_WSP], wsp, SEQ, SEQ, 64, 64);
  make2d(enc, &maps.m[M_H], h, FH, SEQ, 64, 64);
  make3d(enc, &maps.m[M_WIN3], win, FF, DM, 64, 3);
  make3d(enc, &maps.m[M_Z23], z2, FH, SEQ, 64, 3);
  make2d(enc, &maps.m[M_WDRE], wdre, DM, DM, 64, 160);
  make2d(enc, &maps.m[M_WDIM], wdim, DM, DM, 64, 160);
  make2d(enc, &maps.m[M_AB], abT, SEQ, 2 * DM, 64, 160);
  make3d(enc, &maps.m[M_WOUT], wout, DM, FH, 32, 5);
  make2d(enc, &maps.m[M_HS], h, FH, SEQ, 64, 16);
  make2d(enc, &maps.m[M_ABS], abT, SEQ, 2 * DM, 64, 40);
  make2d(enc, &maps.m[M_OUT], d_out, DM, SEQ, 160, 16, false);

  cudaFuncSetAttribute(fused_kernel, cudaFuncAttributeMaxDynamicSharedMemorySize, SMEM_BYTES);
  fused_kernel<<<128, 384, SMEM_BYTES>>>(maps, x, win, bsp);
}
```

```cpp
#include <cuda_runtime.h>
#include <cuda_bf16.h>
#include <cuda.h>
#include <stdint.h>

namespace {

typedef __nv_bfloat16 bf16;

constexpr int SEQ = 2048, DM = 640, FF = 1536, FH = 768;
#define NXV 11
constexpr int NX = NXV;
constexpr int STAGES = 4;
constexpr int A_BYTES = 16384;
constexpr int BIAS_OFF = 0;
constexpr int BAR_OFF = 512;
constexpr int READY_OFF = 640;
constexpr int ROWSTAT_OFF = 1024;
constexpr int COLSUM_OFF = 2048;
constexpr int RED_OFF = 2560;
constexpr int RING_OFF = 3072;
constexpr int STAGE_A = 40960, STAGE_B = 36864;
constexpr int SMEM_BYTES = RING_OFF + 4 * STAGE_A + 49152;
constexpr int KB_A = 20 + 32 + NX + 12;
constexpr int KB_B = 30 + 64 - NX;
constexpr float LN_EPS = 1e-5f;
constexpr unsigned POLL_LIMIT = 100000;
#define POLL_NS 100
#define PF_D 0
#define ROT 0
#define Z1_NS 0
#define INFL 2
#define LIM_G 1000
#define MAPV 0
#define PROMO CU_TENSOR_MAP_L2_PROMOTION_L2_128B
#define WATCH_NS 40
#define PF_NS 150

constexpr int BAR_ORD1 = 1, BAR_ORD2 = 2, BAR_WG1 = 3, BAR_WG2 = 4, BAR_LN = 5, BAR_BUF = 6, BAR_Z1 = 7, BAR_PUB1 = 8, BAR_PUB2 = 9, BAR_STATS = 10;

enum { M_X, M_XN, M_XR, M_WIN32, M_Z232, M_WSRE, M_WSIM, M_WSP, M_H, M_WIN3, M_Z23, M_WDRE, M_WDIM, M_AB, M_WOUT, M_OUT, M_HS, M_ABS, M_COUNT };
struct Maps { CUtensorMap m[M_COUNT]; };

__device__ __align__(1024) bf16 g_abT[2 * DM * SEQ];
__device__ __align__(1024) bf16 g_z2[SEQ * FH];
__device__ __align__(1024) bf16 g_h[SEQ * FH];
__device__ __align__(1024) bf16 g_xn[SEQ * DM];
__device__ __align__(16) uint2 g_xstat[SEQ];
__device__ __align__(16) uint2 g_csum[5 * FH];
__device__ __align__(16) uint2 g_zstat[128 * 128];
__device__ __align__(256) unsigned char g_flags[108 * 256];
constexpr int F_A = 0, F_B = 4, F_Z = 8, F_H = 12, F_XN = 28, F_Y = 44;
__device__ unsigned g_done;
#define TS(role, ev)
#define TC(i)

extern __shared__ __align__(1024) uint8_t smem[];

__device__ __forceinline__ uint32_t smem_u32(const void* p) { return (uint32_t)__cvta_generic_to_shared(p); }
__device__ __forceinline__ void mbar_init(uint32_t bar, uint32_t cnt) { asm volatile("mbarrier.init.shared::cta.b64 [%0], %1;" :: "r"(bar), "r"(cnt)); }
__device__ __forceinline__ void mbar_expect_tx(uint32_t bar, uint32_t bytes) { asm volatile("mbarrier.arrive.expect_tx.shared::cta.b64 _, [%0], %1;" :: "r"(bar), "r"(bytes) : "memory"); }
__device__ __forceinline__ void mbar_arrive(uint32_t bar) { asm volatile("mbarrier.arrive.shared::cta.b64 _, [%0];" :: "r"(bar) : "memory"); }
__device__ __forceinline__ void mbar_arrive_cluster(uint32_t bar, uint32_t cta) {
  asm volatile("{\n.reg .b32 ra;\nmapa.shared::cluster.u32 ra, %0, %1;\nmbarrier.arrive.shared::cluster.b64 _, [ra];\n}" :: "r"(bar), "r"(cta) : "memory");
}
__device__ __forceinline__ void mbar_wait(uint32_t bar, uint32_t parity) {
  asm volatile("{\n.reg .pred p;\n.reg .u32 n;\nmov.u32 n, 0;\n"
               "LW: mbarrier.try_wait.parity.shared::cta.b64 p, [%0], %1, 2000;\n@p bra LD;\n"
               "add.u32 n, n, 1;\nsetp.lt.u32 p, n, 20000;\n@p bra LW;\nLD:\n}" :: "r"(bar), "r"(parity) : "memory");
}
__device__ __forceinline__ void tma_load_2d(uint32_t dst, const CUtensorMap* map, uint32_t bar, int c0, int c1) {
  asm volatile("cp.async.bulk.tensor.2d.shared::cluster.global.mbarrier::complete_tx::bytes [%0], [%1, {%3, %4}], [%2];"
    :: "r"(dst), "l"((uint64_t)map), "r"(bar), "r"(c0), "r"(c1) : "memory");
}
__device__ __forceinline__ void tma_load_3d(uint32_t dst, const CUtensorMap* map, uint32_t bar, int c0, int c1, int c2) {
  asm volatile("cp.async.bulk.tensor.3d.shared::cluster.global.mbarrier::complete_tx::bytes [%0], [%1, {%3, %4, %5}], [%2];"
    :: "r"(dst), "l"((uint64_t)map), "r"(bar), "r"(c0), "r"(c1), "r"(c2) : "memory");
}
__device__ __forceinline__ void tma_load_2d_mc(uint32_t dst, const CUtensorMap* map, uint32_t bar, int c0, int c1, uint16_t mask) {
  asm volatile("cp.async.bulk.tensor.2d.shared::cluster.global.mbarrier::complete_tx::bytes.multicast::cluster [%0], [%1, {%3, %4}], [%2], %5;"
    :: "r"(dst), "l"((uint64_t)map), "r"(bar), "r"(c0), "r"(c1), "h"(mask) : "memory");
}
__device__ __forceinline__ void tma_store_2d(const CUtensorMap* map, uint32_t src, int c0, int c1) {
  asm volatile("cp.async.bulk.tensor.2d.global.shared::cta.bulk_group [%0, {%2, %3}], [%1];"
    :: "l"((uint64_t)map), "r"(src), "r"(c0), "r"(c1) : "memory");
}
__device__ __forceinline__ void tma_store_3d(const CUtensorMap* map, uint32_t src, int c0, int c1, int c2) {
  asm volatile("cp.async.bulk.tensor.3d.global.shared::cta.bulk_group [%0, {%2, %3, %4}], [%1];"
    :: "l"((uint64_t)map), "r"(src), "r"(c0), "r"(c1), "r"(c2) : "memory");
}
__device__ __forceinline__ void tma_reduce_2d(const CUtensorMap* map, uint32_t src, int c0, int c1) {
  asm volatile("cp.reduce.async.bulk.tensor.2d.global.shared::cta.add.tile.bulk_group [%0, {%2, %3}], [%1];"
    :: "l"((uint64_t)map), "r"(src), "r"(c0), "r"(c1) : "memory");
}
__device__ __forceinline__ void bulk_wait_all() { asm volatile("cp.async.bulk.wait_group 0;" ::: "memory"); }
__device__ __forceinline__ void bulk_commit() { asm volatile("cp.async.bulk.commit_group;" ::: "memory"); }
__device__ __forceinline__ void bulk_wait_read() { asm volatile("cp.async.bulk.wait_group.read 0;" ::: "memory"); }
__device__ __forceinline__ void fence_async_smem() { asm volatile("fence.proxy.async.shared::cta;" ::: "memory"); }
__device__ __forceinline__ void fence_async_global() { asm volatile("fence.proxy.async.global;" ::: "memory"); }
__device__ __forceinline__ void wgmma_fence() { asm volatile("wgmma.fence.sync.aligned;" ::: "memory"); }
__device__ __forceinline__ void wgmma_commit() { asm volatile("wgmma.commit_group.sync.aligned;" ::: "memory"); }
template<int N> __device__ __forceinline__ void wgmma_wait() { asm volatile("wgmma.wait_group.sync.aligned %0;" :: "n"(N) : "memory"); }
template<int ID> __device__ __forceinline__ void bar_sync(int n) { asm volatile("bar.sync %0, %1;" :: "n"(ID), "r"(n) : "memory"); }
template<int ID> __device__ __forceinline__ void bar_arrive(int n) { asm volatile("bar.arrive %0, %1;" :: "n"(ID), "r"(n) : "memory"); }
__device__ __forceinline__ void cluster_wait() { asm volatile("barrier.cluster.wait.aligned;" ::: "memory"); }
__device__ __forceinline__ uint64_t desc64(uint32_t lo, uint32_t hi) { return (uint64_t)lo | ((uint64_t)hi << 32); }
__device__ __forceinline__ uint4 ld_vol4(const uint4* p) {
  uint4 v; asm volatile("ld.relaxed.gpu.global.v4.u32 {%0,%1,%2,%3}, [%4];" : "=r"(v.x), "=r"(v.y), "=r"(v.z), "=r"(v.w) : "l"(p) : "memory"); return v;
}
__device__ __forceinline__ uint2 ld_vol2(const uint2* p) {
  uint2 v; asm volatile("ld.relaxed.gpu.global.v2.u32 {%0,%1}, [%2];" : "=r"(v.x), "=r"(v.y) : "l"(p) : "memory"); return v;
}
__device__ __forceinline__ void st_vol4(uint4* p, uint32_t a, uint32_t b, uint32_t c, uint32_t d) {
  asm volatile("st.relaxed.gpu.global.v4.u32 [%0], {%1,%2,%3,%4};" :: "l"(p), "r"(a), "r"(b), "r"(c), "r"(d) : "memory");
}
__device__ __forceinline__ void st_vol2(uint2* p, uint32_t a, uint32_t b) {
  asm volatile("st.relaxed.gpu.global.v2.u32 [%0], {%1,%2};" :: "l"(p), "r"(a), "r"(b) : "memory");
}
__device__ __forceinline__ void stg128(void* p, uint4 v) {
  asm volatile("st.global.v4.u32 [%0], {%1,%2,%3,%4};" :: "l"(p), "r"(v.x), "r"(v.y), "r"(v.z), "r"(v.w));
}
__device__ __forceinline__ unsigned ld_relaxed(const unsigned* p) {
  unsigned v; asm volatile("ld.relaxed.gpu.global.u32 %0, [%1];" : "=r"(v) : "l"(p) : "memory"); return v;
}
__device__ __forceinline__ uint32_t pack_bf16(float lo, float hi) {
  uint32_t r; asm("cvt.rn.bf16x2.f32 %0, %1, %2;" : "=r"(r) : "f"(hi), "f"(lo)); return r;
}
__device__ __forceinline__ float bf_lo(uint32_t v) { return __uint_as_float(v << 16); }
__device__ __forceinline__ float bf_hi(uint32_t v) { return __uint_as_float(v & 0xFFFF0000u); }
__device__ __forceinline__ void stsm4(uint32_t addr, uint32_t a, uint32_t b, uint32_t c, uint32_t d) {
  asm volatile("stmatrix.sync.aligned.m8n8.x4.shared.b16 [%0], {%1,%2,%3,%4};" :: "r"(addr), "r"(a), "r"(b), "r"(c), "r"(d));
}
__device__ __forceinline__ void stsm4_t(uint32_t addr, uint32_t a, uint32_t b, uint32_t c, uint32_t d) {
  asm volatile("stmatrix.sync.aligned.m8n8.x4.trans.shared.b16 [%0], {%1,%2,%3,%4};" :: "r"(addr), "r"(a), "r"(b), "r"(c), "r"(d));
}
__device__ __forceinline__ void ldsm4(uint32_t addr, uint32_t& a, uint32_t& b, uint32_t& c, uint32_t& d) {
  asm volatile("ldmatrix.sync.aligned.m8n8.x4.shared.b16 {%0,%1,%2,%3}, [%4];" : "=r"(a), "=r"(b), "=r"(c), "=r"(d) : "r"(addr));
}
__device__ __forceinline__ uint4 lds128(uint32_t a) {
  uint4 v; asm volatile("ld.shared.v4.u32 {%0,%1,%2,%3}, [%4];" : "=r"(v.x), "=r"(v.y), "=r"(v.z), "=r"(v.w) : "r"(a)); return v;
}
__device__ __forceinline__ void sts128(uint32_t a, uint32_t x, uint32_t y, uint32_t z, uint32_t w) {
  asm volatile("st.shared.v4.u32 [%0], {%1,%2,%3,%4};" :: "r"(a), "r"(x), "r"(y), "r"(z), "r"(w));
}
__device__ __forceinline__ uint32_t hmul2_bf16(uint32_t a, uint32_t b) {
  uint32_t r; asm("mul.rn.bf16x2 %0, %1, %2;" : "=r"(r) : "r"(a), "r"(b)); return r;
}
__device__ __forceinline__ float gelu_tanh(float v) {
  float u = v * fmaf(0.0356774081f, v * v, 0.7978845608f);
  float t; asm("tanh.approx.f32 %0, %1;" : "=f"(t) : "f"(u));
  float hv = 0.5f * v;
  return fmaf(hv, t, hv);
}

template<int TB>
__device__ __forceinline__ void wgmma_n192(float (&d)[96], uint64_t da, uint64_t db, int scale_d) {
  asm volatile("{\n.reg .pred p;\nsetp.ne.b32 p, %98, 0;\n"
   "wgmma.mma_async.sync.aligned.m64n192k16.f32.bf16.bf16 {%0,%1,%2,%3,%4,%5,%6,%7,%8,%9,%10,%11,%12,%13,%14,%15,%16,%17,%18,%19,%20,%21,%22,%23,%24,%25,%26,%27,%28,%29,%30,%31,%32,%33,%34,%35,%36,%37,%38,%39,%40,%41,%42,%43,%44,%45,%46,%47,%48,%49,%50,%51,%52,%53,%54,%55,%56,%57,%58,%59,%60,%61,%62,%63,%64,%65,%66,%67,%68,%69,%70,%71,%72,%73,%74,%75,%76,%77,%78,%79,%80,%81,%82,%83,%84,%85,%86,%87,%88,%89,%90,%91,%92,%93,%94,%95}, %96, %97, p, 1, 1, 0, %99;\n}"
   : "+f"(d[0]),"+f"(d[1]),"+f"(d[2]),"+f"(d[3]),"+f"(d[4]),"+f"(d[5]),"+f"(d[6]),"+f"(d[7]),"+f"(d[8]),"+f"(d[9]),"+f"(d[10]),"+f"(d[11]),"+f"(d[12]),"+f"(d[13]),"+f"(d[14]),"+f"(d[15]),"+f"(d[16]),"+f"(d[17]),"+f"(d[18]),"+f"(d[19]),"+f"(d[20]),"+f"(d[21]),"+f"(d[22]),"+f"(d[23]),"+f"(d[24]),"+f"(d[25]),"+f"(d[26]),"+f"(d[27]),"+f"(d[28]),"+f"(d[29]),"+f"(d[30]),"+f"(d[31]),"+f"(d[32]),"+f"(d[33]),"+f"(d[34]),"+f"(d[35]),"+f"(d[36]),"+f"(d[37]),"+f"(d[38]),"+f"(d[39]),"+f"(d[40]),"+f"(d[41]),"+f"(d[42]),"+f"(d[43]),"+f"(d[44]),"+f"(d[45]),"+f"(d[46]),"+f"(d[47]),"+f"(d[48]),"+f"(d[49]),"+f"(d[50]),"+f"(d[51]),"+f"(d[52]),"+f"(d[53]),"+f"(d[54]),"+f"(d[55]),"+f"(d[56]),"+f"(d[57]),"+f"(d[58]),"+f"(d[59]),"+f"(d[60]),"+f"(d[61]),"+f"(d[62]),"+f"(d[63]),"+f"(d[64]),"+f"(d[65]),"+f"(d[66]),"+f"(d[67]),"+f"(d[68]),"+f"(d[69]),"+f"(d[70]),"+f"(d[71]),"+f"(d[72]),"+f"(d[73]),"+f"(d[74]),"+f"(d[75]),"+f"(d[76]),"+f"(d[77]),"+f"(d[78]),"+f"(d[79]),"+f"(d[80]),"+f"(d[81]),"+f"(d[82]),"+f"(d[83]),"+f"(d[84]),"+f"(d[85]),"+f"(d[86]),"+f"(d[87]),"+f"(d[88]),"+f"(d[89]),"+f"(d[90]),"+f"(d[91]),"+f"(d[92]),"+f"(d[93]),"+f"(d[94]),"+f"(d[95])
   : "l"(da), "l"(db), "r"(scale_d), "n"(TB));
}
template<int TB>
__device__ __forceinline__ void wgmma_n160(float (&d)[80], uint64_t da, uint64_t db, int scale_d) {
  asm volatile("{\n.reg .pred p;\nsetp.ne.b32 p, %82, 0;\n"
   "wgmma.mma_async.sync.aligned.m64n160k16.f32.bf16.bf16 {%0,%1,%2,%3,%4,%5,%6,%7,%8,%9,%10,%11,%12,%13,%14,%15,%16,%17,%18,%19,%20,%21,%22,%23,%24,%25,%26,%27,%28,%29,%30,%31,%32,%33,%34,%35,%36,%37,%38,%39,%40,%41,%42,%43,%44,%45,%46,%47,%48,%49,%50,%51,%52,%53,%54,%55,%56,%57,%58,%59,%60,%61,%62,%63,%64,%65,%66,%67,%68,%69,%70,%71,%72,%73,%74,%75,%76,%77,%78,%79}, %80, %81, p, 1, 1, 0, %83;\n}"
   : "+f"(d[0]),"+f"(d[1]),"+f"(d[2]),"+f"(d[3]),"+f"(d[4]),"+f"(d[5]),"+f"(d[6]),"+f"(d[7]),"+f"(d[8]),"+f"(d[9]),"+f"(d[10]),"+f"(d[11]),"+f"(d[12]),"+f"(d[13]),"+f"(d[14]),"+f"(d[15]),"+f"(d[16]),"+f"(d[17]),"+f"(d[18]),"+f"(d[19]),"+f"(d[20]),"+f"(d[21]),"+f"(d[22]),"+f"(d[23]),"+f"(d[24]),"+f"(d[25]),"+f"(d[26]),"+f"(d[27]),"+f"(d[28]),"+f"(d[29]),"+f"(d[30]),"+f"(d[31]),"+f"(d[32]),"+f"(d[33]),"+f"(d[34]),"+f"(d[35]),"+f"(d[36]),"+f"(d[37]),"+f"(d[38]),"+f"(d[39]),"+f"(d[40]),"+f"(d[41]),"+f"(d[42]),"+f"(d[43]),"+f"(d[44]),"+f"(d[45]),"+f"(d[46]),"+f"(d[47]),"+f"(d[48]),"+f"(d[49]),"+f"(d[50]),"+f"(d[51]),"+f"(d[52]),"+f"(d[53]),"+f"(d[54]),"+f"(d[55]),"+f"(d[56]),"+f"(d[57]),"+f"(d[58]),"+f"(d[59]),"+f"(d[60]),"+f"(d[61]),"+f"(d[62]),"+f"(d[63]),"+f"(d[64]),"+f"(d[65]),"+f"(d[66]),"+f"(d[67]),"+f"(d[68]),"+f"(d[69]),"+f"(d[70]),"+f"(d[71]),"+f"(d[72]),"+f"(d[73]),"+f"(d[74]),"+f"(d[75]),"+f"(d[76]),"+f"(d[77]),"+f"(d[78]),"+f"(d[79])
   : "l"(da), "l"(db), "r"(scale_d), "n"(TB));
}
template<int TB>
__device__ __forceinline__ void wgmma_n96(float (&d)[48], uint64_t da, uint64_t db, int scale_d) {
  asm volatile("{\n.reg .pred p;\nsetp.ne.b32 p, %50, 0;\n"
   "wgmma.mma_async.sync.aligned.m64n96k16.f32.bf16.bf16 {%0,%1,%2,%3,%4,%5,%6,%7,%8,%9,%10,%11,%12,%13,%14,%15,%16,%17,%18,%19,%20,%21,%22,%23,%24,%25,%26,%27,%28,%29,%30,%31,%32,%33,%34,%35,%36,%37,%38,%39,%40,%41,%42,%43,%44,%45,%46,%47}, %48, %49, p, 1, 1, 0, %51;\n}"
   : "+f"(d[0]),"+f"(d[1]),"+f"(d[2]),"+f"(d[3]),"+f"(d[4]),"+f"(d[5]),"+f"(d[6]),"+f"(d[7]),"+f"(d[8]),"+f"(d[9]),"+f"(d[10]),"+f"(d[11]),"+f"(d[12]),"+f"(d[13]),"+f"(d[14]),"+f"(d[15]),"+f"(d[16]),"+f"(d[17]),"+f"(d[18]),"+f"(d[19]),"+f"(d[20]),"+f"(d[21]),"+f"(d[22]),"+f"(d[23]),"+f"(d[24]),"+f"(d[25]),"+f"(d[26]),"+f"(d[27]),"+f"(d[28]),"+f"(d[29]),"+f"(d[30]),"+f"(d[31]),"+f"(d[32]),"+f"(d[33]),"+f"(d[34]),"+f"(d[35]),"+f"(d[36]),"+f"(d[37]),"+f"(d[38]),"+f"(d[39]),"+f"(d[40]),"+f"(d[41]),"+f"(d[42]),"+f"(d[43]),"+f"(d[44]),"+f"(d[45]),"+f"(d[46]),"+f"(d[47])
   : "l"(da), "l"(db), "r"(scale_d), "n"(TB));
}

template<int N, int TB>
__device__ __forceinline__ void wgmma_n(float (&d)[N / 2], uint64_t da, uint64_t db) {
  if constexpr (N == 192) wgmma_n192<TB>(d, da, db, 1);
  else if constexpr (N == 160) wgmma_n160<TB>(d, da, db, 1);
  else wgmma_n96<TB>(d, da, db, 1);
}

template<int R>
__device__ __forceinline__ void pin(float (&acc)[2][R]) {
  #pragma unroll
  for (int mi = 0; mi < 2; mi++)
    #pragma unroll
    for (int i = 0; i < R; i++) asm volatile("" : "+f"(acc[mi][i]) :: "memory");
}
template<int R>
__device__ __forceinline__ void zero(float (&acc)[2][R]) {
  #pragma unroll
  for (int i = 0; i < R; i++) { acc[0][i] = 0.f; acc[1][i] = 0.f; }
  pin(acc);
}

template<int N, int TB, bool CONT, int ORD_BAR>
__device__ __forceinline__ void mainloop(float (&acc)[2][N / 2], uint32_t sbase, uint32_t stage_bytes, int g0, int nk, int total, int mswap) {
  const uint32_t full0 = sbase + BAR_OFF, empty0 = full0 + 8 * STAGES, ring = sbase + RING_OFF;
  const int t = threadIdx.x & 127;
  const uint32_t da0 = (((ring + mswap * 8192) & 0x3FFFF) >> 4) | 0x10000u, da1 = (((ring + (mswap ^ 1) * 8192) & 0x3FFFF) >> 4) | 0x10000u;
  const uint32_t db0 = (((ring + A_BYTES) & 0x3FFFF) >> 4) | ((TB == 2 ? 256u : TB ? 512u : 1u) << 16);
  constexpr uint32_t HI_A = 0x40000040u, HI_B = TB == 2 ? 0x80000020u : 0x40000040u;
  #pragma unroll 1
  for (int g = g0; g < g0 + nk; g++) {
    const int s = g & (STAGES - 1);
    const uint32_t so = s * (stage_bytes >> 4);
    mbar_wait(full0 + 8 * s, (g / STAGES) & 1);
    wgmma_fence();
    #pragma unroll
    for (int k = 0; k < 4; k++) {
      const uint64_t db = desc64(db0 + so + (TB == 2 ? k * 64 : TB ? k * 128 : k * 2), HI_B);
      wgmma_n<N, TB != 0>(acc[0], desc64(da0 + so + k * 2, HI_A), db);
      wgmma_n<N, TB != 0>(acc[1], desc64(da1 + so + k * 2, HI_A), db);
    }
    wgmma_commit();
    if (ORD_BAR != 0 && g == g0 + nk - 1) bar_arrive<ORD_BAR>(256);
    wgmma_wait<1>();
    if (t < 2 && (CONT || g > g0) && g - 1 + STAGES < total) mbar_arrive_cluster(empty0 + 8 * ((g - 1) & (STAGES - 1)), t);
  }
}
template<int R>
__device__ __forceinline__ void drain(float (&acc)[2][R], uint32_t sbase, int glast, int total) {
  wgmma_wait<0>();
  pin(acc);
  const int t = threadIdx.x & 127;
  if (t < 2 && glast + STAGES < total) mbar_arrive_cluster(sbase + BAR_OFF + 8 * STAGES + 8 * (glast & (STAGES - 1)), t);
}

__device__ __forceinline__ void set_flag(int slot, int byte, unsigned epoch) {
  asm volatile("st.relaxed.gpu.global.u8 [%0], %1;" :: "l"(g_flags + slot * 256 + byte), "r"(epoch & 255u) : "memory");
}
__device__ __forceinline__ unsigned get_flag(int slot, int byte) {
  unsigned v; asm volatile("ld.relaxed.gpu.global.u8 %0, [%1];" : "=r"(v) : "l"(g_flags + slot * 256 + byte) : "memory"); return v;
}
__device__ __forceinline__ void publish(int slot, int byte, unsigned epoch) {
  asm volatile("fence.acq_rel.gpu;" ::: "memory");
  set_flag(slot, byte, epoch);
}

__device__ __forceinline__ float sum8(uint4 v) {
  return ((bf_lo(v.x) + bf_hi(v.x)) + (bf_lo(v.y) + bf_hi(v.y))) + ((bf_lo(v.z) + bf_hi(v.z)) + (bf_lo(v.w) + bf_hi(v.w)));
}
__device__ __forceinline__ uint4 ldg128(const void* p) {
  uint4 v; asm volatile("ld.global.nc.v4.u32 {%0,%1,%2,%3}, [%4];" : "=r"(v.x), "=r"(v.y), "=r"(v.z), "=r"(v.w) : "l"(p)); return v;
}
__device__ __forceinline__ void ln_load(const bf16* __restrict__ x, int cta, uint4 (&rv)[5]) {
  const int t = threadIdx.x - 128, row = cta * 16 + (t >> 4), c = t & 15;
  #pragma unroll
  for (int j = 0; j < 5; j++) rv[j] = ldg128(reinterpret_cast<const uint4*>(x + (size_t)row * DM) + c + 16 * j);
}
__device__ __forceinline__ void ln_rows(const uint4 (&rv)[5], int cta, unsigned epoch) {
  const int t = threadIdx.x - 128, row = cta * 16 + (t >> 4), c = t & 15;
  const float sh = __shfl_sync(0xffffffffu, bf_lo(rv[0].x), t & 16);
  float d[40], s = 0.f, q = 0.f;
  #pragma unroll
  for (int j = 0; j < 5; j++) {
    const uint32_t u[4] = {rv[j].x, rv[j].y, rv[j].z, rv[j].w};
    #pragma unroll
    for (int e = 0; e < 4; e++) {
      const float d0 = bf_lo(u[e]) - sh, d1 = bf_hi(u[e]) - sh;
      d[j * 8 + e * 2] = d0; d[j * 8 + e * 2 + 1] = d1;
      s += d0 + d1; q = fmaf(d0, d0, q); q = fmaf(d1, d1, q);
    }
  }
  #pragma unroll
  for (int o = 1; o < 16; o <<= 1) { s += __shfl_xor_sync(0xffffffffu, s, o); q += __shfl_xor_sync(0xffffffffu, q, o); }
  const float md = s * (1.f / DM);
  const float r = rsqrtf(fmaxf(fmaf(q, 1.f / DM, -md * md), 0.f) + LN_EPS), o = -md * r;
  if (c == 0) st_vol2(&g_xstat[row], __float_as_uint(r), (__float_as_uint(-(md + sh) * r) & ~255u) | (epoch & 255u));
  #pragma unroll
  for (int j = 0; j < 5; j++) {
    const float* a = &d[j * 8];
    stg128(reinterpret_cast<uint4*>(g_xn + (size_t)row * DM) + c + 16 * j, make_uint4(
           pack_bf16(fmaf(a[0], r, o), fmaf(a[1], r, o)), pack_bf16(fmaf(a[2], r, o), fmaf(a[3], r, o)),
           pack_bf16(fmaf(a[4], r, o), fmaf(a[5], r, o)), pack_bf16(fmaf(a[6], r, o), fmaf(a[7], r, o))));
  }
  bar_arrive<BAR_LN>(288);
}
__device__ __forceinline__ void colsum_part(const bf16* __restrict__ win, int cta, unsigned epoch) {
  const int t = threadIdx.x & 127, w = t >> 5, l = t & 31;
  const int cj = min(cta, 119), cg = cj % 24, rg = cj / 24;
  uint4 cv[4];
  #pragma unroll
  for (int j = 0; j < 4; j++) cv[j] = ldg128(reinterpret_cast<const uint4*>(win + (size_t)(rg * 128 + w * 32 + j * 8 + (l >> 2)) * FF + FH + cg * 32) + (l & 3));
  float v[8];
  v[0] = (bf_lo(cv[0].x) + bf_lo(cv[1].x)) + (bf_lo(cv[2].x) + bf_lo(cv[3].x)); v[1] = (bf_hi(cv[0].x) + bf_hi(cv[1].x)) + (bf_hi(cv[2].x) + bf_hi(cv[3].x));
  v[2] = (bf_lo(cv[0].y) + bf_lo(cv[1].y)) + (bf_lo(cv[2].y) + bf_lo(cv[3].y)); v[3] = (bf_hi(cv[0].y) + bf_hi(cv[1].y)) + (bf_hi(cv[2].y) + bf_hi(cv[3].y));
  v[4] = (bf_lo(cv[0].z) + bf_lo(cv[1].z)) + (bf_lo(cv[2].z) + bf_lo(cv[3].z)); v[5] = (bf_hi(cv[0].z) + bf_hi(cv[1].z)) + (bf_hi(cv[2].z) + bf_hi(cv[3].z));
  v[6] = (bf_lo(cv[0].w) + bf_lo(cv[1].w)) + (bf_lo(cv[2].w) + bf_lo(cv[3].w)); v[7] = (bf_hi(cv[0].w) + bf_hi(cv[1].w)) + (bf_hi(cv[2].w) + bf_hi(cv[3].w));
  #pragma unroll
  for (int st = 0; st < 3; st++) {
    const int n = 4 >> st;
    const bool up = (l & (4 * n)) != 0;
    #pragma unroll
    for (int e = 0; e < 4; e++)
      if (e < n) { const float keep = up ? v[e + n] : v[e], send = up ? v[e] : v[e + n]; v[e] = keep + __shfl_xor_sync(0xffffffffu, send, 4 * n); }
  }
  float* red = reinterpret_cast<float*>(smem + RED_OFF);
  red[w * 32 + (l & 3) * 8 + (l >> 2)] = v[0];
  bar_sync<BAR_WG2>(128);
  if (t < 32) st_vol2(&g_csum[rg * FH + cg * 32 + t], __float_as_uint((red[t] + red[32 + t]) + (red[64 + t] + red[96 + t])), epoch);
}

__device__ __forceinline__ void a_entry(int g, int grp, int rb, int& mi, int& kb) {
  if (g < 10) { mi = M_X; kb = g; }
  else if (g < 20) { mi = M_XN; kb = g - 10; }
  else if (grp == 0) {
    if (g < 52) { mi = M_WSP; kb = (g - 20); }
    else if (g < 52 + NX) { mi = M_WSIM; kb = g - 52 + 32 - NX; }
    else { mi = M_H; kb = g - 52 - NX; }
  } else {
    if (g < 30) { mi = M_XN; kb = g - 20; }
    else if (g < 62) { mi = M_WSRE; kb = (g - 30); }
    else { mi = M_WSIM; kb = g - 62; }
  }
}

__global__ void __cluster_dims__(2, 1, 1) __launch_bounds__(384, 1)
fused_kernel(const __grid_constant__ Maps maps, const bf16* __restrict__ x, const bf16* __restrict__ win, const bf16* __restrict__ bsp) {
  const uint32_t sbase = smem_u32(smem);
  const uint32_t full0 = sbase + BAR_OFF, empty0 = full0 + 8 * STAGES, dep0 = empty0 + 8 * STAGES, ring = sbase + RING_OFF;
  const int tid = threadIdx.x, wg = __shfl_sync(0xffffffffu, tid >> 7, 0);
  const int rank = blockIdx.x & 1;
  const int grp = (blockIdx.x >> 1) & 1, half = (blockIdx.x >> 2) & 1, rb = blockIdx.x >> 3;
  const int ct = half * 2 + rank, c8 = grp * 4 + ct;
  const int cta = rb * 8 + half * 4 + grp * 2 + rank;
  const int total = grp == 0 ? KB_A : KB_B;
  const uint32_t stage_bytes = grp == 0 ? STAGE_A : STAGE_B;

  uint4 rv[5];
  if (wg != 0) ln_load(x, cta, rv);
  const unsigned epoch = (ld_relaxed(&g_done) >> 7) + 1u;
  if (tid == 0) {
    TS(0, 0);
    for (int s = 0; s < STAGES; s++) { mbar_init(full0 + 8 * s, 2); mbar_init(empty0 + 8 * s, 2); mbar_init(dep0 + 8 * s, 1); }
    mbar_init(dep0 + 8 * STAGES, 1);
    *reinterpret_cast<volatile int*>(smem + READY_OFF) = 0;
    asm volatile("fence.mbarrier_init.release.cluster;" ::: "memory");
  }
  __syncthreads();
  asm volatile("barrier.cluster.arrive.relaxed.aligned;" ::: "memory");

  if (wg == 0) {
    asm volatile("setmaxnreg.dec.sync.aligned.u32 40;");
    const int warp = tid >> 5, lane = tid & 31;
    if (warp == 0) {
      const int row = rb * 128;
      if (lane == 0) {
        for (int g = 0; g < STAGES; g++) {
          mbar_expect_tx(full0 + 8 * g, A_BYTES);
          tma_load_2d(ring + g * stage_bytes, &maps.m[M_X], full0 + 8 * g, g * 64, row);
          tma_load_2d(ring + g * stage_bytes + 8192, &maps.m[M_X], full0 + 8 * g, g * 64, row + 64);
        }
      }
      __syncwarp();
      cluster_wait();
      if (lane == 0) {
        #pragma unroll 1
        for (int g = STAGES; g < total; g++) {
          int mi, kb;
          a_entry(g, grp, rb, mi, kb);
          if (g == 10 || (mi == M_H && kb == 0)) { TS(0, g > 10 ? 3 : 1); mbar_wait(dep0 + (g > 10 ? 24 : 0), 0); fence_async_global(); TS(0, g > 10 ? 4 : 2); }
          const int s = g & (STAGES - 1);
          mbar_wait(empty0 + 8 * s, ((g / STAGES) & 1) ^ 1);
          mbar_expect_tx(full0 + 8 * s, A_BYTES);
          tma_load_2d_mc(ring + s * stage_bytes + rank * 8192, &maps.m[mi], full0 + 8 * s, kb * 64, row + rank * 64, 3);
        }
        TS(0, 5);
      }
    } else if (warp == 1) {
      if (lane == 0) {
        int have = 0;
        #pragma unroll 1
        for (int g = 0; g < total; g++) {
          int kind = 1, mi, kb, c, dep = 0, need = 0;
          uint32_t bytes = 20480;
          if (g < 10) { kind = 0; mi = M_WIN32; kb = g; c = 24 + 3 * c8; bytes = 12288; }
          else if (grp == 0) {
            if (g < 20) { kind = 0; mi = M_WIN3; kb = g - 10; c = 3 * ct; bytes = 24576; }
            else if (g < 52) { kind = 0; mi = M_Z23; kb = (g - 20); c = 3 * ct; bytes = 24576; need = ((g - 20) >> 1) + 1; }
            else if (g < 52 + NX) { mi = M_AB; kb = g - 52 + 32 - NX; c = DM + ct * 160; dep = g == 52 ? 2 : 0; }
            else { kind = 0; mi = M_WOUT; kb = g - 52 - NX; c = ct * 5; }
          } else {
            if (g < 30) { mi = g < 20 ? M_WDRE : M_WDIM; kb = g < 20 ? g - 10 : g - 20; c = ct * 160; }
            else if (g < 62) { mi = M_AB; kb = (g - 30); c = ct * 160; need = ((g - 30) >> 1) + 1; }
            else { mi = M_AB; kb = g - 62; c = ct * 160 + DM; dep = g == 62 ? 2 : 0; }
          }
          if (need > have) {
            if (need == 1) TS(1, 0);
            unsigned it = 0;
            while ((have = *reinterpret_cast<volatile int*>(smem + READY_OFF)) < need && ++it < 50 * POLL_LIMIT) {}
            fence_async_global();
            if (need == 1) { TS(1, 1); TC(1); }
          }
          if (dep) { TS(1, dep * 2 - 2); mbar_wait(dep0 + 8 * dep, 0); fence_async_global(); TS(1, dep * 2 - 1); TC(dep); }
          const int s = g & (STAGES - 1);
          const uint32_t dst = ring + s * stage_bytes + A_BYTES, fb = full0 + 8 * s;
          mbar_wait(empty0 + 8 * s, ((g / STAGES) & 1) ^ 1);
          mbar_expect_tx(fb, bytes);
          if (kind == 0) tma_load_3d(dst, &maps.m[mi], fb, 0, kb * 64, c);
          else tma_load_2d(dst, &maps.m[mi], fb, kb * 64, c);
        }
      }
      __syncwarp();
      cluster_wait();
    } else if (warp == 2) {
      cluster_wait();
      {
        unsigned it = 0;
        uint2 v[4];
        while (true) {
          bool ok = true;
          #pragma unroll
          for (int i = 0; i < 4; i++) { v[i] = ld_vol2(&g_xstat[rb * 128 + i * 32 + lane]); ok = ok && ((v[i].y ^ epoch) & 255u) == 0; }
          if (ok || ++it > POLL_LIMIT) break;
          __nanosleep(POLL_NS);
        }
        #pragma unroll
        for (int i = 0; i < 4; i++) reinterpret_cast<uint2*>(smem + ROWSTAT_OFF)[i * 32 + lane] = make_uint2(v[i].x, v[i].y & ~255u);
        __syncwarp();
        TS(0, 6);
        bar_arrive<BAR_STATS>(192);
      }
      #pragma unroll 1
      for (int d = 0; d < 5 - 2 * grp; d++) {
        const int slot = d == 0 ? F_XN + rb : d == 4 ? F_Y + rb * 4 + ct : d == 3 ? F_H + rb : d == 2 ? F_B + ct : grp == 0 ? F_Z + ct : F_A + ct;
        const int byte = d == 0 ? lane & 7 : d == 4 ? 0 : d == 3 ? lane & 3 : (d == 1 && grp == 0) ? lane : lane >> 1;
        unsigned it = 0, m;
        while ((m = __ballot_sync(0xffffffffu, get_flag(slot, byte) != (epoch & 255u))) != 0 && ++it < POLL_LIMIT) {
          if (d == 1 && lane == 0) *reinterpret_cast<volatile int*>(smem + READY_OFF) = (__ffs(m) - 1) >> 1;
          __nanosleep(WATCH_NS);
        }
        if (d == 1 && lane == 0) *reinterpret_cast<volatile int*>(smem + READY_OFF) = 16;
        if (d < 4) TS(0, 8 + d * 2); else TS(0, 7);
        fence_async_global();
        __syncwarp();
        if (lane == 0 && d != 1) mbar_arrive(dep0 + 8 * d);
      }
    } else {
      cluster_wait();
      bar_sync<BAR_LN>(288);
      if (lane == 0) { TS(1, 5); publish(F_XN + rb, cta & 7, epoch); TS(1, 6); }
      __syncwarp();
      #pragma unroll 1
      for (int i = 0; i < 3; i++) {
        unsigned it = 0;
        while (true) {
          bool ok = true;
          float a = 0.f;
          #pragma unroll
          for (int p = 0; p < 5; p++) { const uint2 u = ld_vol2(&g_csum[p * FH + c8 * 96 + i * 32 + lane]); ok = ok && u.y == epoch; a += __uint_as_float(u.x); }
          reinterpret_cast<float*>(smem + COLSUM_OFF)[i * 32 + lane] = a;
          if (ok || ++it > POLL_LIMIT) break;
          __nanosleep(POLL_NS);
        }
      }
      __syncwarp();
      TS(1, 4);
      bar_arrive<BAR_STATS>(192);
      bar_sync<BAR_PUB1>(160);
      if (lane == 0) {
        TS(1, 7);
        tma_store_3d(&maps.m[M_Z232], ring + 4 * stage_bytes, 0, rb * 128, 3 * c8);
        bulk_commit();
        bulk_wait_all();
        set_flag(F_Z + (c8 >> 1), rb * 2 + (c8 & 1), epoch);
        TS(1, 8);
      }
      __syncwarp();
      if (grp == 0) {
        bar_arrive<BAR_BUF>(160);
      } else {
        bar_sync<BAR_PUB2>(160);
        if (lane == 0) set_flag(F_A + ct, rb, epoch);
        TS(1, 9);
        __syncwarp();
      }
      bar_sync<BAR_PUB1>(160);
      if (lane == 0) set_flag(grp == 0 ? F_H + rb : F_B + ct, grp == 0 ? ct : rb, epoch);
      TS(1, 10);
      if (grp == 0) {
        __syncwarp();
        bar_arrive<BAR_BUF>(160);
      } else {
        if (lane == 0) {
          mbar_expect_tx(dep0 + 8, 40960);
          tma_load_2d(ring + 4 * stage_bytes + 24576, &maps.m[M_XR], dep0 + 8, ct * 160, rb * 128);
          mbar_wait(dep0 + 8, 0);
          #pragma unroll 1
          for (int i = 0; i < 8; i++) {
            tma_store_2d(&maps.m[M_OUT], ring + 4 * stage_bytes + 24576 + i * 5120, ct * 160, rb * 128 + i * 16);
            bulk_commit();
            bulk_wait_all();
          }
          set_flag(F_Y + rb * 4 + ct, 0, epoch);
        }
        __syncwarp();
        bar_arrive<BAR_PUB2>(160);
      }
    }
  } else {
    asm volatile("setmaxnreg.inc.sync.aligned.u32 232;");
    const int t = tid & 127, w = t >> 5, l = t & 31;
    const uint32_t buf = ring + 4 * stage_bytes;
    ln_rows(rv, cta, epoch);
    if (wg == 2) colsum_part(win, cta, epoch);
    TS(wg + 1, 0);
    cluster_wait();
    const int rl = w * 16 + ((l >> 3) & 1) * 8 + (l & 7);
    const int gr = w * 16 + (l & 15);
    const uint32_t st_base = buf + rl * 128;
    const uint32_t st_x = ((l >> 4) ^ (l & 7)) << 4;
    if (wg == 1) {
      float acc[2][48];
      zero(acc);
      mainloop<96, 2, false, BAR_ORD1>(acc, sbase, stage_bytes, 0, 10, total, 0);
      drain(acc, sbase, 9, total);
      TS(2, 2);
      bar_sync<BAR_STATS>(192);
      const float2* rs = reinterpret_cast<const float2*>(smem + ROWSTAT_OFF) + w * 16 + (l >> 2);
      const float2* cs = reinterpret_cast<const float2*>(smem + COLSUM_OFF) + (l & 3);
      float sum[4], sq[4];
      #pragma unroll
      for (int r = 0; r < 4; r++) {
        const float2 st = rs[(r >> 1) * 64 + (r & 1) * 8];
        float s0 = 0.f, q0 = 0.f;
        #pragma unroll
        for (int j = 0; j < 12; j++) {
          const float2 c = cs[j * 4];
          float* a = &acc[r >> 1][4 * j + (r & 1) * 2];
          a[0] = gelu_tanh(fmaf(a[0], st.x, st.y * c.x));
          a[1] = gelu_tanh(fmaf(a[1], st.x, st.y * c.y));
          s0 += a[0] + a[1]; q0 = fmaf(a[0], a[0], q0); q0 = fmaf(a[1], a[1], q0);
        }
        s0 += __shfl_xor_sync(0xffffffffu, s0, 1); q0 += __shfl_xor_sync(0xffffffffu, q0, 1);
        s0 += __shfl_xor_sync(0xffffffffu, s0, 2); q0 += __shfl_xor_sync(0xffffffffu, q0, 2);
        sum[r] = s0; sq[r] = q0;
      }
      TS(2, 4);
      float rstd, off;
      {
        const int qd = l & 3;
        const float sm = qd == 0 ? sum[0] : qd == 1 ? sum[1] : qd == 2 ? sum[2] : sum[3];
        const float sv = qd == 0 ? sq[0] : qd == 1 ? sq[1] : qd == 2 ? sq[2] : sq[3];
        const int row = (qd >> 1) * 64 + w * 16 + (qd & 1) * 8 + (l >> 2);
        const float mu = sm * (1.f / 96), m2 = fmaxf(sv - sm * mu, 0.f);
        st_vol2(&g_zstat[(rb * 8 + c8) * 128 + row], __float_as_uint(mu), (__float_as_uint(m2) & ~255u) | (epoch & 255u));
        uint2 v[7];
        unsigned n = 0;
        while (true) {
          bool ok = true;
          #pragma unroll
          for (int j = 0; j < 7; j++) v[j] = ld_vol2(&g_zstat[(rb * 8 + ((c8 + 1 + j) & 7)) * 128 + row]);
          #pragma unroll
          for (int j = 0; j < 7; j++) ok = ok && ((v[j].y ^ epoch) & 255u) == 0;
          if (ok || ++n > POLL_LIMIT) break;
          __nanosleep(POLL_NS);
        }
        float mean = mu, var = m2;
        #pragma unroll
        for (int j = 0; j < 7; j++) { mean += __uint_as_float(v[j].x); var += __uint_as_float(v[j].y & ~255u); }
        mean *= 0.125f;
        float d = (mu - mean) * (mu - mean);
        #pragma unroll
        for (int j = 0; j < 7; j++) d = fmaf(__uint_as_float(v[j].x) - mean, __uint_as_float(v[j].x) - mean, d);
        rstd = rsqrtf(fmaf(96.f, d, var) * (1.f / FH) + LN_EPS); off = -mean * rstd;
        __syncwarp();
      }
      TS(2, 5);
      #pragma unroll
      for (int mi = 0; mi < 2; mi++) {
        const float r0 = __shfl_sync(0xffffffffu, rstd, (l & 28) + mi * 2), o0 = __shfl_sync(0xffffffffu, off, (l & 28) + mi * 2);
        const float r1 = __shfl_sync(0xffffffffu, rstd, (l & 28) + mi * 2 + 1), o1 = __shfl_sync(0xffffffffu, off, (l & 28) + mi * 2 + 1);
        #pragma unroll
        for (int jj = 0; jj < 6; jj++) {
          const float* a = &acc[mi][8 * jj];
          stsm4(buf + (jj >> 1) * 8192 + mi * 4096 + rl * 64 + ((((jj & 1) * 2 + (l >> 4)) ^ ((l >> 1) & 3)) << 4),
                pack_bf16(fmaf(a[0], r0, o0), fmaf(a[1], r0, o0)), pack_bf16(fmaf(a[2], r1, o1), fmaf(a[3], r1, o1)),
                pack_bf16(fmaf(a[4], r0, o0), fmaf(a[5], r0, o0)), pack_bf16(fmaf(a[6], r1, o1), fmaf(a[7], r1, o1)));
        }
      }
      fence_async_smem();
      bar_arrive<BAR_PUB1>(160);
      TS(2, 6);
      if (grp == 0) {
        float acc[2][96];
        zero(acc);
        bar_sync<BAR_ORD2>(256);
        mainloop<192, 1, false, BAR_ORD1>(acc, sbase, STAGE_A, 20, 32, KB_A, 0);
        const float* bias = reinterpret_cast<const float*>(smem + BIAS_OFF) + w * 16 + (l >> 2);
        bar_sync<BAR_Z1>(256);
        drain(acc, sbase, 51, KB_A);
        TS(2, 7);
        {
          const float bb[4] = {bias[0], bias[8], bias[64], bias[72]};
          uint32_t z[2][4][4];
          #pragma unroll
          for (int i = 0; i < 4; i++) ldsm4(st_base + (st_x ^ (i << 5)), z[0][i][0], z[0][i][1], z[0][i][2], z[0][i][3]);
          #pragma unroll
          for (int bx = 0; bx < 6; bx++) {
            if (bx < 5) {
              #pragma unroll
              for (int i = 0; i < 4; i++)
                ldsm4(st_base + (bx + 1) * 8192 + (st_x ^ (i << 5)), z[(bx + 1) & 1][i][0], z[(bx + 1) & 1][i][1], z[(bx + 1) & 1][i][2], z[(bx + 1) & 1][i][3]);
            }
            const float b0 = bb[(bx / 3) * 2], b1 = bb[(bx / 3) * 2 + 1];
            #pragma unroll
            for (int i = 0; i < 4; i++) {
              const float* a = &acc[bx / 3][8 * ((bx % 3) * 4 + i)];
              const uint32_t* zz = z[bx & 1][i];
              stsm4(st_base + bx * 8192 + (st_x ^ (i << 5)),
                    hmul2_bf16(zz[0], pack_bf16(a[0] + b0, a[1] + b0)), hmul2_bf16(zz[1], pack_bf16(a[2] + b1, a[3] + b1)),
                    hmul2_bf16(zz[2], pack_bf16(a[4] + b0, a[5] + b0)), hmul2_bf16(zz[3], pack_bf16(a[6] + b1, a[7] + b1)));
            }
            fence_async_smem();
            __syncwarp();
            if (l == 0) {
              tma_store_2d(&maps.m[M_HS], buf + bx * 8192 + w * 2048, ct * 192 + (bx % 3) * 64, rb * 128 + (bx / 3) * 64 + w * 16);
              bulk_commit();
            }
          }
        }
        TS(2, 8);
        if (l == 0) bulk_wait_all();
        __syncwarp();
        bar_arrive<BAR_PUB1>(160);
        TS(2, 9);
        return;
      }
    } else {
      if (grp == 0) {
        reinterpret_cast<float*>(smem + BIAS_OFF)[t] = __bfloat162float(bsp[rb * 128 + t]);
        float acc[2][96];
        zero(acc);
        bar_sync<BAR_ORD1>(256);
        mainloop<192, 1, false, BAR_ORD2>(acc, sbase, STAGE_A, 10, 10, KB_A, 0);
        drain(acc, sbase, 19, KB_A);
        TS(3, 2);
        bar_sync<BAR_BUF>(160);
        #pragma unroll
        for (int mi = 0; mi < 2; mi++)
          #pragma unroll
          for (int jj = 0; jj < 12; jj++) {
            const float* a = &acc[mi][8 * jj];
            stsm4(st_base + mi * 24576 + (jj >> 2) * 8192 + (st_x ^ ((jj & 3) << 5)),
                  pack_bf16(a[0], a[1]), pack_bf16(a[2], a[3]), pack_bf16(a[4], a[5]), pack_bf16(a[6], a[7]));
          }
        __syncwarp();
        TS(3, 3);
        const uint32_t rbase = buf + (l >> 4) * 24576 + gr * 128;
        #pragma unroll 1
        for (int c2 = 0; c2 < 12; c2++) {
          const uint32_t ab = rbase + (c2 >> 2) * 8192;
          uint4 v[2];
          #pragma unroll
          for (int i = 0; i < 2; i++) v[i] = lds128(ab + (((((c2 & 3) * 2 + i) ^ l) & 7) << 4));
          #pragma unroll
          for (int i = 0; i < 2; i++)
            sts128(ab + (((((c2 & 3) * 2 + i) ^ l) & 7) << 4),
                   pack_bf16(gelu_tanh(bf_lo(v[i].x)), gelu_tanh(bf_hi(v[i].x))), pack_bf16(gelu_tanh(bf_lo(v[i].y)), gelu_tanh(bf_hi(v[i].y))),
                   pack_bf16(gelu_tanh(bf_lo(v[i].z)), gelu_tanh(bf_hi(v[i].z))), pack_bf16(gelu_tanh(bf_lo(v[i].w)), gelu_tanh(bf_hi(v[i].w))));
        }
        TS(3, 4);
        bar_arrive<BAR_Z1>(256);
      }
    }
    float acc[2][80];
    if (grp == 1) {
      zero(acc);
      if (wg == 2) {
        bar_sync<BAR_ORD1>(256);
        mainloop<160, 0, false, BAR_ORD2>(acc, sbase, STAGE_B, 10, 10, KB_B, 0);
      } else {
        bar_sync<BAR_ORD2>(256);
        mainloop<160, 0, false, BAR_ORD1>(acc, sbase, STAGE_B, 20, 10, KB_B, 0);
      }
      drain(acc, sbase, wg == 2 ? 19 : 29, KB_B);
      TS(wg + 1, wg == 1 ? 7 : 2);
      if (wg == 1) bar_sync<BAR_BUF>(256);
      const uint32_t sg = wg == 1 ? 0x80008000u : 0u;
      const uint32_t tb = buf + 24576 + ((l >> 4) * 8 + (l & 7)) * 128 + (((w * 2 + ((l >> 3) & 1)) ^ (l & 7)) << 4);
      #pragma unroll
      for (int mi = 0; mi < 2; mi++)
        #pragma unroll
        for (int jj = 0; jj < 10; jj++) {
          const float* a = &acc[mi][8 * jj];
          stsm4_t(tb + mi * 20480 + jj * 2048, pack_bf16(a[0], a[1]) ^ sg, pack_bf16(a[2], a[3]) ^ sg, pack_bf16(a[4], a[5]) ^ sg, pack_bf16(a[6], a[7]) ^ sg);
        }
      fence_async_smem();
      if (wg == 1) bar_sync<BAR_WG1>(128); else bar_sync<BAR_WG2>(128);
      TS(wg + 1, wg == 1 ? 8 : 6);
      if (l == 0) {
        #pragma unroll 1
        for (int i = 0; i < 2; i++) {
          tma_store_2d(&maps.m[M_ABS], buf + 24576 + i * 20480 + w * 5120, rb * 128 + i * 64, (2 - wg) * DM + ct * 160 + w * 40);
          bulk_commit();
        }
        bulk_wait_all();
      }
      __syncwarp();
      TS(wg + 1, wg == 1 ? 9 : 10);
      if (wg == 1) { bar_arrive<BAR_PUB1>(160); return; }
      bar_arrive<BAR_PUB2>(160);
      bar_arrive<BAR_BUF>(256);
    }
    zero(acc);
    bar_sync<BAR_ORD1>(256);
    mainloop<160, 0, false, 0>(acc, sbase, stage_bytes, grp == 0 ? 52 : 30, grp == 0 ? NX : 64 - NX, total, 0);
    if (grp == 0) mainloop<160, 2, true, 0>(acc, sbase, STAGE_A, 52 + NX, 12, KB_A, 0);
    const uint32_t slab = buf + grp * 24576 + w * (16 * 320);
    const uint32_t addr = slab + (((l >> 3) & 1) * 8 + (l & 7)) * 320 + (l >> 4) * 16;
    if (grp == 0) { bar_sync<BAR_BUF>(160); mbar_wait(dep0 + 32, 0); } else bar_sync<BAR_PUB2>(160);
    drain(acc, sbase, total - 1, total);
    TS(3, 12);
    #pragma unroll
    for (int mi = 0; mi < 2; mi++) {
      #pragma unroll
      for (int jj = 0; jj < 10; jj++) {
        const float* a = &acc[mi][8 * jj];
        stsm4(addr + mi * 20480 + jj * 32, pack_bf16(a[0], a[1]), pack_bf16(a[2], a[3]), pack_bf16(a[4], a[5]), pack_bf16(a[6], a[7]));
      }
      fence_async_smem();
      __syncwarp();
      if (l == 0) {
        tma_reduce_2d(&maps.m[M_OUT], slab + mi * 20480, ct * 160, rb * 128 + mi * 64 + w * 16);
        bulk_commit();
      }
    }
    TS(3, 13);
    if (l == 0) {
      bulk_wait_read();
      if (w == 0) atomicAdd(&g_done, 1u);
    }
    TS(3, 15);
  }
}

typedef CUresult (*EncodeFn)(CUtensorMap*, CUtensorMapDataType, cuuint32_t, void*, const cuuint64_t*, const cuuint64_t*,
                             const cuuint32_t*, const cuuint32_t*, CUtensorMapInterleave, CUtensorMapSwizzle,
                             CUtensorMapL2promotion, CUtensorMapFloatOOBfill);

void make2d(EncodeFn enc, CUtensorMap* m, const void* p, uint64_t cols, uint64_t rows, uint32_t bc, uint32_t br, bool swz = true) {
  cuuint64_t gd[2] = {cols, rows}, gs[1] = {cols * 2};
  cuuint32_t bd[2] = {bc, br}, es[2] = {1, 1};
  enc(m, CU_TENSOR_MAP_DATA_TYPE_BFLOAT16, 2, const_cast<void*>(p), gd, gs, bd, es, CU_TENSOR_MAP_INTERLEAVE_NONE,
      swz ? CU_TENSOR_MAP_SWIZZLE_128B : CU_TENSOR_MAP_SWIZZLE_NONE, PROMO, CU_TENSOR_MAP_FLOAT_OOB_FILL_NONE);
}
void make3d(EncodeFn enc, CUtensorMap* m, const void* p, uint64_t cols, uint64_t rows, uint32_t cw, uint32_t nc, uint32_t br = 64) {
  cuuint64_t gd[3] = {cw, rows, cols / cw}, gs[2] = {cols * 2, cw * 2};
  cuuint32_t bd[3] = {cw, br, nc}, es[3] = {1, 1, 1};
  enc(m, CU_TENSOR_MAP_DATA_TYPE_BFLOAT16, 3, const_cast<void*>(p), gd, gs, bd, es, CU_TENSOR_MAP_INTERLEAVE_NONE,
      cw == 64 ? CU_TENSOR_MAP_SWIZZLE_128B : CU_TENSOR_MAP_SWIZZLE_64B, PROMO, CU_TENSOR_MAP_FLOAT_OOB_FILL_NONE);
}

}

extern "C" void kernel_launch(void* const* d_in, const int* in_sizes, int n_in, void* d_out, int out_size) {
  const bf16* x = (const bf16*)d_in[0];
  const bf16* wsre = (const bf16*)d_in[1];
  const bf16* wsim = (const bf16*)d_in[2];
  const bf16* wdre = (const bf16*)d_in[3];
  const bf16* wdim = (const bf16*)d_in[4];
  const bf16* win = (const bf16*)d_in[6];
  const bf16* wsp = (const bf16*)d_in[7];
  const bf16* bsp = (const bf16*)d_in[8];
  const bf16* wout = (const bf16*)d_in[9];

  void* fn = nullptr;
  cudaDriverEntryPointQueryResult qr;
  cudaGetDriverEntryPoint("cuTensorMapEncodeTiled", &fn, cudaEnableDefault, &qr);
  EncodeFn enc = (EncodeFn)fn;
  void *abT, *z2, *h, *xn;
  cudaGetSymbolAddress(&xn, g_xn);
  cudaGetSymbolAddress(&abT, g_abT);
  cudaGetSymbolAddress(&z2, g_z2);
  cudaGetSymbolAddress(&h, g_h);

  Maps maps;
  make2d(enc, &maps.m[M_X], x, DM, SEQ, 64, 64);
  make2d(enc, &maps.m[M_XN], xn, DM, SEQ, 64, 64);
  make3d(enc, &maps.m[M_Z232], z2, FH, SEQ, 32, 3, 128);
  make2d(enc, &maps.m[M_XR], x, DM, SEQ, 160, 128, false);
  make3d(enc, &maps.m[M_WIN32], win, FF, DM, 32, 3);
  make2d(enc, &maps.m[M_WSRE], wsre, SEQ, SEQ, 64, 64);
  make2d(enc, &maps.m[M_WSIM], wsim, SEQ, SEQ, 64, 64);
  make2d(enc, &maps.m[M_WSP], wsp, SEQ, SEQ, 64, 64);
  make2d(enc, &maps.m[M_H], h, FH, SEQ, 64, 64);
  make3d(enc, &maps.m[M_WIN3], win, FF, DM, 64, 3);
  make3d(enc, &maps.m[M_Z23], z2, FH, SEQ, 64, 3);
  make2d(enc, &maps.m[M_WDRE], wdre, DM, DM, 64, 160);
  make2d(enc, &maps.m[M_WDIM], wdim, DM, DM, 64, 160);
  make2d(enc, &maps.m[M_AB], abT, SEQ, 2 * DM, 64, 160);
  make3d(enc, &maps.m[M_WOUT], wout, DM, FH, 32, 5);
  make2d(enc, &maps.m[M_HS], h, FH, SEQ, 64, 16);
  make2d(enc, &maps.m[M_ABS], abT, SEQ, 2 * DM, 64, 40);
  make2d(enc, &maps.m[M_OUT], d_out, DM, SEQ, 160, 16, false);

  cudaFuncSetAttribute(fused_kernel, cudaFuncAttributeMaxDynamicSharedMemorySize, SMEM_BYTES);
  fused_kernel<<<128, 384, SMEM_BYTES>>>(maps, x, win, bsp);
}
```

```cpp
#include <cuda_runtime.h>
#include <cuda_bf16.h>
#include <cuda.h>
#include <stdint.h>

namespace {

typedef __nv_bfloat16 bf16;

constexpr int SEQ = 2048, DM = 640, FF = 1536, FH = 768;
#define NXV 11
constexpr int NX = NXV;
#define NSTB 5
constexpr int NST_A = 4, NST_B = NSTB, MAXST = 5;
constexpr int A_BYTES = 16384;
constexpr int BIAS_OFF = 0;
constexpr int BAR_OFF = 512;
constexpr int READY_OFF = 640;
constexpr int ROWSTAT_OFF = 1024;
constexpr int COLSUM_OFF = 2048;
constexpr int RED_OFF = 2560;
constexpr int RING_OFF = 3072;
constexpr int STAGE_A = 40960, STAGE_B = 36864;
constexpr int SMEM_BYTES = RING_OFF + 5 * STAGE_B + 40960;
constexpr int KB_A = 20 + 32 + NX + 12;
constexpr int KB_B = 30 + 64 - NX;
constexpr float LN_EPS = 1e-5f;
constexpr unsigned POLL_LIMIT = 100000;
#define POLL_NS 100
#define PF_D 8
#define ROT 0
#define Z1_NS 0
#define INFL 2
#define LIM_G 1000
#define MAPV 0
#define PROMO CU_TENSOR_MAP_L2_PROMOTION_L2_128B
#define WATCH_NS 40
#define PF_COND ((kb & 1) == (ct >> 1))
#define PF_NS 150

constexpr int BAR_ORD1 = 1, BAR_ORD2 = 2, BAR_WG1 = 3, BAR_WG2 = 4, BAR_LN = 5, BAR_BUF = 6, BAR_Z1 = 7, BAR_PUB1 = 8, BAR_PUB2 = 9, BAR_STATS = 10;

enum { M_X, M_XN, M_WIN32, M_Z232, M_WSRE, M_WSIM, M_WSP, M_H, M_WIN3, M_Z23, M_WDRE, M_WDIM, M_AB, M_WOUT, M_OUT, M_HS, M_ABS, M_COUNT };
struct Maps { CUtensorMap m[M_COUNT]; };

__device__ __align__(1024) bf16 g_abT[2 * DM * SEQ];
__device__ __align__(1024) bf16 g_z2[SEQ * FH];
__device__ __align__(1024) bf16 g_h[SEQ * FH];
__device__ __align__(1024) bf16 g_xn[SEQ * DM];
__device__ __align__(16) uint2 g_xstat[SEQ];
__device__ __align__(16) uint2 g_csum[5 * FH];
__device__ __align__(16) uint2 g_zstat[128 * 128];
__device__ __align__(256) unsigned char g_flags[44 * 256];
constexpr int F_A = 0, F_B = 4, F_Z = 8, F_H = 12, F_XN = 28;
__device__ unsigned g_done;
#define TS(role, ev)
#define TC(i)

extern __shared__ __align__(1024) uint8_t smem[];

__device__ __forceinline__ uint32_t smem_u32(const void* p) { return (uint32_t)__cvta_generic_to_shared(p); }
__device__ __forceinline__ void mbar_init(uint32_t bar, uint32_t cnt) { asm volatile("mbarrier.init.shared::cta.b64 [%0], %1;" :: "r"(bar), "r"(cnt)); }
__device__ __forceinline__ void mbar_expect_tx(uint32_t bar, uint32_t bytes) { asm volatile("mbarrier.arrive.expect_tx.shared::cta.b64 _, [%0], %1;" :: "r"(bar), "r"(bytes) : "memory"); }
__device__ __forceinline__ void mbar_arrive(uint32_t bar) { asm volatile("mbarrier.arrive.shared::cta.b64 _, [%0];" :: "r"(bar) : "memory"); }
__device__ __forceinline__ void mbar_arrive_cluster(uint32_t bar, uint32_t cta) {
  asm volatile("{\n.reg .b32 ra;\nmapa.shared::cluster.u32 ra, %0, %1;\nmbarrier.arrive.shared::cluster.b64 _, [ra];\n}" :: "r"(bar), "r"(cta) : "memory");
}
__device__ __forceinline__ void mbar_wait(uint32_t bar, uint32_t parity) {
  asm volatile("{\n.reg .pred p;\n.reg .u32 n;\nmov.u32 n, 0;\n"
               "LW: mbarrier.try_wait.parity.shared::cta.b64 p, [%0], %1, 2000;\n@p bra LD;\n"
               "add.u32 n, n, 1;\nsetp.lt.u32 p, n, 20000;\n@p bra LW;\nLD:\n}" :: "r"(bar), "r"(parity) : "memory");
}
__device__ __forceinline__ void tma_load_2d(uint32_t dst, const CUtensorMap* map, uint32_t bar, int c0, int c1) {
  asm volatile("cp.async.bulk.tensor.2d.shared::cluster.global.mbarrier::complete_tx::bytes [%0], [%1, {%3, %4}], [%2];"
    :: "r"(dst), "l"((uint64_t)map), "r"(bar), "r"(c0), "r"(c1) : "memory");
}
__device__ __forceinline__ void tma_load_3d(uint32_t dst, const CUtensorMap* map, uint32_t bar, int c0, int c1, int c2) {
  asm volatile("cp.async.bulk.tensor.3d.shared::cluster.global.mbarrier::complete_tx::bytes [%0], [%1, {%3, %4, %5}], [%2];"
    :: "r"(dst), "l"((uint64_t)map), "r"(bar), "r"(c0), "r"(c1), "r"(c2) : "memory");
}
__device__ __forceinline__ void tma_load_2d_mc(uint32_t dst, const CUtensorMap* map, uint32_t bar, int c0, int c1, uint16_t mask) {
  asm volatile("cp.async.bulk.tensor.2d.shared::cluster.global.mbarrier::complete_tx::bytes.multicast::cluster [%0], [%1, {%3, %4}], [%2], %5;"
    :: "r"(dst), "l"((uint64_t)map), "r"(bar), "r"(c0), "r"(c1), "h"(mask) : "memory");
}
__device__ __forceinline__ void tma_store_2d(const CUtensorMap* map, uint32_t src, int c0, int c1) {
  asm volatile("cp.async.bulk.tensor.2d.global.shared::cta.bulk_group [%0, {%2, %3}], [%1];"
    :: "l"((uint64_t)map), "r"(src), "r"(c0), "r"(c1) : "memory");
}
__device__ __forceinline__ void tma_store_3d(const CUtensorMap* map, uint32_t src, int c0, int c1, int c2) {
  asm volatile("cp.async.bulk.tensor.3d.global.shared::cta.bulk_group [%0, {%2, %3, %4}], [%1];"
    :: "l"((uint64_t)map), "r"(src), "r"(c0), "r"(c1), "r"(c2) : "memory");
}
__device__ __forceinline__ void tma_reduce_2d(const CUtensorMap* map, uint32_t src, int c0, int c1) {
  asm volatile("cp.reduce.async.bulk.tensor.2d.global.shared::cta.add.tile.bulk_group [%0, {%2, %3}], [%1];"
    :: "l"((uint64_t)map), "r"(src), "r"(c0), "r"(c1) : "memory");
}
__device__ __forceinline__ void bulk_wait_all() { asm volatile("cp.async.bulk.wait_group 0;" ::: "memory"); }
__device__ __forceinline__ void bulk_commit() { asm volatile("cp.async.bulk.commit_group;" ::: "memory"); }
__device__ __forceinline__ void bulk_wait_read() { asm volatile("cp.async.bulk.wait_group.read 0;" ::: "memory"); }
__device__ __forceinline__ void fence_async_smem() { asm volatile("fence.proxy.async.shared::cta;" ::: "memory"); }
__device__ __forceinline__ void fence_async_global() { asm volatile("fence.proxy.async.global;" ::: "memory"); }
__device__ __forceinline__ void wgmma_fence() { asm volatile("wgmma.fence.sync.aligned;" ::: "memory"); }
__device__ __forceinline__ void wgmma_commit() { asm volatile("wgmma.commit_group.sync.aligned;" ::: "memory"); }
template<int N> __device__ __forceinline__ void wgmma_wait() { asm volatile("wgmma.wait_group.sync.aligned %0;" :: "n"(N) : "memory"); }
template<int ID> __device__ __forceinline__ void bar_sync(int n) { asm volatile("bar.sync %0, %1;" :: "n"(ID), "r"(n) : "memory"); }
template<int ID> __device__ __forceinline__ void bar_arrive(int n) { asm volatile("bar.arrive %0, %1;" :: "n"(ID), "r"(n) : "memory"); }
__device__ __forceinline__ void cluster_wait() { asm volatile("barrier.cluster.wait.aligned;" ::: "memory"); }
__device__ __forceinline__ uint64_t desc64(uint32_t lo, uint32_t hi) { return (uint64_t)lo | ((uint64_t)hi << 32); }
__device__ __forceinline__ uint4 ld_vol4(const uint4* p) {
  uint4 v; asm volatile("ld.relaxed.gpu.global.v4.u32 {%0,%1,%2,%3}, [%4];" : "=r"(v.x), "=r"(v.y), "=r"(v.z), "=r"(v.w) : "l"(p) : "memory"); return v;
}
__device__ __forceinline__ uint2 ld_vol2(const uint2* p) {
  uint2 v; asm volatile("ld.relaxed.gpu.global.v2.u32 {%0,%1}, [%2];" : "=r"(v.x), "=r"(v.y) : "l"(p) : "memory"); return v;
}
__device__ __forceinline__ void st_vol4(uint4* p, uint32_t a, uint32_t b, uint32_t c, uint32_t d) {
  asm volatile("st.relaxed.gpu.global.v4.u32 [%0], {%1,%2,%3,%4};" :: "l"(p), "r"(a), "r"(b), "r"(c), "r"(d) : "memory");
}
__device__ __forceinline__ void st_vol2(uint2* p, uint32_t a, uint32_t b) {
  asm volatile("st.relaxed.gpu.global.v2.u32 [%0], {%1,%2};" :: "l"(p), "r"(a), "r"(b) : "memory");
}
__device__ __forceinline__ void stg128(void* p, uint4 v) {
  asm volatile("st.global.v4.u32 [%0], {%1,%2,%3,%4};" :: "l"(p), "r"(v.x), "r"(v.y), "r"(v.z), "r"(v.w));
}
__device__ __forceinline__ unsigned ld_relaxed(const unsigned* p) {
  unsigned v; asm volatile("ld.relaxed.gpu.global.u32 %0, [%1];" : "=r"(v) : "l"(p) : "memory"); return v;
}
__device__ __forceinline__ uint32_t pack_bf16(float lo, float hi) {
  uint32_t r; asm("cvt.rn.bf16x2.f32 %0, %1, %2;" : "=r"(r) : "f"(hi), "f"(lo)); return r;
}
__device__ __forceinline__ float bf_lo(uint32_t v) { return __uint_as_float(v << 16); }
__device__ __forceinline__ float bf_hi(uint32_t v) { return __uint_as_float(v & 0xFFFF0000u); }
__device__ __forceinline__ void stsm4(uint32_t addr, uint32_t a, uint32_t b, uint32_t c, uint32_t d) {
  asm volatile("stmatrix.sync.aligned.m8n8.x4.shared.b16 [%0], {%1,%2,%3,%4};" :: "r"(addr), "r"(a), "r"(b), "r"(c), "r"(d));
}
__device__ __forceinline__ void stsm4_t(uint32_t addr, uint32_t a, uint32_t b, uint32_t c, uint32_t d) {
  asm volatile("stmatrix.sync.aligned.m8n8.x4.trans.shared.b16 [%0], {%1,%2,%3,%4};" :: "r"(addr), "r"(a), "r"(b), "r"(c), "r"(d));
}
__device__ __forceinline__ void ldsm4(uint32_t addr, uint32_t& a, uint32_t& b, uint32_t& c, uint32_t& d) {
  asm volatile("ldmatrix.sync.aligned.m8n8.x4.shared.b16 {%0,%1,%2,%3}, [%4];" : "=r"(a), "=r"(b), "=r"(c), "=r"(d) : "r"(addr));
}
__device__ __forceinline__ uint4 lds128(uint32_t a) {
  uint4 v; asm volatile("ld.shared.v4.u32 {%0,%1,%2,%3}, [%4];" : "=r"(v.x), "=r"(v.y), "=r"(v.z), "=r"(v.w) : "r"(a)); return v;
}
__device__ __forceinline__ void sts128(uint32_t a, uint32_t x, uint32_t y, uint32_t z, uint32_t w) {
  asm volatile("st.shared.v4.u32 [%0], {%1,%2,%3,%4};" :: "r"(a), "r"(x), "r"(y), "r"(z), "r"(w));
}
__device__ __forceinline__ uint32_t hmul2_bf16(uint32_t a, uint32_t b) {
  uint32_t r; asm("mul.rn.bf16x2 %0, %1, %2;" : "=r"(r) : "r"(a), "r"(b)); return r;
}
__device__ __forceinline__ float gelu_tanh(float v) {
  float u = v * fmaf(0.0356774081f, v * v, 0.7978845608f);
  float t; asm("tanh.approx.f32 %0, %1;" : "=f"(t) : "f"(u));
  float hv = 0.5f * v;
  return fmaf(hv, t, hv);
}

template<int TB>
__device__ __forceinline__ void wgmma_n192(float (&d)[96], uint64_t da, uint64_t db, int scale_d) {
  asm volatile("{\n.reg .pred p;\nsetp.ne.b32 p, %98, 0;\n"
   "wgmma.mma_async.sync.aligned.m64n192k16.f32.bf16.bf16 {%0,%1,%2,%3,%4,%5,%6,%7,%8,%9,%10,%11,%12,%13,%14,%15,%16,%17,%18,%19,%20,%21,%22,%23,%24,%25,%26,%27,%28,%29,%30,%31,%32,%33,%34,%35,%36,%37,%38,%39,%40,%41,%42,%43,%44,%45,%46,%47,%48,%49,%50,%51,%52,%53,%54,%55,%56,%57,%58,%59,%60,%61,%62,%63,%64,%65,%66,%67,%68,%69,%70,%71,%72,%73,%74,%75,%76,%77,%78,%79,%80,%81,%82,%83,%84,%85,%86,%87,%88,%89,%90,%91,%92,%93,%94,%95}, %96, %97, p, 1, 1, 0, %99;\n}"
   : "+f"(d[0]),"+f"(d[1]),"+f"(d[2]),"+f"(d[3]),"+f"(d[4]),"+f"(d[5]),"+f"(d[6]),"+f"(d[7]),"+f"(d[8]),"+f"(d[9]),"+f"(d[10]),"+f"(d[11]),"+f"(d[12]),"+f"(d[13]),"+f"(d[14]),"+f"(d[15]),"+f"(d[16]),"+f"(d[17]),"+f"(d[18]),"+f"(d[19]),"+f"(d[20]),"+f"(d[21]),"+f"(d[22]),"+f"(d[23]),"+f"(d[24]),"+f"(d[25]),"+f"(d[26]),"+f"(d[27]),"+f"(d[28]),"+f"(d[29]),"+f"(d[30]),"+f"(d[31]),"+f"(d[32]),"+f"(d[33]),"+f"(d[34]),"+f"(d[35]),"+f"(d[36]),"+f"(d[37]),"+f"(d[38]),"+f"(d[39]),"+f"(d[40]),"+f"(d[41]),"+f"(d[42]),"+f"(d[43]),"+f"(d[44]),"+f"(d[45]),"+f"(d[46]),"+f"(d[47]),"+f"(d[48]),"+f"(d[49]),"+f"(d[50]),"+f"(d[51]),"+f"(d[52]),"+f"(d[53]),"+f"(d[54]),"+f"(d[55]),"+f"(d[56]),"+f"(d[57]),"+f"(d[58]),"+f"(d[59]),"+f"(d[60]),"+f"(d[61]),"+f"(d[62]),"+f"(d[63]),"+f"(d[64]),"+f"(d[65]),"+f"(d[66]),"+f"(d[67]),"+f"(d[68]),"+f"(d[69]),"+f"(d[70]),"+f"(d[71]),"+f"(d[72]),"+f"(d[73]),"+f"(d[74]),"+f"(d[75]),"+f"(d[76]),"+f"(d[77]),"+f"(d[78]),"+f"(d[79]),"+f"(d[80]),"+f"(d[81]),"+f"(d[82]),"+f"(d[83]),"+f"(d[84]),"+f"(d[85]),"+f"(d[86]),"+f"(d[87]),"+f"(d[88]),"+f"(d[89]),"+f"(d[90]),"+f"(d[91]),"+f"(d[92]),"+f"(d[93]),"+f"(d[94]),"+f"(d[95])
   : "l"(da), "l"(db), "r"(scale_d), "n"(TB));
}
template<int TB>
__device__ __forceinline__ void wgmma_n160(float (&d)[80], uint64_t da, uint64_t db, int scale_d) {
  asm volatile("{\n.reg .pred p;\nsetp.ne.b32 p, %82, 0;\n"
   "wgmma.mma_async.sync.aligned.m64n160k16.f32.bf16.bf16 {%0,%1,%2,%3,%4,%5,%6,%7,%8,%9,%10,%11,%12,%13,%14,%15,%16,%17,%18,%19,%20,%21,%22,%23,%24,%25,%26,%27,%28,%29,%30,%31,%32,%33,%34,%35,%36,%37,%38,%39,%40,%41,%42,%43,%44,%45,%46,%47,%48,%49,%50,%51,%52,%53,%54,%55,%56,%57,%58,%59,%60,%61,%62,%63,%64,%65,%66,%67,%68,%69,%70,%71,%72,%73,%74,%75,%76,%77,%78,%79}, %80, %81, p, 1, 1, 0, %83;\n}"
   : "+f"(d[0]),"+f"(d[1]),"+f"(d[2]),"+f"(d[3]),"+f"(d[4]),"+f"(d[5]),"+f"(d[6]),"+f"(d[7]),"+f"(d[8]),"+f"(d[9]),"+f"(d[10]),"+f"(d[11]),"+f"(d[12]),"+f"(d[13]),"+f"(d[14]),"+f"(d[15]),"+f"(d[16]),"+f"(d[17]),"+f"(d[18]),"+f"(d[19]),"+f"(d[20]),"+f"(d[21]),"+f"(d[22]),"+f"(d[23]),"+f"(d[24]),"+f"(d[25]),"+f"(d[26]),"+f"(d[27]),"+f"(d[28]),"+f"(d[29]),"+f"(d[30]),"+f"(d[31]),"+f"(d[32]),"+f"(d[33]),"+f"(d[34]),"+f"(d[35]),"+f"(d[36]),"+f"(d[37]),"+f"(d[38]),"+f"(d[39]),"+f"(d[40]),"+f"(d[41]),"+f"(d[42]),"+f"(d[43]),"+f"(d[44]),"+f"(d[45]),"+f"(d[46]),"+f"(d[47]),"+f"(d[48]),"+f"(d[49]),"+f"(d[50]),"+f"(d[51]),"+f"(d[52]),"+f"(d[53]),"+f"(d[54]),"+f"(d[55]),"+f"(d[56]),"+f"(d[57]),"+f"(d[58]),"+f"(d[59]),"+f"(d[60]),"+f"(d[61]),"+f"(d[62]),"+f"(d[63]),"+f"(d[64]),"+f"(d[65]),"+f"(d[66]),"+f"(d[67]),"+f"(d[68]),"+f"(d[69]),"+f"(d[70]),"+f"(d[71]),"+f"(d[72]),"+f"(d[73]),"+f"(d[74]),"+f"(d[75]),"+f"(d[76]),"+f"(d[77]),"+f"(d[78]),"+f"(d[79])
   : "l"(da), "l"(db), "r"(scale_d), "n"(TB));
}
template<int TB>
__device__ __forceinline__ void wgmma_n96(float (&d)[48], uint64_t da, uint64_t db, int scale_d) {
  asm volatile("{\n.reg .pred p;\nsetp.ne.b32 p, %50, 0;\n"
   "wgmma.mma_async.sync.aligned.m64n96k16.f32.bf16.bf16 {%0,%1,%2,%3,%4,%5,%6,%7,%8,%9,%10,%11,%12,%13,%14,%15,%16,%17,%18,%19,%20,%21,%22,%23,%24,%25,%26,%27,%28,%29,%30,%31,%32,%33,%34,%35,%36,%37,%38,%39,%40,%41,%42,%43,%44,%45,%46,%47}, %48, %49, p, 1, 1, 0, %51;\n}"
   : "+f"(d[0]),"+f"(d[1]),"+f"(d[2]),"+f"(d[3]),"+f"(d[4]),"+f"(d[5]),"+f"(d[6]),"+f"(d[7]),"+f"(d[8]),"+f"(d[9]),"+f"(d[10]),"+f"(d[11]),"+f"(d[12]),"+f"(d[13]),"+f"(d[14]),"+f"(d[15]),"+f"(d[16]),"+f"(d[17]),"+f"(d[18]),"+f"(d[19]),"+f"(d[20]),"+f"(d[21]),"+f"(d[22]),"+f"(d[23]),"+f"(d[24]),"+f"(d[25]),"+f"(d[26]),"+f"(d[27]),"+f"(d[28]),"+f"(d[29]),"+f"(d[30]),"+f"(d[31]),"+f"(d[32]),"+f"(d[33]),"+f"(d[34]),"+f"(d[35]),"+f"(d[36]),"+f"(d[37]),"+f"(d[38]),"+f"(d[39]),"+f"(d[40]),"+f"(d[41]),"+f"(d[42]),"+f"(d[43]),"+f"(d[44]),"+f"(d[45]),"+f"(d[46]),"+f"(d[47])
   : "l"(da), "l"(db), "r"(scale_d), "n"(TB));
}

template<int N, int TB>
__device__ __forceinline__ void wgmma_n(float (&d)[N / 2], uint64_t da, uint64_t db) {
  if constexpr (N == 192) wgmma_n192<TB>(d, da, db, 1);
  else if constexpr (N == 160) wgmma_n160<TB>(d, da, db, 1);
  else wgmma_n96<TB>(d, da, db, 1);
}

template<int R>
__device__ __forceinline__ void pin(float (&acc)[2][R]) {
  #pragma unroll
  for (int mi = 0; mi < 2; mi++)
    #pragma unroll
    for (int i = 0; i < R; i++) asm volatile("" : "+f"(acc[mi][i]) :: "memory");
}
template<int R>
__device__ __forceinline__ void zero(float (&acc)[2][R]) {
  #pragma unroll
  for (int i = 0; i < R; i++) { acc[0][i] = 0.f; acc[1][i] = 0.f; }
  pin(acc);
}

template<int N, int TB, bool CONT, int ORD_BAR>
__device__ __forceinline__ void mainloop(float (&acc)[2][N / 2], uint32_t sbase, int grp, int g0, int nk) {
  const uint32_t full0 = sbase + BAR_OFF, empty0 = full0 + 8 * MAXST, ring = sbase + RING_OFF;
  const int nst = grp == 0 ? NST_A : NST_B, total = grp == 0 ? KB_A : KB_B;
  const uint32_t sstep = (grp == 0 ? STAGE_A : STAGE_B) >> 4;
  const int t = threadIdx.x & 127;
  const uint32_t da0 = ((ring & 0x3FFFF) >> 4) | 0x10000u;
  const uint32_t db0 = (((ring + A_BYTES) & 0x3FFFF) >> 4) | ((TB == 2 ? 256u : TB ? 512u : 1u) << 16);
  constexpr uint32_t HI_A = 0x40000040u, HI_B = TB == 2 ? 0x80000020u : 0x40000040u;
  int s = g0 % nst, ph = (g0 / nst) & 1, ps = s == 0 ? nst - 1 : s - 1;
  #pragma unroll 1
  for (int g = g0; g < g0 + nk; g++) {
    const uint32_t so = s * sstep;
    mbar_wait(full0 + 8 * s, ph);
    wgmma_fence();
    #pragma unroll
    for (int k = 0; k < 4; k++) {
      const uint64_t db = desc64(db0 + so + (TB == 2 ? k * 64 : TB ? k * 128 : k * 2), HI_B);
      wgmma_n<N, TB != 0>(acc[0], desc64(da0 + so + k * 2, HI_A), db);
      wgmma_n<N, TB != 0>(acc[1], desc64(da0 + so + 512 + k * 2, HI_A), db);
    }
    wgmma_commit();
    if (ORD_BAR != 0 && g == g0 + nk - 1) bar_arrive<ORD_BAR>(256);
    wgmma_wait<1>();
    if (t < 2 && (CONT || g > g0) && g - 1 + nst < total) mbar_arrive_cluster(empty0 + 8 * ps, t);
    ps = s;
    if (++s == nst) { s = 0; ph ^= 1; }
  }
}
template<int R>
__device__ __forceinline__ void drain(float (&acc)[2][R], uint32_t sbase, int grp, int glast) {
  wgmma_wait<0>();
  pin(acc);
  const int t = threadIdx.x & 127;
  const int nst = grp == 0 ? NST_A : NST_B, total = grp == 0 ? KB_A : KB_B;
  if (t < 2 && glast + nst < total) mbar_arrive_cluster(sbase + BAR_OFF + 8 * MAXST + 8 * (glast % nst), t);
}

__device__ __forceinline__ void set_flag(int slot, int byte, unsigned epoch) {
  asm volatile("st.relaxed.gpu.global.u8 [%0], %1;" :: "l"(g_flags + slot * 256 + byte), "r"(epoch & 255u) : "memory");
}
__device__ __forceinline__ unsigned get_flag(int slot, int byte) {
  unsigned v; asm volatile("ld.relaxed.gpu.global.u8 %0, [%1];" : "=r"(v) : "l"(g_flags + slot * 256 + byte) : "memory"); return v;
}
__device__ __forceinline__ void publish(int slot, int byte, unsigned epoch) {
  asm volatile("fence.acq_rel.gpu;" ::: "memory");
  set_flag(slot, byte, epoch);
}

__device__ __forceinline__ float sum8(uint4 v) {
  return ((bf_lo(v.x) + bf_hi(v.x)) + (bf_lo(v.y) + bf_hi(v.y))) + ((bf_lo(v.z) + bf_hi(v.z)) + (bf_lo(v.w) + bf_hi(v.w)));
}
__device__ __forceinline__ uint4 ldg128(const void* p) {
  uint4 v; asm volatile("ld.global.nc.v4.u32 {%0,%1,%2,%3}, [%4];" : "=r"(v.x), "=r"(v.y), "=r"(v.z), "=r"(v.w) : "l"(p)); return v;
}
__device__ __forceinline__ void ln_load(const bf16* __restrict__ x, int cta, uint4 (&rv)[5]) {
  const int t = threadIdx.x - 128, row = cta * 16 + (t >> 4), c = t & 15;
  #pragma unroll
  for (int j = 0; j < 5; j++) rv[j] = ldg128(reinterpret_cast<const uint4*>(x + (size_t)row * DM) + c + 16 * j);
}
__device__ __forceinline__ void ln_rows(const uint4 (&rv)[5], bf16* __restrict__ out, int cta, unsigned epoch) {
  const int t = threadIdx.x - 128, row = cta * 16 + (t >> 4), c = t & 15;
  const float sh = __shfl_sync(0xffffffffu, bf_lo(rv[0].x), t & 16);
  float d[40], s = 0.f, q = 0.f;
  #pragma unroll
  for (int j = 0; j < 5; j++) {
    const uint32_t u[4] = {rv[j].x, rv[j].y, rv[j].z, rv[j].w};
    #pragma unroll
    for (int e = 0; e < 4; e++) {
      const float d0 = bf_lo(u[e]) - sh, d1 = bf_hi(u[e]) - sh;
      d[j * 8 + e * 2] = d0; d[j * 8 + e * 2 + 1] = d1;
      s += d0 + d1; q = fmaf(d0, d0, q); q = fmaf(d1, d1, q);
    }
  }
  #pragma unroll
  for (int o = 1; o < 16; o <<= 1) { s += __shfl_xor_sync(0xffffffffu, s, o); q += __shfl_xor_sync(0xffffffffu, q, o); }
  const float md = s * (1.f / DM);
  const float r = rsqrtf(fmaxf(fmaf(q, 1.f / DM, -md * md), 0.f) + LN_EPS), o = -md * r;
  if (c == 0) st_vol2(&g_xstat[row], __float_as_uint(r), (__float_as_uint(-(md + sh) * r) & ~255u) | (epoch & 255u));
  #pragma unroll
  for (int j = 0; j < 5; j++) {
    const float* a = &d[j * 8];
    stg128(reinterpret_cast<uint4*>(g_xn + (size_t)row * DM) + c + 16 * j, make_uint4(
           pack_bf16(fmaf(a[0], r, o), fmaf(a[1], r, o)), pack_bf16(fmaf(a[2], r, o), fmaf(a[3], r, o)),
           pack_bf16(fmaf(a[4], r, o), fmaf(a[5], r, o)), pack_bf16(fmaf(a[6], r, o), fmaf(a[7], r, o))));
  }
  #pragma unroll
  for (int j = 0; j < 5; j++) stg128(reinterpret_cast<uint4*>(out + (size_t)row * DM) + c + 16 * j, rv[j]);
  bar_arrive<BAR_LN>(288);
}
__device__ __forceinline__ void colsum_part(const bf16* __restrict__ win, int cta, unsigned epoch) {
  const int t = threadIdx.x & 127, w = t >> 5, l = t & 31;
  const int cj = min(cta, 119), cg = cj % 24, rg = cj / 24;
  uint4 cv[4];
  #pragma unroll
  for (int j = 0; j < 4; j++) cv[j] = ldg128(reinterpret_cast<const uint4*>(win + (size_t)(rg * 128 + w * 32 + j * 8 + (l >> 2)) * FF + FH + cg * 32) + (l & 3));
  float v[8];
  v[0] = (bf_lo(cv[0].x) + bf_lo(cv[1].x)) + (bf_lo(cv[2].x) + bf_lo(cv[3].x)); v[1] = (bf_hi(cv[0].x) + bf_hi(cv[1].x)) + (bf_hi(cv[2].x) + bf_hi(cv[3].x));
  v[2] = (bf_lo(cv[0].y) + bf_lo(cv[1].y)) + (bf_lo(cv[2].y) + bf_lo(cv[3].y)); v[3] = (bf_hi(cv[0].y) + bf_hi(cv[1].y)) + (bf_hi(cv[2].y) + bf_hi(cv[3].y));
  v[4] = (bf_lo(cv[0].z) + bf_lo(cv[1].z)) + (bf_lo(cv[2].z) + bf_lo(cv[3].z)); v[5] = (bf_hi(cv[0].z) + bf_hi(cv[1].z)) + (bf_hi(cv[2].z) + bf_hi(cv[3].z));
  v[6] = (bf_lo(cv[0].w) + bf_lo(cv[1].w)) + (bf_lo(cv[2].w) + bf_lo(cv[3].w)); v[7] = (bf_hi(cv[0].w) + bf_hi(cv[1].w)) + (bf_hi(cv[2].w) + bf_hi(cv[3].w));
  #pragma unroll
  for (int st = 0; st < 3; st++) {
    const int n = 4 >> st;
    const bool up = (l & (4 * n)) != 0;
    #pragma unroll
    for (int e = 0; e < 4; e++)
      if (e < n) { const float keep = up ? v[e + n] : v[e], send = up ? v[e] : v[e + n]; v[e] = keep + __shfl_xor_sync(0xffffffffu, send, 4 * n); }
  }
  float* red = reinterpret_cast<float*>(smem + RED_OFF);
  red[w * 32 + (l & 3) * 8 + (l >> 2)] = v[0];
  bar_sync<BAR_WG2>(128);
  if (t < 32) st_vol2(&g_csum[rg * FH + cg * 32 + t], __float_as_uint((red[t] + red[32 + t]) + (red[64 + t] + red[96 + t])), epoch);
}

__device__ __forceinline__ void a_entry(int g, int grp, int rb, int& mi, int& kb) {
  if (g < 10) { mi = M_X; kb = g; }
  else if (g < 20) { mi = M_XN; kb = g - 10; }
  else if (grp == 0) {
    if (g < 52) { mi = M_WSP; kb = (g - 20); }
    else if (g < 52 + NX) { mi = M_WSIM; kb = g - 52 + 32 - NX; }
    else { mi = M_H; kb = g - 52 - NX; }
  } else {
    if (g < 30) { mi = M_XN; kb = g - 20; }
    else if (g < 62) { mi = M_WSRE; kb = (g - 30); }
    else { mi = M_WSIM; kb = g - 62; }
  }
}

__global__ void __cluster_dims__(2, 1, 1) __launch_bounds__(384, 1)
fused_kernel(const __grid_constant__ Maps maps, const bf16* __restrict__ x, const bf16* __restrict__ win, const bf16* __restrict__ bsp,
             bf16* __restrict__ out) {
  const uint32_t sbase = smem_u32(smem);
  const uint32_t full0 = sbase + BAR_OFF, empty0 = full0 + 8 * MAXST, dep0 = empty0 + 8 * MAXST, ring = sbase + RING_OFF;
  const int tid = threadIdx.x, wg = __shfl_sync(0xffffffffu, tid >> 7, 0);
  const int rank = blockIdx.x & 1;
  const int grp = (blockIdx.x >> 1) & 1, half = (blockIdx.x >> 2) & 1, rb = blockIdx.x >> 3;
  const int ct = half * 2 + rank, c8 = grp * 4 + ct;
  const int cta = rb * 8 + half * 4 + grp * 2 + rank;
  const int total = grp == 0 ? KB_A : KB_B;
  const uint32_t stage_bytes = grp == 0 ? STAGE_A : STAGE_B;
  const int nst = grp == 0 ? NST_A : NST_B;
  const uint32_t buf = ring + nst * stage_bytes;

  uint4 rv[5];
  if (wg != 0) ln_load(x, cta, rv);
  const unsigned epoch = (ld_relaxed(&g_done) >> 7) + 1u;
  if (tid == 0) {
    TS(0, 0);
    for (int s = 0; s < MAXST; s++) { mbar_init(full0 + 8 * s, 2); mbar_init(empty0 + 8 * s, 2); }
    for (int s = 0; s < 4; s++) mbar_init(dep0 + 8 * s, 1);
    *reinterpret_cast<volatile int*>(smem + READY_OFF) = 0;
    asm volatile("fence.mbarrier_init.release.cluster;" ::: "memory");
  }
  __syncthreads();
  asm volatile("barrier.cluster.arrive.relaxed.aligned;" ::: "memory");

  if (wg == 0) {
    asm volatile("setmaxnreg.dec.sync.aligned.u32 40;");
    const int warp = tid >> 5, lane = tid & 31;
    if (warp == 0) {
      const int row = rb * 128;
      if (lane == 0) {
        for (int g = 0; g < nst; g++) {
          mbar_expect_tx(full0 + 8 * g, A_BYTES);
          tma_load_2d(ring + g * stage_bytes, &maps.m[M_X], full0 + 8 * g, g * 64, row);
          tma_load_2d(ring + g * stage_bytes + 8192, &maps.m[M_X], full0 + 8 * g, g * 64, row + 64);
        }
      }
      __syncwarp();
      cluster_wait();
      if (lane == 0) {
        int s = 0, ph = 0;
        #pragma unroll 1
        for (int g = nst; g < total; g++) {
          int mi, kb;
          a_entry(g, grp, rb, mi, kb);
          if (g == 10 || (mi == M_H && kb == 0)) { TS(0, g > 10 ? 3 : 1); mbar_wait(dep0 + (g > 10 ? 24 : 0), 0); fence_async_global(); TS(0, g > 10 ? 4 : 2); }
          mbar_wait(empty0 + 8 * s, ph);
          mbar_expect_tx(full0 + 8 * s, A_BYTES);
          tma_load_2d_mc(ring + s * stage_bytes + rank * 8192, &maps.m[mi], full0 + 8 * s, kb * 64, row + rank * 64, 3);
          if (++s == nst) { s = 0; ph ^= 1; }
          if (g + PF_D < total) {
            a_entry(g + PF_D, grp, rb, mi, kb);
            if (mi >= M_WSRE && mi <= M_WSP && PF_COND)
              asm volatile("cp.async.bulk.prefetch.tensor.2d.L2.global.tile [%0, {%1, %2}];" :: "l"((uint64_t)&maps.m[mi]), "r"(kb * 64), "r"(row + rank * 64) : "memory");
          }
        }
        TS(0, 5);
      }
    } else if (warp == 1) {
      if (lane == 0) {
        int s = 0, ph = 1;
        int have = 0;
        #pragma unroll 1
        for (int g = 0; g < total; g++) {
          int kind = 1, mi, kb, c, dep = 0, need = 0;
          uint32_t bytes = 20480;
          if (g < 10) { kind = 0; mi = M_WIN32; kb = g; c = 24 + 3 * c8; bytes = 12288; }
          else if (grp == 0) {
            if (g < 20) { kind = 0; mi = M_WIN3; kb = g - 10; c = 3 * ct; bytes = 24576; }
            else if (g < 52) { kind = 0; mi = M_Z23; kb = (g - 20); c = 3 * ct; bytes = 24576; need = ((g - 20) >> 1) + 1; }
            else if (g < 52 + NX) { mi = M_AB; kb = g - 52 + 32 - NX; c = DM + ct * 160; dep = g == 52 ? 2 : 0; }
            else { kind = 0; mi = M_WOUT; kb = g - 52 - NX; c = ct * 5; }
          } else {
            if (g < 30) { mi = g < 20 ? M_WDRE : M_WDIM; kb = g < 20 ? g - 10 : g - 20; c = ct * 160; }
            else if (g < 62) { mi = M_AB; kb = (g - 30); c = ct * 160; need = ((g - 30) >> 1) + 1; }
            else { mi = M_AB; kb = g - 62; c = ct * 160 + DM; dep = g == 62 ? 2 : 0; }
          }
          if (need > have) {
            if (need == 1) TS(1, 0);
            unsigned it = 0;
            while ((have = *reinterpret_cast<volatile int*>(smem + READY_OFF)) < need && ++it < 50 * POLL_LIMIT) {}
            fence_async_global();
            if (need == 1) { TS(1, 1); TC(1); }
          }
          if (dep) { TS(1, dep * 2 - 2); mbar_wait(dep0 + 8 * dep, 0); fence_async_global(); TS(1, dep * 2 - 1); TC(dep); }
          const uint32_t dst = ring + s * stage_bytes + A_BYTES, fb = full0 + 8 * s;
          mbar_wait(empty0 + 8 * s, ph);
          if (++s == nst) { s = 0; ph ^= 1; }
          mbar_expect_tx(fb, bytes);
          if (kind == 0) tma_load_3d(dst, &maps.m[mi], fb, 0, kb * 64, c);
          else tma_load_2d(dst, &maps.m[mi], fb, kb * 64, c);
        }
      }
      __syncwarp();
      cluster_wait();
    } else if (warp == 2) {
      cluster_wait();
      {
        unsigned it = 0;
        uint2 v[4];
        while (true) {
          bool ok = true;
          #pragma unroll
          for (int i = 0; i < 4; i++) { v[i] = ld_vol2(&g_xstat[rb * 128 + i * 32 + lane]); ok = ok && ((v[i].y ^ epoch) & 255u) == 0; }
          if (ok || ++it > POLL_LIMIT) break;
          __nanosleep(POLL_NS);
        }
        #pragma unroll
        for (int i = 0; i < 4; i++) reinterpret_cast<uint2*>(smem + ROWSTAT_OFF)[i * 32 + lane] = make_uint2(v[i].x, v[i].y & ~255u);
        __syncwarp();
        TS(0, 6);
        bar_arrive<BAR_STATS>(192);
      }
      #pragma unroll 1
      for (int d = 0; d < 4 - grp; d++) {
        const int slot = d == 0 ? F_XN + rb : d == 3 ? F_H + rb : d == 2 ? F_B + ct : grp == 0 ? F_Z + ct : F_A + ct;
        const int byte = d == 0 ? lane & 7 : d == 3 ? lane & 3 : (d == 1 && grp == 0) ? lane : lane >> 1;
        unsigned it = 0, m;
        while ((m = __ballot_sync(0xffffffffu, get_flag(slot, byte) != (epoch & 255u))) != 0 && ++it < POLL_LIMIT) {
          if (d == 1 && lane == 0) *reinterpret_cast<volatile int*>(smem + READY_OFF) = (__ffs(m) - 1) >> 1;
          __nanosleep(WATCH_NS);
        }
        if (d == 1 && lane == 0) *reinterpret_cast<volatile int*>(smem + READY_OFF) = 16;
        TS(0, 8 + d * 2);
        fence_async_global();
        __syncwarp();
        if (lane == 0 && d != 1) mbar_arrive(dep0 + 8 * d);
      }
    } else {
      cluster_wait();
      bar_sync<BAR_LN>(288);
      if (lane == 0) { TS(1, 5); publish(F_XN + rb, cta & 7, epoch); TS(1, 6); }
      __syncwarp();
      #pragma unroll 1
      for (int i = 0; i < 3; i++) {
        unsigned it = 0;
        while (true) {
          bool ok = true;
          float a = 0.f;
          #pragma unroll
          for (int p = 0; p < 5; p++) { const uint2 u = ld_vol2(&g_csum[p * FH + c8 * 96 + i * 32 + lane]); ok = ok && u.y == epoch; a += __uint_as_float(u.x); }
          reinterpret_cast<float*>(smem + COLSUM_OFF)[i * 32 + lane] = a;
          if (ok || ++it > POLL_LIMIT) break;
          __nanosleep(POLL_NS);
        }
      }
      __syncwarp();
      TS(1, 4);
      bar_arrive<BAR_STATS>(192);
      bar_sync<BAR_PUB1>(160);
      if (lane == 0) {
        TS(1, 7);
        tma_store_3d(&maps.m[M_Z232], buf, 0, rb * 128, 3 * c8);
        bulk_commit();
        bulk_wait_all();
        set_flag(F_Z + (c8 >> 1), rb * 2 + (c8 & 1), epoch);
        TS(1, 8);
      }
      __syncwarp();
      bar_arrive<BAR_BUF>(160);
      if (grp == 1) {
        bar_sync<BAR_PUB2>(160);
        if (lane == 0) set_flag(F_A + ct, rb, epoch);
        TS(1, 9);
        __syncwarp();
      }
      bar_sync<BAR_PUB1>(160);
      if (lane == 0) set_flag(grp == 0 ? F_H + rb : F_B + ct, grp == 0 ? ct : rb, epoch);
      TS(1, 10);
      __syncwarp();
      bar_arrive<BAR_BUF>(160);
    }
  } else {
    asm volatile("setmaxnreg.inc.sync.aligned.u32 232;");
    const int t = tid & 127, w = t >> 5, l = t & 31;
    ln_rows(rv, out, cta, epoch);
    if (wg == 2) colsum_part(win, cta, epoch);
    TS(wg + 1, 0);
    cluster_wait();
    const int rl = w * 16 + ((l >> 3) & 1) * 8 + (l & 7);
    const int gr = w * 16 + (l & 15);
    const uint32_t st_base = buf + rl * 128;
    const uint32_t st_x = ((l >> 4) ^ (l & 7)) << 4;
    if (wg == 1) {
      float acc[2][48];
      zero(acc);
      mainloop<96, 2, false, BAR_ORD1>(acc, sbase, grp, 0, 10);
      drain(acc, sbase, grp, 9);
      TS(2, 2);
      bar_sync<BAR_STATS>(192);
      const float2* rs = reinterpret_cast<const float2*>(smem + ROWSTAT_OFF) + w * 16 + (l >> 2);
      const float2* cs = reinterpret_cast<const float2*>(smem + COLSUM_OFF) + (l & 3);
      float sum[4], sq[4];
      #pragma unroll
      for (int r = 0; r < 4; r++) {
        const float2 st = rs[(r >> 1) * 64 + (r & 1) * 8];
        float s0 = 0.f, q0 = 0.f;
        #pragma unroll
        for (int j = 0; j < 12; j++) {
          const float2 c = cs[j * 4];
          float* a = &acc[r >> 1][4 * j + (r & 1) * 2];
          a[0] = gelu_tanh(fmaf(a[0], st.x, st.y * c.x));
          a[1] = gelu_tanh(fmaf(a[1], st.x, st.y * c.y));
          s0 += a[0] + a[1]; q0 = fmaf(a[0], a[0], q0); q0 = fmaf(a[1], a[1], q0);
        }
        s0 += __shfl_xor_sync(0xffffffffu, s0, 1); q0 += __shfl_xor_sync(0xffffffffu, q0, 1);
        s0 += __shfl_xor_sync(0xffffffffu, s0, 2); q0 += __shfl_xor_sync(0xffffffffu, q0, 2);
        sum[r] = s0; sq[r] = q0;
      }
      TS(2, 4);
      float rstd, off;
      {
        const int qd = l & 3;
        const float sm = qd == 0 ? sum[0] : qd == 1 ? sum[1] : qd == 2 ? sum[2] : sum[3];
        const float sv = qd == 0 ? sq[0] : qd == 1 ? sq[1] : qd == 2 ? sq[2] : sq[3];
        const int row = (qd >> 1) * 64 + w * 16 + (qd & 1) * 8 + (l >> 2);
        const float mu = sm * (1.f / 96), m2 = fmaxf(sv - sm * mu, 0.f);
        st_vol2(&g_zstat[(rb * 8 + c8) * 128 + row], __float_as_uint(mu), (__float_as_uint(m2) & ~255u) | (epoch & 255u));
        uint2 v[7];
        unsigned n = 0;
        while (true) {
          bool ok = true;
          #pragma unroll
          for (int j = 0; j < 7; j++) v[j] = ld_vol2(&g_zstat[(rb * 8 + ((c8 + 1 + j) & 7)) * 128 + row]);
          #pragma unroll
          for (int j = 0; j < 7; j++) ok = ok && ((v[j].y ^ epoch) & 255u) == 0;
          if (ok || ++n > POLL_LIMIT) break;
          __nanosleep(POLL_NS);
        }
        float mean = mu, var = m2;
        #pragma unroll
        for (int j = 0; j < 7; j++) { mean += __uint_as_float(v[j].x); var += __uint_as_float(v[j].y & ~255u); }
        mean *= 0.125f;
        float d = (mu - mean) * (mu - mean);
        #pragma unroll
        for (int j = 0; j < 7; j++) d = fmaf(__uint_as_float(v[j].x) - mean, __uint_as_float(v[j].x) - mean, d);
        rstd = rsqrtf(fmaf(96.f, d, var) * (1.f / FH) + LN_EPS); off = -mean * rstd;
        __syncwarp();
      }
      TS(2, 5);
      #pragma unroll
      for (int mi = 0; mi < 2; mi++) {
        const float r0 = __shfl_sync(0xffffffffu, rstd, (l & 28) + mi * 2), o0 = __shfl_sync(0xffffffffu, off, (l & 28) + mi * 2);
        const float r1 = __shfl_sync(0xffffffffu, rstd, (l & 28) + mi * 2 + 1), o1 = __shfl_sync(0xffffffffu, off, (l & 28) + mi * 2 + 1);
        #pragma unroll
        for (int jj = 0; jj < 6; jj++) {
          const float* a = &acc[mi][8 * jj];
          stsm4(buf + (jj >> 1) * 8192 + mi * 4096 + rl * 64 + ((((jj & 1) * 2 + (l >> 4)) ^ ((l >> 1) & 3)) << 4),
                pack_bf16(fmaf(a[0], r0, o0), fmaf(a[1], r0, o0)), pack_bf16(fmaf(a[2], r1, o1), fmaf(a[3], r1, o1)),
                pack_bf16(fmaf(a[4], r0, o0), fmaf(a[5], r0, o0)), pack_bf16(fmaf(a[6], r1, o1), fmaf(a[7], r1, o1)));
        }
      }
      fence_async_smem();
      bar_arrive<BAR_PUB1>(160);
      TS(2, 6);
      if (grp == 0) {
        float acc[2][96];
        zero(acc);
        bar_sync<BAR_ORD2>(256);
        mainloop<192, 1, false, BAR_ORD1>(acc, sbase, 0, 20, 32);
        const float* bias = reinterpret_cast<const float*>(smem + BIAS_OFF) + w * 16 + (l >> 2);
        bar_sync<BAR_Z1>(256);
        drain(acc, sbase, 0, 51);
        TS(2, 7);
        {
          const float bb[4] = {bias[0], bias[8], bias[64], bias[72]};
          uint32_t z[2][4][4];
          #pragma unroll
          for (int i = 0; i < 4; i++) ldsm4(st_base + (st_x ^ (i << 5)), z[0][i][0], z[0][i][1], z[0][i][2], z[0][i][3]);
          #pragma unroll
          for (int bx = 0; bx < 6; bx++) {
            if (bx < 5) {
              #pragma unroll
              for (int i = 0; i < 4; i++)
                ldsm4(st_base + (bx + 1) * 8192 + (st_x ^ (i << 5)), z[(bx + 1) & 1][i][0], z[(bx + 1) & 1][i][1], z[(bx + 1) & 1][i][2], z[(bx + 1) & 1][i][3]);
            }
            const float b0 = bb[(bx / 3) * 2], b1 = bb[(bx / 3) * 2 + 1];
            #pragma unroll
            for (int i = 0; i < 4; i++) {
              const float* a = &acc[bx / 3][8 * ((bx % 3) * 4 + i)];
              const uint32_t* zz = z[bx & 1][i];
              stsm4(st_base + bx * 8192 + (st_x ^ (i << 5)),
                    hmul2_bf16(zz[0], pack_bf16(a[0] + b0, a[1] + b0)), hmul2_bf16(zz[1], pack_bf16(a[2] + b1, a[3] + b1)),
                    hmul2_bf16(zz[2], pack_bf16(a[4] + b0, a[5] + b0)), hmul2_bf16(zz[3], pack_bf16(a[6] + b1, a[7] + b1)));
            }
            fence_async_smem();
            __syncwarp();
            if (l == 0) {
              tma_store_2d(&maps.m[M_HS], buf + bx * 8192 + w * 2048, ct * 192 + (bx % 3) * 64, rb * 128 + (bx / 3) * 64 + w * 16);
              bulk_commit();
            }
          }
        }
        TS(2, 8);
        if (l == 0) bulk_wait_all();
        __syncwarp();
        bar_arrive<BAR_PUB1>(160);
        TS(2, 9);
        return;
      }
    } else {
      if (grp == 0) {
        reinterpret_cast<float*>(smem + BIAS_OFF)[t] = __bfloat162float(bsp[rb * 128 + t]);
        float acc[2][96];
        zero(acc);
        bar_sync<BAR_ORD1>(256);
        mainloop<192, 1, false, BAR_ORD2>(acc, sbase, 0, 10, 10);
        drain(acc, sbase, 0, 19);
        TS(3, 2);
        bar_sync<BAR_BUF>(160);
        #pragma unroll
        for (int mi = 0; mi < 2; mi++)
          #pragma unroll
          for (int jj = 0; jj < 12; jj++) {
            const float* a = &acc[mi][8 * jj];
            stsm4(st_base + mi * 24576 + (jj >> 2) * 8192 + (st_x ^ ((jj & 3) << 5)),
                  pack_bf16(a[0], a[1]), pack_bf16(a[2], a[3]), pack_bf16(a[4], a[5]), pack_bf16(a[6], a[7]));
          }
        __syncwarp();
        TS(3, 3);
        const uint32_t rbase = buf + (l >> 4) * 24576 + gr * 128;
        #pragma unroll 1
        for (int c2 = 0; c2 < 12; c2++) {
          const uint32_t ab = rbase + (c2 >> 2) * 8192;
          uint4 v[2];
          #pragma unroll
          for (int i = 0; i < 2; i++) v[i] = lds128(ab + (((((c2 & 3) * 2 + i) ^ l) & 7) << 4));
          #pragma unroll
          for (int i = 0; i < 2; i++)
            sts128(ab + (((((c2 & 3) * 2 + i) ^ l) & 7) << 4),
                   pack_bf16(gelu_tanh(bf_lo(v[i].x)), gelu_tanh(bf_hi(v[i].x))), pack_bf16(gelu_tanh(bf_lo(v[i].y)), gelu_tanh(bf_hi(v[i].y))),
                   pack_bf16(gelu_tanh(bf_lo(v[i].z)), gelu_tanh(bf_hi(v[i].z))), pack_bf16(gelu_tanh(bf_lo(v[i].w)), gelu_tanh(bf_hi(v[i].w))));
        }
        TS(3, 4);
        bar_arrive<BAR_Z1>(256);
      }
    }
    float acc[2][80];
    if (grp == 1) {
      zero(acc);
      if (wg == 2) {
        bar_sync<BAR_ORD1>(256);
        mainloop<160, 0, false, BAR_ORD2>(acc, sbase, 1, 10, 10);
      } else {
        bar_sync<BAR_ORD2>(256);
        mainloop<160, 0, false, BAR_ORD1>(acc, sbase, 1, 20, 10);
      }
      drain(acc, sbase, 1, wg == 2 ? 19 : 29);
      TS(wg + 1, wg == 1 ? 7 : 2);
      if (wg == 1) bar_sync<BAR_Z1>(256); else bar_sync<BAR_BUF>(160);
      const uint32_t sg = wg == 1 ? 0x80008000u : 0u;
      const uint32_t tb = buf + ((l >> 4) * 8 + (l & 7)) * 128 + (((w * 2 + ((l >> 3) & 1)) ^ (l & 7)) << 4);
      #pragma unroll
      for (int mi = 0; mi < 2; mi++)
        #pragma unroll
        for (int jj = 0; jj < 10; jj++) {
          const float* a = &acc[mi][8 * jj];
          stsm4_t(tb + mi * 20480 + jj * 2048, pack_bf16(a[0], a[1]) ^ sg, pack_bf16(a[2], a[3]) ^ sg, pack_bf16(a[4], a[5]) ^ sg, pack_bf16(a[6], a[7]) ^ sg);
        }
      fence_async_smem();
      if (wg == 1) bar_sync<BAR_WG1>(128); else bar_sync<BAR_WG2>(128);
      TS(wg + 1, wg == 1 ? 8 : 6);
      if (l == 0) {
        #pragma unroll 1
        for (int i = 0; i < 2; i++) {
          tma_store_2d(&maps.m[M_ABS], buf + i * 20480 + w * 5120, rb * 128 + i * 64, (2 - wg) * DM + ct * 160 + w * 40);
          bulk_commit();
        }
        bulk_wait_all();
      }
      __syncwarp();
      TS(wg + 1, wg == 1 ? 9 : 10);
      if (wg == 1) { bar_arrive<BAR_PUB1>(160); return; }
      bar_arrive<BAR_PUB2>(160);
      bar_arrive<BAR_Z1>(256);
    }
    zero(acc);
    bar_sync<BAR_ORD1>(256);
    mainloop<160, 0, false, 0>(acc, sbase, grp, grp == 0 ? 52 : 30, grp == 0 ? NX : 64 - NX);
    if (grp == 0) mainloop<160, 2, true, 0>(acc, sbase, 0, 52 + NX, 12);
    const uint32_t slab = buf + w * (16 * 320);
    const uint32_t addr = slab + (((l >> 3) & 1) * 8 + (l & 7)) * 320 + (l >> 4) * 16;
    bar_sync<BAR_BUF>(160);
    drain(acc, sbase, grp, total - 1);
    TS(3, 12);
    #pragma unroll
    for (int mi = 0; mi < 2; mi++) {
      #pragma unroll
      for (int jj = 0; jj < 10; jj++) {
        const float* a = &acc[mi][8 * jj];
        stsm4(addr + mi * 20480 + jj * 32, pack_bf16(a[0], a[1]), pack_bf16(a[2], a[3]), pack_bf16(a[4], a[5]), pack_bf16(a[6], a[7]));
      }
      fence_async_smem();
      __syncwarp();
      if (l == 0) {
        tma_reduce_2d(&maps.m[M_OUT], slab + mi * 20480, ct * 160, rb * 128 + mi * 64 + w * 16);
        bulk_commit();
      }
    }
    TS(3, 13);
    if (l == 0) {
      bulk_wait_read();
      if (w == 0) atomicAdd(&g_done, 1u);
    }
    TS(3, 15);
  }
}

typedef CUresult (*EncodeFn)(CUtensorMap*, CUtensorMapDataType, cuuint32_t, void*, const cuuint64_t*, const cuuint64_t*,
                             const cuuint32_t*, const cuuint32_t*, CUtensorMapInterleave, CUtensorMapSwizzle,
                             CUtensorMapL2promotion, CUtensorMapFloatOOBfill);

void make2d(EncodeFn enc, CUtensorMap* m, const void* p, uint64_t cols, uint64_t rows, uint32_t bc, uint32_t br, bool swz = true) {
  cuuint64_t gd[2] = {cols, rows}, gs[1] = {cols * 2};
  cuuint32_t bd[2] = {bc, br}, es[2] = {1, 1};
  enc(m, CU_TENSOR_MAP_DATA_TYPE_BFLOAT16, 2, const_cast<void*>(p), gd, gs, bd, es, CU_TENSOR_MAP_INTERLEAVE_NONE,
      swz ? CU_TENSOR_MAP_SWIZZLE_128B : CU_TENSOR_MAP_SWIZZLE_NONE, PROMO, CU_TENSOR_MAP_FLOAT_OOB_FILL_NONE);
}
void make3d(EncodeFn enc, CUtensorMap* m, const void* p, uint64_t cols, uint64_t rows, uint32_t cw, uint32_t nc, uint32_t br = 64) {
  cuuint64_t gd[3] = {cw, rows, cols / cw}, gs[2] = {cols * 2, cw * 2};
  cuuint32_t bd[3] = {cw, br, nc}, es[3] = {1, 1, 1};
  enc(m, CU_TENSOR_MAP_DATA_TYPE_BFLOAT16, 3, const_cast<void*>(p), gd, gs, bd, es, CU_TENSOR_MAP_INTERLEAVE_NONE,
      cw == 64 ? CU_TENSOR_MAP_SWIZZLE_128B : CU_TENSOR_MAP_SWIZZLE_64B, PROMO, CU_TENSOR_MAP_FLOAT_OOB_FILL_NONE);
}

}

extern "C" void kernel_launch(void* const* d_in, const int* in_sizes, int n_in, void* d_out, int out_size) {
  const bf16* x = (const bf16*)d_in[0];
  const bf16* wsre = (const bf16*)d_in[1];
  const bf16* wsim = (const bf16*)d_in[2];
  const bf16* wdre = (const bf16*)d_in[3];
  const bf16* wdim = (const bf16*)d_in[4];
  const bf16* win = (const bf16*)d_in[6];
  const bf16* wsp = (const bf16*)d_in[7];
  const bf16* bsp = (const bf16*)d_in[8];
  const bf16* wout = (const bf16*)d_in[9];

  void* fn = nullptr;
  cudaDriverEntryPointQueryResult qr;
  cudaGetDriverEntryPoint("cuTensorMapEncodeTiled", &fn, cudaEnableDefault, &qr);
  EncodeFn enc = (EncodeFn)fn;
  void *abT, *z2, *h, *xn;
  cudaGetSymbolAddress(&xn, g_xn);
  cudaGetSymbolAddress(&abT, g_abT);
  cudaGetSymbolAddress(&z2, g_z2);
  cudaGetSymbolAddress(&h, g_h);

  Maps maps;
  make2d(enc, &maps.m[M_X], x, DM, SEQ, 64, 64);
  make2d(enc, &maps.m[M_XN], xn, DM, SEQ, 64, 64);
  make3d(enc, &maps.m[M_Z232], z2, FH, SEQ, 32, 3, 128);
  make3d(enc, &maps.m[M_WIN32], win, FF, DM, 32, 3);
  make2d(enc, &maps.m[M_WSRE], wsre, SEQ, SEQ, 64, 64);
  make2d(enc, &maps.m[M_WSIM], wsim, SEQ, SEQ, 64, 64);
  make2d(enc, &maps.m[M_WSP], wsp, SEQ, SEQ, 64, 64);
  make2d(enc, &maps.m[M_H], h, FH, SEQ, 64, 64);
  make3d(enc, &maps.m[M_WIN3], win, FF, DM, 64, 3);
  make3d(enc, &maps.m[M_Z23], z2, FH, SEQ, 64, 3);
  make2d(enc, &maps.m[M_WDRE], wdre, DM, DM, 64, 160);
  make2d(enc, &maps.m[M_WDIM], wdim, DM, DM, 64, 160);
  make2d(enc, &maps.m[M_AB], abT, SEQ, 2 * DM, 64, 160);
  make3d(enc, &maps.m[M_WOUT], wout, DM, FH, 32, 5);
  make2d(enc, &maps.m[M_HS], h, FH, SEQ, 64, 16);
  make2d(enc, &maps.m[M_ABS], abT, SEQ, 2 * DM, 64, 40);
  make2d(enc, &maps.m[M_OUT], d_out, DM, SEQ, 160, 16, false);

  cudaFuncSetAttribute(fused_kernel, cudaFuncAttributeMaxDynamicSharedMemorySize, SMEM_BYTES);
  fused_kernel<<<128, 384, SMEM_BYTES>>>(maps, x, win, bsp, (bf16*)d_out);
}
```

```cpp
#include <cuda_runtime.h>
#include <cuda_bf16.h>
#include <cuda.h>
#include <stdint.h>

namespace {

typedef __nv_bfloat16 bf16;

constexpr int SEQ = 2048, DM = 640, FF = 1536, FH = 768;
#define NXV 10
constexpr int NX = NXV;
#define NSTB 5
constexpr int NST_A = 4, NST_B = NSTB, MAXST = 5;
constexpr int A_BYTES = 16384;
constexpr int BAR_OFF = 512;
constexpr int READY_OFF = 640;
constexpr int ROWSTAT_OFF = 1024;
constexpr int COLSUM_OFF = 2048;
constexpr int RED_OFF = 2560;
constexpr int RING_OFF = 3072;
constexpr int STAGE_A = 40960, STAGE_B = 36864;
constexpr int SMEM_BYTES = RING_OFF + 5 * STAGE_B + 40960;
constexpr int KB_A = 20 + 32 + NX + 12;
constexpr int KB_B = 30 + 64 - NX;
constexpr float LN_EPS = 1e-5f;
constexpr unsigned POLL_LIMIT = 100000;
#define POLL_NS 100
#define PF_D 8
#define ROT 0
#define Z1_NS 0
#define INFL 2
#define LIM_G 1000
#define MAPV 0
#define PROMO CU_TENSOR_MAP_L2_PROMOTION_L2_128B
#define WATCH_NS 40
#define PF_COND ((kb & 1) == (ct >> 1))
#define WPF 1
#define PF_NS 150

constexpr int BAR_ORD1 = 1, BAR_ORD2 = 2, BAR_WG1 = 3, BAR_WG2 = 4, BAR_LN = 5, BAR_BUF = 6, BAR_Z1 = 7, BAR_PUB1 = 8, BAR_PUB2 = 9, BAR_STATS = 10;

enum { M_X, M_XN, M_WIN32, M_Z232, M_WSRE, M_WSIM, M_WSP, M_H, M_WIN3, M_Z23, M_WDRE, M_WDIM, M_AB, M_WOUT, M_OUT, M_HS, M_ABS, M_COUNT };
struct Maps { CUtensorMap m[M_COUNT]; };

__device__ __align__(1024) bf16 g_abT[2 * DM * SEQ];
__device__ __align__(1024) bf16 g_z2[SEQ * FH];
__device__ __align__(1024) bf16 g_h[SEQ * FH];
__device__ __align__(1024) bf16 g_xn[SEQ * DM];
__device__ __align__(16) uint2 g_xstat[SEQ];
__device__ __align__(16) uint2 g_csum[5 * FH];
__device__ __align__(16) uint2 g_zstat[128 * 128];
__device__ __align__(256) unsigned char g_flags[44 * 256];
constexpr int F_A = 0, F_B = 4, F_Z = 8, F_H = 12, F_XN = 28;
__device__ unsigned g_done;
#define TS(role, ev)
#define TC(i)

extern __shared__ __align__(1024) uint8_t smem[];

__device__ __forceinline__ uint32_t smem_u32(const void* p) { return (uint32_t)__cvta_generic_to_shared(p); }
__device__ __forceinline__ void mbar_init(uint32_t bar, uint32_t cnt) { asm volatile("mbarrier.init.shared::cta.b64 [%0], %1;" :: "r"(bar), "r"(cnt)); }
__device__ __forceinline__ void mbar_expect_tx(uint32_t bar, uint32_t bytes) { asm volatile("mbarrier.arrive.expect_tx.shared::cta.b64 _, [%0], %1;" :: "r"(bar), "r"(bytes) : "memory"); }
__device__ __forceinline__ void mbar_arrive(uint32_t bar) { asm volatile("mbarrier.arrive.shared::cta.b64 _, [%0];" :: "r"(bar) : "memory"); }
__device__ __forceinline__ void mbar_arrive_cluster(uint32_t bar, uint32_t cta) {
  asm volatile("{\n.reg .b32 ra;\nmapa.shared::cluster.u32 ra, %0, %1;\nmbarrier.arrive.shared::cluster.b64 _, [ra];\n}" :: "r"(bar), "r"(cta) : "memory");
}
__device__ __forceinline__ void mbar_wait(uint32_t bar, uint32_t parity) {
  asm volatile("{\n.reg .pred p;\n.reg .u32 n;\nmov.u32 n, 0;\n"
               "LW: mbarrier.try_wait.parity.shared::cta.b64 p, [%0], %1, 2000;\n@p bra LD;\n"
               "add.u32 n, n, 1;\nsetp.lt.u32 p, n, 20000;\n@p bra LW;\nLD:\n}" :: "r"(bar), "r"(parity) : "memory");
}
__device__ __forceinline__ void tma_load_2d(uint32_t dst, const CUtensorMap* map, uint32_t bar, int c0, int c1) {
  asm volatile("cp.async.bulk.tensor.2d.shared::cluster.global.mbarrier::complete_tx::bytes [%0], [%1, {%3, %4}], [%2];"
    :: "r"(dst), "l"((uint64_t)map), "r"(bar), "r"(c0), "r"(c1) : "memory");
}
__device__ __forceinline__ void tma_load_3d(uint32_t dst, const CUtensorMap* map, uint32_t bar, int c0, int c1, int c2) {
  asm volatile("cp.async.bulk.tensor.3d.shared::cluster.global.mbarrier::complete_tx::bytes [%0], [%1, {%3, %4, %5}], [%2];"
    :: "r"(dst), "l"((uint64_t)map), "r"(bar), "r"(c0), "r"(c1), "r"(c2) : "memory");
}
__device__ __forceinline__ void tma_load_2d_mc(uint32_t dst, const CUtensorMap* map, uint32_t bar, int c0, int c1, uint16_t mask) {
  asm volatile("cp.async.bulk.tensor.2d.shared::cluster.global.mbarrier::complete_tx::bytes.multicast::cluster [%0], [%1, {%3, %4}], [%2], %5;"
    :: "r"(dst), "l"((uint64_t)map), "r"(bar), "r"(c0), "r"(c1), "h"(mask) : "memory");
}
__device__ __forceinline__ void tma_store_2d(const CUtensorMap* map, uint32_t src, int c0, int c1) {
  asm volatile("cp.async.bulk.tensor.2d.global.shared::cta.bulk_group [%0, {%2, %3}], [%1];"
    :: "l"((uint64_t)map), "r"(src), "r"(c0), "r"(c1) : "memory");
}
__device__ __forceinline__ void tma_store_3d(const CUtensorMap* map, uint32_t src, int c0, int c1, int c2) {
  asm volatile("cp.async.bulk.tensor.3d.global.shared::cta.bulk_group [%0, {%2, %3, %4}], [%1];"
    :: "l"((uint64_t)map), "r"(src), "r"(c0), "r"(c1), "r"(c2) : "memory");
}
__device__ __forceinline__ void tma_reduce_2d(const CUtensorMap* map, uint32_t src, int c0, int c1) {
  asm volatile("cp.reduce.async.bulk.tensor.2d.global.shared::cta.add.tile.bulk_group [%0, {%2, %3}], [%1];"
    :: "l"((uint64_t)map), "r"(src), "r"(c0), "r"(c1) : "memory");
}
__device__ __forceinline__ void bulk_wait_all() { asm volatile("cp.async.bulk.wait_group 0;" ::: "memory"); }
__device__ __forceinline__ void bulk_commit() { asm volatile("cp.async.bulk.commit_group;" ::: "memory"); }
__device__ __forceinline__ void bulk_wait_read() { asm volatile("cp.async.bulk.wait_group.read 0;" ::: "memory"); }
__device__ __forceinline__ void fence_async_smem() { asm volatile("fence.proxy.async.shared::cta;" ::: "memory"); }
__device__ __forceinline__ void fence_async_global() { asm volatile("fence.proxy.async.global;" ::: "memory"); }
__device__ __forceinline__ void wgmma_fence() { asm volatile("wgmma.fence.sync.aligned;" ::: "memory"); }
__device__ __forceinline__ void wgmma_commit() { asm volatile("wgmma.commit_group.sync.aligned;" ::: "memory"); }
template<int N> __device__ __forceinline__ void wgmma_wait() { asm volatile("wgmma.wait_group.sync.aligned %0;" :: "n"(N) : "memory"); }
template<int ID> __device__ __forceinline__ void bar_sync(int n) { asm volatile("bar.sync %0, %1;" :: "n"(ID), "r"(n) : "memory"); }
template<int ID> __device__ __forceinline__ void bar_arrive(int n) { asm volatile("bar.arrive %0, %1;" :: "n"(ID), "r"(n) : "memory"); }
__device__ __forceinline__ void cluster_wait() { asm volatile("barrier.cluster.wait.aligned;" ::: "memory"); }
__device__ __forceinline__ uint64_t desc64(uint32_t lo, uint32_t hi) { return (uint64_t)lo | ((uint64_t)hi << 32); }
__device__ __forceinline__ uint4 ld_vol4(const uint4* p) {
  uint4 v; asm volatile("ld.relaxed.gpu.global.v4.u32 {%0,%1,%2,%3}, [%4];" : "=r"(v.x), "=r"(v.y), "=r"(v.z), "=r"(v.w) : "l"(p) : "memory"); return v;
}
__device__ __forceinline__ uint2 ld_vol2(const uint2* p) {
  uint2 v; asm volatile("ld.relaxed.gpu.global.v2.u32 {%0,%1}, [%2];" : "=r"(v.x), "=r"(v.y) : "l"(p) : "memory"); return v;
}
__device__ __forceinline__ void st_vol4(uint4* p, uint32_t a, uint32_t b, uint32_t c, uint32_t d) {
  asm volatile("st.relaxed.gpu.global.v4.u32 [%0], {%1,%2,%3,%4};" :: "l"(p), "r"(a), "r"(b), "r"(c), "r"(d) : "memory");
}
__device__ __forceinline__ void st_vol2(uint2* p, uint32_t a, uint32_t b) {
  asm volatile("st.relaxed.gpu.global.v2.u32 [%0], {%1,%2};" :: "l"(p), "r"(a), "r"(b) : "memory");
}
__device__ __forceinline__ void stg128(void* p, uint4 v) {
  asm volatile("st.global.v4.u32 [%0], {%1,%2,%3,%4};" :: "l"(p), "r"(v.x), "r"(v.y), "r"(v.z), "r"(v.w));
}
__device__ __forceinline__ unsigned ld_relaxed(const unsigned* p) {
  unsigned v; asm volatile("ld.relaxed.gpu.global.u32 %0, [%1];" : "=r"(v) : "l"(p) : "memory"); return v;
}
__device__ __forceinline__ uint32_t pack_bf16(float lo, float hi) {
  uint32_t r; asm("cvt.rn.bf16x2.f32 %0, %1, %2;" : "=r"(r) : "f"(hi), "f"(lo)); return r;
}
__device__ __forceinline__ float bf_lo(uint32_t v) { return __uint_as_float(v << 16); }
__device__ __forceinline__ float bf_hi(uint32_t v) { return __uint_as_float(v & 0xFFFF0000u); }
__device__ __forceinline__ void stsm4(uint32_t addr, uint32_t a, uint32_t b, uint32_t c, uint32_t d) {
  asm volatile("stmatrix.sync.aligned.m8n8.x4.shared.b16 [%0], {%1,%2,%3,%4};" :: "r"(addr), "r"(a), "r"(b), "r"(c), "r"(d));
}
__device__ __forceinline__ void stsm4_t(uint32_t addr, uint32_t a, uint32_t b, uint32_t c, uint32_t d) {
  asm volatile("stmatrix.sync.aligned.m8n8.x4.trans.shared.b16 [%0], {%1,%2,%3,%4};" :: "r"(addr), "r"(a), "r"(b), "r"(c), "r"(d));
}
__device__ __forceinline__ void ldsm4(uint32_t addr, uint32_t& a, uint32_t& b, uint32_t& c, uint32_t& d) {
  asm volatile("ldmatrix.sync.aligned.m8n8.x4.shared.b16 {%0,%1,%2,%3}, [%4];" : "=r"(a), "=r"(b), "=r"(c), "=r"(d) : "r"(addr));
}
__device__ __forceinline__ uint4 lds128(uint32_t a) {
  uint4 v; asm volatile("ld.shared.v4.u32 {%0,%1,%2,%3}, [%4];" : "=r"(v.x), "=r"(v.y), "=r"(v.z), "=r"(v.w) : "r"(a)); return v;
}
__device__ __forceinline__ void sts128(uint32_t a, uint32_t x, uint32_t y, uint32_t z, uint32_t w) {
  asm volatile("st.shared.v4.u32 [%0], {%1,%2,%3,%4};" :: "r"(a), "r"(x), "r"(y), "r"(z), "r"(w));
}
__device__ __forceinline__ uint32_t hmul2_bf16(uint32_t a, uint32_t b) {
  uint32_t r; asm("mul.rn.bf16x2 %0, %1, %2;" : "=r"(r) : "r"(a), "r"(b)); return r;
}
__device__ __forceinline__ float gelu_tanh(float v) {
  float u = v * fmaf(0.0356774081f, v * v, 0.7978845608f);
  float t; asm("tanh.approx.f32 %0, %1;" : "=f"(t) : "f"(u));
  float hv = 0.5f * v;
  return fmaf(hv, t, hv);
}

template<int TB>
__device__ __forceinline__ void wgmma_n192(float (&d)[96], uint64_t da, uint64_t db, int scale_d) {
  asm volatile("{\n.reg .pred p;\nsetp.ne.b32 p, %98, 0;\n"
   "wgmma.mma_async.sync.aligned.m64n192k16.f32.bf16.bf16 {%0,%1,%2,%3,%4,%5,%6,%7,%8,%9,%10,%11,%12,%13,%14,%15,%16,%17,%18,%19,%20,%21,%22,%23,%24,%25,%26,%27,%28,%29,%30,%31,%32,%33,%34,%35,%36,%37,%38,%39,%40,%41,%42,%43,%44,%45,%46,%47,%48,%49,%50,%51,%52,%53,%54,%55,%56,%57,%58,%59,%60,%61,%62,%63,%64,%65,%66,%67,%68,%69,%70,%71,%72,%73,%74,%75,%76,%77,%78,%79,%80,%81,%82,%83,%84,%85,%86,%87,%88,%89,%90,%91,%92,%93,%94,%95}, %96, %97, p, 1, 1, 0, %99;\n}"
   : "+f"(d[0]),"+f"(d[1]),"+f"(d[2]),"+f"(d[3]),"+f"(d[4]),"+f"(d[5]),"+f"(d[6]),"+f"(d[7]),"+f"(d[8]),"+f"(d[9]),"+f"(d[10]),"+f"(d[11]),"+f"(d[12]),"+f"(d[13]),"+f"(d[14]),"+f"(d[15]),"+f"(d[16]),"+f"(d[17]),"+f"(d[18]),"+f"(d[19]),"+f"(d[20]),"+f"(d[21]),"+f"(d[22]),"+f"(d[23]),"+f"(d[24]),"+f"(d[25]),"+f"(d[26]),"+f"(d[27]),"+f"(d[28]),"+f"(d[29]),"+f"(d[30]),"+f"(d[31]),"+f"(d[32]),"+f"(d[33]),"+f"(d[34]),"+f"(d[35]),"+f"(d[36]),"+f"(d[37]),"+f"(d[38]),"+f"(d[39]),"+f"(d[40]),"+f"(d[41]),"+f"(d[42]),"+f"(d[43]),"+f"(d[44]),"+f"(d[45]),"+f"(d[46]),"+f"(d[47]),"+f"(d[48]),"+f"(d[49]),"+f"(d[50]),"+f"(d[51]),"+f"(d[52]),"+f"(d[53]),"+f"(d[54]),"+f"(d[55]),"+f"(d[56]),"+f"(d[57]),"+f"(d[58]),"+f"(d[59]),"+f"(d[60]),"+f"(d[61]),"+f"(d[62]),"+f"(d[63]),"+f"(d[64]),"+f"(d[65]),"+f"(d[66]),"+f"(d[67]),"+f"(d[68]),"+f"(d[69]),"+f"(d[70]),"+f"(d[71]),"+f"(d[72]),"+f"(d[73]),"+f"(d[74]),"+f"(d[75]),"+f"(d[76]),"+f"(d[77]),"+f"(d[78]),"+f"(d[79]),"+f"(d[80]),"+f"(d[81]),"+f"(d[82]),"+f"(d[83]),"+f"(d[84]),"+f"(d[85]),"+f"(d[86]),"+f"(d[87]),"+f"(d[88]),"+f"(d[89]),"+f"(d[90]),"+f"(d[91]),"+f"(d[92]),"+f"(d[93]),"+f"(d[94]),"+f"(d[95])
   : "l"(da), "l"(db), "r"(scale_d), "n"(TB));
}
template<int TB>
__device__ __forceinline__ void wgmma_n160(float (&d)[80], uint64_t da, uint64_t db, int scale_d) {
  asm volatile("{\n.reg .pred p;\nsetp.ne.b32 p, %82, 0;\n"
   "wgmma.mma_async.sync.aligned.m64n160k16.f32.bf16.bf16 {%0,%1,%2,%3,%4,%5,%6,%7,%8,%9,%10,%11,%12,%13,%14,%15,%16,%17,%18,%19,%20,%21,%22,%23,%24,%25,%26,%27,%28,%29,%30,%31,%32,%33,%34,%35,%36,%37,%38,%39,%40,%41,%42,%43,%44,%45,%46,%47,%48,%49,%50,%51,%52,%53,%54,%55,%56,%57,%58,%59,%60,%61,%62,%63,%64,%65,%66,%67,%68,%69,%70,%71,%72,%73,%74,%75,%76,%77,%78,%79}, %80, %81, p, 1, 1, 0, %83;\n}"
   : "+f"(d[0]),"+f"(d[1]),"+f"(d[2]),"+f"(d[3]),"+f"(d[4]),"+f"(d[5]),"+f"(d[6]),"+f"(d[7]),"+f"(d[8]),"+f"(d[9]),"+f"(d[10]),"+f"(d[11]),"+f"(d[12]),"+f"(d[13]),"+f"(d[14]),"+f"(d[15]),"+f"(d[16]),"+f"(d[17]),"+f"(d[18]),"+f"(d[19]),"+f"(d[20]),"+f"(d[21]),"+f"(d[22]),"+f"(d[23]),"+f"(d[24]),"+f"(d[25]),"+f"(d[26]),"+f"(d[27]),"+f"(d[28]),"+f"(d[29]),"+f"(d[30]),"+f"(d[31]),"+f"(d[32]),"+f"(d[33]),"+f"(d[34]),"+f"(d[35]),"+f"(d[36]),"+f"(d[37]),"+f"(d[38]),"+f"(d[39]),"+f"(d[40]),"+f"(d[41]),"+f"(d[42]),"+f"(d[43]),"+f"(d[44]),"+f"(d[45]),"+f"(d[46]),"+f"(d[47]),"+f"(d[48]),"+f"(d[49]),"+f"(d[50]),"+f"(d[51]),"+f"(d[52]),"+f"(d[53]),"+f"(d[54]),"+f"(d[55]),"+f"(d[56]),"+f"(d[57]),"+f"(d[58]),"+f"(d[59]),"+f"(d[60]),"+f"(d[61]),"+f"(d[62]),"+f"(d[63]),"+f"(d[64]),"+f"(d[65]),"+f"(d[66]),"+f"(d[67]),"+f"(d[68]),"+f"(d[69]),"+f"(d[70]),"+f"(d[71]),"+f"(d[72]),"+f"(d[73]),"+f"(d[74]),"+f"(d[75]),"+f"(d[76]),"+f"(d[77]),"+f"(d[78]),"+f"(d[79])
   : "l"(da), "l"(db), "r"(scale_d), "n"(TB));
}
template<int TB>
__device__ __forceinline__ void wgmma_n96(float (&d)[48], uint64_t da, uint64_t db, int scale_d) {
  asm volatile("{\n.reg .pred p;\nsetp.ne.b32 p, %50, 0;\n"
   "wgmma.mma_async.sync.aligned.m64n96k16.f32.bf16.bf16 {%0,%1,%2,%3,%4,%5,%6,%7,%8,%9,%10,%11,%12,%13,%14,%15,%16,%17,%18,%19,%20,%21,%22,%23,%24,%25,%26,%27,%28,%29,%30,%31,%32,%33,%34,%35,%36,%37,%38,%39,%40,%41,%42,%43,%44,%45,%46,%47}, %48, %49, p, 1, 1, 0, %51;\n}"
   : "+f"(d[0]),"+f"(d[1]),"+f"(d[2]),"+f"(d[3]),"+f"(d[4]),"+f"(d[5]),"+f"(d[6]),"+f"(d[7]),"+f"(d[8]),"+f"(d[9]),"+f"(d[10]),"+f"(d[11]),"+f"(d[12]),"+f"(d[13]),"+f"(d[14]),"+f"(d[15]),"+f"(d[16]),"+f"(d[17]),"+f"(d[18]),"+f"(d[19]),"+f"(d[20]),"+f"(d[21]),"+f"(d[22]),"+f"(d[23]),"+f"(d[24]),"+f"(d[25]),"+f"(d[26]),"+f"(d[27]),"+f"(d[28]),"+f"(d[29]),"+f"(d[30]),"+f"(d[31]),"+f"(d[32]),"+f"(d[33]),"+f"(d[34]),"+f"(d[35]),"+f"(d[36]),"+f"(d[37]),"+f"(d[38]),"+f"(d[39]),"+f"(d[40]),"+f"(d[41]),"+f"(d[42]),"+f"(d[43]),"+f"(d[44]),"+f"(d[45]),"+f"(d[46]),"+f"(d[47])
   : "l"(da), "l"(db), "r"(scale_d), "n"(TB));
}

template<int N, int TB>
__device__ __forceinline__ void wgmma_n(float (&d)[N / 2], uint64_t da, uint64_t db) {
  if constexpr (N == 192) wgmma_n192<TB>(d, da, db, 1);
  else if constexpr (N == 160) wgmma_n160<TB>(d, da, db, 1);
  else wgmma_n96<TB>(d, da, db, 1);
}

template<int R>
__device__ __forceinline__ void pin(float (&acc)[2][R]) {
  #pragma unroll
  for (int mi = 0; mi < 2; mi++)
    #pragma unroll
    for (int i = 0; i < R; i++) asm volatile("" : "+f"(acc[mi][i]) :: "memory");
}
template<int R>
__device__ __forceinline__ void zero(float (&acc)[2][R]) {
  #pragma unroll
  for (int i = 0; i < R; i++) { acc[0][i] = 0.f; acc[1][i] = 0.f; }
  pin(acc);
}

template<int N, int TB, bool CONT, int ORD_BAR>
__device__ __forceinline__ void mainloop(float (&acc)[2][N / 2], uint32_t sbase, int grp, int g0, int nk) {
  const uint32_t full0 = sbase + BAR_OFF, empty0 = full0 + 8 * MAXST, ring = sbase + RING_OFF;
  const int nst = grp == 0 ? NST_A : NST_B, total = grp == 0 ? KB_A : KB_B;
  const uint32_t sstep = (grp == 0 ? STAGE_A : STAGE_B) >> 4;
  const int t = threadIdx.x & 127;
  const uint32_t da0 = ((ring & 0x3FFFF) >> 4) | 0x10000u;
  const uint32_t db0 = (((ring + A_BYTES) & 0x3FFFF) >> 4) | ((TB == 2 ? 256u : TB ? 512u : 1u) << 16);
  constexpr uint32_t HI_A = 0x40000040u, HI_B = TB == 2 ? 0x80000020u : 0x40000040u;
  int s = g0 % nst, ph = (g0 / nst) & 1, ps = s == 0 ? nst - 1 : s - 1;
  #pragma unroll 1
  for (int g = g0; g < g0 + nk; g++) {
    const uint32_t so = s * sstep;
    mbar_wait(full0 + 8 * s, ph);
    wgmma_fence();
    #pragma unroll
    for (int k = 0; k < 4; k++) {
      const uint64_t db = desc64(db0 + so + (TB == 2 ? k * 64 : TB ? k * 128 : k * 2), HI_B);
      wgmma_n<N, TB != 0>(acc[0], desc64(da0 + so + k * 2, HI_A), db);
      wgmma_n<N, TB != 0>(acc[1], desc64(da0 + so + 512 + k * 2, HI_A), db);
    }
    wgmma_commit();
    if (ORD_BAR != 0 && g == g0 + nk - 1) bar_arrive<ORD_BAR>(256);
    wgmma_wait<1>();
    if (t < 2 && (CONT || g > g0) && g - 1 + nst < total) mbar_arrive_cluster(empty0 + 8 * ps, t);
    ps = s;
    if (++s == nst) { s = 0; ph ^= 1; }
  }
}
template<int R>
__device__ __forceinline__ void drain(float (&acc)[2][R], uint32_t sbase, int grp, int glast) {
  wgmma_wait<0>();
  pin(acc);
  const int t = threadIdx.x & 127;
  const int nst = grp == 0 ? NST_A : NST_B, total = grp == 0 ? KB_A : KB_B;
  if (t < 2 && glast + nst < total) mbar_arrive_cluster(sbase + BAR_OFF + 8 * MAXST + 8 * (glast % nst), t);
}

__device__ __forceinline__ void set_flag(int slot, int byte, unsigned epoch) {
  asm volatile("st.relaxed.gpu.global.u8 [%0], %1;" :: "l"(g_flags + slot * 256 + byte), "r"(epoch & 255u) : "memory");
}
__device__ __forceinline__ unsigned get_flag(int slot, int byte) {
  unsigned v; asm volatile("ld.relaxed.gpu.global.u8 %0, [%1];" : "=r"(v) : "l"(g_flags + slot * 256 + byte) : "memory"); return v;
}
__device__ __forceinline__ void publish(int slot, int byte, unsigned epoch) {
  asm volatile("fence.acq_rel.gpu;" ::: "memory");
  set_flag(slot, byte, epoch);
}

__device__ __forceinline__ float sum8(uint4 v) {
  return ((bf_lo(v.x) + bf_hi(v.x)) + (bf_lo(v.y) + bf_hi(v.y))) + ((bf_lo(v.z) + bf_hi(v.z)) + (bf_lo(v.w) + bf_hi(v.w)));
}
__device__ __forceinline__ uint4 ldg128(const void* p) {
  uint4 v; asm volatile("ld.global.nc.v4.u32 {%0,%1,%2,%3}, [%4];" : "=r"(v.x), "=r"(v.y), "=r"(v.z), "=r"(v.w) : "l"(p)); return v;
}
__device__ __forceinline__ void ln_load(const bf16* __restrict__ x, int cta, uint4 (&rv)[5]) {
  const int t = threadIdx.x - 128, row = cta * 16 + (t >> 4), c = t & 15;
  #pragma unroll
  for (int j = 0; j < 5; j++) rv[j] = ldg128(reinterpret_cast<const uint4*>(x + (size_t)row * DM) + c + 16 * j);
}
__device__ __forceinline__ void ln_rows(const uint4 (&rv)[5], bf16* __restrict__ out, int cta, unsigned epoch) {
  const int t = threadIdx.x - 128, row = cta * 16 + (t >> 4), c = t & 15;
  const float sh = __shfl_sync(0xffffffffu, bf_lo(rv[0].x), t & 16);
  float d[40], s = 0.f, q = 0.f;
  #pragma unroll
  for (int j = 0; j < 5; j++) {
    const uint32_t u[4] = {rv[j].x, rv[j].y, rv[j].z, rv[j].w};
    #pragma unroll
    for (int e = 0; e < 4; e++) {
      const float d0 = bf_lo(u[e]) - sh, d1 = bf_hi(u[e]) - sh;
      d[j * 8 + e * 2] = d0; d[j * 8 + e * 2 + 1] = d1;
      s += d0 + d1; q = fmaf(d0, d0, q); q = fmaf(d1, d1, q);
    }
  }
  #pragma unroll
  for (int o = 1; o < 16; o <<= 1) { s += __shfl_xor_sync(0xffffffffu, s, o); q += __shfl_xor_sync(0xffffffffu, q, o); }
  const float md = s * (1.f / DM);
  const float r = rsqrtf(fmaxf(fmaf(q, 1.f / DM, -md * md), 0.f) + LN_EPS), o = -md * r;
  if (c == 0) st_vol2(&g_xstat[row], __float_as_uint(r), (__float_as_uint(-(md + sh) * r) & ~255u) | (epoch & 255u));
  #pragma unroll
  for (int j = 0; j < 5; j++) {
    const float* a = &d[j * 8];
    stg128(reinterpret_cast<uint4*>(g_xn + (size_t)row * DM) + c + 16 * j, make_uint4(
           pack_bf16(fmaf(a[0], r, o), fmaf(a[1], r, o)), pack_bf16(fmaf(a[2], r, o), fmaf(a[3], r, o)),
           pack_bf16(fmaf(a[4], r, o), fmaf(a[5], r, o)), pack_bf16(fmaf(a[6], r, o), fmaf(a[7], r, o))));
  }
  #pragma unroll
  for (int j = 0; j < 5; j++) stg128(reinterpret_cast<uint4*>(out + (size_t)row * DM) + c + 16 * j, rv[j]);
  bar_arrive<BAR_LN>(288);
}
__device__ __forceinline__ void colsum_part(const bf16* __restrict__ win, int cta, unsigned epoch) {
  const int t = threadIdx.x & 127, w = t >> 5, l = t & 31;
  const int cj = min(cta, 119), cg = cj % 24, rg = cj / 24;
  uint4 cv[4];
  #pragma unroll
  for (int j = 0; j < 4; j++) cv[j] = ldg128(reinterpret_cast<const uint4*>(win + (size_t)(rg * 128 + w * 32 + j * 8 + (l >> 2)) * FF + FH + cg * 32) + (l & 3));
  float v[8];
  v[0] = (bf_lo(cv[0].x) + bf_lo(cv[1].x)) + (bf_lo(cv[2].x) + bf_lo(cv[3].x)); v[1] = (bf_hi(cv[0].x) + bf_hi(cv[1].x)) + (bf_hi(cv[2].x) + bf_hi(cv[3].x));
  v[2] = (bf_lo(cv[0].y) + bf_lo(cv[1].y)) + (bf_lo(cv[2].y) + bf_lo(cv[3].y)); v[3] = (bf_hi(cv[0].y) + bf_hi(cv[1].y)) + (bf_hi(cv[2].y) + bf_hi(cv[3].y));
  v[4] = (bf_lo(cv[0].z) + bf_lo(cv[1].z)) + (bf_lo(cv[2].z) + bf_lo(cv[3].z)); v[5] = (bf_hi(cv[0].z) + bf_hi(cv[1].z)) + (bf_hi(cv[2].z) + bf_hi(cv[3].z));
  v[6] = (bf_lo(cv[0].w) + bf_lo(cv[1].w)) + (bf_lo(cv[2].w) + bf_lo(cv[3].w)); v[7] = (bf_hi(cv[0].w) + bf_hi(cv[1].w)) + (bf_hi(cv[2].w) + bf_hi(cv[3].w));
  #pragma unroll
  for (int st = 0; st < 3; st++) {
    const int n = 4 >> st;
    const bool up = (l & (4 * n)) != 0;
    #pragma unroll
    for (int e = 0; e < 4; e++)
      if (e < n) { const float keep = up ? v[e + n] : v[e], send = up ? v[e] : v[e + n]; v[e] = keep + __shfl_xor_sync(0xffffffffu, send, 4 * n); }
  }
  float* red = reinterpret_cast<float*>(smem + RED_OFF);
  red[w * 32 + (l & 3) * 8 + (l >> 2)] = v[0];
  bar_sync<BAR_WG2>(128);
  if (t < 32) st_vol2(&g_csum[rg * FH + cg * 32 + t], __float_as_uint((red[t] + red[32 + t]) + (red[64 + t] + red[96 + t])), epoch);
}

__device__ __forceinline__ void a_entry(int g, int grp, int rb, int& mi, int& kb) {
  if (g < 10) { mi = M_X; kb = g; }
  else if (g < 20) { mi = M_XN; kb = g - 10; }
  else if (grp == 0) {
    if (g < 52) { mi = M_WSP; kb = (g - 20); }
    else if (g < 52 + NX) { mi = M_WSIM; kb = g - 52 + 32 - NX; }
    else { mi = M_H; kb = g - 52 - NX; }
  } else {
    if (g < 30) { mi = M_XN; kb = g - 20; }
    else if (g < 62) { mi = M_WSRE; kb = (g - 30); }
    else { mi = M_WSIM; kb = g - 62; }
  }
}

__global__ void __cluster_dims__(2, 1, 1) __launch_bounds__(384, 1)
fused_kernel(const __grid_constant__ Maps maps, const bf16* __restrict__ x, const bf16* __restrict__ win, const bf16* __restrict__ bsp,
             bf16* __restrict__ out) {
  const uint32_t sbase = smem_u32(smem);
  const uint32_t full0 = sbase + BAR_OFF, empty0 = full0 + 8 * MAXST, dep0 = empty0 + 8 * MAXST, ring = sbase + RING_OFF;
  const int tid = threadIdx.x, wg = __shfl_sync(0xffffffffu, tid >> 7, 0);
  const int rank = blockIdx.x & 1;
  const int grp = (blockIdx.x >> 1) & 1, half = (blockIdx.x >> 2) & 1, rb = blockIdx.x >> 3;
  const int ct = half * 2 + rank, c8 = grp * 4 + ct;
  const int cta = rb * 8 + half * 4 + grp * 2 + rank;
  const int total = grp == 0 ? KB_A : KB_B;
  const uint32_t stage_bytes = grp == 0 ? STAGE_A : STAGE_B;
  const int nst = grp == 0 ? NST_A : NST_B;
  const uint32_t buf = ring + nst * stage_bytes;

  uint4 rv[5];
  if (wg != 0) ln_load(x, cta, rv);
  if (wg == 2) {
    const int t = tid & 127;
    if (t < 60) asm volatile("prefetch.global.L2 [%0];" :: "l"(win + (size_t)(cta * 5 + t / 12) * FF + FH + (t % 12) * 64));
  }
  const unsigned epoch = (ld_relaxed(&g_done) >> 7) + 1u;
  if (tid == 0) {
    TS(0, 0);
    for (int s = 0; s < MAXST; s++) { mbar_init(full0 + 8 * s, 2); mbar_init(empty0 + 8 * s, 2); }
    for (int s = 0; s < 4; s++) mbar_init(dep0 + 8 * s, 1);
    *reinterpret_cast<volatile int*>(smem + READY_OFF) = 0;
    asm volatile("fence.mbarrier_init.release.cluster;" ::: "memory");
  }
  __syncthreads();
  asm volatile("barrier.cluster.arrive.relaxed.aligned;" ::: "memory");

  if (wg == 0) {
    asm volatile("setmaxnreg.dec.sync.aligned.u32 40;");
    const int warp = tid >> 5, lane = tid & 31;
    if (warp == 0) {
      const int row = rb * 128;
      if (lane == 0) {
        for (int g = 0; g < nst; g++) {
          mbar_expect_tx(full0 + 8 * g, A_BYTES);
          tma_load_2d(ring + g * stage_bytes, &maps.m[M_X], full0 + 8 * g, g * 64, row);
          tma_load_2d(ring + g * stage_bytes + 8192, &maps.m[M_X], full0 + 8 * g, g * 64, row + 64);
        }
      }
      __syncwarp();
      cluster_wait();
      if (lane == 0) {
        int s = 0, ph = 0;
        #pragma unroll 1
        for (int g = nst; g < total; g++) {
          int mi, kb;
          a_entry(g, grp, rb, mi, kb);
          if (g == 10 || (mi == M_H && kb == 0)) { TS(0, g > 10 ? 3 : 1); mbar_wait(dep0 + (g > 10 ? 24 : 0), 0); fence_async_global(); TS(0, g > 10 ? 4 : 2); }
          mbar_wait(empty0 + 8 * s, ph);
          mbar_expect_tx(full0 + 8 * s, A_BYTES);
          tma_load_2d_mc(ring + s * stage_bytes + rank * 8192, &maps.m[mi], full0 + 8 * s, kb * 64, row + rank * 64, 3);
          if (++s == nst) { s = 0; ph ^= 1; }
          if (g + PF_D < total) {
            a_entry(g + PF_D, grp, rb, mi, kb);
            if (mi >= M_WSRE && mi <= M_WSP && PF_COND)
              asm volatile("cp.async.bulk.prefetch.tensor.2d.L2.global.tile [%0, {%1, %2}];" :: "l"((uint64_t)&maps.m[mi]), "r"(kb * 64), "r"(row + rank * 64) : "memory");
          }
        }
        TS(0, 5);
      }
    } else if (warp == 1) {
      if (lane == 0) {
        int s = 0, ph = 1;
        int have = 0;
        #pragma unroll 1
        for (int g = 0; g < total; g++) {
          int kind = 1, mi, kb, c, dep = 0, need = 0;
          uint32_t bytes = 20480;
          if (g < 10) { kind = 0; mi = M_WIN32; kb = g; c = 24 + 3 * c8; bytes = 12288; }
          else if (grp == 0) {
            if (g < 20) { kind = 0; mi = M_WIN3; kb = g - 10; c = 3 * ct; bytes = 24576; }
            else if (g < 52) { kind = 0; mi = M_Z23; kb = (g - 20); c = 3 * ct; bytes = 24576; need = ((g - 20) >> 1) + 1; }
            else if (g < 52 + NX) { mi = M_AB; kb = g - 52 + 32 - NX; c = DM + ct * 160; dep = g == 52 ? 2 : 0; }
            else { kind = 0; mi = M_WOUT; kb = g - 52 - NX; c = ct * 5; }
          } else {
            if (g < 30) { mi = g < 20 ? M_WDRE : M_WDIM; kb = g < 20 ? g - 10 : g - 20; c = ct * 160; }
            else if (g < 62) { mi = M_AB; kb = (g - 30); c = ct * 160; need = ((g - 30) >> 1) + 1; }
            else { mi = M_AB; kb = g - 62; c = ct * 160 + DM; dep = g == 62 ? 2 : 0; }
          }
          if (need > have) {
            if (need == 1) TS(1, 0);
            unsigned it = 0;
            while ((have = *reinterpret_cast<volatile int*>(smem + READY_OFF)) < need && ++it < 50 * POLL_LIMIT) {}
            fence_async_global();
            if (need == 1) { TS(1, 1); TC(1); }
          }
          if (dep) { TS(1, dep * 2 - 2); mbar_wait(dep0 + 8 * dep, 0); fence_async_global(); TS(1, dep * 2 - 1); TC(dep); }
          const uint32_t dst = ring + s * stage_bytes + A_BYTES, fb = full0 + 8 * s;
          mbar_wait(empty0 + 8 * s, ph);
          if (++s == nst) { s = 0; ph ^= 1; }
          mbar_expect_tx(fb, bytes);
          if (kind == 0) tma_load_3d(dst, &maps.m[mi], fb, 0, kb * 64, c);
          else tma_load_2d(dst, &maps.m[mi], fb, kb * 64, c);
        }
      }
      __syncwarp();
      cluster_wait();
    } else if (warp == 2) {
      cluster_wait();
      {
        unsigned it = 0;
        uint2 v[4];
        while (true) {
          bool ok = true;
          #pragma unroll
          for (int i = 0; i < 4; i++) { v[i] = ld_vol2(&g_xstat[rb * 128 + i * 32 + lane]); ok = ok && ((v[i].y ^ epoch) & 255u) == 0; }
          if (ok || ++it > POLL_LIMIT) break;
          __nanosleep(POLL_NS);
        }
        #pragma unroll
        for (int i = 0; i < 4; i++) reinterpret_cast<uint2*>(smem + ROWSTAT_OFF)[i * 32 + lane] = make_uint2(v[i].x, v[i].y & ~255u);
        __syncwarp();
        TS(0, 6);
        bar_arrive<BAR_STATS>(192);
      }
      #pragma unroll 1
      for (int d = 0; d < 4 - grp; d++) {
        const int slot = d == 0 ? F_XN + rb : d == 3 ? F_H + rb : d == 2 ? F_B + ct : grp == 0 ? F_Z + ct : F_A + ct;
        const int byte = d == 0 ? lane & 7 : d == 3 ? lane & 3 : (d == 1 && grp == 0) ? lane : lane >> 1;
        unsigned it = 0, m;
        while ((m = __ballot_sync(0xffffffffu, get_flag(slot, byte) != (epoch & 255u))) != 0 && ++it < POLL_LIMIT) {
          if (d == 1 && lane == 0) *reinterpret_cast<volatile int*>(smem + READY_OFF) = (__ffs(m) - 1) >> 1;
          __nanosleep(WATCH_NS);
        }
        if (d == 1 && lane == 0) *reinterpret_cast<volatile int*>(smem + READY_OFF) = 16;
        TS(0, 8 + d * 2);
        fence_async_global();
        __syncwarp();
        if (lane == 0 && d != 1) mbar_arrive(dep0 + 8 * d);
      }
    } else {
      cluster_wait();
      bar_sync<BAR_LN>(288);
      if (lane == 0) { TS(1, 5); publish(F_XN + rb, cta & 7, epoch); TS(1, 6); }
      __syncwarp();
      {
        unsigned it = 0;
        while (true) {
          bool ok = true;
          uint2 u[15];
          #pragma unroll
          for (int i = 0; i < 15; i++) u[i] = ld_vol2(&g_csum[(i % 5) * FH + c8 * 96 + (i / 5) * 32 + lane]);
          #pragma unroll
          for (int i = 0; i < 15; i++) ok = ok && u[i].y == epoch;
          #pragma unroll
          for (int i = 0; i < 3; i++)
            reinterpret_cast<float*>(smem + COLSUM_OFF)[i * 32 + lane] = ((__uint_as_float(u[i * 5].x) + __uint_as_float(u[i * 5 + 1].x)) +
                (__uint_as_float(u[i * 5 + 2].x) + __uint_as_float(u[i * 5 + 3].x))) + __uint_as_float(u[i * 5 + 4].x);
          if (ok || ++it > POLL_LIMIT) break;
          __nanosleep(POLL_NS);
        }
      }
      __syncwarp();
      TS(1, 4);
      bar_arrive<BAR_STATS>(192);
      bar_sync<BAR_PUB1>(160);
      if (lane == 0) {
        TS(1, 7);
        tma_store_3d(&maps.m[M_Z232], buf, 0, rb * 128, 3 * c8);
        bulk_commit();
        bulk_wait_all();
        set_flag(F_Z + (c8 >> 1), rb * 2 + (c8 & 1), epoch);
        TS(1, 8);
      }
      __syncwarp();
      bar_arrive<BAR_BUF>(160);
      if (grp == 1) {
        bar_sync<BAR_PUB2>(160);
        if (lane == 0) set_flag(F_A + ct, rb, epoch);
        TS(1, 9);
        __syncwarp();
      }
      bar_sync<BAR_PUB1>(160);
      if (lane == 0) set_flag(grp == 0 ? F_H + rb : F_B + ct, grp == 0 ? ct : rb, epoch);
      TS(1, 10);
      __syncwarp();
      bar_arrive<BAR_BUF>(160);
    }
  } else {
    asm volatile("setmaxnreg.inc.sync.aligned.u32 232;");
    const int t = tid & 127, w = t >> 5, l = t & 31;
    ln_rows(rv, out, cta, epoch);
    if (wg == 2) colsum_part(win, cta, epoch);
    TS(wg + 1, 0);
    cluster_wait();
    const int rl = w * 16 + ((l >> 3) & 1) * 8 + (l & 7);
    const int gr = w * 16 + (l & 15);
    const uint32_t st_base = buf + rl * 128;
    const uint32_t st_x = ((l >> 4) ^ (l & 7)) << 4;
    if (wg == 1) {
      float acc[2][48];
      zero(acc);
      mainloop<96, 2, false, BAR_ORD1>(acc, sbase, grp, 0, 10);
      drain(acc, sbase, grp, 9);
      TS(2, 2);
      bar_sync<BAR_STATS>(192);
      const float2* rs = reinterpret_cast<const float2*>(smem + ROWSTAT_OFF) + w * 16 + (l >> 2);
      const float2* cs = reinterpret_cast<const float2*>(smem + COLSUM_OFF) + (l & 3);
      float sum[4], sq[4];
      #pragma unroll
      for (int r = 0; r < 4; r++) {
        const float2 st = rs[(r >> 1) * 64 + (r & 1) * 8];
        float s0 = 0.f, q0 = 0.f;
        #pragma unroll
        for (int j = 0; j < 12; j++) {
          const float2 c = cs[j * 4];
          float* a = &acc[r >> 1][4 * j + (r & 1) * 2];
          a[0] = gelu_tanh(fmaf(a[0], st.x, st.y * c.x));
          a[1] = gelu_tanh(fmaf(a[1], st.x, st.y * c.y));
          s0 += a[0] + a[1]; q0 = fmaf(a[0], a[0], q0); q0 = fmaf(a[1], a[1], q0);
        }
        s0 += __shfl_xor_sync(0xffffffffu, s0, 1); q0 += __shfl_xor_sync(0xffffffffu, q0, 1);
        s0 += __shfl_xor_sync(0xffffffffu, s0, 2); q0 += __shfl_xor_sync(0xffffffffu, q0, 2);
        sum[r] = s0; sq[r] = q0;
      }
      TS(2, 4);
      float rstd, off;
      {
        const int qd = l & 3;
        const float sm = qd == 0 ? sum[0] : qd == 1 ? sum[1] : qd == 2 ? sum[2] : sum[3];
        const float sv = qd == 0 ? sq[0] : qd == 1 ? sq[1] : qd == 2 ? sq[2] : sq[3];
        const int row = (qd >> 1) * 64 + w * 16 + (qd & 1) * 8 + (l >> 2);
        const float mu = sm * (1.f / 96), m2 = fmaxf(sv - sm * mu, 0.f);
        st_vol2(&g_zstat[(rb * 8 + c8) * 128 + row], __float_as_uint(mu), (__float_as_uint(m2) & ~255u) | (epoch & 255u));
        uint2 v[7];
        unsigned n = 0;
        while (true) {
          bool ok = true;
          #pragma unroll
          for (int j = 0; j < 7; j++) v[j] = ld_vol2(&g_zstat[(rb * 8 + ((c8 + 1 + j) & 7)) * 128 + row]);
          #pragma unroll
          for (int j = 0; j < 7; j++) ok = ok && ((v[j].y ^ epoch) & 255u) == 0;
          if (ok || ++n > POLL_LIMIT) break;
          __nanosleep(POLL_NS);
        }
        float mean = mu, var = m2;
        #pragma unroll
        for (int j = 0; j < 7; j++) { mean += __uint_as_float(v[j].x); var += __uint_as_float(v[j].y & ~255u); }
        mean *= 0.125f;
        float d = (mu - mean) * (mu - mean);
        #pragma unroll
        for (int j = 0; j < 7; j++) d = fmaf(__uint_as_float(v[j].x) - mean, __uint_as_float(v[j].x) - mean, d);
        rstd = rsqrtf(fmaf(96.f, d, var) * (1.f / FH) + LN_EPS); off = -mean * rstd;
        __syncwarp();
      }
      TS(2, 5);
      #pragma unroll
      for (int mi = 0; mi < 2; mi++) {
        const float r0 = __shfl_sync(0xffffffffu, rstd, (l & 28) + mi * 2), o0 = __shfl_sync(0xffffffffu, off, (l & 28) + mi * 2);
        const float r1 = __shfl_sync(0xffffffffu, rstd, (l & 28) + mi * 2 + 1), o1 = __shfl_sync(0xffffffffu, off, (l & 28) + mi * 2 + 1);
        #pragma unroll
        for (int jj = 0; jj < 6; jj++) {
          const float* a = &acc[mi][8 * jj];
          stsm4(buf + (jj >> 1) * 8192 + mi * 4096 + rl * 64 + ((((jj & 1) * 2 + (l >> 4)) ^ ((l >> 1) & 3)) << 4),
                pack_bf16(fmaf(a[0], r0, o0), fmaf(a[1], r0, o0)), pack_bf16(fmaf(a[2], r1, o1), fmaf(a[3], r1, o1)),
                pack_bf16(fmaf(a[4], r0, o0), fmaf(a[5], r0, o0)), pack_bf16(fmaf(a[6], r1, o1), fmaf(a[7], r1, o1)));
        }
      }
      fence_async_smem();
      bar_arrive<BAR_PUB1>(160);
      TS(2, 6);
      if (grp == 0) {
        float acc[2][96];
        {
          const bf16* bp = bsp + rb * 128 + w * 16 + (l >> 2);
          const float bb[4] = {__bfloat162float(bp[0]), __bfloat162float(bp[8]), __bfloat162float(bp[64]), __bfloat162float(bp[72])};
          #pragma unroll
          for (int i = 0; i < 96; i++) { acc[0][i] = bb[(i >> 1) & 1]; acc[1][i] = bb[2 + ((i >> 1) & 1)]; }
          pin(acc);
        }
        bar_sync<BAR_ORD2>(256);
        mainloop<192, 1, false, BAR_ORD1>(acc, sbase, 0, 20, 32);
        bar_sync<BAR_Z1>(256);
        drain(acc, sbase, 0, 51);
        TS(2, 7);
        {
          uint32_t z[2][4][4];
          #pragma unroll
          for (int i = 0; i < 4; i++) ldsm4(st_base + (st_x ^ (i << 5)), z[0][i][0], z[0][i][1], z[0][i][2], z[0][i][3]);
          #pragma unroll
          for (int bx = 0; bx < 6; bx++) {
            if (bx < 5) {
              #pragma unroll
              for (int i = 0; i < 4; i++)
                ldsm4(st_base + (bx + 1) * 8192 + (st_x ^ (i << 5)), z[(bx + 1) & 1][i][0], z[(bx + 1) & 1][i][1], z[(bx + 1) & 1][i][2], z[(bx + 1) & 1][i][3]);
            }
            #pragma unroll
            for (int i = 0; i < 4; i++) {
              const float* a = &acc[bx / 3][8 * ((bx % 3) * 4 + i)];
              const uint32_t* zz = z[bx & 1][i];
              stsm4(st_base + bx * 8192 + (st_x ^ (i << 5)),
                    hmul2_bf16(zz[0], pack_bf16(a[0], a[1])), hmul2_bf16(zz[1], pack_bf16(a[2], a[3])),
                    hmul2_bf16(zz[2], pack_bf16(a[4], a[5])), hmul2_bf16(zz[3], pack_bf16(a[6], a[7])));
            }
            if (bx % 3 == 2) {
              fence_async_smem();
              __syncwarp();
              if (l < 3) {
                tma_store_2d(&maps.m[M_HS], buf + (bx - 2 + l) * 8192 + w * 2048, ct * 192 + l * 64, rb * 128 + (bx / 3) * 64 + w * 16);
                bulk_commit();
              }
            }
          }
        }
        TS(2, 8);
        if (l < 3) bulk_wait_all();
        __syncwarp();
        bar_arrive<BAR_PUB1>(160);
        TS(2, 9);
        return;
      }
    } else {
      if (grp == 0) {
        float acc[2][96];
        zero(acc);
        bar_sync<BAR_ORD1>(256);
        mainloop<192, 1, false, BAR_ORD2>(acc, sbase, 0, 10, 10);
        drain(acc, sbase, 0, 19);
        TS(3, 2);
        bar_sync<BAR_BUF>(160);
        #pragma unroll
        for (int mi = 0; mi < 2; mi++)
          #pragma unroll
          for (int jj = 0; jj < 12; jj++) {
            const float* a = &acc[mi][8 * jj];
            stsm4(st_base + mi * 24576 + (jj >> 2) * 8192 + (st_x ^ ((jj & 3) << 5)),
                  pack_bf16(a[0], a[1]), pack_bf16(a[2], a[3]), pack_bf16(a[4], a[5]), pack_bf16(a[6], a[7]));
          }
        __syncwarp();
        TS(3, 3);
        const uint32_t rbase = buf + (l >> 4) * 24576 + gr * 128;
        #pragma unroll 1
        for (int c2 = 0; c2 < 12; c2++) {
          const uint32_t ab = rbase + (c2 >> 2) * 8192;
          uint4 v[2];
          #pragma unroll
          for (int i = 0; i < 2; i++) v[i] = lds128(ab + (((((c2 & 3) * 2 + i) ^ l) & 7) << 4));
          #pragma unroll
          for (int i = 0; i < 2; i++)
            sts128(ab + (((((c2 & 3) * 2 + i) ^ l) & 7) << 4),
                   pack_bf16(gelu_tanh(bf_lo(v[i].x)), gelu_tanh(bf_hi(v[i].x))), pack_bf16(gelu_tanh(bf_lo(v[i].y)), gelu_tanh(bf_hi(v[i].y))),
                   pack_bf16(gelu_tanh(bf_lo(v[i].z)), gelu_tanh(bf_hi(v[i].z))), pack_bf16(gelu_tanh(bf_lo(v[i].w)), gelu_tanh(bf_hi(v[i].w))));
        }
        TS(3, 4);
        bar_arrive<BAR_Z1>(256);
      }
    }
    float acc[2][80];
    if (grp == 1) {
      zero(acc);
      if (wg == 2) {
        bar_sync<BAR_ORD1>(256);
        mainloop<160, 0, false, BAR_ORD2>(acc, sbase, 1, 10, 10);
      } else {
        bar_sync<BAR_ORD2>(256);
        mainloop<160, 0, false, BAR_ORD1>(acc, sbase, 1, 20, 10);
      }
      drain(acc, sbase, 1, wg == 2 ? 19 : 29);
      TS(wg + 1, wg == 1 ? 7 : 2);
      if (wg == 1) bar_sync<BAR_Z1>(256); else bar_sync<BAR_BUF>(160);
      const uint32_t sg = wg == 1 ? 0x80008000u : 0u;
      const uint32_t tb = buf + ((l >> 4) * 8 + (l & 7)) * 128 + (((w * 2 + ((l >> 3) & 1)) ^ (l & 7)) << 4);
      #pragma unroll
      for (int mi = 0; mi < 2; mi++)
        #pragma unroll
        for (int jj = 0; jj < 10; jj++) {
          const float* a = &acc[mi][8 * jj];
          stsm4_t(tb + mi * 20480 + jj * 2048, pack_bf16(a[0], a[1]) ^ sg, pack_bf16(a[2], a[3]) ^ sg, pack_bf16(a[4], a[5]) ^ sg, pack_bf16(a[6], a[7]) ^ sg);
        }
      fence_async_smem();
      if (wg == 1) bar_sync<BAR_WG1>(128); else bar_sync<BAR_WG2>(128);
      TS(wg + 1, wg == 1 ? 8 : 6);
      if (l == 0) {
        #pragma unroll 1
        for (int i = 0; i < 2; i++) {
          tma_store_2d(&maps.m[M_ABS], buf + i * 20480 + w * 5120, rb * 128 + i * 64, (2 - wg) * DM + ct * 160 + w * 40);
          bulk_commit();
        }
        bulk_wait_all();
      }
      __syncwarp();
      TS(wg + 1, wg == 1 ? 9 : 10);
      if (wg == 1) { bar_arrive<BAR_PUB1>(160); return; }
      bar_arrive<BAR_PUB2>(160);
      bar_arrive<BAR_Z1>(256);
    }
    zero(acc);
    bar_sync<BAR_ORD1>(256);
    mainloop<160, 0, false, 0>(acc, sbase, grp, grp == 0 ? 52 : 30, grp == 0 ? NX : 64 - NX);
    if (grp == 0) mainloop<160, 2, true, 0>(acc, sbase, 0, 52 + NX, 12);
    const uint32_t slab = buf + w * (16 * 320);
    const uint32_t addr = slab + (((l >> 3) & 1) * 8 + (l & 7)) * 320 + (l >> 4) * 16;
    bar_sync<BAR_BUF>(160);
    drain(acc, sbase, grp, total - 1);
    TS(3, 12);
    #pragma unroll
    for (int mi = 0; mi < 2; mi++) {
      #pragma unroll
      for (int jj = 0; jj < 10; jj++) {
        const float* a = &acc[mi][8 * jj];
        stsm4(addr + mi * 20480 + jj * 32, pack_bf16(a[0], a[1]), pack_bf16(a[2], a[3]), pack_bf16(a[4], a[5]), pack_bf16(a[6], a[7]));
      }
      fence_async_smem();
      __syncwarp();
      if (l == 0) {
        tma_reduce_2d(&maps.m[M_OUT], slab + mi * 20480, ct * 160, rb * 128 + mi * 64 + w * 16);
        bulk_commit();
      }
    }
    TS(3, 13);
    if (l == 0) {
      bulk_wait_read();
      if (w == 0) atomicAdd(&g_done, 1u);
    }
    TS(3, 15);
  }
}

typedef CUresult (*EncodeFn)(CUtensorMap*, CUtensorMapDataType, cuuint32_t, void*, const cuuint64_t*, const cuuint64_t*,
                             const cuuint32_t*, const cuuint32_t*, CUtensorMapInterleave, CUtensorMapSwizzle,
                             CUtensorMapL2promotion, CUtensorMapFloatOOBfill);

void make2d(EncodeFn enc, CUtensorMap* m, const void* p, uint64_t cols, uint64_t rows, uint32_t bc, uint32_t br, bool swz = true) {
  cuuint64_t gd[2] = {cols, rows}, gs[1] = {cols * 2};
  cuuint32_t bd[2] = {bc, br}, es[2] = {1, 1};
  enc(m, CU_TENSOR_MAP_DATA_TYPE_BFLOAT16, 2, const_cast<void*>(p), gd, gs, bd, es, CU_TENSOR_MAP_INTERLEAVE_NONE,
      swz ? CU_TENSOR_MAP_SWIZZLE_128B : CU_TENSOR_MAP_SWIZZLE_NONE, PROMO, CU_TENSOR_MAP_FLOAT_OOB_FILL_NONE);
}
void make3d(EncodeFn enc, CUtensorMap* m, const void* p, uint64_t cols, uint64_t rows, uint32_t cw, uint32_t nc, uint32_t br = 64) {
  cuuint64_t gd[3] = {cw, rows, cols / cw}, gs[2] = {cols * 2, cw * 2};
  cuuint32_t bd[3] = {cw, br, nc}, es[3] = {1, 1, 1};
  enc(m, CU_TENSOR_MAP_DATA_TYPE_BFLOAT16, 3, const_cast<void*>(p), gd, gs, bd, es, CU_TENSOR_MAP_INTERLEAVE_NONE,
      cw == 64 ? CU_TENSOR_MAP_SWIZZLE_128B : CU_TENSOR_MAP_SWIZZLE_64B, PROMO, CU_TENSOR_MAP_FLOAT_OOB_FILL_NONE);
}

}

extern "C" void kernel_launch(void* const* d_in, const int* in_sizes, int n_in, void* d_out, int out_size) {
  const bf16* x = (const bf16*)d_in[0];
  const bf16* wsre = (const bf16*)d_in[1];
  const bf16* wsim = (const bf16*)d_in[2];
  const bf16* wdre = (const bf16*)d_in[3];
  const bf16* wdim = (const bf16*)d_in[4];
  const bf16* win = (const bf16*)d_in[6];
  const bf16* wsp = (const bf16*)d_in[7];
  const bf16* bsp = (const bf16*)d_in[8];
  const bf16* wout = (const bf16*)d_in[9];

  void* fn = nullptr;
  cudaDriverEntryPointQueryResult qr;
  cudaGetDriverEntryPoint("cuTensorMapEncodeTiled", &fn, cudaEnableDefault, &qr);
  EncodeFn enc = (EncodeFn)fn;
  void *abT, *z2, *h, *xn;
  cudaGetSymbolAddress(&xn, g_xn);
  cudaGetSymbolAddress(&abT, g_abT);
  cudaGetSymbolAddress(&z2, g_z2);
  cudaGetSymbolAddress(&h, g_h);

  Maps maps;
  make2d(enc, &maps.m[M_X], x, DM, SEQ, 64, 64);
  make2d(enc, &maps.m[M_XN], xn, DM, SEQ, 64, 64);
  make3d(enc, &maps.m[M_Z232], z2, FH, SEQ, 32, 3, 128);
  make3d(enc, &maps.m[M_WIN32], win, FF, DM, 32, 3);
  make2d(enc, &maps.m[M_WSRE], wsre, SEQ, SEQ, 64, 64);
  make2d(enc, &maps.m[M_WSIM], wsim, SEQ, SEQ, 64, 64);
  make2d(enc, &maps.m[M_WSP], wsp, SEQ, SEQ, 64, 64);
  make2d(enc, &maps.m[M_H], h, FH, SEQ, 64, 64);
  make3d(enc, &maps.m[M_WIN3], win, FF, DM, 64, 3);
  make3d(enc, &maps.m[M_Z23], z2, FH, SEQ, 64, 3);
  make2d(enc, &maps.m[M_WDRE], wdre, DM, DM, 64, 160);
  make2d(enc, &maps.m[M_WDIM], wdim, DM, DM, 64, 160);
  make2d(enc, &maps.m[M_AB], abT, SEQ, 2 * DM, 64, 160);
  make3d(enc, &maps.m[M_WOUT], wout, DM, FH, 32, 5);
  make2d(enc, &maps.m[M_HS], h, FH, SEQ, 64, 16);
  make2d(enc, &maps.m[M_ABS], abT, SEQ, 2 * DM, 64, 40);
  make2d(enc, &maps.m[M_OUT], d_out, DM, SEQ, 160, 16, false);

  cudaFuncSetAttribute(fused_kernel, cudaFuncAttributeMaxDynamicSharedMemorySize, SMEM_BYTES);
  fused_kernel<<<128, 384, SMEM_BYTES>>>(maps, x, win, bsp, (bf16*)d_out);
}
```

```cpp
#include <cuda_runtime.h>
#include <cuda_bf16.h>
#include <cuda.h>
#include <stdint.h>

namespace {

typedef __nv_bfloat16 bf16;

constexpr int SEQ = 2048, DM = 640, FF = 1536, FH = 768;
#define NXV 10
constexpr int NX = NXV;
#define NSTB 5
constexpr int NST_A = 4, NST_B = NSTB, MAXST = 5;
constexpr int A_BYTES = 16384;
constexpr int BAR_OFF = 512;
constexpr int READY_OFF = 640;
constexpr int ROWSTAT_OFF = 1024;
constexpr int COLSUM_OFF = 2048;
constexpr int RED_OFF = 2560;
constexpr int RING_OFF = 3072;
constexpr int STAGE_A = 40960, STAGE_B = 36864;
constexpr int SMEM_BYTES = RING_OFF + 5 * STAGE_B + 40960;
constexpr int KB_A = 20 + 32 + NX + 12;
constexpr int KB_B = 30 + 64 - NX;
constexpr float LN_EPS = 1e-5f;
constexpr unsigned POLL_LIMIT = 100000;
#define POLL_NS 100
#define PF_D 8
#define ROT 0
#define Z1_NS 0
#define INFL 2
#define LIM_G 1000
#define MAPV 0
#define PROMO CU_TENSOR_MAP_L2_PROMOTION_L2_128B
#define WATCH_NS 40
#define PF_COND ((kb & 1) == (ct >> 1))
#define WPF 1
#define PF_NS 150

constexpr int BAR_ORD1 = 1, BAR_ORD2 = 2, BAR_WG1 = 3, BAR_WG2 = 4, BAR_LN = 5, BAR_BUF = 6, BAR_Z1 = 7, BAR_PUB1 = 8, BAR_PUB2 = 9, BAR_STATS = 10;

enum { M_X, M_XN, M_WIN32, M_Z232, M_WSRE, M_WSIM, M_WSP, M_H, M_WIN3, M_Z23, M_WDRE, M_WDIM, M_AB, M_WOUT, M_OUT, M_HS, M_ABS, M_COUNT };
struct Maps { CUtensorMap m[M_COUNT]; };

__device__ __align__(1024) bf16 g_abT[2 * DM * SEQ];
__device__ __align__(1024) bf16 g_z2[SEQ * FH];
__device__ __align__(1024) bf16 g_h[SEQ * FH];
__device__ __align__(1024) bf16 g_xn[SEQ * DM];
__device__ __align__(16) uint2 g_xstat[SEQ];
__device__ __align__(16) uint2 g_csum[5 * FH];
__device__ __align__(16) uint2 g_zstat[128 * 128];
__device__ __align__(256) unsigned char g_flags[44 * 256];
constexpr int F_A = 0, F_B = 4, F_Z = 8, F_H = 12, F_XN = 28;
__device__ unsigned g_done;
#define TS(role, ev)
#define TC(i)

extern __shared__ __align__(1024) uint8_t smem[];

__device__ __forceinline__ uint32_t smem_u32(const void* p) { return (uint32_t)__cvta_generic_to_shared(p); }
__device__ __forceinline__ void mbar_init(uint32_t bar, uint32_t cnt) { asm volatile("mbarrier.init.shared::cta.b64 [%0], %1;" :: "r"(bar), "r"(cnt)); }
__device__ __forceinline__ void mbar_expect_tx(uint32_t bar, uint32_t bytes) { asm volatile("mbarrier.arrive.expect_tx.shared::cta.b64 _, [%0], %1;" :: "r"(bar), "r"(bytes) : "memory"); }
__device__ __forceinline__ void mbar_arrive(uint32_t bar) { asm volatile("mbarrier.arrive.shared::cta.b64 _, [%0];" :: "r"(bar) : "memory"); }
__device__ __forceinline__ void mbar_arrive_cluster(uint32_t bar, uint32_t cta) {
  asm volatile("{\n.reg .b32 ra;\nmapa.shared::cluster.u32 ra, %0, %1;\nmbarrier.arrive.shared::cluster.b64 _, [ra];\n}" :: "r"(bar), "r"(cta) : "memory");
}
__device__ __forceinline__ void mbar_wait(uint32_t bar, uint32_t parity) {
  asm volatile("{\n.reg .pred p;\n.reg .u32 n;\nmov.u32 n, 0;\n"
               "LW: mbarrier.try_wait.parity.shared::cta.b64 p, [%0], %1, 2000;\n@p bra LD;\n"
               "add.u32 n, n, 1;\nsetp.lt.u32 p, n, 20000;\n@p bra LW;\nLD:\n}" :: "r"(bar), "r"(parity) : "memory");
}
__device__ __forceinline__ void tma_load_2d(uint32_t dst, const CUtensorMap* map, uint32_t bar, int c0, int c1) {
  asm volatile("cp.async.bulk.tensor.2d.shared::cluster.global.mbarrier::complete_tx::bytes [%0], [%1, {%3, %4}], [%2];"
    :: "r"(dst), "l"((uint64_t)map), "r"(bar), "r"(c0), "r"(c1) : "memory");
}
__device__ __forceinline__ void tma_load_3d(uint32_t dst, const CUtensorMap* map, uint32_t bar, int c0, int c1, int c2) {
  asm volatile("cp.async.bulk.tensor.3d.shared::cluster.global.mbarrier::complete_tx::bytes [%0], [%1, {%3, %4, %5}], [%2];"
    :: "r"(dst), "l"((uint64_t)map), "r"(bar), "r"(c0), "r"(c1), "r"(c2) : "memory");
}
__device__ __forceinline__ void tma_load_2d_mc(uint32_t dst, const CUtensorMap* map, uint32_t bar, int c0, int c1, uint16_t mask) {
  asm volatile("cp.async.bulk.tensor.2d.shared::cluster.global.mbarrier::complete_tx::bytes.multicast::cluster [%0], [%1, {%3, %4}], [%2], %5;"
    :: "r"(dst), "l"((uint64_t)map), "r"(bar), "r"(c0), "r"(c1), "h"(mask) : "memory");
}
__device__ __forceinline__ void tma_store_2d(const CUtensorMap* map, uint32_t src, int c0, int c1) {
  asm volatile("cp.async.bulk.tensor.2d.global.shared::cta.bulk_group [%0, {%2, %3}], [%1];"
    :: "l"((uint64_t)map), "r"(src), "r"(c0), "r"(c1) : "memory");
}
__device__ __forceinline__ void tma_store_3d(const CUtensorMap* map, uint32_t src, int c0, int c1, int c2) {
  asm volatile("cp.async.bulk.tensor.3d.global.shared::cta.bulk_group [%0, {%2, %3, %4}], [%1];"
    :: "l"((uint64_t)map), "r"(src), "r"(c0), "r"(c1), "r"(c2) : "memory");
}
__device__ __forceinline__ void tma_reduce_2d(const CUtensorMap* map, uint32_t src, int c0, int c1) {
  asm volatile("cp.reduce.async.bulk.tensor.2d.global.shared::cta.add.tile.bulk_group [%0, {%2, %3}], [%1];"
    :: "l"((uint64_t)map), "r"(src), "r"(c0), "r"(c1) : "memory");
}
__device__ __forceinline__ void bulk_wait_all() { asm volatile("cp.async.bulk.wait_group 0;" ::: "memory"); }
__device__ __forceinline__ void bulk_commit() { asm volatile("cp.async.bulk.commit_group;" ::: "memory"); }
__device__ __forceinline__ void bulk_wait_read() { asm volatile("cp.async.bulk.wait_group.read 0;" ::: "memory"); }
__device__ __forceinline__ void fence_async_smem() { asm volatile("fence.proxy.async.shared::cta;" ::: "memory"); }
__device__ __forceinline__ void fence_async_global() { asm volatile("fence.proxy.async.global;" ::: "memory"); }
__device__ __forceinline__ void wgmma_fence() { asm volatile("wgmma.fence.sync.aligned;" ::: "memory"); }
__device__ __forceinline__ void wgmma_commit() { asm volatile("wgmma.commit_group.sync.aligned;" ::: "memory"); }
template<int N> __device__ __forceinline__ void wgmma_wait() { asm volatile("wgmma.wait_group.sync.aligned %0;" :: "n"(N) : "memory"); }
template<int ID> __device__ __forceinline__ void bar_sync(int n) { asm volatile("bar.sync %0, %1;" :: "n"(ID), "r"(n) : "memory"); }
template<int ID> __device__ __forceinline__ void bar_arrive(int n) { asm volatile("bar.arrive %0, %1;" :: "n"(ID), "r"(n) : "memory"); }
__device__ __forceinline__ void cluster_wait() { asm volatile("barrier.cluster.wait.aligned;" ::: "memory"); }
__device__ __forceinline__ uint64_t desc64(uint32_t lo, uint32_t hi) { return (uint64_t)lo | ((uint64_t)hi << 32); }
__device__ __forceinline__ uint4 ld_vol4(const uint4* p) {
  uint4 v; asm volatile("ld.relaxed.gpu.global.v4.u32 {%0,%1,%2,%3}, [%4];" : "=r"(v.x), "=r"(v.y), "=r"(v.z), "=r"(v.w) : "l"(p) : "memory"); return v;
}
__device__ __forceinline__ uint2 ld_vol2(const uint2* p) {
  uint2 v; asm volatile("ld.relaxed.gpu.global.v2.u32 {%0,%1}, [%2];" : "=r"(v.x), "=r"(v.y) : "l"(p) : "memory"); return v;
}
__device__ __forceinline__ void st_vol4(uint4* p, uint32_t a, uint32_t b, uint32_t c, uint32_t d) {
  asm volatile("st.relaxed.gpu.global.v4.u32 [%0], {%1,%2,%3,%4};" :: "l"(p), "r"(a), "r"(b), "r"(c), "r"(d) : "memory");
}
__device__ __forceinline__ void st_vol2(uint2* p, uint32_t a, uint32_t b) {
  asm volatile("st.relaxed.gpu.global.v2.u32 [%0], {%1,%2};" :: "l"(p), "r"(a), "r"(b) : "memory");
}
__device__ __forceinline__ void stg128(void* p, uint4 v) {
  asm volatile("st.global.v4.u32 [%0], {%1,%2,%3,%4};" :: "l"(p), "r"(v.x), "r"(v.y), "r"(v.z), "r"(v.w));
}
__device__ __forceinline__ unsigned ld_relaxed(const unsigned* p) {
  unsigned v; asm volatile("ld.relaxed.gpu.global.u32 %0, [%1];" : "=r"(v) : "l"(p) : "memory"); return v;
}
__device__ __forceinline__ uint32_t pack_bf16(float lo, float hi) {
  uint32_t r; asm("cvt.rn.bf16x2.f32 %0, %1, %2;" : "=r"(r) : "f"(hi), "f"(lo)); return r;
}
__device__ __forceinline__ float bf_lo(uint32_t v) { return __uint_as_float(v << 16); }
__device__ __forceinline__ float bf_hi(uint32_t v) { return __uint_as_float(v & 0xFFFF0000u); }
__device__ __forceinline__ void stsm4(uint32_t addr, uint32_t a, uint32_t b, uint32_t c, uint32_t d) {
  asm volatile("stmatrix.sync.aligned.m8n8.x4.shared.b16 [%0], {%1,%2,%3,%4};" :: "r"(addr), "r"(a), "r"(b), "r"(c), "r"(d));
}
__device__ __forceinline__ void stsm4_t(uint32_t addr, uint32_t a, uint32_t b, uint32_t c, uint32_t d) {
  asm volatile("stmatrix.sync.aligned.m8n8.x4.trans.shared.b16 [%0], {%1,%2,%3,%4};" :: "r"(addr), "r"(a), "r"(b), "r"(c), "r"(d));
}
__device__ __forceinline__ void ldsm4(uint32_t addr, uint32_t& a, uint32_t& b, uint32_t& c, uint32_t& d) {
  asm volatile("ldmatrix.sync.aligned.m8n8.x4.shared.b16 {%0,%1,%2,%3}, [%4];" : "=r"(a), "=r"(b), "=r"(c), "=r"(d) : "r"(addr));
}
__device__ __forceinline__ uint4 lds128(uint32_t a) {
  uint4 v; asm volatile("ld.shared.v4.u32 {%0,%1,%2,%3}, [%4];" : "=r"(v.x), "=r"(v.y), "=r"(v.z), "=r"(v.w) : "r"(a)); return v;
}
__device__ __forceinline__ void sts128(uint32_t a, uint32_t x, uint32_t y, uint32_t z, uint32_t w) {
  asm volatile("st.shared.v4.u32 [%0], {%1,%2,%3,%4};" :: "r"(a), "r"(x), "r"(y), "r"(z), "r"(w));
}
__device__ __forceinline__ uint32_t hmul2_bf16(uint32_t a, uint32_t b) {
  uint32_t r; asm("mul.rn.bf16x2 %0, %1, %2;" : "=r"(r) : "r"(a), "r"(b)); return r;
}
__device__ __forceinline__ float gelu_tanh(float v) {
  float u = v * fmaf(0.0356774081f, v * v, 0.7978845608f);
  float t; asm("tanh.approx.f32 %0, %1;" : "=f"(t) : "f"(u));
  float hv = 0.5f * v;
  return fmaf(hv, t, hv);
}

template<int TB>
__device__ __forceinline__ void wgmma_n192(float (&d)[96], uint64_t da, uint64_t db, int scale_d) {
  asm volatile("{\n.reg .pred p;\nsetp.ne.b32 p, %98, 0;\n"
   "wgmma.mma_async.sync.aligned.m64n192k16.f32.bf16.bf16 {%0,%1,%2,%3,%4,%5,%6,%7,%8,%9,%10,%11,%12,%13,%14,%15,%16,%17,%18,%19,%20,%21,%22,%23,%24,%25,%26,%27,%28,%29,%30,%31,%32,%33,%34,%35,%36,%37,%38,%39,%40,%41,%42,%43,%44,%45,%46,%47,%48,%49,%50,%51,%52,%53,%54,%55,%56,%57,%58,%59,%60,%61,%62,%63,%64,%65,%66,%67,%68,%69,%70,%71,%72,%73,%74,%75,%76,%77,%78,%79,%80,%81,%82,%83,%84,%85,%86,%87,%88,%89,%90,%91,%92,%93,%94,%95}, %96, %97, p, 1, 1, 0, %99;\n}"
   : "+f"(d[0]),"+f"(d[1]),"+f"(d[2]),"+f"(d[3]),"+f"(d[4]),"+f"(d[5]),"+f"(d[6]),"+f"(d[7]),"+f"(d[8]),"+f"(d[9]),"+f"(d[10]),"+f"(d[11]),"+f"(d[12]),"+f"(d[13]),"+f"(d[14]),"+f"(d[15]),"+f"(d[16]),"+f"(d[17]),"+f"(d[18]),"+f"(d[19]),"+f"(d[20]),"+f"(d[21]),"+f"(d[22]),"+f"(d[23]),"+f"(d[24]),"+f"(d[25]),"+f"(d[26]),"+f"(d[27]),"+f"(d[28]),"+f"(d[29]),"+f"(d[30]),"+f"(d[31]),"+f"(d[32]),"+f"(d[33]),"+f"(d[34]),"+f"(d[35]),"+f"(d[36]),"+f"(d[37]),"+f"(d[38]),"+f"(d[39]),"+f"(d[40]),"+f"(d[41]),"+f"(d[42]),"+f"(d[43]),"+f"(d[44]),"+f"(d[45]),"+f"(d[46]),"+f"(d[47]),"+f"(d[48]),"+f"(d[49]),"+f"(d[50]),"+f"(d[51]),"+f"(d[52]),"+f"(d[53]),"+f"(d[54]),"+f"(d[55]),"+f"(d[56]),"+f"(d[57]),"+f"(d[58]),"+f"(d[59]),"+f"(d[60]),"+f"(d[61]),"+f"(d[62]),"+f"(d[63]),"+f"(d[64]),"+f"(d[65]),"+f"(d[66]),"+f"(d[67]),"+f"(d[68]),"+f"(d[69]),"+f"(d[70]),"+f"(d[71]),"+f"(d[72]),"+f"(d[73]),"+f"(d[74]),"+f"(d[75]),"+f"(d[76]),"+f"(d[77]),"+f"(d[78]),"+f"(d[79]),"+f"(d[80]),"+f"(d[81]),"+f"(d[82]),"+f"(d[83]),"+f"(d[84]),"+f"(d[85]),"+f"(d[86]),"+f"(d[87]),"+f"(d[88]),"+f"(d[89]),"+f"(d[90]),"+f"(d[91]),"+f"(d[92]),"+f"(d[93]),"+f"(d[94]),"+f"(d[95])
   : "l"(da), "l"(db), "r"(scale_d), "n"(TB));
}
template<int TB>
__device__ __forceinline__ void wgmma_n160(float (&d)[80], uint64_t da, uint64_t db, int scale_d) {
  asm volatile("{\n.reg .pred p;\nsetp.ne.b32 p, %82, 0;\n"
   "wgmma.mma_async.sync.aligned.m64n160k16.f32.bf16.bf16 {%0,%1,%2,%3,%4,%5,%6,%7,%8,%9,%10,%11,%12,%13,%14,%15,%16,%17,%18,%19,%20,%21,%22,%23,%24,%25,%26,%27,%28,%29,%30,%31,%32,%33,%34,%35,%36,%37,%38,%39,%40,%41,%42,%43,%44,%45,%46,%47,%48,%49,%50,%51,%52,%53,%54,%55,%56,%57,%58,%59,%60,%61,%62,%63,%64,%65,%66,%67,%68,%69,%70,%71,%72,%73,%74,%75,%76,%77,%78,%79}, %80, %81, p, 1, 1, 0, %83;\n}"
   : "+f"(d[0]),"+f"(d[1]),"+f"(d[2]),"+f"(d[3]),"+f"(d[4]),"+f"(d[5]),"+f"(d[6]),"+f"(d[7]),"+f"(d[8]),"+f"(d[9]),"+f"(d[10]),"+f"(d[11]),"+f"(d[12]),"+f"(d[13]),"+f"(d[14]),"+f"(d[15]),"+f"(d[16]),"+f"(d[17]),"+f"(d[18]),"+f"(d[19]),"+f"(d[20]),"+f"(d[21]),"+f"(d[22]),"+f"(d[23]),"+f"(d[24]),"+f"(d[25]),"+f"(d[26]),"+f"(d[27]),"+f"(d[28]),"+f"(d[29]),"+f"(d[30]),"+f"(d[31]),"+f"(d[32]),"+f"(d[33]),"+f"(d[34]),"+f"(d[35]),"+f"(d[36]),"+f"(d[37]),"+f"(d[38]),"+f"(d[39]),"+f"(d[40]),"+f"(d[41]),"+f"(d[42]),"+f"(d[43]),"+f"(d[44]),"+f"(d[45]),"+f"(d[46]),"+f"(d[47]),"+f"(d[48]),"+f"(d[49]),"+f"(d[50]),"+f"(d[51]),"+f"(d[52]),"+f"(d[53]),"+f"(d[54]),"+f"(d[55]),"+f"(d[56]),"+f"(d[57]),"+f"(d[58]),"+f"(d[59]),"+f"(d[60]),"+f"(d[61]),"+f"(d[62]),"+f"(d[63]),"+f"(d[64]),"+f"(d[65]),"+f"(d[66]),"+f"(d[67]),"+f"(d[68]),"+f"(d[69]),"+f"(d[70]),"+f"(d[71]),"+f"(d[72]),"+f"(d[73]),"+f"(d[74]),"+f"(d[75]),"+f"(d[76]),"+f"(d[77]),"+f"(d[78]),"+f"(d[79])
   : "l"(da), "l"(db), "r"(scale_d), "n"(TB));
}
template<int TB>
__device__ __forceinline__ void wgmma_n96(float (&d)[48], uint64_t da, uint64_t db, int scale_d) {
  asm volatile("{\n.reg .pred p;\nsetp.ne.b32 p, %50, 0;\n"
   "wgmma.mma_async.sync.aligned.m64n96k16.f32.bf16.bf16 {%0,%1,%2,%3,%4,%5,%6,%7,%8,%9,%10,%11,%12,%13,%14,%15,%16,%17,%18,%19,%20,%21,%22,%23,%24,%25,%26,%27,%28,%29,%30,%31,%32,%33,%34,%35,%36,%37,%38,%39,%40,%41,%42,%43,%44,%45,%46,%47}, %48, %49, p, 1, 1, 0, %51;\n}"
   : "+f"(d[0]),"+f"(d[1]),"+f"(d[2]),"+f"(d[3]),"+f"(d[4]),"+f"(d[5]),"+f"(d[6]),"+f"(d[7]),"+f"(d[8]),"+f"(d[9]),"+f"(d[10]),"+f"(d[11]),"+f"(d[12]),"+f"(d[13]),"+f"(d[14]),"+f"(d[15]),"+f"(d[16]),"+f"(d[17]),"+f"(d[18]),"+f"(d[19]),"+f"(d[20]),"+f"(d[21]),"+f"(d[22]),"+f"(d[23]),"+f"(d[24]),"+f"(d[25]),"+f"(d[26]),"+f"(d[27]),"+f"(d[28]),"+f"(d[29]),"+f"(d[30]),"+f"(d[31]),"+f"(d[32]),"+f"(d[33]),"+f"(d[34]),"+f"(d[35]),"+f"(d[36]),"+f"(d[37]),"+f"(d[38]),"+f"(d[39]),"+f"(d[40]),"+f"(d[41]),"+f"(d[42]),"+f"(d[43]),"+f"(d[44]),"+f"(d[45]),"+f"(d[46]),"+f"(d[47])
   : "l"(da), "l"(db), "r"(scale_d), "n"(TB));
}

template<int N, int TB>
__device__ __forceinline__ void wgmma_n(float (&d)[N / 2], uint64_t da, uint64_t db) {
  if constexpr (N == 192) wgmma_n192<TB>(d, da, db, 1);
  else if constexpr (N == 160) wgmma_n160<TB>(d, da, db, 1);
  else wgmma_n96<TB>(d, da, db, 1);
}

template<int R>
__device__ __forceinline__ void pin(float (&acc)[2][R]) {
  #pragma unroll
  for (int mi = 0; mi < 2; mi++)
    #pragma unroll
    for (int i = 0; i < R; i++) asm volatile("" : "+f"(acc[mi][i]) :: "memory");
}
template<int R>
__device__ __forceinline__ void zero(float (&acc)[2][R]) {
  #pragma unroll
  for (int i = 0; i < R; i++) { acc[0][i] = 0.f; acc[1][i] = 0.f; }
  pin(acc);
}

template<int N, int TB, bool CONT, int ORD_BAR>
__device__ __forceinline__ void mainloop(float (&acc)[2][N / 2], uint32_t sbase, int grp, int g0, int nk) {
  const uint32_t full0 = sbase + BAR_OFF, empty0 = full0 + 8 * MAXST, ring = sbase + RING_OFF;
  const int nst = grp == 0 ? NST_A : NST_B, total = grp == 0 ? KB_A : KB_B;
  const uint32_t sstep = (grp == 0 ? STAGE_A : STAGE_B) >> 4;
  const int t = threadIdx.x & 127;
  const uint32_t da0 = ((ring & 0x3FFFF) >> 4) | 0x10000u;
  const uint32_t db0 = (((ring + A_BYTES) & 0x3FFFF) >> 4) | ((TB == 2 ? 256u : TB ? 512u : 1u) << 16);
  constexpr uint32_t HI_A = 0x40000040u, HI_B = TB == 2 ? 0x80000020u : 0x40000040u;
  int s = g0 % nst, ph = (g0 / nst) & 1, ps = s == 0 ? nst - 1 : s - 1;
  #pragma unroll 1
  for (int g = g0; g < g0 + nk; g++) {
    const uint32_t so = s * sstep;
    mbar_wait(full0 + 8 * s, ph);
    wgmma_fence();
    #pragma unroll
    for (int k = 0; k < 4; k++) {
      const uint64_t db = desc64(db0 + so + (TB == 2 ? k * 64 : TB ? k * 128 : k * 2), HI_B);
      wgmma_n<N, TB != 0>(acc[0], desc64(da0 + so + k * 2, HI_A), db);
      wgmma_n<N, TB != 0>(acc[1], desc64(da0 + so + 512 + k * 2, HI_A), db);
    }
    wgmma_commit();
    if (ORD_BAR != 0 && g == g0 + nk - 1) bar_arrive<ORD_BAR>(256);
    wgmma_wait<1>();
    if (t < 2 && (CONT || g > g0) && g - 1 + nst < total) mbar_arrive_cluster(empty0 + 8 * ps, t);
    ps = s;
    if (++s == nst) { s = 0; ph ^= 1; }
  }
}
template<int R>
__device__ __forceinline__ void drain(float (&acc)[2][R], uint32_t sbase, int grp, int glast) {
  wgmma_wait<0>();
  pin(acc);
  const int t = threadIdx.x & 127;
  const int nst = grp == 0 ? NST_A : NST_B, total = grp == 0 ? KB_A : KB_B;
  if (t < 2 && glast + nst < total) mbar_arrive_cluster(sbase + BAR_OFF + 8 * MAXST + 8 * (glast % nst), t);
}

__device__ __forceinline__ void set_flag(int slot, int byte, unsigned epoch) {
  asm volatile("st.relaxed.gpu.global.u8 [%0], %1;" :: "l"(g_flags + slot * 256 + byte), "r"(epoch & 255u) : "memory");
}
__device__ __forceinline__ unsigned get_flag(int slot, int byte) {
  unsigned v; asm volatile("ld.relaxed.gpu.global.u8 %0, [%1];" : "=r"(v) : "l"(g_flags + slot * 256 + byte) : "memory"); return v;
}
__device__ __forceinline__ void publish(int slot, int byte, unsigned epoch) {
  asm volatile("fence.acq_rel.gpu;" ::: "memory");
  set_flag(slot, byte, epoch);
}

__device__ __forceinline__ float sum8(uint4 v) {
  return ((bf_lo(v.x) + bf_hi(v.x)) + (bf_lo(v.y) + bf_hi(v.y))) + ((bf_lo(v.z) + bf_hi(v.z)) + (bf_lo(v.w) + bf_hi(v.w)));
}
__device__ __forceinline__ uint4 ldg128(const void* p) {
  uint4 v; asm volatile("ld.global.nc.v4.u32 {%0,%1,%2,%3}, [%4];" : "=r"(v.x), "=r"(v.y), "=r"(v.z), "=r"(v.w) : "l"(p)); return v;
}
__device__ __forceinline__ void ln_load(const bf16* __restrict__ x, int cta, uint4 (&rv)[5]) {
  const int t = threadIdx.x - 128, row = cta * 16 + (t >> 4), c = t & 15;
  #pragma unroll
  for (int j = 0; j < 5; j++) rv[j] = ldg128(reinterpret_cast<const uint4*>(x + (size_t)row * DM) + c + 16 * j);
}
__device__ __forceinline__ void ln_rows(const uint4 (&rv)[5], int cta, unsigned epoch) {
  const int t = threadIdx.x - 128, row = cta * 16 + (t >> 4), c = t & 15;
  const float sh = __shfl_sync(0xffffffffu, bf_lo(rv[0].x), t & 16);
  float d[40], s = 0.f, q = 0.f;
  #pragma unroll
  for (int j = 0; j < 5; j++) {
    const uint32_t u[4] = {rv[j].x, rv[j].y, rv[j].z, rv[j].w};
    #pragma unroll
    for (int e = 0; e < 4; e++) {
      const float d0 = bf_lo(u[e]) - sh, d1 = bf_hi(u[e]) - sh;
      d[j * 8 + e * 2] = d0; d[j * 8 + e * 2 + 1] = d1;
      s += d0 + d1; q = fmaf(d0, d0, q); q = fmaf(d1, d1, q);
    }
  }
  #pragma unroll
  for (int o = 1; o < 16; o <<= 1) { s += __shfl_xor_sync(0xffffffffu, s, o); q += __shfl_xor_sync(0xffffffffu, q, o); }
  const float md = s * (1.f / DM);
  const float r = rsqrtf(fmaxf(fmaf(q, 1.f / DM, -md * md), 0.f) + LN_EPS), o = -md * r;
  if (c == 0) st_vol2(&g_xstat[row], __float_as_uint(r), (__float_as_uint(-(md + sh) * r) & ~255u) | (epoch & 255u));
  #pragma unroll
  for (int j = 0; j < 5; j++) {
    const float* a = &d[j * 8];
    stg128(reinterpret_cast<uint4*>(g_xn + (size_t)row * DM) + c + 16 * j, make_uint4(
           pack_bf16(fmaf(a[0], r, o), fmaf(a[1], r, o)), pack_bf16(fmaf(a[2], r, o), fmaf(a[3], r, o)),
           pack_bf16(fmaf(a[4], r, o), fmaf(a[5], r, o)), pack_bf16(fmaf(a[6], r, o), fmaf(a[7], r, o))));
  }
  bar_arrive<BAR_LN>(288);
}
__device__ __forceinline__ void colsum_part(const bf16* __restrict__ win, int cta, unsigned epoch) {
  const int t = threadIdx.x & 127, w = t >> 5, l = t & 31;
  const int cj = min(cta, 119), cg = cj % 24, rg = cj / 24;
  uint4 cv[4];
  #pragma unroll
  for (int j = 0; j < 4; j++) cv[j] = ldg128(reinterpret_cast<const uint4*>(win + (size_t)(rg * 128 + w * 32 + j * 8 + (l >> 2)) * FF + FH + cg * 32) + (l & 3));
  float v[8];
  v[0] = (bf_lo(cv[0].x) + bf_lo(cv[1].x)) + (bf_lo(cv[2].x) + bf_lo(cv[3].x)); v[1] = (bf_hi(cv[0].x) + bf_hi(cv[1].x)) + (bf_hi(cv[2].x) + bf_hi(cv[3].x));
  v[2] = (bf_lo(cv[0].y) + bf_lo(cv[1].y)) + (bf_lo(cv[2].y) + bf_lo(cv[3].y)); v[3] = (bf_hi(cv[0].y) + bf_hi(cv[1].y)) + (bf_hi(cv[2].y) + bf_hi(cv[3].y));
  v[4] = (bf_lo(cv[0].z) + bf_lo(cv[1].z)) + (bf_lo(cv[2].z) + bf_lo(cv[3].z)); v[5] = (bf_hi(cv[0].z) + bf_hi(cv[1].z)) + (bf_hi(cv[2].z) + bf_hi(cv[3].z));
  v[6] = (bf_lo(cv[0].w) + bf_lo(cv[1].w)) + (bf_lo(cv[2].w) + bf_lo(cv[3].w)); v[7] = (bf_hi(cv[0].w) + bf_hi(cv[1].w)) + (bf_hi(cv[2].w) + bf_hi(cv[3].w));
  #pragma unroll
  for (int st = 0; st < 3; st++) {
    const int n = 4 >> st;
    const bool up = (l & (4 * n)) != 0;
    #pragma unroll
    for (int e = 0; e < 4; e++)
      if (e < n) { const float keep = up ? v[e + n] : v[e], send = up ? v[e] : v[e + n]; v[e] = keep + __shfl_xor_sync(0xffffffffu, send, 4 * n); }
  }
  float* red = reinterpret_cast<float*>(smem + RED_OFF);
  red[w * 32 + (l & 3) * 8 + (l >> 2)] = v[0];
  bar_sync<BAR_WG2>(128);
  if (t < 32) st_vol2(&g_csum[rg * FH + cg * 32 + t], __float_as_uint((red[t] + red[32 + t]) + (red[64 + t] + red[96 + t])), epoch);
}

__device__ __forceinline__ void a_entry(int g, int grp, int rb, int& mi, int& kb) {
  if (g < 10) { mi = M_X; kb = g; }
  else if (g < 20) { mi = M_XN; kb = g - 10; }
  else if (grp == 0) {
    if (g < 52) { mi = M_WSP; kb = (g - 20); }
    else if (g < 52 + NX) { mi = M_WSIM; kb = g - 52 + 32 - NX; }
    else { mi = M_H; kb = g - 52 - NX; }
  } else {
    if (g < 30) { mi = M_XN; kb = g - 20; }
    else if (g < 62) { mi = M_WSRE; kb = (g - 30); }
    else { mi = M_WSIM; kb = g - 62; }
  }
}

__global__ void __cluster_dims__(2, 1, 1) __launch_bounds__(384, 1)
fused_kernel(const __grid_constant__ Maps maps, const bf16* __restrict__ x, const bf16* __restrict__ win, const bf16* __restrict__ bsp,
             bf16* __restrict__ out) {
  const uint32_t sbase = smem_u32(smem);
  const uint32_t full0 = sbase + BAR_OFF, empty0 = full0 + 8 * MAXST, dep0 = empty0 + 8 * MAXST, ring = sbase + RING_OFF;
  const int tid = threadIdx.x, wg = __shfl_sync(0xffffffffu, tid >> 7, 0);
  const int rank = blockIdx.x & 1;
  const int grp = (blockIdx.x >> 1) & 1, half = (blockIdx.x >> 2) & 1, rb = blockIdx.x >> 3;
  const int ct = half * 2 + rank, c8 = grp * 4 + ct;
  const int cta = rb * 8 + half * 4 + grp * 2 + rank;
  const int total = grp == 0 ? KB_A : KB_B;
  const uint32_t stage_bytes = grp == 0 ? STAGE_A : STAGE_B;
  const int nst = grp == 0 ? NST_A : NST_B;
  const uint32_t buf = ring + nst * stage_bytes;

  uint4 rv[5];
  if (wg != 0) ln_load(x, cta, rv);
  if (wg == 2) {
    const int t = tid & 127;
    if (t < 60) asm volatile("prefetch.global.L2 [%0];" :: "l"(win + (size_t)(cta * 5 + t / 12) * FF + FH + (t % 12) * 64));
  }
  const unsigned epoch = (ld_relaxed(&g_done) >> 7) + 1u;
  if (tid == 0) {
    TS(0, 0);
    for (int s = 0; s < MAXST; s++) { mbar_init(full0 + 8 * s, 2); mbar_init(empty0 + 8 * s, 2); }
    for (int s = 0; s < 4; s++) mbar_init(dep0 + 8 * s, 1);
    *reinterpret_cast<volatile int*>(smem + READY_OFF) = 0;
    asm volatile("fence.mbarrier_init.release.cluster;" ::: "memory");
  }
  __syncthreads();
  asm volatile("barrier.cluster.arrive.relaxed.aligned;" ::: "memory");

  if (wg == 0) {
    asm volatile("setmaxnreg.dec.sync.aligned.u32 40;");
    const int warp = tid >> 5, lane = tid & 31;
    if (warp == 0) {
      const int row = rb * 128;
      if (lane == 0) {
        for (int g = 0; g < nst; g++) {
          mbar_expect_tx(full0 + 8 * g, A_BYTES);
          tma_load_2d(ring + g * stage_bytes, &maps.m[M_X], full0 + 8 * g, g * 64, row);
          tma_load_2d(ring + g * stage_bytes + 8192, &maps.m[M_X], full0 + 8 * g, g * 64, row + 64);
        }
      }
      __syncwarp();
      cluster_wait();
      if (lane == 0) {
        int s = 0, ph = 0;
        #pragma unroll 1
        for (int g = nst; g < total; g++) {
          int mi, kb;
          a_entry(g, grp, rb, mi, kb);
          if (g == 10 || (mi == M_H && kb == 0)) { TS(0, g > 10 ? 3 : 1); mbar_wait(dep0 + (g > 10 ? 24 : 0), 0); fence_async_global(); TS(0, g > 10 ? 4 : 2); }
          mbar_wait(empty0 + 8 * s, ph);
          mbar_expect_tx(full0 + 8 * s, A_BYTES);
          tma_load_2d_mc(ring + s * stage_bytes + rank * 8192, &maps.m[mi], full0 + 8 * s, kb * 64, row + rank * 64, 3);
          if (++s == nst) { s = 0; ph ^= 1; }
          if (g + PF_D < total) {
            a_entry(g + PF_D, grp, rb, mi, kb);
            if (mi >= M_WSRE && mi <= M_WSP && PF_COND)
              asm volatile("cp.async.bulk.prefetch.tensor.2d.L2.global.tile [%0, {%1, %2}];" :: "l"((uint64_t)&maps.m[mi]), "r"(kb * 64), "r"(row + rank * 64) : "memory");
          }
        }
        TS(0, 5);
      }
    } else if (warp == 1) {
      if (lane == 0) {
        int s = 0, ph = 1;
        int have = 0;
        #pragma unroll 1
        for (int g = 0; g < total; g++) {
          int kind = 1, mi, kb, c, dep = 0, need = 0;
          uint32_t bytes = 20480;
          if (g < 10) { kind = 0; mi = M_WIN32; kb = g; c = 24 + 3 * c8; bytes = 12288; }
          else if (grp == 0) {
            if (g < 20) { kind = 0; mi = M_WIN3; kb = g - 10; c = 3 * ct; bytes = 24576; }
            else if (g < 52) { kind = 0; mi = M_Z23; kb = (g - 20); c = 3 * ct; bytes = 24576; need = ((g - 20) >> 1) + 1; }
            else if (g < 52 + NX) { mi = M_AB; kb = g - 52 + 32 - NX; c = DM + ct * 160; dep = g == 52 ? 2 : 0; }
            else { kind = 0; mi = M_WOUT; kb = g - 52 - NX; c = ct * 5; }
          } else {
            if (g < 30) { mi = g < 20 ? M_WDRE : M_WDIM; kb = g < 20 ? g - 10 : g - 20; c = ct * 160; }
            else if (g < 62) { mi = M_AB; kb = (g - 30); c = ct * 160; need = ((g - 30) >> 1) + 1; }
            else { mi = M_AB; kb = g - 62; c = ct * 160 + DM; dep = g == 62 ? 2 : 0; }
          }
          if (need > have) {
            if (need == 1) TS(1, 0);
            unsigned it = 0;
            while ((have = *reinterpret_cast<volatile int*>(smem + READY_OFF)) < need && ++it < 50 * POLL_LIMIT) {}
            fence_async_global();
            if (need == 1) { TS(1, 1); TC(1); }
          }
          if (dep) { TS(1, dep * 2 - 2); mbar_wait(dep0 + 8 * dep, 0); fence_async_global(); TS(1, dep * 2 - 1); TC(dep); }
          const uint32_t dst = ring + s * stage_bytes + A_BYTES, fb = full0 + 8 * s;
          mbar_wait(empty0 + 8 * s, ph);
          if (++s == nst) { s = 0; ph ^= 1; }
          mbar_expect_tx(fb, bytes);
          if (kind == 0) tma_load_3d(dst, &maps.m[mi], fb, 0, kb * 64, c);
          else tma_load_2d(dst, &maps.m[mi], fb, kb * 64, c);
        }
      }
      __syncwarp();
      cluster_wait();
    } else if (warp == 2) {
      if (lane < M_COUNT) asm volatile("prefetch.tensormap [%0];" :: "l"((uint64_t)&maps.m[lane]) : "memory");
      cluster_wait();
      {
        unsigned it = 0;
        uint2 v[4];
        while (true) {
          bool ok = true;
          #pragma unroll
          for (int i = 0; i < 4; i++) { v[i] = ld_vol2(&g_xstat[rb * 128 + i * 32 + lane]); ok = ok && ((v[i].y ^ epoch) & 255u) == 0; }
          if (ok || ++it > POLL_LIMIT) break;
          __nanosleep(POLL_NS);
        }
        #pragma unroll
        for (int i = 0; i < 4; i++) reinterpret_cast<uint2*>(smem + ROWSTAT_OFF)[i * 32 + lane] = make_uint2(v[i].x, v[i].y & ~255u);
        __syncwarp();
        TS(0, 6);
        bar_arrive<BAR_STATS>(192);
      }
      #pragma unroll 1
      for (int d = 0; d < 4 - grp; d++) {
        const int slot = d == 0 ? F_XN + rb : d == 3 ? F_H + rb : d == 2 ? F_B + ct : grp == 0 ? F_Z + ct : F_A + ct;
        const int byte = d == 0 ? lane & 7 : d == 3 ? lane & 3 : (d == 1 && grp == 0) ? lane : lane >> 1;
        unsigned it = 0, m;
        while ((m = __ballot_sync(0xffffffffu, get_flag(slot, byte) != (epoch & 255u))) != 0 && ++it < POLL_LIMIT) {
          if (d == 1 && lane == 0) *reinterpret_cast<volatile int*>(smem + READY_OFF) = (__ffs(m) - 1) >> 1;
          __nanosleep(WATCH_NS);
        }
        if (d == 1 && lane == 0) *reinterpret_cast<volatile int*>(smem + READY_OFF) = 16;
        TS(0, 8 + d * 2);
        fence_async_global();
        __syncwarp();
        if (lane == 0 && d != 1) mbar_arrive(dep0 + 8 * d);
      }
    } else {
      cluster_wait();
      bar_sync<BAR_LN>(288);
      if (lane == 0) { TS(1, 5); publish(F_XN + rb, cta & 7, epoch); TS(1, 6); }
      __syncwarp();
      {
        unsigned it = 0;
        while (true) {
          bool ok = true;
          uint2 u[15];
          #pragma unroll
          for (int i = 0; i < 15; i++) u[i] = ld_vol2(&g_csum[(i % 5) * FH + c8 * 96 + (i / 5) * 32 + lane]);
          #pragma unroll
          for (int i = 0; i < 15; i++) ok = ok && u[i].y == epoch;
          #pragma unroll
          for (int i = 0; i < 3; i++)
            reinterpret_cast<float*>(smem + COLSUM_OFF)[i * 32 + lane] = ((__uint_as_float(u[i * 5].x) + __uint_as_float(u[i * 5 + 1].x)) +
                (__uint_as_float(u[i * 5 + 2].x) + __uint_as_float(u[i * 5 + 3].x))) + __uint_as_float(u[i * 5 + 4].x);
          if (ok || ++it > POLL_LIMIT) break;
          __nanosleep(POLL_NS);
        }
      }
      __syncwarp();
      TS(1, 4);
      bar_arrive<BAR_STATS>(192);
      bar_sync<BAR_PUB1>(160);
      if (lane == 0) {
        TS(1, 7);
        tma_store_3d(&maps.m[M_Z232], buf, 0, rb * 128, 3 * c8);
        bulk_commit();
        bulk_wait_all();
        set_flag(F_Z + (c8 >> 1), rb * 2 + (c8 & 1), epoch);
        TS(1, 8);
      }
      __syncwarp();
      bar_arrive<BAR_BUF>(160);
      if (grp == 1) {
        bar_sync<BAR_PUB2>(160);
        if (lane == 0) set_flag(F_A + ct, rb, epoch);
        TS(1, 9);
        __syncwarp();
      }
      bar_sync<BAR_PUB1>(160);
      if (lane == 0) { if (grp == 0) set_flag(F_H + rb, ct, epoch); else publish(F_B + ct, rb, epoch); }
      TS(1, 10);
      __syncwarp();
      bar_arrive<BAR_BUF>(160);
    }
  } else {
    asm volatile("setmaxnreg.inc.sync.aligned.u32 232;");
    const int t = tid & 127, w = t >> 5, l = t & 31;
    ln_rows(rv, cta, epoch);
    if (wg == 2) colsum_part(win, cta, epoch);
    TS(wg + 1, 0);
    cluster_wait();
    const int rl = w * 16 + ((l >> 3) & 1) * 8 + (l & 7);
    const int gr = w * 16 + (l & 15);
    const uint32_t st_base = buf + rl * 128;
    const uint32_t st_x = ((l >> 4) ^ (l & 7)) << 4;
    if (wg == 1) {
      float acc[2][48];
      zero(acc);
      mainloop<96, 2, false, BAR_ORD1>(acc, sbase, grp, 0, 10);
      drain(acc, sbase, grp, 9);
      TS(2, 2);
      bar_sync<BAR_STATS>(192);
      const float2* rs = reinterpret_cast<const float2*>(smem + ROWSTAT_OFF) + w * 16 + (l >> 2);
      const float2* cs = reinterpret_cast<const float2*>(smem + COLSUM_OFF) + (l & 3);
      float sum[4], sq[4];
      #pragma unroll
      for (int r = 0; r < 4; r++) {
        const float2 st = rs[(r >> 1) * 64 + (r & 1) * 8];
        float s0 = 0.f, q0 = 0.f;
        #pragma unroll
        for (int j = 0; j < 12; j++) {
          const float2 c = cs[j * 4];
          float* a = &acc[r >> 1][4 * j + (r & 1) * 2];
          a[0] = gelu_tanh(fmaf(a[0], st.x, st.y * c.x));
          a[1] = gelu_tanh(fmaf(a[1], st.x, st.y * c.y));
          s0 += a[0] + a[1]; q0 = fmaf(a[0], a[0], q0); q0 = fmaf(a[1], a[1], q0);
        }
        s0 += __shfl_xor_sync(0xffffffffu, s0, 1); q0 += __shfl_xor_sync(0xffffffffu, q0, 1);
        s0 += __shfl_xor_sync(0xffffffffu, s0, 2); q0 += __shfl_xor_sync(0xffffffffu, q0, 2);
        sum[r] = s0; sq[r] = q0;
      }
      TS(2, 4);
      float rstd, off;
      {
        const int qd = l & 3;
        const float sm = qd == 0 ? sum[0] : qd == 1 ? sum[1] : qd == 2 ? sum[2] : sum[3];
        const float sv = qd == 0 ? sq[0] : qd == 1 ? sq[1] : qd == 2 ? sq[2] : sq[3];
        const int row = (qd >> 1) * 64 + w * 16 + (qd & 1) * 8 + (l >> 2);
        const float mu = sm * (1.f / 96), m2 = fmaxf(sv - sm * mu, 0.f);
        st_vol2(&g_zstat[(rb * 8 + c8) * 128 + row], __float_as_uint(mu), (__float_as_uint(m2) & ~255u) | (epoch & 255u));
        uint2 v[7];
        unsigned n = 0;
        while (true) {
          bool ok = true;
          #pragma unroll
          for (int j = 0; j < 7; j++) v[j] = ld_vol2(&g_zstat[(rb * 8 + ((c8 + 1 + j) & 7)) * 128 + row]);
          #pragma unroll
          for (int j = 0; j < 7; j++) ok = ok && ((v[j].y ^ epoch) & 255u) == 0;
          if (ok || ++n > POLL_LIMIT) break;
          __nanosleep(POLL_NS);
        }
        float mean = mu, var = m2;
        #pragma unroll
        for (int j = 0; j < 7; j++) { mean += __uint_as_float(v[j].x); var += __uint_as_float(v[j].y & ~255u); }
        mean *= 0.125f;
        float d = (mu - mean) * (mu - mean);
        #pragma unroll
        for (int j = 0; j < 7; j++) d = fmaf(__uint_as_float(v[j].x) - mean, __uint_as_float(v[j].x) - mean, d);
        rstd = rsqrtf(fmaf(96.f, d, var) * (1.f / FH) + LN_EPS); off = -mean * rstd;
        __syncwarp();
      }
      TS(2, 5);
      #pragma unroll
      for (int mi = 0; mi < 2; mi++) {
        const float r0 = __shfl_sync(0xffffffffu, rstd, (l & 28) + mi * 2), o0 = __shfl_sync(0xffffffffu, off, (l & 28) + mi * 2);
        const float r1 = __shfl_sync(0xffffffffu, rstd, (l & 28) + mi * 2 + 1), o1 = __shfl_sync(0xffffffffu, off, (l & 28) + mi * 2 + 1);
        #pragma unroll
        for (int jj = 0; jj < 6; jj++) {
          const float* a = &acc[mi][8 * jj];
          stsm4(buf + (jj >> 1) * 8192 + mi * 4096 + rl * 64 + ((((jj & 1) * 2 + (l >> 4)) ^ ((l >> 1) & 3)) << 4),
                pack_bf16(fmaf(a[0], r0, o0), fmaf(a[1], r0, o0)), pack_bf16(fmaf(a[2], r1, o1), fmaf(a[3], r1, o1)),
                pack_bf16(fmaf(a[4], r0, o0), fmaf(a[5], r0, o0)), pack_bf16(fmaf(a[6], r1, o1), fmaf(a[7], r1, o1)));
        }
      }
      fence_async_smem();
      bar_arrive<BAR_PUB1>(160);
      TS(2, 6);
      if (grp == 0) {
        float acc[2][96];
        {
          const bf16* bp = bsp + rb * 128 + w * 16 + (l >> 2);
          const float bb[4] = {__bfloat162float(bp[0]), __bfloat162float(bp[8]), __bfloat162float(bp[64]), __bfloat162float(bp[72])};
          #pragma unroll
          for (int i = 0; i < 96; i++) { acc[0][i] = bb[(i >> 1) & 1]; acc[1][i] = bb[2 + ((i >> 1) & 1)]; }
          pin(acc);
        }
        bar_sync<BAR_ORD2>(256);
        mainloop<192, 1, false, BAR_ORD1>(acc, sbase, 0, 20, 32);
        bar_sync<BAR_Z1>(256);
        drain(acc, sbase, 0, 51);
        TS(2, 7);
        {
          uint32_t z[2][4][4];
          #pragma unroll
          for (int i = 0; i < 4; i++) ldsm4(st_base + (st_x ^ (i << 5)), z[0][i][0], z[0][i][1], z[0][i][2], z[0][i][3]);
          #pragma unroll
          for (int bx = 0; bx < 6; bx++) {
            if (bx < 5) {
              #pragma unroll
              for (int i = 0; i < 4; i++)
                ldsm4(st_base + (bx + 1) * 8192 + (st_x ^ (i << 5)), z[(bx + 1) & 1][i][0], z[(bx + 1) & 1][i][1], z[(bx + 1) & 1][i][2], z[(bx + 1) & 1][i][3]);
            }
            #pragma unroll
            for (int i = 0; i < 4; i++) {
              const float* a = &acc[bx / 3][8 * ((bx % 3) * 4 + i)];
              const uint32_t* zz = z[bx & 1][i];
              stsm4(st_base + bx * 8192 + (st_x ^ (i << 5)),
                    hmul2_bf16(zz[0], pack_bf16(a[0], a[1])), hmul2_bf16(zz[1], pack_bf16(a[2], a[3])),
                    hmul2_bf16(zz[2], pack_bf16(a[4], a[5])), hmul2_bf16(zz[3], pack_bf16(a[6], a[7])));
            }
            if (bx % 3 == 2) {
              fence_async_smem();
              __syncwarp();
              if (l < 3) {
                tma_store_2d(&maps.m[M_HS], buf + (bx - 2 + l) * 8192 + w * 2048, ct * 192 + l * 64, rb * 128 + (bx / 3) * 64 + w * 16);
                bulk_commit();
              }
            }
          }
        }
        TS(2, 8);
        if (l < 3) bulk_wait_all();
        __syncwarp();
        bar_arrive<BAR_PUB1>(160);
        TS(2, 9);
        return;
      }
    } else {
      if (grp == 0) {
        float acc[2][96];
        zero(acc);
        bar_sync<BAR_ORD1>(256);
        mainloop<192, 1, false, BAR_ORD2>(acc, sbase, 0, 10, 10);
        drain(acc, sbase, 0, 19);
        TS(3, 2);
        bar_sync<BAR_BUF>(160);
        #pragma unroll
        for (int mi = 0; mi < 2; mi++)
          #pragma unroll
          for (int jj = 0; jj < 12; jj++) {
            const float* a = &acc[mi][8 * jj];
            stsm4(st_base + mi * 24576 + (jj >> 2) * 8192 + (st_x ^ ((jj & 3) << 5)),
                  pack_bf16(a[0], a[1]), pack_bf16(a[2], a[3]), pack_bf16(a[4], a[5]), pack_bf16(a[6], a[7]));
          }
        __syncwarp();
        TS(3, 3);
        const uint32_t rbase = buf + (l >> 4) * 24576 + gr * 128;
        #pragma unroll 1
        for (int c2 = 0; c2 < 12; c2++) {
          const uint32_t ab = rbase + (c2 >> 2) * 8192;
          uint4 v[2];
          #pragma unroll
          for (int i = 0; i < 2; i++) v[i] = lds128(ab + (((((c2 & 3) * 2 + i) ^ l) & 7) << 4));
          #pragma unroll
          for (int i = 0; i < 2; i++)
            sts128(ab + (((((c2 & 3) * 2 + i) ^ l) & 7) << 4),
                   pack_bf16(gelu_tanh(bf_lo(v[i].x)), gelu_tanh(bf_hi(v[i].x))), pack_bf16(gelu_tanh(bf_lo(v[i].y)), gelu_tanh(bf_hi(v[i].y))),
                   pack_bf16(gelu_tanh(bf_lo(v[i].z)), gelu_tanh(bf_hi(v[i].z))), pack_bf16(gelu_tanh(bf_lo(v[i].w)), gelu_tanh(bf_hi(v[i].w))));
        }
        TS(3, 4);
        bar_arrive<BAR_Z1>(256);
      }
    }
    float acc[2][80];
    if (grp == 1) {
      zero(acc);
      if (wg == 2) {
        bar_sync<BAR_ORD1>(256);
        mainloop<160, 0, false, BAR_ORD2>(acc, sbase, 1, 10, 10);
      } else {
        bar_sync<BAR_ORD2>(256);
        mainloop<160, 0, false, BAR_ORD1>(acc, sbase, 1, 20, 10);
      }
      drain(acc, sbase, 1, wg == 2 ? 19 : 29);
      TS(wg + 1, wg == 1 ? 7 : 2);
      if (wg == 1) bar_sync<BAR_Z1>(256); else bar_sync<BAR_BUF>(160);
      const uint32_t sg = wg == 1 ? 0x80008000u : 0u;
      const uint32_t tb = buf + ((l >> 4) * 8 + (l & 7)) * 128 + (((w * 2 + ((l >> 3) & 1)) ^ (l & 7)) << 4);
      #pragma unroll
      for (int mi = 0; mi < 2; mi++)
        #pragma unroll
        for (int jj = 0; jj < 10; jj++) {
          const float* a = &acc[mi][8 * jj];
          stsm4_t(tb + mi * 20480 + jj * 2048, pack_bf16(a[0], a[1]) ^ sg, pack_bf16(a[2], a[3]) ^ sg, pack_bf16(a[4], a[5]) ^ sg, pack_bf16(a[6], a[7]) ^ sg);
        }
      fence_async_smem();
      if (wg == 1) bar_sync<BAR_WG1>(128); else bar_sync<BAR_WG2>(128);
      TS(wg + 1, wg == 1 ? 8 : 6);
      if (l == 0) {
        #pragma unroll 1
        for (int i = 0; i < 2; i++) {
          tma_store_2d(&maps.m[M_ABS], buf + i * 20480 + w * 5120, rb * 128 + i * 64, (2 - wg) * DM + ct * 160 + w * 40);
          bulk_commit();
        }
        bulk_wait_all();
      }
      __syncwarp();
      TS(wg + 1, wg == 1 ? 9 : 10);
      if (wg == 1) {
        #pragma unroll 1
        for (int i = 0; i < 4; i++) {
          uint4 v[5];
          #pragma unroll
          for (int j = 0; j < 5; j++) {
            const int e = (i * 5 + j) * 128 + t;
            v[j] = ldg128(x + (size_t)(rb * 128 + e / 20) * DM + ct * 160 + (e % 20) * 8);
          }
          #pragma unroll
          for (int j = 0; j < 5; j++) {
            const int e = (i * 5 + j) * 128 + t;
            stg128(out + (size_t)(rb * 128 + e / 20) * DM + ct * 160 + (e % 20) * 8, v[j]);
          }
        }
        bar_arrive<BAR_PUB1>(160);
        return;
      }
      bar_arrive<BAR_PUB2>(160);
      bar_arrive<BAR_Z1>(256);
    }
    zero(acc);
    bar_sync<BAR_ORD1>(256);
    mainloop<160, 0, false, 0>(acc, sbase, grp, grp == 0 ? 52 : 30, grp == 0 ? NX : 64 - NX);
    if (grp == 0) mainloop<160, 2, true, 0>(acc, sbase, 0, 52 + NX, 12);
    const uint32_t slab = buf + w * (16 * 320);
    const uint32_t addr = slab + (((l >> 3) & 1) * 8 + (l & 7)) * 320 + (l >> 4) * 16;
    bar_sync<BAR_BUF>(160);
    drain(acc, sbase, grp, total - 1);
    TS(3, 12);
    #pragma unroll
    for (int mi = 0; mi < 2; mi++) {
      #pragma unroll
      for (int jj = 0; jj < 10; jj++) {
        const float* a = &acc[mi][8 * jj];
        stsm4(addr + mi * 20480 + jj * 32, pack_bf16(a[0], a[1]), pack_bf16(a[2], a[3]), pack_bf16(a[4], a[5]), pack_bf16(a[6], a[7]));
      }
      fence_async_smem();
      __syncwarp();
      if (l == 0) {
        tma_reduce_2d(&maps.m[M_OUT], slab + mi * 20480, ct * 160, rb * 128 + mi * 64 + w * 16);
        bulk_commit();
      }
    }
    TS(3, 13);
    if (l == 0) {
      bulk_wait_read();
      if (w == 0) atomicAdd(&g_done, 1u);
    }
    TS(3, 15);
  }
}

typedef CUresult (*EncodeFn)(CUtensorMap*, CUtensorMapDataType, cuuint32_t, void*, const cuuint64_t*, const cuuint64_t*,
                             const cuuint32_t*, const cuuint32_t*, CUtensorMapInterleave, CUtensorMapSwizzle,
                             CUtensorMapL2promotion, CUtensorMapFloatOOBfill);

void make2d(EncodeFn enc, CUtensorMap* m, const void* p, uint64_t cols, uint64_t rows, uint32_t bc, uint32_t br, bool swz = true) {
  cuuint64_t gd[2] = {cols, rows}, gs[1] = {cols * 2};
  cuuint32_t bd[2] = {bc, br}, es[2] = {1, 1};
  enc(m, CU_TENSOR_MAP_DATA_TYPE_BFLOAT16, 2, const_cast<void*>(p), gd, gs, bd, es, CU_TENSOR_MAP_INTERLEAVE_NONE,
      swz ? CU_TENSOR_MAP_SWIZZLE_128B : CU_TENSOR_MAP_SWIZZLE_NONE, PROMO, CU_TENSOR_MAP_FLOAT_OOB_FILL_NONE);
}
void make3d(EncodeFn enc, CUtensorMap* m, const void* p, uint64_t cols, uint64_t rows, uint32_t cw, uint32_t nc, uint32_t br = 64) {
  cuuint64_t gd[3] = {cw, rows, cols / cw}, gs[2] = {cols * 2, cw * 2};
  cuuint32_t bd[3] = {cw, br, nc}, es[3] = {1, 1, 1};
  enc(m, CU_TENSOR_MAP_DATA_TYPE_BFLOAT16, 3, const_cast<void*>(p), gd, gs, bd, es, CU_TENSOR_MAP_INTERLEAVE_NONE,
      cw == 64 ? CU_TENSOR_MAP_SWIZZLE_128B : CU_TENSOR_MAP_SWIZZLE_64B, PROMO, CU_TENSOR_MAP_FLOAT_OOB_FILL_NONE);
}

}

extern "C" void kernel_launch(void* const* d_in, const int* in_sizes, int n_in, void* d_out, int out_size) {
  const bf16* x = (const bf16*)d_in[0];
  const bf16* wsre = (const bf16*)d_in[1];
  const bf16* wsim = (const bf16*)d_in[2];
  const bf16* wdre = (const bf16*)d_in[3];
  const bf16* wdim = (const bf16*)d_in[4];
  const bf16* win = (const bf16*)d_in[6];
  const bf16* wsp = (const bf16*)d_in[7];
  const bf16* bsp = (const bf16*)d_in[8];
  const bf16* wout = (const bf16*)d_in[9];

  void* fn = nullptr;
  cudaDriverEntryPointQueryResult qr;
  cudaGetDriverEntryPoint("cuTensorMapEncodeTiled", &fn, cudaEnableDefault, &qr);
  EncodeFn enc = (EncodeFn)fn;
  void *abT, *z2, *h, *xn;
  cudaGetSymbolAddress(&xn, g_xn);
  cudaGetSymbolAddress(&abT, g_abT);
  cudaGetSymbolAddress(&z2, g_z2);
  cudaGetSymbolAddress(&h, g_h);

  Maps maps;
  make2d(enc, &maps.m[M_X], x, DM, SEQ, 64, 64);
  make2d(enc, &maps.m[M_XN], xn, DM, SEQ, 64, 64);
  make3d(enc, &maps.m[M_Z232], z2, FH, SEQ, 32, 3, 128);
  make3d(enc, &maps.m[M_WIN32], win, FF, DM, 32, 3);
  make2d(enc, &maps.m[M_WSRE], wsre, SEQ, SEQ, 64, 64);
  make2d(enc, &maps.m[M_WSIM], wsim, SEQ, SEQ, 64, 64);
  make2d(enc, &maps.m[M_WSP], wsp, SEQ, SEQ, 64, 64);
  make2d(enc, &maps.m[M_H], h, FH, SEQ, 64, 64);
  make3d(enc, &maps.m[M_WIN3], win, FF, DM, 64, 3);
  make3d(enc, &maps.m[M_Z23], z2, FH, SEQ, 64, 3);
  make2d(enc, &maps.m[M_WDRE], wdre, DM, DM, 64, 160);
  make2d(enc, &maps.m[M_WDIM], wdim, DM, DM, 64, 160);
  make2d(enc, &maps.m[M_AB], abT, SEQ, 2 * DM, 64, 160);
  make3d(enc, &maps.m[M_WOUT], wout, DM, FH, 32, 5);
  make2d(enc, &maps.m[M_HS], h, FH, SEQ, 64, 16);
  make2d(enc, &maps.m[M_ABS], abT, SEQ, 2 * DM, 64, 40);
  make2d(enc, &maps.m[M_OUT], d_out, DM, SEQ, 160, 16, false);

  cudaFuncSetAttribute(fused_kernel, cudaFuncAttributeMaxDynamicSharedMemorySize, SMEM_BYTES);
  fused_kernel<<<128, 384, SMEM_BYTES>>>(maps, x, win, bsp, (bf16*)d_out);
}
```

```cpp
#include <cuda_runtime.h>
#include <cuda_bf16.h>
#include <cuda.h>
#include <stdint.h>

namespace {

typedef __nv_bfloat16 bf16;

constexpr int SEQ = 2048, DM = 640, FF = 1536, FH = 768;
#define NXV 10
constexpr int NX = NXV;
constexpr int NA = 5;
constexpr int NB_A = 4, NB_B = 5;
constexpr int A_BYTES = 16384;
constexpr int BAR_OFF = 512;
constexpr int READY_OFF = 768;
constexpr int ROWSTAT_OFF = 1024;
constexpr int COLSUM_OFF = 2048;
constexpr int RED_OFF = 2560;
constexpr int RING_OFF = 3072;
constexpr int BRING_OFF = RING_OFF + NA * A_BYTES;
constexpr int BSZ_A = 24576, BSZ_B = 20480;
constexpr int SMEM_BYTES = BRING_OFF + NB_A * BSZ_A + 49152;
constexpr int KB_A = 20 + 32 + NX + 12;
constexpr int KB_B = 30 + 64 - NX;
constexpr float LN_EPS = 1e-5f;
constexpr unsigned POLL_LIMIT = 100000;
#define POLL_NS 100
#define PF_D 8
#define ROT 0
#define Z1_NS 0
#define INFL 2
#define LIM_G 1000
#define MAPV 0
#define PROMO CU_TENSOR_MAP_L2_PROMOTION_L2_128B
#define WATCH_NS 40
#define PF_COND ((kb & 1) == (ct >> 1))
#define WPF 1
#define PF_NS 150

constexpr int BAR_ORD1 = 1, BAR_ORD2 = 2, BAR_WG1 = 3, BAR_WG2 = 4, BAR_LN = 5, BAR_BUF = 6, BAR_Z1 = 7, BAR_PUB1 = 8, BAR_PUB2 = 9, BAR_STATS = 10;

enum { M_X, M_XN, M_WIN32, M_Z232, M_WSRE, M_WSIM, M_WSP, M_H, M_WIN3, M_Z23, M_WDRE, M_WDIM, M_AB, M_WOUT, M_OUT, M_HS, M_ABS, M_COUNT };
struct Maps { CUtensorMap m[M_COUNT]; };

__device__ __align__(1024) bf16 g_abT[2 * DM * SEQ];
__device__ __align__(1024) bf16 g_z2[SEQ * FH];
__device__ __align__(1024) bf16 g_h[SEQ * FH];
__device__ __align__(1024) bf16 g_xn[SEQ * DM];
__device__ __align__(16) uint2 g_xstat[SEQ];
__device__ __align__(16) uint2 g_csum[5 * FH];
__device__ __align__(16) uint2 g_zstat[128 * 128];
__device__ __align__(256) unsigned char g_flags[108 * 256];
constexpr int F_A = 0, F_B = 4, F_Z = 8, F_H = 12, F_XN = 28, F_Y = 44;
__device__ unsigned g_done;
#define TS(role, ev)
#define TC(i)

extern __shared__ __align__(1024) uint8_t smem[];

__device__ __forceinline__ uint32_t smem_u32(const void* p) { return (uint32_t)__cvta_generic_to_shared(p); }
__device__ __forceinline__ void mbar_init(uint32_t bar, uint32_t cnt) { asm volatile("mbarrier.init.shared::cta.b64 [%0], %1;" :: "r"(bar), "r"(cnt)); }
__device__ __forceinline__ void mbar_expect_tx(uint32_t bar, uint32_t bytes) { asm volatile("mbarrier.arrive.expect_tx.shared::cta.b64 _, [%0], %1;" :: "r"(bar), "r"(bytes) : "memory"); }
__device__ __forceinline__ void mbar_arrive(uint32_t bar) { asm volatile("mbarrier.arrive.shared::cta.b64 _, [%0];" :: "r"(bar) : "memory"); }
__device__ __forceinline__ void mbar_arrive_cluster(uint32_t bar, uint32_t cta) {
  asm volatile("{\n.reg .b32 ra;\nmapa.shared::cluster.u32 ra, %0, %1;\nmbarrier.arrive.shared::cluster.b64 _, [ra];\n}" :: "r"(bar), "r"(cta) : "memory");
}
__device__ __forceinline__ void mbar_wait(uint32_t bar, uint32_t parity) {
  asm volatile("{\n.reg .pred p;\n.reg .u32 n;\nmov.u32 n, 0;\n"
               "LW: mbarrier.try_wait.parity.shared::cta.b64 p, [%0], %1, 2000;\n@p bra LD;\n"
               "add.u32 n, n, 1;\nsetp.lt.u32 p, n, 20000;\n@p bra LW;\nLD:\n}" :: "r"(bar), "r"(parity) : "memory");
}
__device__ __forceinline__ void tma_load_2d(uint32_t dst, const CUtensorMap* map, uint32_t bar, int c0, int c1) {
  asm volatile("cp.async.bulk.tensor.2d.shared::cluster.global.mbarrier::complete_tx::bytes [%0], [%1, {%3, %4}], [%2];"
    :: "r"(dst), "l"((uint64_t)map), "r"(bar), "r"(c0), "r"(c1) : "memory");
}
__device__ __forceinline__ void tma_load_3d(uint32_t dst, const CUtensorMap* map, uint32_t bar, int c0, int c1, int c2) {
  asm volatile("cp.async.bulk.tensor.3d.shared::cluster.global.mbarrier::complete_tx::bytes [%0], [%1, {%3, %4, %5}], [%2];"
    :: "r"(dst), "l"((uint64_t)map), "r"(bar), "r"(c0), "r"(c1), "r"(c2) : "memory");
}
__device__ __forceinline__ void tma_load_2d_mc(uint32_t dst, const CUtensorMap* map, uint32_t bar, int c0, int c1, uint16_t mask) {
  asm volatile("cp.async.bulk.tensor.2d.shared::cluster.global.mbarrier::complete_tx::bytes.multicast::cluster [%0], [%1, {%3, %4}], [%2], %5;"
    :: "r"(dst), "l"((uint64_t)map), "r"(bar), "r"(c0), "r"(c1), "h"(mask) : "memory");
}
__device__ __forceinline__ void tma_store_2d(const CUtensorMap* map, uint32_t src, int c0, int c1) {
  asm volatile("cp.async.bulk.tensor.2d.global.shared::cta.bulk_group [%0, {%2, %3}], [%1];"
    :: "l"((uint64_t)map), "r"(src), "r"(c0), "r"(c1) : "memory");
}
__device__ __forceinline__ void tma_store_3d(const CUtensorMap* map, uint32_t src, int c0, int c1, int c2) {
  asm volatile("cp.async.bulk.tensor.3d.global.shared::cta.bulk_group [%0, {%2, %3, %4}], [%1];"
    :: "l"((uint64_t)map), "r"(src), "r"(c0), "r"(c1), "r"(c2) : "memory");
}
__device__ __forceinline__ void tma_reduce_2d(const CUtensorMap* map, uint32_t src, int c0, int c1) {
  asm volatile("cp.reduce.async.bulk.tensor.2d.global.shared::cta.add.tile.bulk_group [%0, {%2, %3}], [%1];"
    :: "l"((uint64_t)map), "r"(src), "r"(c0), "r"(c1) : "memory");
}
__device__ __forceinline__ void bulk_wait_all() { asm volatile("cp.async.bulk.wait_group 0;" ::: "memory"); }
__device__ __forceinline__ void bulk_commit() { asm volatile("cp.async.bulk.commit_group;" ::: "memory"); }
__device__ __forceinline__ void bulk_wait_read() { asm volatile("cp.async.bulk.wait_group.read 0;" ::: "memory"); }
__device__ __forceinline__ void fence_async_smem() { asm volatile("fence.proxy.async.shared::cta;" ::: "memory"); }
__device__ __forceinline__ void fence_async_global() { asm volatile("fence.proxy.async.global;" ::: "memory"); }
__device__ __forceinline__ void wgmma_fence() { asm volatile("wgmma.fence.sync.aligned;" ::: "memory"); }
__device__ __forceinline__ void wgmma_commit() { asm volatile("wgmma.commit_group.sync.aligned;" ::: "memory"); }
template<int N> __device__ __forceinline__ void wgmma_wait() { asm volatile("wgmma.wait_group.sync.aligned %0;" :: "n"(N) : "memory"); }
template<int ID> __device__ __forceinline__ void bar_sync(int n) { asm volatile("bar.sync %0, %1;" :: "n"(ID), "r"(n) : "memory"); }
template<int ID> __device__ __forceinline__ void bar_arrive(int n) { asm volatile("bar.arrive %0, %1;" :: "n"(ID), "r"(n) : "memory"); }
__device__ __forceinline__ void cluster_wait() { asm volatile("barrier.cluster.wait.aligned;" ::: "memory"); }
__device__ __forceinline__ uint64_t desc64(uint32_t lo, uint32_t hi) { return (uint64_t)lo | ((uint64_t)hi << 32); }
__device__ __forceinline__ uint4 ld_vol4(const uint4* p) {
  uint4 v; asm volatile("ld.relaxed.gpu.global.v4.u32 {%0,%1,%2,%3}, [%4];" : "=r"(v.x), "=r"(v.y), "=r"(v.z), "=r"(v.w) : "l"(p) : "memory"); return v;
}
__device__ __forceinline__ uint2 ld_vol2(const uint2* p) {
  uint2 v; asm volatile("ld.relaxed.gpu.global.v2.u32 {%0,%1}, [%2];" : "=r"(v.x), "=r"(v.y) : "l"(p) : "memory"); return v;
}
__device__ __forceinline__ void st_vol4(uint4* p, uint32_t a, uint32_t b, uint32_t c, uint32_t d) {
  asm volatile("st.relaxed.gpu.global.v4.u32 [%0], {%1,%2,%3,%4};" :: "l"(p), "r"(a), "r"(b), "r"(c), "r"(d) : "memory");
}
__device__ __forceinline__ void st_vol2(uint2* p, uint32_t a, uint32_t b) {
  asm volatile("st.relaxed.gpu.global.v2.u32 [%0], {%1,%2};" :: "l"(p), "r"(a), "r"(b) : "memory");
}
__device__ __forceinline__ void stg128(void* p, uint4 v) {
  asm volatile("st.global.v4.u32 [%0], {%1,%2,%3,%4};" :: "l"(p), "r"(v.x), "r"(v.y), "r"(v.z), "r"(v.w));
}
__device__ __forceinline__ unsigned ld_relaxed(const unsigned* p) {
  unsigned v; asm volatile("ld.relaxed.gpu.global.u32 %0, [%1];" : "=r"(v) : "l"(p) : "memory"); return v;
}
__device__ __forceinline__ uint32_t pack_bf16(float lo, float hi) {
  uint32_t r; asm("cvt.rn.bf16x2.f32 %0, %1, %2;" : "=r"(r) : "f"(hi), "f"(lo)); return r;
}
__device__ __forceinline__ float bf_lo(uint32_t v) { return __uint_as_float(v << 16); }
__device__ __forceinline__ float bf_hi(uint32_t v) { return __uint_as_float(v & 0xFFFF0000u); }
__device__ __forceinline__ void stsm4(uint32_t addr, uint32_t a, uint32_t b, uint32_t c, uint32_t d) {
  asm volatile("stmatrix.sync.aligned.m8n8.x4.shared.b16 [%0], {%1,%2,%3,%4};" :: "r"(addr), "r"(a), "r"(b), "r"(c), "r"(d));
}
__device__ __forceinline__ void stsm4_t(uint32_t addr, uint32_t a, uint32_t b, uint32_t c, uint32_t d) {
  asm volatile("stmatrix.sync.aligned.m8n8.x4.trans.shared.b16 [%0], {%1,%2,%3,%4};" :: "r"(addr), "r"(a), "r"(b), "r"(c), "r"(d));
}
__device__ __forceinline__ void ldsm4(uint32_t addr, uint32_t& a, uint32_t& b, uint32_t& c, uint32_t& d) {
  asm volatile("ldmatrix.sync.aligned.m8n8.x4.shared.b16 {%0,%1,%2,%3}, [%4];" : "=r"(a), "=r"(b), "=r"(c), "=r"(d) : "r"(addr));
}
__device__ __forceinline__ uint4 lds128(uint32_t a) {
  uint4 v; asm volatile("ld.shared.v4.u32 {%0,%1,%2,%3}, [%4];" : "=r"(v.x), "=r"(v.y), "=r"(v.z), "=r"(v.w) : "r"(a)); return v;
}
__device__ __forceinline__ void sts128(uint32_t a, uint32_t x, uint32_t y, uint32_t z, uint32_t w) {
  asm volatile("st.shared.v4.u32 [%0], {%1,%2,%3,%4};" :: "r"(a), "r"(x), "r"(y), "r"(z), "r"(w));
}
__device__ __forceinline__ uint32_t hmul2_bf16(uint32_t a, uint32_t b) {
  uint32_t r; asm("mul.rn.bf16x2 %0, %1, %2;" : "=r"(r) : "r"(a), "r"(b)); return r;
}
__device__ __forceinline__ float gelu_tanh(float v) {
  float u = v * fmaf(0.0356774081f, v * v, 0.7978845608f);
  float t; asm("tanh.approx.f32 %0, %1;" : "=f"(t) : "f"(u));
  float hv = 0.5f * v;
  return fmaf(hv, t, hv);
}

template<int TB>
__device__ __forceinline__ void wgmma_n192(float (&d)[96], uint64_t da, uint64_t db, int scale_d) {
  asm volatile("{\n.reg .pred p;\nsetp.ne.b32 p, %98, 0;\n"
   "wgmma.mma_async.sync.aligned.m64n192k16.f32.bf16.bf16 {%0,%1,%2,%3,%4,%5,%6,%7,%8,%9,%10,%11,%12,%13,%14,%15,%16,%17,%18,%19,%20,%21,%22,%23,%24,%25,%26,%27,%28,%29,%30,%31,%32,%33,%34,%35,%36,%37,%38,%39,%40,%41,%42,%43,%44,%45,%46,%47,%48,%49,%50,%51,%52,%53,%54,%55,%56,%57,%58,%59,%60,%61,%62,%63,%64,%65,%66,%67,%68,%69,%70,%71,%72,%73,%74,%75,%76,%77,%78,%79,%80,%81,%82,%83,%84,%85,%86,%87,%88,%89,%90,%91,%92,%93,%94,%95}, %96, %97, p, 1, 1, 0, %99;\n}"
   : "+f"(d[0]),"+f"(d[1]),"+f"(d[2]),"+f"(d[3]),"+f"(d[4]),"+f"(d[5]),"+f"(d[6]),"+f"(d[7]),"+f"(d[8]),"+f"(d[9]),"+f"(d[10]),"+f"(d[11]),"+f"(d[12]),"+f"(d[13]),"+f"(d[14]),"+f"(d[15]),"+f"(d[16]),"+f"(d[17]),"+f"(d[18]),"+f"(d[19]),"+f"(d[20]),"+f"(d[21]),"+f"(d[22]),"+f"(d[23]),"+f"(d[24]),"+f"(d[25]),"+f"(d[26]),"+f"(d[27]),"+f"(d[28]),"+f"(d[29]),"+f"(d[30]),"+f"(d[31]),"+f"(d[32]),"+f"(d[33]),"+f"(d[34]),"+f"(d[35]),"+f"(d[36]),"+f"(d[37]),"+f"(d[38]),"+f"(d[39]),"+f"(d[40]),"+f"(d[41]),"+f"(d[42]),"+f"(d[43]),"+f"(d[44]),"+f"(d[45]),"+f"(d[46]),"+f"(d[47]),"+f"(d[48]),"+f"(d[49]),"+f"(d[50]),"+f"(d[51]),"+f"(d[52]),"+f"(d[53]),"+f"(d[54]),"+f"(d[55]),"+f"(d[56]),"+f"(d[57]),"+f"(d[58]),"+f"(d[59]),"+f"(d[60]),"+f"(d[61]),"+f"(d[62]),"+f"(d[63]),"+f"(d[64]),"+f"(d[65]),"+f"(d[66]),"+f"(d[67]),"+f"(d[68]),"+f"(d[69]),"+f"(d[70]),"+f"(d[71]),"+f"(d[72]),"+f"(d[73]),"+f"(d[74]),"+f"(d[75]),"+f"(d[76]),"+f"(d[77]),"+f"(d[78]),"+f"(d[79]),"+f"(d[80]),"+f"(d[81]),"+f"(d[82]),"+f"(d[83]),"+f"(d[84]),"+f"(d[85]),"+f"(d[86]),"+f"(d[87]),"+f"(d[88]),"+f"(d[89]),"+f"(d[90]),"+f"(d[91]),"+f"(d[92]),"+f"(d[93]),"+f"(d[94]),"+f"(d[95])
   : "l"(da), "l"(db), "r"(scale_d), "n"(TB));
}
template<int TB>
__device__ __forceinline__ void wgmma_n160(float (&d)[80], uint64_t da, uint64_t db, int scale_d) {
  asm volatile("{\n.reg .pred p;\nsetp.ne.b32 p, %82, 0;\n"
   "wgmma.mma_async.sync.aligned.m64n160k16.f32.bf16.bf16 {%0,%1,%2,%3,%4,%5,%6,%7,%8,%9,%10,%11,%12,%13,%14,%15,%16,%17,%18,%19,%20,%21,%22,%23,%24,%25,%26,%27,%28,%29,%30,%31,%32,%33,%34,%35,%36,%37,%38,%39,%40,%41,%42,%43,%44,%45,%46,%47,%48,%49,%50,%51,%52,%53,%54,%55,%56,%57,%58,%59,%60,%61,%62,%63,%64,%65,%66,%67,%68,%69,%70,%71,%72,%73,%74,%75,%76,%77,%78,%79}, %80, %81, p, 1, 1, 0, %83;\n}"
   : "+f"(d[0]),"+f"(d[1]),"+f"(d[2]),"+f"(d[3]),"+f"(d[4]),"+f"(d[5]),"+f"(d[6]),"+f"(d[7]),"+f"(d[8]),"+f"(d[9]),"+f"(d[10]),"+f"(d[11]),"+f"(d[12]),"+f"(d[13]),"+f"(d[14]),"+f"(d[15]),"+f"(d[16]),"+f"(d[17]),"+f"(d[18]),"+f"(d[19]),"+f"(d[20]),"+f"(d[21]),"+f"(d[22]),"+f"(d[23]),"+f"(d[24]),"+f"(d[25]),"+f"(d[26]),"+f"(d[27]),"+f"(d[28]),"+f"(d[29]),"+f"(d[30]),"+f"(d[31]),"+f"(d[32]),"+f"(d[33]),"+f"(d[34]),"+f"(d[35]),"+f"(d[36]),"+f"(d[37]),"+f"(d[38]),"+f"(d[39]),"+f"(d[40]),"+f"(d[41]),"+f"(d[42]),"+f"(d[43]),"+f"(d[44]),"+f"(d[45]),"+f"(d[46]),"+f"(d[47]),"+f"(d[48]),"+f"(d[49]),"+f"(d[50]),"+f"(d[51]),"+f"(d[52]),"+f"(d[53]),"+f"(d[54]),"+f"(d[55]),"+f"(d[56]),"+f"(d[57]),"+f"(d[58]),"+f"(d[59]),"+f"(d[60]),"+f"(d[61]),"+f"(d[62]),"+f"(d[63]),"+f"(d[64]),"+f"(d[65]),"+f"(d[66]),"+f"(d[67]),"+f"(d[68]),"+f"(d[69]),"+f"(d[70]),"+f"(d[71]),"+f"(d[72]),"+f"(d[73]),"+f"(d[74]),"+f"(d[75]),"+f"(d[76]),"+f"(d[77]),"+f"(d[78]),"+f"(d[79])
   : "l"(da), "l"(db), "r"(scale_d), "n"(TB));
}
template<int TB>
__device__ __forceinline__ void wgmma_n96(float (&d)[48], uint64_t da, uint64_t db, int scale_d) {
  asm volatile("{\n.reg .pred p;\nsetp.ne.b32 p, %50, 0;\n"
   "wgmma.mma_async.sync.aligned.m64n96k16.f32.bf16.bf16 {%0,%1,%2,%3,%4,%5,%6,%7,%8,%9,%10,%11,%12,%13,%14,%15,%16,%17,%18,%19,%20,%21,%22,%23,%24,%25,%26,%27,%28,%29,%30,%31,%32,%33,%34,%35,%36,%37,%38,%39,%40,%41,%42,%43,%44,%45,%46,%47}, %48, %49, p, 1, 1, 0, %51;\n}"
   : "+f"(d[0]),"+f"(d[1]),"+f"(d[2]),"+f"(d[3]),"+f"(d[4]),"+f"(d[5]),"+f"(d[6]),"+f"(d[7]),"+f"(d[8]),"+f"(d[9]),"+f"(d[10]),"+f"(d[11]),"+f"(d[12]),"+f"(d[13]),"+f"(d[14]),"+f"(d[15]),"+f"(d[16]),"+f"(d[17]),"+f"(d[18]),"+f"(d[19]),"+f"(d[20]),"+f"(d[21]),"+f"(d[22]),"+f"(d[23]),"+f"(d[24]),"+f"(d[25]),"+f"(d[26]),"+f"(d[27]),"+f"(d[28]),"+f"(d[29]),"+f"(d[30]),"+f"(d[31]),"+f"(d[32]),"+f"(d[33]),"+f"(d[34]),"+f"(d[35]),"+f"(d[36]),"+f"(d[37]),"+f"(d[38]),"+f"(d[39]),"+f"(d[40]),"+f"(d[41]),"+f"(d[42]),"+f"(d[43]),"+f"(d[44]),"+f"(d[45]),"+f"(d[46]),"+f"(d[47])
   : "l"(da), "l"(db), "r"(scale_d), "n"(TB));
}

template<int N, int TB>
__device__ __forceinline__ void wgmma_n(float (&d)[N / 2], uint64_t da, uint64_t db) {
  if constexpr (N == 192) wgmma_n192<TB>(d, da, db, 1);
  else if constexpr (N == 160) wgmma_n160<TB>(d, da, db, 1);
  else wgmma_n96<TB>(d, da, db, 1);
}

template<int R>
__device__ __forceinline__ void pin(float (&acc)[2][R]) {
  #pragma unroll
  for (int mi = 0; mi < 2; mi++)
    #pragma unroll
    for (int i = 0; i < R; i++) asm volatile("" : "+f"(acc[mi][i]) :: "memory");
}
template<int R>
__device__ __forceinline__ void zero(float (&acc)[2][R]) {
  #pragma unroll
  for (int i = 0; i < R; i++) { acc[0][i] = 0.f; acc[1][i] = 0.f; }
  pin(acc);
}

__device__ __forceinline__ void release(uint32_t sbase, int t, int sa, int sb, bool rel_a, bool rel_b) {
  if (t < 2) { if (rel_a) mbar_arrive_cluster(sbase + BAR_OFF + 40 + 8 * sa, t); }
  else if (t == 2 && rel_b) mbar_arrive(sbase + BAR_OFF + 120 + 8 * sb);
}
template<int N, int TB, bool CONT, int ORD_BAR>
__device__ __forceinline__ void mainloop(float (&acc)[2][N / 2], uint32_t sbase, int grp, int g0, int nk) {
  const uint32_t fullA = sbase + BAR_OFF, fullB = fullA + 80;
  const int nb = grp == 0 ? NB_A : NB_B, total = grp == 0 ? KB_A : KB_B;
  const uint32_t bstep = (grp == 0 ? BSZ_A : BSZ_B) >> 4;
  const int t = threadIdx.x & 127;
  const uint32_t da0 = (((sbase + RING_OFF) & 0x3FFFF) >> 4) | 0x10000u;
  const uint32_t db0 = (((sbase + BRING_OFF) & 0x3FFFF) >> 4) | ((TB == 2 ? 256u : TB ? 512u : 1u) << 16);
  constexpr uint32_t HI_A = 0x40000040u, HI_B = TB == 2 ? 0x80000020u : 0x40000040u;
  int sa = g0 % NA, pa = (g0 / NA) & 1, psa = sa == 0 ? NA - 1 : sa - 1;
  int sb = g0 % nb, pb = (g0 / nb) & 1, psb = sb == 0 ? nb - 1 : sb - 1;
  #pragma unroll 1
  for (int g = g0; g < g0 + nk; g++) {
    const uint32_t da = da0 + sa * (A_BYTES >> 4), db = db0 + sb * bstep;
    mbar_wait(fullB + 8 * sb, pb);
    mbar_wait(fullA + 8 * sa, pa);
    wgmma_fence();
    #pragma unroll
    for (int k = 0; k < 4; k++) {
      const uint64_t dbk = desc64(db + (TB == 2 ? k * 64 : TB ? k * 128 : k * 2), HI_B);
      wgmma_n<N, TB != 0>(acc[0], desc64(da + k * 2, HI_A), dbk);
      wgmma_n<N, TB != 0>(acc[1], desc64(da + 512 + k * 2, HI_A), dbk);
    }
    wgmma_commit();
    if (ORD_BAR != 0 && g == g0 + nk - 1) bar_arrive<ORD_BAR>(256);
    wgmma_wait<1>();
    if (CONT || g > g0) release(sbase, t, psa, psb, g - 1 + NA < total, true);
    psa = sa; psb = sb;
    if (++sa == NA) { sa = 0; pa ^= 1; }
    if (++sb == nb) { sb = 0; pb ^= 1; }
  }
}
template<int R>
__device__ __forceinline__ void drain(float (&acc)[2][R], uint32_t sbase, int grp, int glast) {
  wgmma_wait<0>();
  pin(acc);
  release(sbase, threadIdx.x & 127, glast % NA, glast % (grp == 0 ? NB_A : NB_B), glast + NA < (grp == 0 ? KB_A : KB_B), true);
}

__device__ __forceinline__ void set_flag(int slot, int byte, unsigned epoch) {
  asm volatile("st.relaxed.gpu.global.u8 [%0], %1;" :: "l"(g_flags + slot * 256 + byte), "r"(epoch & 255u) : "memory");
}
__device__ __forceinline__ unsigned get_flag(int slot, int byte) {
  unsigned v; asm volatile("ld.relaxed.gpu.global.u8 %0, [%1];" : "=r"(v) : "l"(g_flags + slot * 256 + byte) : "memory"); return v;
}
__device__ __forceinline__ void publish(int slot, int byte, unsigned epoch) {
  asm volatile("fence.acq_rel.gpu;" ::: "memory");
  set_flag(slot, byte, epoch);
}

__device__ __forceinline__ float sum8(uint4 v) {
  return ((bf_lo(v.x) + bf_hi(v.x)) + (bf_lo(v.y) + bf_hi(v.y))) + ((bf_lo(v.z) + bf_hi(v.z)) + (bf_lo(v.w) + bf_hi(v.w)));
}
__device__ __forceinline__ uint4 ldg128(const void* p) {
  uint4 v; asm volatile("ld.global.nc.v4.u32 {%0,%1,%2,%3}, [%4];" : "=r"(v.x), "=r"(v.y), "=r"(v.z), "=r"(v.w) : "l"(p)); return v;
}
__device__ __forceinline__ void ln_load(const bf16* __restrict__ x, int cta, uint4 (&rv)[5]) {
  const int t = threadIdx.x - 128, row = cta * 16 + (t >> 4), c = t & 15;
  #pragma unroll
  for (int j = 0; j < 5; j++) rv[j] = ldg128(reinterpret_cast<const uint4*>(x + (size_t)row * DM) + c + 16 * j);
}
__device__ __forceinline__ void ln_rows(const uint4 (&rv)[5], int cta, unsigned epoch) {
  const int t = threadIdx.x - 128, row = cta * 16 + (t >> 4), c = t & 15;
  const float sh = __shfl_sync(0xffffffffu, bf_lo(rv[0].x), t & 16);
  float d[40], s = 0.f, q = 0.f;
  #pragma unroll
  for (int j = 0; j < 5; j++) {
    const uint32_t u[4] = {rv[j].x, rv[j].y, rv[j].z, rv[j].w};
    #pragma unroll
    for (int e = 0; e < 4; e++) {
      const float d0 = bf_lo(u[e]) - sh, d1 = bf_hi(u[e]) - sh;
      d[j * 8 + e * 2] = d0; d[j * 8 + e * 2 + 1] = d1;
      s += d0 + d1; q = fmaf(d0, d0, q); q = fmaf(d1, d1, q);
    }
  }
  #pragma unroll
  for (int o = 1; o < 16; o <<= 1) { s += __shfl_xor_sync(0xffffffffu, s, o); q += __shfl_xor_sync(0xffffffffu, q, o); }
  const float md = s * (1.f / DM);
  const float r = rsqrtf(fmaxf(fmaf(q, 1.f / DM, -md * md), 0.f) + LN_EPS), o = -md * r;
  if (c == 0) st_vol2(&g_xstat[row], __float_as_uint(r), (__float_as_uint(-(md + sh) * r) & ~255u) | (epoch & 255u));
  #pragma unroll
  for (int j = 0; j < 5; j++) {
    const float* a = &d[j * 8];
    stg128(reinterpret_cast<uint4*>(g_xn + (size_t)row * DM) + c + 16 * j, make_uint4(
           pack_bf16(fmaf(a[0], r, o), fmaf(a[1], r, o)), pack_bf16(fmaf(a[2], r, o), fmaf(a[3], r, o)),
           pack_bf16(fmaf(a[4], r, o), fmaf(a[5], r, o)), pack_bf16(fmaf(a[6], r, o), fmaf(a[7], r, o))));
  }
  bar_arrive<BAR_LN>(288);
}
__device__ __forceinline__ void colsum_part(const bf16* __restrict__ win, int cta, unsigned epoch) {
  const int t = threadIdx.x & 127, w = t >> 5, l = t & 31;
  const int cj = min(cta, 119), cg = cj % 24, rg = cj / 24;
  uint4 cv[4];
  #pragma unroll
  for (int j = 0; j < 4; j++) cv[j] = ldg128(reinterpret_cast<const uint4*>(win + (size_t)(rg * 128 + w * 32 + j * 8 + (l >> 2)) * FF + FH + cg * 32) + (l & 3));
  float v[8];
  v[0] = (bf_lo(cv[0].x) + bf_lo(cv[1].x)) + (bf_lo(cv[2].x) + bf_lo(cv[3].x)); v[1] = (bf_hi(cv[0].x) + bf_hi(cv[1].x)) + (bf_hi(cv[2].x) + bf_hi(cv[3].x));
  v[2] = (bf_lo(cv[0].y) + bf_lo(cv[1].y)) + (bf_lo(cv[2].y) + bf_lo(cv[3].y)); v[3] = (bf_hi(cv[0].y) + bf_hi(cv[1].y)) + (bf_hi(cv[2].y) + bf_hi(cv[3].y));
  v[4] = (bf_lo(cv[0].z) + bf_lo(cv[1].z)) + (bf_lo(cv[2].z) + bf_lo(cv[3].z)); v[5] = (bf_hi(cv[0].z) + bf_hi(cv[1].z)) + (bf_hi(cv[2].z) + bf_hi(cv[3].z));
  v[6] = (bf_lo(cv[0].w) + bf_lo(cv[1].w)) + (bf_lo(cv[2].w) + bf_lo(cv[3].w)); v[7] = (bf_hi(cv[0].w) + bf_hi(cv[1].w)) + (bf_hi(cv[2].w) + bf_hi(cv[3].w));
  #pragma unroll
  for (int st = 0; st < 3; st++) {
    const int n = 4 >> st;
    const bool up = (l & (4 * n)) != 0;
    #pragma unroll
    for (int e = 0; e < 4; e++)
      if (e < n) { const float keep = up ? v[e + n] : v[e], send = up ? v[e] : v[e + n]; v[e] = keep + __shfl_xor_sync(0xffffffffu, send, 4 * n); }
  }
  float* red = reinterpret_cast<float*>(smem + RED_OFF);
  red[w * 32 + (l & 3) * 8 + (l >> 2)] = v[0];
  bar_sync<BAR_WG2>(128);
  if (t < 32) st_vol2(&g_csum[rg * FH + cg * 32 + t], __float_as_uint((red[t] + red[32 + t]) + (red[64 + t] + red[96 + t])), epoch);
}

__device__ __forceinline__ void a_entry(int g, int grp, int rb, int& mi, int& kb) {
  if (g < 10) { mi = M_X; kb = g; }
  else if (g < 20) { mi = M_XN; kb = g - 10; }
  else if (grp == 0) {
    if (g < 52) { mi = M_WSP; kb = (g - 20); }
    else if (g < 52 + NX) { mi = M_WSIM; kb = g - 52 + 32 - NX; }
    else { mi = M_H; kb = g - 52 - NX; }
  } else {
    if (g < 30) { mi = M_XN; kb = g - 20; }
    else if (g < 62) { mi = M_WSRE; kb = (g - 30); }
    else { mi = M_WSIM; kb = g - 62; }
  }
}

__global__ void __cluster_dims__(2, 1, 1) __launch_bounds__(384, 1)
fused_kernel(const __grid_constant__ Maps maps, const bf16* __restrict__ x, const bf16* __restrict__ win, const bf16* __restrict__ bsp,
             bf16* __restrict__ out) {
  const uint32_t sbase = smem_u32(smem);
  const uint32_t fullA = sbase + BAR_OFF, emptyA = fullA + 40, fullB = fullA + 80, emptyB = fullA + 120, dep0 = fullA + 160;
  const int tid = threadIdx.x, wg = __shfl_sync(0xffffffffu, tid >> 7, 0);
  const int rank = blockIdx.x & 1;
  const int grp = (blockIdx.x >> 1) & 1, half = (blockIdx.x >> 2) & 1, rb = blockIdx.x >> 3;
  const int ct = half * 2 + rank, c8 = grp * 4 + ct;
  const int cta = rb * 8 + half * 4 + grp * 2 + rank;
  const int total = grp == 0 ? KB_A : KB_B;
  const uint32_t bsz = grp == 0 ? BSZ_A : BSZ_B;
  const int nb = grp == 0 ? NB_A : NB_B;
  const uint32_t buf = sbase + BRING_OFF + nb * bsz;

  uint4 rv[5];
  if (wg != 0) ln_load(x, cta, rv);
  if (wg == 2) {
    const int t = tid & 127;
    if (t < 60) asm volatile("prefetch.global.L2 [%0];" :: "l"(win + (size_t)(cta * 5 + t / 12) * FF + FH + (t % 12) * 64));
  }
  const unsigned epoch = (ld_relaxed(&g_done) >> 7) + 1u;
  if (tid == 0) {
    TS(0, 0);
    for (int s = 0; s < 25; s++) mbar_init(fullA + 8 * s, (s >= 5 && s < 10) ? 2 : 1);
    *reinterpret_cast<volatile int*>(smem + READY_OFF) = 0;
    asm volatile("fence.mbarrier_init.release.cluster;" ::: "memory");
  }
  __syncthreads();
  asm volatile("barrier.cluster.arrive.relaxed.aligned;" ::: "memory");

  if (wg == 0) {
    asm volatile("setmaxnreg.dec.sync.aligned.u32 40;");
    const int warp = tid >> 5, lane = tid & 31;
    if (warp == 0) {
      const int row = rb * 128;
      if (lane == 0) {
        for (int g = 0; g < NA; g++) {
          mbar_expect_tx(fullA + 8 * g, A_BYTES);
          tma_load_2d(sbase + RING_OFF + g * A_BYTES, &maps.m[M_X], fullA + 8 * g, g * 64, row);
          tma_load_2d(sbase + RING_OFF + g * A_BYTES + 8192, &maps.m[M_X], fullA + 8 * g, g * 64, row + 64);
        }
      }
      __syncwarp();
      cluster_wait();
      if (lane == 0) {
        int s = 0, ph = 0;
        #pragma unroll 1
        for (int g = NA; g < total; g++) {
          int mi, kb;
          a_entry(g, grp, rb, mi, kb);
          if (g == 10 || (mi == M_H && kb == 0)) { TS(0, g > 10 ? 3 : 1); mbar_wait(dep0 + (g > 10 ? 24 : 0), 0); fence_async_global(); TS(0, g > 10 ? 4 : 2); }
          mbar_wait(emptyA + 8 * s, ph);
          mbar_expect_tx(fullA + 8 * s, A_BYTES);
          tma_load_2d_mc(sbase + RING_OFF + s * A_BYTES + rank * 8192, &maps.m[mi], fullA + 8 * s, kb * 64, row + rank * 64, 3);
          if (++s == NA) { s = 0; ph ^= 1; }
          if (g + PF_D < total) {
            a_entry(g + PF_D, grp, rb, mi, kb);
            if (mi >= M_WSRE && mi <= M_WSP && PF_COND)
              asm volatile("cp.async.bulk.prefetch.tensor.2d.L2.global.tile [%0, {%1, %2}];" :: "l"((uint64_t)&maps.m[mi]), "r"(kb * 64), "r"(row + rank * 64) : "memory");
          }
        }
        TS(0, 5);
      }
    } else if (warp == 1) {
      if (lane == 0) {
        int s = 0, ph = 1;
        int have = 0;
        #pragma unroll 1
        for (int g = 0; g < total; g++) {
          int kind = 1, mi, kb, c, dep = 0, need = 0;
          uint32_t bytes = 20480;
          if (g < 10) { kind = 0; mi = M_WIN32; kb = g; c = 24 + 3 * c8; bytes = 12288; }
          else if (grp == 0) {
            if (g < 20) { kind = 0; mi = M_WIN3; kb = g - 10; c = 3 * ct; bytes = 24576; }
            else if (g < 52) { kind = 0; mi = M_Z23; kb = (g - 20); c = 3 * ct; bytes = 24576; need = ((g - 20) >> 1) + 1; }
            else if (g < 52 + NX) { mi = M_AB; kb = g - 52 + 32 - NX; c = DM + ct * 160; dep = g == 52 ? 2 : 0; }
            else { kind = 0; mi = M_WOUT; kb = g - 52 - NX; c = ct * 5; }
          } else {
            if (g < 30) { mi = g < 20 ? M_WDRE : M_WDIM; kb = g < 20 ? g - 10 : g - 20; c = ct * 160; }
            else if (g < 62) { mi = M_AB; kb = (g - 30); c = ct * 160; need = ((g - 30) >> 1) + 1; }
            else { mi = M_AB; kb = g - 62; c = ct * 160 + DM; dep = g == 62 ? 2 : 0; }
          }
          if (need > have) {
            if (need == 1) TS(1, 0);
            unsigned it = 0;
            while ((have = *reinterpret_cast<volatile int*>(smem + READY_OFF)) < need && ++it < 50 * POLL_LIMIT) {}
            fence_async_global();
            if (need == 1) { TS(1, 1); TC(1); }
          }
          if (dep) { TS(1, dep * 2 - 2); mbar_wait(dep0 + 8 * dep, 0); fence_async_global(); TS(1, dep * 2 - 1); TC(dep); }
          const uint32_t dst = sbase + BRING_OFF + s * bsz, fb = fullB + 8 * s;
          mbar_wait(emptyB + 8 * s, ph);
          if (++s == nb) { s = 0; ph ^= 1; }
          mbar_expect_tx(fb, bytes);
          if (kind == 0) tma_load_3d(dst, &maps.m[mi], fb, 0, kb * 64, c);
          else tma_load_2d(dst, &maps.m[mi], fb, kb * 64, c);
        }
      }
      __syncwarp();
      cluster_wait();
    } else if (warp == 2) {
      if (lane < M_COUNT) asm volatile("prefetch.tensormap [%0];" :: "l"((uint64_t)&maps.m[lane]) : "memory");
      cluster_wait();
      {
        unsigned it = 0;
        uint2 v[4];
        while (true) {
          bool ok = true;
          #pragma unroll
          for (int i = 0; i < 4; i++) { v[i] = ld_vol2(&g_xstat[rb * 128 + i * 32 + lane]); ok = ok && ((v[i].y ^ epoch) & 255u) == 0; }
          if (ok || ++it > POLL_LIMIT) break;
          __nanosleep(POLL_NS);
        }
        #pragma unroll
        for (int i = 0; i < 4; i++) reinterpret_cast<uint2*>(smem + ROWSTAT_OFF)[i * 32 + lane] = make_uint2(v[i].x, v[i].y & ~255u);
        __syncwarp();
        TS(0, 6);
        bar_arrive<BAR_STATS>(192);
      }
      #pragma unroll 1
      for (int d = 0; d < 5; d++) {
        if (d == 3 && grp == 1) continue;
        const int slot = d == 0 ? F_XN + rb : d == 4 ? F_Y + rb * 4 + ct : d == 3 ? F_H + rb : d == 2 ? F_B + ct : grp == 0 ? F_Z + ct : F_A + ct;
        const int byte = d == 0 ? lane & 7 : d == 4 ? 0 : d == 3 ? lane & 3 : (d == 1 && grp == 0) ? lane : lane >> 1;
        unsigned it = 0, m;
        while ((m = __ballot_sync(0xffffffffu, get_flag(slot, byte) != (epoch & 255u))) != 0 && ++it < POLL_LIMIT) {
          if (d == 1 && lane == 0) *reinterpret_cast<volatile int*>(smem + READY_OFF) = (__ffs(m) - 1) >> 1;
          __nanosleep(WATCH_NS);
        }
        if (d == 1 && lane == 0) *reinterpret_cast<volatile int*>(smem + READY_OFF) = 16;
        if (d < 4) TS(0, 8 + d * 2); else TS(0, 7);
        fence_async_global();
        __syncwarp();
        if (lane == 0 && d != 1) mbar_arrive(dep0 + 8 * d);
      }
    } else {
      cluster_wait();
      bar_sync<BAR_LN>(288);
      if (lane == 0) { TS(1, 5); publish(F_XN + rb, cta & 7, epoch); TS(1, 6); }
      __syncwarp();
      {
        unsigned it = 0;
        while (true) {
          bool ok = true;
          uint2 u[15];
          #pragma unroll
          for (int i = 0; i < 15; i++) u[i] = ld_vol2(&g_csum[(i % 5) * FH + c8 * 96 + (i / 5) * 32 + lane]);
          #pragma unroll
          for (int i = 0; i < 15; i++) ok = ok && u[i].y == epoch;
          #pragma unroll
          for (int i = 0; i < 3; i++)
            reinterpret_cast<float*>(smem + COLSUM_OFF)[i * 32 + lane] = ((__uint_as_float(u[i * 5].x) + __uint_as_float(u[i * 5 + 1].x)) +
                (__uint_as_float(u[i * 5 + 2].x) + __uint_as_float(u[i * 5 + 3].x))) + __uint_as_float(u[i * 5 + 4].x);
          if (ok || ++it > POLL_LIMIT) break;
          __nanosleep(POLL_NS);
        }
      }
      __syncwarp();
      TS(1, 4);
      bar_arrive<BAR_STATS>(192);
      bar_sync<BAR_PUB1>(160);
      if (lane == 0) {
        TS(1, 7);
        tma_store_3d(&maps.m[M_Z232], buf, 0, rb * 128, 3 * c8);
        bulk_commit();
        bulk_wait_all();
        set_flag(F_Z + (c8 >> 1), rb * 2 + (c8 & 1), epoch);
        TS(1, 8);
      }
      __syncwarp();
      bar_arrive<BAR_BUF>(160);
      if (grp == 1) {
        bar_sync<BAR_PUB2>(160);
        if (lane == 0) set_flag(F_A + ct, rb, epoch);
        TS(1, 9);
        __syncwarp();
      }
      bar_sync<BAR_PUB1>(160);
      if (lane == 0) set_flag(grp == 0 ? F_H + rb : F_B + ct, grp == 0 ? ct : rb, epoch);
      TS(1, 10);
      __syncwarp();
      bar_arrive<BAR_BUF>(160);
    }
  } else {
    asm volatile("setmaxnreg.inc.sync.aligned.u32 232;");
    const int t = tid & 127, w = t >> 5, l = t & 31;
    ln_rows(rv, cta, epoch);
    if (wg == 2) colsum_part(win, cta, epoch);
    TS(wg + 1, 0);
    cluster_wait();
    const int rl = w * 16 + ((l >> 3) & 1) * 8 + (l & 7);
    const int gr = w * 16 + (l & 15);
    const uint32_t st_base = buf + rl * 128;
    const uint32_t st_x = ((l >> 4) ^ (l & 7)) << 4;
    if (wg == 1) {
      float acc[2][48];
      zero(acc);
      mainloop<96, 2, false, BAR_ORD1>(acc, sbase, grp, 0, 10);
      drain(acc, sbase, grp, 9);
      TS(2, 2);
      bar_sync<BAR_STATS>(192);
      const float2* rs = reinterpret_cast<const float2*>(smem + ROWSTAT_OFF) + w * 16 + (l >> 2);
      const float2* cs = reinterpret_cast<const float2*>(smem + COLSUM_OFF) + (l & 3);
      float sum[4], sq[4];
      #pragma unroll
      for (int r = 0; r < 4; r++) {
        const float2 st = rs[(r >> 1) * 64 + (r & 1) * 8];
        float s0 = 0.f, q0 = 0.f;
        #pragma unroll
        for (int j = 0; j < 12; j++) {
          const float2 c = cs[j * 4];
          float* a = &acc[r >> 1][4 * j + (r & 1) * 2];
          a[0] = gelu_tanh(fmaf(a[0], st.x, st.y * c.x));
          a[1] = gelu_tanh(fmaf(a[1], st.x, st.y * c.y));
          s0 += a[0] + a[1]; q0 = fmaf(a[0], a[0], q0); q0 = fmaf(a[1], a[1], q0);
        }
        s0 += __shfl_xor_sync(0xffffffffu, s0, 1); q0 += __shfl_xor_sync(0xffffffffu, q0, 1);
        s0 += __shfl_xor_sync(0xffffffffu, s0, 2); q0 += __shfl_xor_sync(0xffffffffu, q0, 2);
        sum[r] = s0; sq[r] = q0;
      }
      TS(2, 4);
      float rstd, off;
      {
        const int qd = l & 3;
        const float sm = qd == 0 ? sum[0] : qd == 1 ? sum[1] : qd == 2 ? sum[2] : sum[3];
        const float sv = qd == 0 ? sq[0] : qd == 1 ? sq[1] : qd == 2 ? sq[2] : sq[3];
        const int row = (qd >> 1) * 64 + w * 16 + (qd & 1) * 8 + (l >> 2);
        const float mu = sm * (1.f / 96), m2 = fmaxf(sv - sm * mu, 0.f);
        st_vol2(&g_zstat[(rb * 8 + c8) * 128 + row], __float_as_uint(mu), (__float_as_uint(m2) & ~255u) | (epoch & 255u));
        uint2 v[7];
        unsigned n = 0;
        while (true) {
          bool ok = true;
          #pragma unroll
          for (int j = 0; j < 7; j++) v[j] = ld_vol2(&g_zstat[(rb * 8 + ((c8 + 1 + j) & 7)) * 128 + row]);
          #pragma unroll
          for (int j = 0; j < 7; j++) ok = ok && ((v[j].y ^ epoch) & 255u) == 0;
          if (ok || ++n > POLL_LIMIT) break;
          __nanosleep(POLL_NS);
        }
        float mean = mu, var = m2;
        #pragma unroll
        for (int j = 0; j < 7; j++) { mean += __uint_as_float(v[j].x); var += __uint_as_float(v[j].y & ~255u); }
        mean *= 0.125f;
        float d = (mu - mean) * (mu - mean);
        #pragma unroll
        for (int j = 0; j < 7; j++) d = fmaf(__uint_as_float(v[j].x) - mean, __uint_as_float(v[j].x) - mean, d);
        rstd = rsqrtf(fmaf(96.f, d, var) * (1.f / FH) + LN_EPS); off = -mean * rstd;
        __syncwarp();
      }
      TS(2, 5);
      #pragma unroll
      for (int mi = 0; mi < 2; mi++) {
        const float r0 = __shfl_sync(0xffffffffu, rstd, (l & 28) + mi * 2), o0 = __shfl_sync(0xffffffffu, off, (l & 28) + mi * 2);
        const float r1 = __shfl_sync(0xffffffffu, rstd, (l & 28) + mi * 2 + 1), o1 = __shfl_sync(0xffffffffu, off, (l & 28) + mi * 2 + 1);
        #pragma unroll
        for (int jj = 0; jj < 6; jj++) {
          const float* a = &acc[mi][8 * jj];
          stsm4(buf + (jj >> 1) * 8192 + mi * 4096 + rl * 64 + ((((jj & 1) * 2 + (l >> 4)) ^ ((l >> 1) & 3)) << 4),
                pack_bf16(fmaf(a[0], r0, o0), fmaf(a[1], r0, o0)), pack_bf16(fmaf(a[2], r1, o1), fmaf(a[3], r1, o1)),
                pack_bf16(fmaf(a[4], r0, o0), fmaf(a[5], r0, o0)), pack_bf16(fmaf(a[6], r1, o1), fmaf(a[7], r1, o1)));
        }
      }
      fence_async_smem();
      bar_arrive<BAR_PUB1>(160);
      TS(2, 6);
      if (grp == 0) {
        float acc[2][96];
        {
          const bf16* bp = bsp + rb * 128 + w * 16 + (l >> 2);
          const float bb[4] = {__bfloat162float(bp[0]), __bfloat162float(bp[8]), __bfloat162float(bp[64]), __bfloat162float(bp[72])};
          #pragma unroll
          for (int i = 0; i < 96; i++) { acc[0][i] = bb[(i >> 1) & 1]; acc[1][i] = bb[2 + ((i >> 1) & 1)]; }
          pin(acc);
        }
        bar_sync<BAR_ORD2>(256);
        mainloop<192, 1, false, BAR_ORD1>(acc, sbase, 0, 20, 32);
        bar_sync<BAR_Z1>(256);
        drain(acc, sbase, 0, 51);
        TS(2, 7);
        {
          uint32_t z[2][4][4];
          #pragma unroll
          for (int i = 0; i < 4; i++) ldsm4(st_base + (st_x ^ (i << 5)), z[0][i][0], z[0][i][1], z[0][i][2], z[0][i][3]);
          #pragma unroll
          for (int bx = 0; bx < 6; bx++) {
            if (bx < 5) {
              #pragma unroll
              for (int i = 0; i < 4; i++)
                ldsm4(st_base + (bx + 1) * 8192 + (st_x ^ (i << 5)), z[(bx + 1) & 1][i][0], z[(bx + 1) & 1][i][1], z[(bx + 1) & 1][i][2], z[(bx + 1) & 1][i][3]);
            }
            #pragma unroll
            for (int i = 0; i < 4; i++) {
              const float* a = &acc[bx / 3][8 * ((bx % 3) * 4 + i)];
              const uint32_t* zz = z[bx & 1][i];
              stsm4(st_base + bx * 8192 + (st_x ^ (i << 5)),
                    hmul2_bf16(zz[0], pack_bf16(a[0], a[1])), hmul2_bf16(zz[1], pack_bf16(a[2], a[3])),
                    hmul2_bf16(zz[2], pack_bf16(a[4], a[5])), hmul2_bf16(zz[3], pack_bf16(a[6], a[7])));
            }
            if (bx % 3 == 2) {
              fence_async_smem();
              __syncwarp();
              if (l < 3) {
                tma_store_2d(&maps.m[M_HS], buf + (bx - 2 + l) * 8192 + w * 2048, ct * 192 + l * 64, rb * 128 + (bx / 3) * 64 + w * 16);
                bulk_commit();
              }
            }
          }
        }
        TS(2, 8);
        if (l < 3) bulk_wait_all();
        __syncwarp();
        bar_arrive<BAR_PUB1>(160);
        TS(2, 9);
        return;
      }
    } else {
      if (grp == 0) {
        float acc[2][96];
        zero(acc);
        bar_sync<BAR_ORD1>(256);
        mainloop<192, 1, false, BAR_ORD2>(acc, sbase, 0, 10, 10);
        drain(acc, sbase, 0, 19);
        TS(3, 2);
        bar_sync<BAR_BUF>(160);
        #pragma unroll
        for (int mi = 0; mi < 2; mi++)
          #pragma unroll
          for (int jj = 0; jj < 12; jj++) {
            const float* a = &acc[mi][8 * jj];
            stsm4(st_base + mi * 24576 + (jj >> 2) * 8192 + (st_x ^ ((jj & 3) << 5)),
                  pack_bf16(a[0], a[1]), pack_bf16(a[2], a[3]), pack_bf16(a[4], a[5]), pack_bf16(a[6], a[7]));
          }
        __syncwarp();
        TS(3, 3);
        const uint32_t rbase = buf + (l >> 4) * 24576 + gr * 128;
        #pragma unroll 1
        for (int c2 = 0; c2 < 12; c2++) {
          const uint32_t ab = rbase + (c2 >> 2) * 8192;
          uint4 v[2];
          #pragma unroll
          for (int i = 0; i < 2; i++) v[i] = lds128(ab + (((((c2 & 3) * 2 + i) ^ l) & 7) << 4));
          #pragma unroll
          for (int i = 0; i < 2; i++)
            sts128(ab + (((((c2 & 3) * 2 + i) ^ l) & 7) << 4),
                   pack_bf16(gelu_tanh(bf_lo(v[i].x)), gelu_tanh(bf_hi(v[i].x))), pack_bf16(gelu_tanh(bf_lo(v[i].y)), gelu_tanh(bf_hi(v[i].y))),
                   pack_bf16(gelu_tanh(bf_lo(v[i].z)), gelu_tanh(bf_hi(v[i].z))), pack_bf16(gelu_tanh(bf_lo(v[i].w)), gelu_tanh(bf_hi(v[i].w))));
        }
        TS(3, 4);
        bar_arrive<BAR_Z1>(256);
      }
    }
    float acc[2][80];
    if (grp == 1) {
      zero(acc);
      if (wg == 2) {
        bar_sync<BAR_ORD1>(256);
        mainloop<160, 0, false, BAR_ORD2>(acc, sbase, 1, 10, 10);
      } else {
        bar_sync<BAR_ORD2>(256);
        mainloop<160, 0, false, BAR_ORD1>(acc, sbase, 1, 20, 10);
      }
      drain(acc, sbase, 1, wg == 2 ? 19 : 29);
      TS(wg + 1, wg == 1 ? 7 : 2);
      if (wg == 1) bar_sync<BAR_Z1>(256); else bar_sync<BAR_BUF>(160);
      const uint32_t sg = wg == 1 ? 0x80008000u : 0u;
      const uint32_t tb = buf + ((l >> 4) * 8 + (l & 7)) * 128 + (((w * 2 + ((l >> 3) & 1)) ^ (l & 7)) << 4);
      #pragma unroll
      for (int mi = 0; mi < 2; mi++)
        #pragma unroll
        for (int jj = 0; jj < 10; jj++) {
          const float* a = &acc[mi][8 * jj];
          stsm4_t(tb + mi * 20480 + jj * 2048, pack_bf16(a[0], a[1]) ^ sg, pack_bf16(a[2], a[3]) ^ sg, pack_bf16(a[4], a[5]) ^ sg, pack_bf16(a[6], a[7]) ^ sg);
        }
      fence_async_smem();
      if (wg == 1) bar_sync<BAR_WG1>(128); else bar_sync<BAR_WG2>(128);
      TS(wg + 1, wg == 1 ? 8 : 6);
      if (l == 0) {
        #pragma unroll 1
        for (int i = 0; i < 2; i++) {
          tma_store_2d(&maps.m[M_ABS], buf + i * 20480 + w * 5120, rb * 128 + i * 64, (2 - wg) * DM + ct * 160 + w * 40);
          bulk_commit();
        }
        bulk_wait_all();
      }
      __syncwarp();
      TS(wg + 1, wg == 1 ? 9 : 10);
      if (wg == 1) {
        bar_arrive<BAR_PUB1>(160);
        #pragma unroll 1
        for (int i = 0; i < 4; i++) {
          uint4 v[5];
          #pragma unroll
          for (int j = 0; j < 5; j++) {
            const int e = (i * 5 + j) * 128 + t;
            v[j] = ldg128(x + (size_t)(rb * 128 + e / 20) * DM + ct * 160 + (e % 20) * 8);
          }
          #pragma unroll
          for (int j = 0; j < 5; j++) {
            const int e = (i * 5 + j) * 128 + t;
            stg128(out + (size_t)(rb * 128 + e / 20) * DM + ct * 160 + (e % 20) * 8, v[j]);
          }
        }
        bar_sync<BAR_WG1>(128);
        if (t == 0) publish(F_Y + rb * 4 + ct, 0, epoch);
        return;
      }
      bar_arrive<BAR_PUB2>(160);
      bar_arrive<BAR_Z1>(256);
    }
    zero(acc);
    bar_sync<BAR_ORD1>(256);
    mainloop<160, 0, false, 0>(acc, sbase, grp, grp == 0 ? 52 : 30, grp == 0 ? NX : 64 - NX);
    if (grp == 0) mainloop<160, 2, true, 0>(acc, sbase, 0, 52 + NX, 12);
    const uint32_t slab = buf + w * (16 * 320);
    const uint32_t addr = slab + (((l >> 3) & 1) * 8 + (l & 7)) * 320 + (l >> 4) * 16;
    bar_sync<BAR_BUF>(160);
    mbar_wait(dep0 + 32, 0);
    drain(acc, sbase, grp, total - 1);
    TS(3, 12);
    #pragma unroll
    for (int mi = 0; mi < 2; mi++) {
      #pragma unroll
      for (int jj = 0; jj < 10; jj++) {
        const float* a = &acc[mi][8 * jj];
        stsm4(addr + mi * 20480 + jj * 32, pack_bf16(a[0], a[1]), pack_bf16(a[2], a[3]), pack_bf16(a[4], a[5]), pack_bf16(a[6], a[7]));
      }
      fence_async_smem();
      __syncwarp();
      if (l == 0) {
        tma_reduce_2d(&maps.m[M_OUT], slab + mi * 20480, ct * 160, rb * 128 + mi * 64 + w * 16);
        bulk_commit();
      }
    }
    TS(3, 13);
    if (l == 0) {
      bulk_wait_read();
      if (w == 0) atomicAdd(&g_done, 1u);
    }
    TS(3, 15);
  }
}

typedef CUresult (*EncodeFn)(CUtensorMap*, CUtensorMapDataType, cuuint32_t, void*, const cuuint64_t*, const cuuint64_t*,
                             const cuuint32_t*, const cuuint32_t*, CUtensorMapInterleave, CUtensorMapSwizzle,
                             CUtensorMapL2promotion, CUtensorMapFloatOOBfill);

void make2d(EncodeFn enc, CUtensorMap* m, const void* p, uint64_t cols, uint64_t rows, uint32_t bc, uint32_t br, bool swz = true) {
  cuuint64_t gd[2] = {cols, rows}, gs[1] = {cols * 2};
  cuuint32_t bd[2] = {bc, br}, es[2] = {1, 1};
  enc(m, CU_TENSOR_MAP_DATA_TYPE_BFLOAT16, 2, const_cast<void*>(p), gd, gs, bd, es, CU_TENSOR_MAP_INTERLEAVE_NONE,
      swz ? CU_TENSOR_MAP_SWIZZLE_128B : CU_TENSOR_MAP_SWIZZLE_NONE, PROMO, CU_TENSOR_MAP_FLOAT_OOB_FILL_NONE);
}
void make3d(EncodeFn enc, CUtensorMap* m, const void* p, uint64_t cols, uint64_t rows, uint32_t cw, uint32_t nc, uint32_t br = 64) {
  cuuint64_t gd[3] = {cw, rows, cols / cw}, gs[2] = {cols * 2, cw * 2};
  cuuint32_t bd[3] = {cw, br, nc}, es[3] = {1, 1, 1};
  enc(m, CU_TENSOR_MAP_DATA_TYPE_BFLOAT16, 3, const_cast<void*>(p), gd, gs, bd, es, CU_TENSOR_MAP_INTERLEAVE_NONE,
      cw == 64 ? CU_TENSOR_MAP_SWIZZLE_128B : CU_TENSOR_MAP_SWIZZLE_64B, PROMO, CU_TENSOR_MAP_FLOAT_OOB_FILL_NONE);
}

}

extern "C" void kernel_launch(void* const* d_in, const int* in_sizes, int n_in, void* d_out, int out_size) {
  const bf16* x = (const bf16*)d_in[0];
  const bf16* wsre = (const bf16*)d_in[1];
  const bf16* wsim = (const bf16*)d_in[2];
  const bf16* wdre = (const bf16*)d_in[3];
  const bf16* wdim = (const bf16*)d_in[4];
  const bf16* win = (const bf16*)d_in[6];
  const bf16* wsp = (const bf16*)d_in[7];
  const bf16* bsp = (const bf16*)d_in[8];
  const bf16* wout = (const bf16*)d_in[9];

  void* fn = nullptr;
  cudaDriverEntryPointQueryResult qr;
  cudaGetDriverEntryPoint("cuTensorMapEncodeTiled", &fn, cudaEnableDefault, &qr);
  EncodeFn enc = (EncodeFn)fn;
  void *abT, *z2, *h, *xn;
  cudaGetSymbolAddress(&xn, g_xn);
  cudaGetSymbolAddress(&abT, g_abT);
  cudaGetSymbolAddress(&z2, g_z2);
  cudaGetSymbolAddress(&h, g_h);

  Maps maps;
  make2d(enc, &maps.m[M_X], x, DM, SEQ, 64, 64);
  make2d(enc, &maps.m[M_XN], xn, DM, SEQ, 64, 64);
  make3d(enc, &maps.m[M_Z232], z2, FH, SEQ, 32, 3, 128);
  make3d(enc, &maps.m[M_WIN32], win, FF, DM, 32, 3);
  make2d(enc, &maps.m[M_WSRE], wsre, SEQ, SEQ, 64, 64);
  make2d(enc, &maps.m[M_WSIM], wsim, SEQ, SEQ, 64, 64);
  make2d(enc, &maps.m[M_WSP], wsp, SEQ, SEQ, 64, 64);
  make2d(enc, &maps.m[M_H], h, FH, SEQ, 64, 64);
  make3d(enc, &maps.m[M_WIN3], win, FF, DM, 64, 3);
  make3d(enc, &maps.m[M_Z23], z2, FH, SEQ, 64, 3);
  make2d(enc, &maps.m[M_WDRE], wdre, DM, DM, 64, 160);
  make2d(enc, &maps.m[M_WDIM], wdim, DM, DM, 64, 160);
  make2d(enc, &maps.m[M_AB], abT, SEQ, 2 * DM, 64, 160);
  make3d(enc, &maps.m[M_WOUT], wout, DM, FH, 32, 5);
  make2d(enc, &maps.m[M_HS], h, FH, SEQ, 64, 16);
  make2d(enc, &maps.m[M_ABS], abT, SEQ, 2 * DM, 64, 40);
  make2d(enc, &maps.m[M_OUT], d_out, DM, SEQ, 160, 16, false);

  cudaFuncSetAttribute(fused_kernel, cudaFuncAttributeMaxDynamicSharedMemorySize, SMEM_BYTES);
  fused_kernel<<<128, 384, SMEM_BYTES>>>(maps, x, win, bsp, (bf16*)d_out);
}
```

```cpp
#include <cuda_runtime.h>
#include <cuda_bf16.h>
#include <cuda.h>
#include <stdint.h>

namespace {

typedef __nv_bfloat16 bf16;

constexpr int SEQ = 2048, DM = 640, FF = 1536, FH = 768;
#define NXV 10
constexpr int NX = NXV;
#define NSTB 5
constexpr int NST_A = 4, NST_B = NSTB, MAXST = 5;
constexpr int A_BYTES = 16384;
constexpr int BAR_OFF = 512;
constexpr int READY_OFF = 640;
constexpr int ROWSTAT_OFF = 1024;
constexpr int COLSUM_OFF = 2048;
constexpr int RED_OFF = 2560;
constexpr int RING_OFF = 3072;
constexpr int STAGE_A = 40960, STAGE_B = 36864;
constexpr int SMEM_BYTES = RING_OFF + 5 * STAGE_B + 40960;
constexpr int KB_A = 20 + 32 + NX + 12;
constexpr int KB_B = 30 + 64 - NX;
constexpr float LN_EPS = 1e-5f;
constexpr unsigned POLL_LIMIT = 100000;
#define POLL_NS 100
#define PF_D 8
#define ROT 0
#define Z1_NS 0
#define INFL 2
#define LIM_G 1000
#define MAPV 0
#define PROMO CU_TENSOR_MAP_L2_PROMOTION_L2_128B
#define WATCH_NS 40
#define PF_COND ((kb & 1) == (ct >> 1))
#define WPF 1
#define Z2SW 1
#define WOSW 0
#define HINT 1
#define PF_NS 150

constexpr int BAR_ORD1 = 1, BAR_ORD2 = 2, BAR_WG1 = 3, BAR_WG2 = 4, BAR_LN = 5, BAR_BUF = 6, BAR_Z1 = 7, BAR_PUB1 = 8, BAR_PUB2 = 9, BAR_STATS = 10;

enum { M_X, M_XN, M_WIN32, M_Z232, M_WSRE, M_WSIM, M_WSP, M_H, M_WIN3, M_Z23, M_WDRE, M_WDIM, M_AB, M_WOUT, M_OUT, M_HS, M_ABS, M_COUNT };
struct Maps { CUtensorMap m[M_COUNT]; };

__device__ __align__(1024) bf16 g_abT[2 * DM * SEQ];
__device__ __align__(1024) bf16 g_z2[SEQ * FH];
__device__ __align__(1024) bf16 g_h[SEQ * FH];
__device__ __align__(1024) bf16 g_xn[SEQ * DM];
__device__ __align__(16) uint2 g_xstat[SEQ];
__device__ __align__(16) uint2 g_csum[5 * FH];
__device__ __align__(16) uint2 g_zstat[128 * 128];
__device__ __align__(256) unsigned char g_flags[108 * 256];
constexpr int F_A = 0, F_B = 4, F_Z = 8, F_H = 12, F_XN = 28, F_Y = 44;
__device__ unsigned g_done;
#define TS(role, ev)
#define TC(i)

extern __shared__ __align__(1024) uint8_t smem[];

__device__ __forceinline__ uint32_t smem_u32(const void* p) { return (uint32_t)__cvta_generic_to_shared(p); }
__device__ __forceinline__ void mbar_init(uint32_t bar, uint32_t cnt) { asm volatile("mbarrier.init.shared::cta.b64 [%0], %1;" :: "r"(bar), "r"(cnt)); }
__device__ __forceinline__ void mbar_expect_tx(uint32_t bar, uint32_t bytes) { asm volatile("mbarrier.arrive.expect_tx.shared::cta.b64 _, [%0], %1;" :: "r"(bar), "r"(bytes) : "memory"); }
__device__ __forceinline__ void mbar_arrive(uint32_t bar) { asm volatile("mbarrier.arrive.shared::cta.b64 _, [%0];" :: "r"(bar) : "memory"); }
__device__ __forceinline__ void mbar_arrive_cluster(uint32_t bar, uint32_t cta) {
  asm volatile("{\n.reg .b32 ra;\nmapa.shared::cluster.u32 ra, %0, %1;\nmbarrier.arrive.shared::cluster.b64 _, [ra];\n}" :: "r"(bar), "r"(cta) : "memory");
}
__device__ __forceinline__ void mbar_wait(uint32_t bar, uint32_t parity) {
  asm volatile("{\n.reg .pred p;\n.reg .u32 n;\nmov.u32 n, 0;\n"
               "LW: mbarrier.try_wait.parity.shared::cta.b64 p, [%0], %1, 2000;\n@p bra LD;\n"
               "add.u32 n, n, 1;\nsetp.lt.u32 p, n, 20000;\n@p bra LW;\nLD:\n}" :: "r"(bar), "r"(parity) : "memory");
}
__device__ __forceinline__ void tma_load_2d(uint32_t dst, const CUtensorMap* map, uint32_t bar, int c0, int c1) {
  asm volatile("cp.async.bulk.tensor.2d.shared::cluster.global.mbarrier::complete_tx::bytes [%0], [%1, {%3, %4}], [%2];"
    :: "r"(dst), "l"((uint64_t)map), "r"(bar), "r"(c0), "r"(c1) : "memory");
}
__device__ __forceinline__ void tma_load_3d(uint32_t dst, const CUtensorMap* map, uint32_t bar, int c0, int c1, int c2) {
  asm volatile("cp.async.bulk.tensor.3d.shared::cluster.global.mbarrier::complete_tx::bytes [%0], [%1, {%3, %4, %5}], [%2];"
    :: "r"(dst), "l"((uint64_t)map), "r"(bar), "r"(c0), "r"(c1), "r"(c2) : "memory");
}
__device__ __forceinline__ void tma_load_2d_mc(uint32_t dst, const CUtensorMap* map, uint32_t bar, int c0, int c1, uint16_t mask) {
  asm volatile("cp.async.bulk.tensor.2d.shared::cluster.global.mbarrier::complete_tx::bytes.multicast::cluster [%0], [%1, {%3, %4}], [%2], %5;"
    :: "r"(dst), "l"((uint64_t)map), "r"(bar), "r"(c0), "r"(c1), "h"(mask) : "memory");
}
__device__ __forceinline__ void tma_store_2d(const CUtensorMap* map, uint32_t src, int c0, int c1) {
  asm volatile("cp.async.bulk.tensor.2d.global.shared::cta.bulk_group [%0, {%2, %3}], [%1];"
    :: "l"((uint64_t)map), "r"(src), "r"(c0), "r"(c1) : "memory");
}
__device__ __forceinline__ void tma_store_3d(const CUtensorMap* map, uint32_t src, int c0, int c1, int c2) {
  asm volatile("cp.async.bulk.tensor.3d.global.shared::cta.bulk_group [%0, {%2, %3, %4}], [%1];"
    :: "l"((uint64_t)map), "r"(src), "r"(c0), "r"(c1), "r"(c2) : "memory");
}
__device__ __forceinline__ void tma_reduce_2d(const CUtensorMap* map, uint32_t src, int c0, int c1) {
  asm volatile("cp.reduce.async.bulk.tensor.2d.global.shared::cta.add.tile.bulk_group [%0, {%2, %3}], [%1];"
    :: "l"((uint64_t)map), "r"(src), "r"(c0), "r"(c1) : "memory");
}
__device__ __forceinline__ void bulk_wait_all() { asm volatile("cp.async.bulk.wait_group 0;" ::: "memory"); }
__device__ __forceinline__ void bulk_commit() { asm volatile("cp.async.bulk.commit_group;" ::: "memory"); }
__device__ __forceinline__ void bulk_wait_read() { asm volatile("cp.async.bulk.wait_group.read 0;" ::: "memory"); }
__device__ __forceinline__ void fence_async_smem() { asm volatile("fence.proxy.async.shared::cta;" ::: "memory"); }
__device__ __forceinline__ void fence_async_global() { asm volatile("fence.proxy.async.global;" ::: "memory"); }
__device__ __forceinline__ void wgmma_fence() { asm volatile("wgmma.fence.sync.aligned;" ::: "memory"); }
__device__ __forceinline__ void wgmma_commit() { asm volatile("wgmma.commit_group.sync.aligned;" ::: "memory"); }
template<int N> __device__ __forceinline__ void wgmma_wait() { asm volatile("wgmma.wait_group.sync.aligned %0;" :: "n"(N) : "memory"); }
template<int ID> __device__ __forceinline__ void bar_sync(int n) { asm volatile("bar.sync %0, %1;" :: "n"(ID), "r"(n) : "memory"); }
template<int ID> __device__ __forceinline__ void bar_arrive(int n) { asm volatile("bar.arrive %0, %1;" :: "n"(ID), "r"(n) : "memory"); }
__device__ __forceinline__ void cluster_wait() { asm volatile("barrier.cluster.wait.aligned;" ::: "memory"); }
__device__ __forceinline__ uint64_t desc64(uint32_t lo, uint32_t hi) { return (uint64_t)lo | ((uint64_t)hi << 32); }
__device__ __forceinline__ uint4 ld_vol4(const uint4* p) {
  uint4 v; asm volatile("ld.relaxed.gpu.global.v4.u32 {%0,%1,%2,%3}, [%4];" : "=r"(v.x), "=r"(v.y), "=r"(v.z), "=r"(v.w) : "l"(p) : "memory"); return v;
}
__device__ __forceinline__ uint2 ld_vol2(const uint2* p) {
  uint2 v; asm volatile("ld.relaxed.gpu.global.v2.u32 {%0,%1}, [%2];" : "=r"(v.x), "=r"(v.y) : "l"(p) : "memory"); return v;
}
__device__ __forceinline__ void st_vol4(uint4* p, uint32_t a, uint32_t b, uint32_t c, uint32_t d) {
  asm volatile("st.relaxed.gpu.global.v4.u32 [%0], {%1,%2,%3,%4};" :: "l"(p), "r"(a), "r"(b), "r"(c), "r"(d) : "memory");
}
__device__ __forceinline__ void st_vol2(uint2* p, uint32_t a, uint32_t b) {
  asm volatile("st.relaxed.gpu.global.v2.u32 [%0], {%1,%2};" :: "l"(p), "r"(a), "r"(b) : "memory");
}
__device__ __forceinline__ void stg128(void* p, uint4 v) {
  asm volatile("st.global.v4.u32 [%0], {%1,%2,%3,%4};" :: "l"(p), "r"(v.x), "r"(v.y), "r"(v.z), "r"(v.w));
}
__device__ __forceinline__ unsigned ld_relaxed(const unsigned* p) {
  unsigned v; asm volatile("ld.relaxed.gpu.global.u32 %0, [%1];" : "=r"(v) : "l"(p) : "memory"); return v;
}
__device__ __forceinline__ uint32_t pack_bf16(float lo, float hi) {
  uint32_t r; asm("cvt.rn.bf16x2.f32 %0, %1, %2;" : "=r"(r) : "f"(hi), "f"(lo)); return r;
}
__device__ __forceinline__ float bf_lo(uint32_t v) { return __uint_as_float(v << 16); }
__device__ __forceinline__ float bf_hi(uint32_t v) { return __uint_as_float(v & 0xFFFF0000u); }
__device__ __forceinline__ void stsm4(uint32_t addr, uint32_t a, uint32_t b, uint32_t c, uint32_t d) {
  asm volatile("stmatrix.sync.aligned.m8n8.x4.shared.b16 [%0], {%1,%2,%3,%4};" :: "r"(addr), "r"(a), "r"(b), "r"(c), "r"(d));
}
__device__ __forceinline__ void stsm4_t(uint32_t addr, uint32_t a, uint32_t b, uint32_t c, uint32_t d) {
  asm volatile("stmatrix.sync.aligned.m8n8.x4.trans.shared.b16 [%0], {%1,%2,%3,%4};" :: "r"(addr), "r"(a), "r"(b), "r"(c), "r"(d));
}
__device__ __forceinline__ void ldsm4(uint32_t addr, uint32_t& a, uint32_t& b, uint32_t& c, uint32_t& d) {
  asm volatile("ldmatrix.sync.aligned.m8n8.x4.shared.b16 {%0,%1,%2,%3}, [%4];" : "=r"(a), "=r"(b), "=r"(c), "=r"(d) : "r"(addr));
}
__device__ __forceinline__ uint4 lds128(uint32_t a) {
  uint4 v; asm volatile("ld.shared.v4.u32 {%0,%1,%2,%3}, [%4];" : "=r"(v.x), "=r"(v.y), "=r"(v.z), "=r"(v.w) : "r"(a)); return v;
}
__device__ __forceinline__ void sts128(uint32_t a, uint32_t x, uint32_t y, uint32_t z, uint32_t w) {
  asm volatile("st.shared.v4.u32 [%0], {%1,%2,%3,%4};" :: "r"(a), "r"(x), "r"(y), "r"(z), "r"(w));
}
__device__ __forceinline__ uint32_t hmul2_bf16(uint32_t a, uint32_t b) {
  uint32_t r; asm("mul.rn.bf16x2 %0, %1, %2;" : "=r"(r) : "r"(a), "r"(b)); return r;
}
__device__ __forceinline__ float gelu_tanh(float v) {
  float u = v * fmaf(0.0356774081f, v * v, 0.7978845608f);
  float t; asm("tanh.approx.f32 %0, %1;" : "=f"(t) : "f"(u));
  float hv = 0.5f * v;
  return fmaf(hv, t, hv);
}

template<int TB>
__device__ __forceinline__ void wgmma_n192(float (&d)[96], uint64_t da, uint64_t db, int scale_d) {
  asm volatile("{\n.reg .pred p;\nsetp.ne.b32 p, %98, 0;\n"
   "wgmma.mma_async.sync.aligned.m64n192k16.f32.bf16.bf16 {%0,%1,%2,%3,%4,%5,%6,%7,%8,%9,%10,%11,%12,%13,%14,%15,%16,%17,%18,%19,%20,%21,%22,%23,%24,%25,%26,%27,%28,%29,%30,%31,%32,%33,%34,%35,%36,%37,%38,%39,%40,%41,%42,%43,%44,%45,%46,%47,%48,%49,%50,%51,%52,%53,%54,%55,%56,%57,%58,%59,%60,%61,%62,%63,%64,%65,%66,%67,%68,%69,%70,%71,%72,%73,%74,%75,%76,%77,%78,%79,%80,%81,%82,%83,%84,%85,%86,%87,%88,%89,%90,%91,%92,%93,%94,%95}, %96, %97, p, 1, 1, 0, %99;\n}"
   : "+f"(d[0]),"+f"(d[1]),"+f"(d[2]),"+f"(d[3]),"+f"(d[4]),"+f"(d[5]),"+f"(d[6]),"+f"(d[7]),"+f"(d[8]),"+f"(d[9]),"+f"(d[10]),"+f"(d[11]),"+f"(d[12]),"+f"(d[13]),"+f"(d[14]),"+f"(d[15]),"+f"(d[16]),"+f"(d[17]),"+f"(d[18]),"+f"(d[19]),"+f"(d[20]),"+f"(d[21]),"+f"(d[22]),"+f"(d[23]),"+f"(d[24]),"+f"(d[25]),"+f"(d[26]),"+f"(d[27]),"+f"(d[28]),"+f"(d[29]),"+f"(d[30]),"+f"(d[31]),"+f"(d[32]),"+f"(d[33]),"+f"(d[34]),"+f"(d[35]),"+f"(d[36]),"+f"(d[37]),"+f"(d[38]),"+f"(d[39]),"+f"(d[40]),"+f"(d[41]),"+f"(d[42]),"+f"(d[43]),"+f"(d[44]),"+f"(d[45]),"+f"(d[46]),"+f"(d[47]),"+f"(d[48]),"+f"(d[49]),"+f"(d[50]),"+f"(d[51]),"+f"(d[52]),"+f"(d[53]),"+f"(d[54]),"+f"(d[55]),"+f"(d[56]),"+f"(d[57]),"+f"(d[58]),"+f"(d[59]),"+f"(d[60]),"+f"(d[61]),"+f"(d[62]),"+f"(d[63]),"+f"(d[64]),"+f"(d[65]),"+f"(d[66]),"+f"(d[67]),"+f"(d[68]),"+f"(d[69]),"+f"(d[70]),"+f"(d[71]),"+f"(d[72]),"+f"(d[73]),"+f"(d[74]),"+f"(d[75]),"+f"(d[76]),"+f"(d[77]),"+f"(d[78]),"+f"(d[79]),"+f"(d[80]),"+f"(d[81]),"+f"(d[82]),"+f"(d[83]),"+f"(d[84]),"+f"(d[85]),"+f"(d[86]),"+f"(d[87]),"+f"(d[88]),"+f"(d[89]),"+f"(d[90]),"+f"(d[91]),"+f"(d[92]),"+f"(d[93]),"+f"(d[94]),"+f"(d[95])
   : "l"(da), "l"(db), "r"(scale_d), "n"(TB));
}
template<int TB>
__device__ __forceinline__ void wgmma_n160(float (&d)[80], uint64_t da, uint64_t db, int scale_d) {
  asm volatile("{\n.reg .pred p;\nsetp.ne.b32 p, %82, 0;\n"
   "wgmma.mma_async.sync.aligned.m64n160k16.f32.bf16.bf16 {%0,%1,%2,%3,%4,%5,%6,%7,%8,%9,%10,%11,%12,%13,%14,%15,%16,%17,%18,%19,%20,%21,%22,%23,%24,%25,%26,%27,%28,%29,%30,%31,%32,%33,%34,%35,%36,%37,%38,%39,%40,%41,%42,%43,%44,%45,%46,%47,%48,%49,%50,%51,%52,%53,%54,%55,%56,%57,%58,%59,%60,%61,%62,%63,%64,%65,%66,%67,%68,%69,%70,%71,%72,%73,%74,%75,%76,%77,%78,%79}, %80, %81, p, 1, 1, 0, %83;\n}"
   : "+f"(d[0]),"+f"(d[1]),"+f"(d[2]),"+f"(d[3]),"+f"(d[4]),"+f"(d[5]),"+f"(d[6]),"+f"(d[7]),"+f"(d[8]),"+f"(d[9]),"+f"(d[10]),"+f"(d[11]),"+f"(d[12]),"+f"(d[13]),"+f"(d[14]),"+f"(d[15]),"+f"(d[16]),"+f"(d[17]),"+f"(d[18]),"+f"(d[19]),"+f"(d[20]),"+f"(d[21]),"+f"(d[22]),"+f"(d[23]),"+f"(d[24]),"+f"(d[25]),"+f"(d[26]),"+f"(d[27]),"+f"(d[28]),"+f"(d[29]),"+f"(d[30]),"+f"(d[31]),"+f"(d[32]),"+f"(d[33]),"+f"(d[34]),"+f"(d[35]),"+f"(d[36]),"+f"(d[37]),"+f"(d[38]),"+f"(d[39]),"+f"(d[40]),"+f"(d[41]),"+f"(d[42]),"+f"(d[43]),"+f"(d[44]),"+f"(d[45]),"+f"(d[46]),"+f"(d[47]),"+f"(d[48]),"+f"(d[49]),"+f"(d[50]),"+f"(d[51]),"+f"(d[52]),"+f"(d[53]),"+f"(d[54]),"+f"(d[55]),"+f"(d[56]),"+f"(d[57]),"+f"(d[58]),"+f"(d[59]),"+f"(d[60]),"+f"(d[61]),"+f"(d[62]),"+f"(d[63]),"+f"(d[64]),"+f"(d[65]),"+f"(d[66]),"+f"(d[67]),"+f"(d[68]),"+f"(d[69]),"+f"(d[70]),"+f"(d[71]),"+f"(d[72]),"+f"(d[73]),"+f"(d[74]),"+f"(d[75]),"+f"(d[76]),"+f"(d[77]),"+f"(d[78]),"+f"(d[79])
   : "l"(da), "l"(db), "r"(scale_d), "n"(TB));
}
template<int TB>
__device__ __forceinline__ void wgmma_n96(float (&d)[48], uint64_t da, uint64_t db, int scale_d) {
  asm volatile("{\n.reg .pred p;\nsetp.ne.b32 p, %50, 0;\n"
   "wgmma.mma_async.sync.aligned.m64n96k16.f32.bf16.bf16 {%0,%1,%2,%3,%4,%5,%6,%7,%8,%9,%10,%11,%12,%13,%14,%15,%16,%17,%18,%19,%20,%21,%22,%23,%24,%25,%26,%27,%28,%29,%30,%31,%32,%33,%34,%35,%36,%37,%38,%39,%40,%41,%42,%43,%44,%45,%46,%47}, %48, %49, p, 1, 1, 0, %51;\n}"
   : "+f"(d[0]),"+f"(d[1]),"+f"(d[2]),"+f"(d[3]),"+f"(d[4]),"+f"(d[5]),"+f"(d[6]),"+f"(d[7]),"+f"(d[8]),"+f"(d[9]),"+f"(d[10]),"+f"(d[11]),"+f"(d[12]),"+f"(d[13]),"+f"(d[14]),"+f"(d[15]),"+f"(d[16]),"+f"(d[17]),"+f"(d[18]),"+f"(d[19]),"+f"(d[20]),"+f"(d[21]),"+f"(d[22]),"+f"(d[23]),"+f"(d[24]),"+f"(d[25]),"+f"(d[26]),"+f"(d[27]),"+f"(d[28]),"+f"(d[29]),"+f"(d[30]),"+f"(d[31]),"+f"(d[32]),"+f"(d[33]),"+f"(d[34]),"+f"(d[35]),"+f"(d[36]),"+f"(d[37]),"+f"(d[38]),"+f"(d[39]),"+f"(d[40]),"+f"(d[41]),"+f"(d[42]),"+f"(d[43]),"+f"(d[44]),"+f"(d[45]),"+f"(d[46]),"+f"(d[47])
   : "l"(da), "l"(db), "r"(scale_d), "n"(TB));
}

template<int N, int TB>
__device__ __forceinline__ void wgmma_n(float (&d)[N / 2], uint64_t da, uint64_t db) {
  if constexpr (N == 192) wgmma_n192<TB>(d, da, db, 1);
  else if constexpr (N == 160) wgmma_n160<TB>(d, da, db, 1);
  else wgmma_n96<TB>(d, da, db, 1);
}

template<int R>
__device__ __forceinline__ void pin(float (&acc)[2][R]) {
  #pragma unroll
  for (int mi = 0; mi < 2; mi++)
    #pragma unroll
    for (int i = 0; i < R; i++) asm volatile("" : "+f"(acc[mi][i]) :: "memory");
}
template<int R>
__device__ __forceinline__ void zero(float (&acc)[2][R]) {
  #pragma unroll
  for (int i = 0; i < R; i++) { acc[0][i] = 0.f; acc[1][i] = 0.f; }
  pin(acc);
}

template<int N, int TB, bool CONT, int ORD_BAR>
__device__ __forceinline__ void mainloop(float (&acc)[2][N / 2], uint32_t sbase, int grp, int g0, int nk) {
  const uint32_t full0 = sbase + BAR_OFF, empty0 = full0 + 8 * MAXST, ring = sbase + RING_OFF;
  const int nst = grp == 0 ? NST_A : NST_B, total = grp == 0 ? KB_A : KB_B;
  const uint32_t sstep = (grp == 0 ? STAGE_A : STAGE_B) >> 4;
  const int t = threadIdx.x & 127;
  const uint32_t da0 = ((ring & 0x3FFFF) >> 4) | 0x10000u;
  const uint32_t db0 = (((ring + A_BYTES) & 0x3FFFF) >> 4) | ((TB == 2 ? 256u : TB ? 512u : 1u) << 16);
  constexpr uint32_t HI_A = 0x40000040u, HI_B = TB == 2 ? 0x80000020u : 0x40000040u;
  int s = g0 % nst, ph = (g0 / nst) & 1, ps = s == 0 ? nst - 1 : s - 1;
  #pragma unroll 1
  for (int g = g0; g < g0 + nk; g++) {
    const uint32_t so = s * sstep;
    mbar_wait(full0 + 8 * s, ph);
    wgmma_fence();
    #pragma unroll
    for (int k = 0; k < 4; k++) {
      const uint64_t db = desc64(db0 + so + (TB == 2 ? k * 64 : TB ? k * 128 : k * 2), HI_B);
      wgmma_n<N, TB != 0>(acc[0], desc64(da0 + so + k * 2, HI_A), db);
      wgmma_n<N, TB != 0>(acc[1], desc64(da0 + so + 512 + k * 2, HI_A), db);
    }
    wgmma_commit();
    if (ORD_BAR != 0 && g == g0 + nk - 1) bar_arrive<ORD_BAR>(256);
    wgmma_wait<1>();
    if (t < 2 && (CONT || g > g0) && g - 1 + nst < total) mbar_arrive_cluster(empty0 + 8 * ps, t);
    ps = s;
    if (++s == nst) { s = 0; ph ^= 1; }
  }
}
template<int R>
__device__ __forceinline__ void drain(float (&acc)[2][R], uint32_t sbase, int grp, int glast) {
  wgmma_wait<0>();
  pin(acc);
  const int t = threadIdx.x & 127;
  const int nst = grp == 0 ? NST_A : NST_B, total = grp == 0 ? KB_A : KB_B;
  if (t < 2 && glast + nst < total) mbar_arrive_cluster(sbase + BAR_OFF + 8 * MAXST + 8 * (glast % nst), t);
}

__device__ __forceinline__ void set_flag(int slot, int byte, unsigned epoch) {
  asm volatile("st.relaxed.gpu.global.u8 [%0], %1;" :: "l"(g_flags + slot * 256 + byte), "r"(epoch & 255u) : "memory");
}
__device__ __forceinline__ unsigned get_flag(int slot, int byte) {
  unsigned v; asm volatile("ld.relaxed.gpu.global.u8 %0, [%1];" : "=r"(v) : "l"(g_flags + slot * 256 + byte) : "memory"); return v;
}
__device__ __forceinline__ void publish(int slot, int byte, unsigned epoch) {
  asm volatile("fence.acq_rel.gpu;" ::: "memory");
  set_flag(slot, byte, epoch);
}

__device__ __forceinline__ float sum8(uint4 v) {
  return ((bf_lo(v.x) + bf_hi(v.x)) + (bf_lo(v.y) + bf_hi(v.y))) + ((bf_lo(v.z) + bf_hi(v.z)) + (bf_lo(v.w) + bf_hi(v.w)));
}
__device__ __forceinline__ uint4 ldg128(const void* p) {
  uint4 v; asm volatile("ld.global.nc.v4.u32 {%0,%1,%2,%3}, [%4];" : "=r"(v.x), "=r"(v.y), "=r"(v.z), "=r"(v.w) : "l"(p)); return v;
}
__device__ __forceinline__ void ln_load(const bf16* __restrict__ x, int cta, uint4 (&rv)[5]) {
  const int t = threadIdx.x - 128, row = cta * 16 + (t >> 4), c = t & 15;
  #pragma unroll
  for (int j = 0; j < 5; j++) rv[j] = ldg128(reinterpret_cast<const uint4*>(x + (size_t)row * DM) + c + 16 * j);
}
__device__ __forceinline__ void ln_rows(const uint4 (&rv)[5], int cta, unsigned epoch) {
  const int t = threadIdx.x - 128, row = cta * 16 + (t >> 4), c = t & 15;
  const float sh = __shfl_sync(0xffffffffu, bf_lo(rv[0].x), t & 16);
  float d[40], s = 0.f, q = 0.f;
  #pragma unroll
  for (int j = 0; j < 5; j++) {
    const uint32_t u[4] = {rv[j].x, rv[j].y, rv[j].z, rv[j].w};
    #pragma unroll
    for (int e = 0; e < 4; e++) {
      const float d0 = bf_lo(u[e]) - sh, d1 = bf_hi(u[e]) - sh;
      d[j * 8 + e * 2] = d0; d[j * 8 + e * 2 + 1] = d1;
      s += d0 + d1; q = fmaf(d0, d0, q); q = fmaf(d1, d1, q);
    }
  }
  #pragma unroll
  for (int o = 1; o < 16; o <<= 1) { s += __shfl_xor_sync(0xffffffffu, s, o); q += __shfl_xor_sync(0xffffffffu, q, o); }
  const float md = s * (1.f / DM);
  const float r = rsqrtf(fmaxf(fmaf(q, 1.f / DM, -md * md), 0.f) + LN_EPS), o = -md * r;
  if (c == 0) st_vol2(&g_xstat[row], __float_as_uint(r), (__float_as_uint(-(md + sh) * r) & ~255u) | (epoch & 255u));
  #pragma unroll
  for (int j = 0; j < 5; j++) {
    const float* a = &d[j * 8];
    stg128(reinterpret_cast<uint4*>(g_xn + (size_t)row * DM) + c + 16 * j, make_uint4(
           pack_bf16(fmaf(a[0], r, o), fmaf(a[1], r, o)), pack_bf16(fmaf(a[2], r, o), fmaf(a[3], r, o)),
           pack_bf16(fmaf(a[4], r, o), fmaf(a[5], r, o)), pack_bf16(fmaf(a[6], r, o), fmaf(a[7], r, o))));
  }
  bar_arrive<BAR_LN>(288);
}
__device__ __forceinline__ void colsum_part(const bf16* __restrict__ win, int cta, unsigned epoch) {
  const int t = threadIdx.x & 127, w = t >> 5, l = t & 31;
  const int cj = min(cta, 119), cg = cj % 24, rg = cj / 24;
  uint4 cv[4];
  #pragma unroll
  for (int j = 0; j < 4; j++) cv[j] = ldg128(reinterpret_cast<const uint4*>(win + (size_t)(rg * 128 + w * 32 + j * 8 + (l >> 2)) * FF + FH + cg * 32) + (l & 3));
  float v[8];
  v[0] = (bf_lo(cv[0].x) + bf_lo(cv[1].x)) + (bf_lo(cv[2].x) + bf_lo(cv[3].x)); v[1] = (bf_hi(cv[0].x) + bf_hi(cv[1].x)) + (bf_hi(cv[2].x) + bf_hi(cv[3].x));
  v[2] = (bf_lo(cv[0].y) + bf_lo(cv[1].y)) + (bf_lo(cv[2].y) + bf_lo(cv[3].y)); v[3] = (bf_hi(cv[0].y) + bf_hi(cv[1].y)) + (bf_hi(cv[2].y) + bf_hi(cv[3].y));
  v[4] = (bf_lo(cv[0].z) + bf_lo(cv[1].z)) + (bf_lo(cv[2].z) + bf_lo(cv[3].z)); v[5] = (bf_hi(cv[0].z) + bf_hi(cv[1].z)) + (bf_hi(cv[2].z) + bf_hi(cv[3].z));
  v[6] = (bf_lo(cv[0].w) + bf_lo(cv[1].w)) + (bf_lo(cv[2].w) + bf_lo(cv[3].w)); v[7] = (bf_hi(cv[0].w) + bf_hi(cv[1].w)) + (bf_hi(cv[2].w) + bf_hi(cv[3].w));
  #pragma unroll
  for (int st = 0; st < 3; st++) {
    const int n = 4 >> st;
    const bool up = (l & (4 * n)) != 0;
    #pragma unroll
    for (int e = 0; e < 4; e++)
      if (e < n) { const float keep = up ? v[e + n] : v[e], send = up ? v[e] : v[e + n]; v[e] = keep + __shfl_xor_sync(0xffffffffu, send, 4 * n); }
  }
  float* red = reinterpret_cast<float*>(smem + RED_OFF);
  red[w * 32 + (l & 3) * 8 + (l >> 2)] = v[0];
  bar_sync<BAR_WG2>(128);
  if (t < 32) st_vol2(&g_csum[rg * FH + cg * 32 + t], __float_as_uint((red[t] + red[32 + t]) + (red[64 + t] + red[96 + t])), epoch);
}

__device__ __forceinline__ void a_entry(int g, int grp, int rb, int& mi, int& kb) {
  if (g < 10) { mi = M_X; kb = g; }
  else if (g < 20) { mi = M_XN; kb = g - 10; }
  else if (grp == 0) {
    if (g < 52) { mi = M_WSP; kb = (g - 20); }
    else if (g < 52 + NX) { mi = M_WSIM; kb = g - 52 + 32 - NX; }
    else { mi = M_H; kb = g - 52 - NX; }
  } else {
    if (g < 30) { mi = M_XN; kb = g - 20; }
    else if (g < 62) { mi = M_WSRE; kb = (g - 30); }
    else { mi = M_WSIM; kb = g - 62; }
  }
}

__global__ void __cluster_dims__(2, 1, 1) __launch_bounds__(384, 1)
fused_kernel(const __grid_constant__ Maps maps, const bf16* __restrict__ x, const bf16* __restrict__ win, const bf16* __restrict__ bsp,
             bf16* __restrict__ out) {
  const uint32_t sbase = smem_u32(smem);
  const uint32_t full0 = sbase + BAR_OFF, empty0 = full0 + 8 * MAXST, dep0 = empty0 + 8 * MAXST, ring = sbase + RING_OFF;
  const int tid = threadIdx.x, wg = __shfl_sync(0xffffffffu, tid >> 7, 0);
  const int rank = blockIdx.x & 1;
  const int grp = (blockIdx.x >> 1) & 1, half = (blockIdx.x >> 2) & 1, rb = blockIdx.x >> 3;
  const int ct = half * 2 + rank, c8 = grp * 4 + ct;
  const int cta = rb * 8 + half * 4 + grp * 2 + rank;
  const int total = grp == 0 ? KB_A : KB_B;
  const uint32_t stage_bytes = grp == 0 ? STAGE_A : STAGE_B;
  const int nst = grp == 0 ? NST_A : NST_B;
  const uint32_t buf = ring + nst * stage_bytes;

  uint4 rv[5];
  if (wg != 0) ln_load(x, cta, rv);
  if (wg == 2) {
    const int t = tid & 127;
    if (t < 60) asm volatile("prefetch.global.L2 [%0];" :: "l"(win + (size_t)(cta * 5 + t / 12) * FF + FH + (t % 12) * 64));
  }
  const unsigned epoch = (ld_relaxed(&g_done) >> 7) + 1u;
  if (tid == 0) {
    TS(0, 0);
    for (int s = 0; s < MAXST; s++) { mbar_init(full0 + 8 * s, 2); mbar_init(empty0 + 8 * s, 2); }
    for (int s = 0; s < 5; s++) mbar_init(dep0 + 8 * s, 1);
    *reinterpret_cast<volatile int*>(smem + READY_OFF) = 0;
    asm volatile("fence.mbarrier_init.release.cluster;" ::: "memory");
  }
  __syncthreads();
  asm volatile("barrier.cluster.arrive.relaxed.aligned;" ::: "memory");

  if (wg == 0) {
    asm volatile("setmaxnreg.dec.sync.aligned.u32 40;");
    const int warp = tid >> 5, lane = tid & 31;
    if (warp == 0) {
      const int row = rb * 128;
      if (lane == 0) {
        for (int g = 0; g < nst; g++) {
          mbar_expect_tx(full0 + 8 * g, A_BYTES);
          tma_load_2d(ring + g * stage_bytes, &maps.m[M_X], full0 + 8 * g, g * 64, row);
          tma_load_2d(ring + g * stage_bytes + 8192, &maps.m[M_X], full0 + 8 * g, g * 64, row + 64);
        }
      }
      __syncwarp();
      cluster_wait();
      if (lane == 0) {
        int s = 0, ph = 0;
        #pragma unroll 1
        for (int g = nst; g < total; g++) {
          int mi, kb;
          a_entry(g, grp, rb, mi, kb);
          if (g == 10 || (mi == M_H && kb == 0)) { TS(0, g > 10 ? 3 : 1); mbar_wait(dep0 + (g > 10 ? 24 : 0), 0); fence_async_global(); TS(0, g > 10 ? 4 : 2); }
          mbar_wait(empty0 + 8 * s, ph);
          mbar_expect_tx(full0 + 8 * s, A_BYTES);
          tma_load_2d_mc(ring + s * stage_bytes + rank * 8192, &maps.m[mi], full0 + 8 * s, kb * 64, row + rank * 64, 3);
          if (++s == nst) { s = 0; ph ^= 1; }
          if (g + PF_D < total) {
            a_entry(g + PF_D, grp, rb, mi, kb);
            if (mi >= M_WSRE && mi <= M_WSP && PF_COND)
              asm volatile("cp.async.bulk.prefetch.tensor.2d.L2.global.tile [%0, {%1, %2}];" :: "l"((uint64_t)&maps.m[mi]), "r"(kb * 64), "r"(row + rank * 64) : "memory");
          }
        }
        TS(0, 5);
      }
    } else if (warp == 1) {
      if (lane == 0) {
        int s = 0, ph = 1;
        int have = 0;
        #pragma unroll 1
        for (int g = 0; g < total; g++) {
          int kind = 1, mi, kb, c, dep = 0, need = 0;
          uint32_t bytes = 20480;

          if (g < 10) { kind = 2; mi = M_WIN32; kb = g; c = FH + 96 * c8; bytes = 16384; }
          else if (grp == 0) {
            if (g < 20) { kind = 0; mi = M_WIN3; kb = g - 10; c = 3 * ct; bytes = 24576; }
            else if (g < 52) { kind = 0; mi = M_Z23; kb = (g - 20); c = 3 * ct; bytes = 24576; need = ((g - 20) >> 1) + 1; }
            else if (g < 52 + NX) { mi = M_AB; kb = g - 52 + 32 - NX; c = DM + ct * 160; dep = g == 52 ? 2 : 0; }

            else { kind = 0; mi = M_WOUT; kb = g - 52 - NX; c = ct * 5; }
          } else {
            if (g < 30) { mi = g < 20 ? M_WDRE : M_WDIM; kb = g < 20 ? g - 10 : g - 20; c = ct * 160; }
            else if (g < 62) { mi = M_AB; kb = (g - 30); c = ct * 160; need = ((g - 30) >> 1) + 1; }
            else { mi = M_AB; kb = g - 62; c = ct * 160 + DM; dep = g == 62 ? 2 : 0; }
          }
          if (need > have) {
            if (need == 1) TS(1, 0);
            unsigned it = 0;
            while ((have = *reinterpret_cast<volatile int*>(smem + READY_OFF)) < need && ++it < 50 * POLL_LIMIT) {}
            fence_async_global();
            if (need == 1) { TS(1, 1); TC(1); }
          }
          if (dep) { TS(1, dep * 2 - 2); mbar_wait(dep0 + 8 * dep, 0); fence_async_global(); TS(1, dep * 2 - 1); TC(dep); }
          const uint32_t dst = ring + s * stage_bytes + A_BYTES, fb = full0 + 8 * s;
          mbar_wait(empty0 + 8 * s, ph);
          if (++s == nst) { s = 0; ph ^= 1; }
          mbar_expect_tx(fb, bytes);
          if (kind == 0) tma_load_3d(dst, &maps.m[mi], fb, 0, kb * 64, c);
          else if (kind == 1) tma_load_2d(dst, &maps.m[mi], fb, kb * 64, c);
          else {
            #pragma unroll 1
            for (uint32_t o = 0; o < bytes; o += 8192) tma_load_2d(dst + o, &maps.m[mi], fb, c + (o >> 7), kb * 64);
          }
        }
      }
      __syncwarp();
      cluster_wait();
    } else if (warp == 2) {
      if (lane < M_COUNT) asm volatile("prefetch.tensormap [%0];" :: "l"((uint64_t)&maps.m[lane]) : "memory");
      cluster_wait();
      {
        unsigned it = 0;
        uint2 v[4];
        while (true) {
          bool ok = true;
          #pragma unroll
          for (int i = 0; i < 4; i++) { v[i] = ld_vol2(&g_xstat[rb * 128 + i * 32 + lane]); ok = ok && ((v[i].y ^ epoch) & 255u) == 0; }
          if (ok || ++it > POLL_LIMIT) break;
          __nanosleep(POLL_NS);
        }
        #pragma unroll
        for (int i = 0; i < 4; i++) reinterpret_cast<uint2*>(smem + ROWSTAT_OFF)[i * 32 + lane] = make_uint2(v[i].x, v[i].y & ~255u);
        __syncwarp();
        TS(0, 6);
        bar_arrive<BAR_STATS>(192);
      }
      #pragma unroll 1
      for (int d = 0; d < 5; d++) {
        if (d == 3 && grp == 1) continue;
        const int slot = d == 0 ? F_XN + rb : d == 4 ? F_Y + rb * 4 + ct : d == 3 ? F_H + rb : d == 2 ? F_B + ct : grp == 0 ? F_Z + ct : F_A + ct;
        const int byte = d == 0 ? lane & 7 : d == 4 ? 0 : d == 3 ? lane & 3 : (d == 1 && grp == 0) ? lane : lane >> 1;
        unsigned it = 0, m;
        while ((m = __ballot_sync(0xffffffffu, get_flag(slot, byte) != (epoch & 255u))) != 0 && ++it < POLL_LIMIT) {
          if (d == 1 && lane == 0) *reinterpret_cast<volatile int*>(smem + READY_OFF) = (__ffs(m) - 1) >> 1;
          __nanosleep(WATCH_NS);
        }
        if (d == 1 && lane == 0) *reinterpret_cast<volatile int*>(smem + READY_OFF) = 16;
        if (d < 4) TS(0, 8 + d * 2); else TS(0, 7);
        fence_async_global();
        __syncwarp();
        if (lane == 0 && d != 1) mbar_arrive(dep0 + 8 * d);
      }
    } else {
      cluster_wait();
      bar_sync<BAR_LN>(288);
      if (lane == 0) { TS(1, 5); publish(F_XN + rb, cta & 7, epoch); TS(1, 6); }
      __syncwarp();
      {
        unsigned it = 0;
        while (true) {
          bool ok = true;
          uint2 u[15];
          #pragma unroll
          for (int i = 0; i < 15; i++) u[i] = ld_vol2(&g_csum[(i % 5) * FH + c8 * 96 + (i / 5) * 32 + lane]);
          #pragma unroll
          for (int i = 0; i < 15; i++) ok = ok && u[i].y == epoch;
          #pragma unroll
          for (int i = 0; i < 3; i++)
            reinterpret_cast<float*>(smem + COLSUM_OFF)[i * 32 + lane] = ((__uint_as_float(u[i * 5].x) + __uint_as_float(u[i * 5 + 1].x)) +
                (__uint_as_float(u[i * 5 + 2].x) + __uint_as_float(u[i * 5 + 3].x))) + __uint_as_float(u[i * 5 + 4].x);
          if (ok || ++it > POLL_LIMIT) break;
          __nanosleep(POLL_NS);
        }
      }
      __syncwarp();
      TS(1, 4);
      bar_arrive<BAR_STATS>(192);
      bar_sync<BAR_PUB1>(160);
      if (lane == 0) {
        TS(1, 7);
        tma_store_3d(&maps.m[M_Z232], buf, 0, rb * 128, 3 * c8);
        bulk_commit();
        bulk_wait_all();
        set_flag(F_Z + (c8 >> 1), rb * 2 + (c8 & 1), epoch);
        TS(1, 8);
      }
      __syncwarp();
      bar_arrive<BAR_BUF>(160);
      if (grp == 1) {
        bar_sync<BAR_PUB2>(160);
        if (lane == 0) set_flag(F_A + ct, rb, epoch);
        TS(1, 9);
        __syncwarp();
      }
      bar_sync<BAR_PUB1>(160);
      if (lane == 0) set_flag(grp == 0 ? F_H + rb : F_B + ct, grp == 0 ? ct : rb, epoch);
      TS(1, 10);
      __syncwarp();
      bar_arrive<BAR_BUF>(160);
    }
  } else {
    asm volatile("setmaxnreg.inc.sync.aligned.u32 232;");
    const int t = tid & 127, w = t >> 5, l = t & 31;
    ln_rows(rv, cta, epoch);
    if (wg == 2) colsum_part(win, cta, epoch);
    TS(wg + 1, 0);
    cluster_wait();
    const int rl = w * 16 + ((l >> 3) & 1) * 8 + (l & 7);
    const int gr = w * 16 + (l & 15);
    const uint32_t st_base = buf + rl * 128;
    const uint32_t st_x = ((l >> 4) ^ (l & 7)) << 4;
    if (wg == 1) {
      float acc[2][48];
      zero(acc);
      mainloop<96, Z2SW ? 1 : 2, false, BAR_ORD1>(acc, sbase, grp, 0, 10);
      drain(acc, sbase, grp, 9);
      TS(2, 2);
      bar_sync<BAR_STATS>(192);
      const float2* rs = reinterpret_cast<const float2*>(smem + ROWSTAT_OFF) + w * 16 + (l >> 2);
      const float2* cs = reinterpret_cast<const float2*>(smem + COLSUM_OFF) + (l & 3);
      float sum[4], sq[4];
      #pragma unroll
      for (int r = 0; r < 4; r++) {
        const float2 st = rs[(r >> 1) * 64 + (r & 1) * 8];
        float s0 = 0.f, q0 = 0.f;
        #pragma unroll
        for (int j = 0; j < 12; j++) {
          const float2 c = cs[j * 4];
          float* a = &acc[r >> 1][4 * j + (r & 1) * 2];
          a[0] = gelu_tanh(fmaf(a[0], st.x, st.y * c.x));
          a[1] = gelu_tanh(fmaf(a[1], st.x, st.y * c.y));
          s0 += a[0] + a[1]; q0 = fmaf(a[0], a[0], q0); q0 = fmaf(a[1], a[1], q0);
        }
        s0 += __shfl_xor_sync(0xffffffffu, s0, 1); q0 += __shfl_xor_sync(0xffffffffu, q0, 1);
        s0 += __shfl_xor_sync(0xffffffffu, s0, 2); q0 += __shfl_xor_sync(0xffffffffu, q0, 2);
        sum[r] = s0; sq[r] = q0;
      }
      TS(2, 4);
      float rstd, off;
      {
        const int qd = l & 3;
        const float sm = qd == 0 ? sum[0] : qd == 1 ? sum[1] : qd == 2 ? sum[2] : sum[3];
        const float sv = qd == 0 ? sq[0] : qd == 1 ? sq[1] : qd == 2 ? sq[2] : sq[3];
        const int row = (qd >> 1) * 64 + w * 16 + (qd & 1) * 8 + (l >> 2);
        const float mu = sm * (1.f / 96), m2 = fmaxf(sv - sm * mu, 0.f);
        st_vol2(&g_zstat[(rb * 8 + c8) * 128 + row], __float_as_uint(mu), (__float_as_uint(m2) & ~255u) | (epoch & 255u));
        uint2 v[7];
        unsigned n = 0;
        while (true) {
          bool ok = true;
          #pragma unroll
          for (int j = 0; j < 7; j++) v[j] = ld_vol2(&g_zstat[(rb * 8 + ((c8 + 1 + j) & 7)) * 128 + row]);
          #pragma unroll
          for (int j = 0; j < 7; j++) ok = ok && ((v[j].y ^ epoch) & 255u) == 0;
          if (ok || ++n > POLL_LIMIT) break;
          __nanosleep(POLL_NS);
        }
        float mean = mu, var = m2;
        #pragma unroll
        for (int j = 0; j < 7; j++) { mean += __uint_as_float(v[j].x); var += __uint_as_float(v[j].y & ~255u); }
        mean *= 0.125f;
        float d = (mu - mean) * (mu - mean);
        #pragma unroll
        for (int j = 0; j < 7; j++) d = fmaf(__uint_as_float(v[j].x) - mean, __uint_as_float(v[j].x) - mean, d);
        rstd = rsqrtf(fmaf(96.f, d, var) * (1.f / FH) + LN_EPS); off = -mean * rstd;
        __syncwarp();
      }
      TS(2, 5);
      #pragma unroll
      for (int mi = 0; mi < 2; mi++) {
        const float r0 = __shfl_sync(0xffffffffu, rstd, (l & 28) + mi * 2), o0 = __shfl_sync(0xffffffffu, off, (l & 28) + mi * 2);
        const float r1 = __shfl_sync(0xffffffffu, rstd, (l & 28) + mi * 2 + 1), o1 = __shfl_sync(0xffffffffu, off, (l & 28) + mi * 2 + 1);
        #pragma unroll
        for (int jj = 0; jj < 6; jj++) {
          const float* a = &acc[mi][8 * jj];
          stsm4(buf + (jj >> 1) * 8192 + mi * 4096 + rl * 64 + ((((jj & 1) * 2 + (l >> 4)) ^ ((l >> 1) & 3)) << 4),
                pack_bf16(fmaf(a[0], r0, o0), fmaf(a[1], r0, o0)), pack_bf16(fmaf(a[2], r1, o1), fmaf(a[3], r1, o1)),
                pack_bf16(fmaf(a[4], r0, o0), fmaf(a[5], r0, o0)), pack_bf16(fmaf(a[6], r1, o1), fmaf(a[7], r1, o1)));
        }
      }
      fence_async_smem();
      bar_arrive<BAR_PUB1>(160);
      TS(2, 6);
      if (grp == 0) {
        float acc[2][96];
        {
          const bf16* bp = bsp + rb * 128 + w * 16 + (l >> 2);
          const float bb[4] = {__bfloat162float(bp[0]), __bfloat162float(bp[8]), __bfloat162float(bp[64]), __bfloat162float(bp[72])};
          #pragma unroll
          for (int i = 0; i < 96; i++) { acc[0][i] = bb[(i >> 1) & 1]; acc[1][i] = bb[2 + ((i >> 1) & 1)]; }
          pin(acc);
        }
        bar_sync<BAR_ORD2>(256);
        mainloop<192, 1, false, BAR_ORD1>(acc, sbase, 0, 20, 32);
        bar_sync<BAR_Z1>(256);
        drain(acc, sbase, 0, 51);
        TS(2, 7);
        {
          uint32_t z[2][4][4];
          #pragma unroll
          for (int i = 0; i < 4; i++) ldsm4(st_base + (st_x ^ (i << 5)), z[0][i][0], z[0][i][1], z[0][i][2], z[0][i][3]);
          #pragma unroll
          for (int bx = 0; bx < 6; bx++) {
            if (bx < 5) {
              #pragma unroll
              for (int i = 0; i < 4; i++)
                ldsm4(st_base + (bx + 1) * 8192 + (st_x ^ (i << 5)), z[(bx + 1) & 1][i][0], z[(bx + 1) & 1][i][1], z[(bx + 1) & 1][i][2], z[(bx + 1) & 1][i][3]);
            }
            #pragma unroll
            for (int i = 0; i < 4; i++) {
              const float* a = &acc[bx / 3][8 * ((bx % 3) * 4 + i)];
              const uint32_t* zz = z[bx & 1][i];
              stsm4(st_base + bx * 8192 + (st_x ^ (i << 5)),
                    hmul2_bf16(zz[0], pack_bf16(a[0], a[1])), hmul2_bf16(zz[1], pack_bf16(a[2], a[3])),
                    hmul2_bf16(zz[2], pack_bf16(a[4], a[5])), hmul2_bf16(zz[3], pack_bf16(a[6], a[7])));
            }
            if (bx % 3 == 2) {
              fence_async_smem();
              __syncwarp();
              if (l < 3) {
                tma_store_2d(&maps.m[M_HS], buf + (bx - 2 + l) * 8192 + w * 2048, ct * 192 + l * 64, rb * 128 + (bx / 3) * 64 + w * 16);
                bulk_commit();
              }
            }
          }
        }
        TS(2, 8);
        if (l < 3) bulk_wait_all();
        __syncwarp();
        bar_arrive<BAR_PUB1>(160);
        TS(2, 9);
        return;
      }
    } else {
      if (grp == 0) {
        float acc[2][96];
        zero(acc);
        bar_sync<BAR_ORD1>(256);
        mainloop<192, 1, false, BAR_ORD2>(acc, sbase, 0, 10, 10);
        drain(acc, sbase, 0, 19);
        TS(3, 2);
        bar_sync<BAR_BUF>(160);
        #pragma unroll
        for (int mi = 0; mi < 2; mi++)
          #pragma unroll
          for (int jj = 0; jj < 12; jj++) {
            const float* a = &acc[mi][8 * jj];
            stsm4(st_base + mi * 24576 + (jj >> 2) * 8192 + (st_x ^ ((jj & 3) << 5)),
                  pack_bf16(a[0], a[1]), pack_bf16(a[2], a[3]), pack_bf16(a[4], a[5]), pack_bf16(a[6], a[7]));
          }
        __syncwarp();
        TS(3, 3);
        const uint32_t rbase = buf + (l >> 4) * 24576 + gr * 128;
        #pragma unroll 1
        for (int c2 = 0; c2 < 12; c2++) {
          const uint32_t ab = rbase + (c2 >> 2) * 8192;
          uint4 v[2];
          #pragma unroll
          for (int i = 0; i < 2; i++) v[i] = lds128(ab + (((((c2 & 3) * 2 + i) ^ l) & 7) << 4));
          #pragma unroll
          for (int i = 0; i < 2; i++)
            sts128(ab + (((((c2 & 3) * 2 + i) ^ l) & 7) << 4),
                   pack_bf16(gelu_tanh(bf_lo(v[i].x)), gelu_tanh(bf_hi(v[i].x))), pack_bf16(gelu_tanh(bf_lo(v[i].y)), gelu_tanh(bf_hi(v[i].y))),
                   pack_bf16(gelu_tanh(bf_lo(v[i].z)), gelu_tanh(bf_hi(v[i].z))), pack_bf16(gelu_tanh(bf_lo(v[i].w)), gelu_tanh(bf_hi(v[i].w))));
        }
        TS(3, 4);
        bar_arrive<BAR_Z1>(256);
      }
    }
    float acc[2][80];
    if (grp == 1) {
      zero(acc);
      if (wg == 2) {
        bar_sync<BAR_ORD1>(256);
        mainloop<160, 0, false, BAR_ORD2>(acc, sbase, 1, 10, 10);
      } else {
        bar_sync<BAR_ORD2>(256);
        mainloop<160, 0, false, BAR_ORD1>(acc, sbase, 1, 20, 10);
      }
      drain(acc, sbase, 1, wg == 2 ? 19 : 29);
      TS(wg + 1, wg == 1 ? 7 : 2);
      if (wg == 1) bar_sync<BAR_Z1>(256); else bar_sync<BAR_BUF>(160);
      const uint32_t sg = wg == 1 ? 0x80008000u : 0u;
      const uint32_t tb = buf + ((l >> 4) * 8 + (l & 7)) * 128 + (((w * 2 + ((l >> 3) & 1)) ^ (l & 7)) << 4);
      #pragma unroll
      for (int mi = 0; mi < 2; mi++)
        #pragma unroll
        for (int jj = 0; jj < 10; jj++) {
          const float* a = &acc[mi][8 * jj];
          stsm4_t(tb + mi * 20480 + jj * 2048, pack_bf16(a[0], a[1]) ^ sg, pack_bf16(a[2], a[3]) ^ sg, pack_bf16(a[4], a[5]) ^ sg, pack_bf16(a[6], a[7]) ^ sg);
        }
      fence_async_smem();
      if (wg == 1) bar_sync<BAR_WG1>(128); else bar_sync<BAR_WG2>(128);
      TS(wg + 1, wg == 1 ? 8 : 6);
      if (l == 0) {
        #pragma unroll 1
        for (int i = 0; i < 2; i++) {
          tma_store_2d(&maps.m[M_ABS], buf + i * 20480 + w * 5120, rb * 128 + i * 64, (2 - wg) * DM + ct * 160 + w * 40);
          bulk_commit();
        }
        bulk_wait_all();
      }
      __syncwarp();
      TS(wg + 1, wg == 1 ? 9 : 10);
      if (wg == 1) {
        bar_arrive<BAR_PUB1>(160);
        #pragma unroll 1
        for (int i = 0; i < 4; i++) {
          uint4 v[5];
          #pragma unroll
          for (int j = 0; j < 5; j++) {
            const int e = (i * 5 + j) * 128 + t;
            v[j] = ldg128(x + (size_t)(rb * 128 + e / 20) * DM + ct * 160 + (e % 20) * 8);
          }
          #pragma unroll
          for (int j = 0; j < 5; j++) {
            const int e = (i * 5 + j) * 128 + t;
            stg128(out + (size_t)(rb * 128 + e / 20) * DM + ct * 160 + (e % 20) * 8, v[j]);
          }
        }
        bar_sync<BAR_WG1>(128);
        if (t == 0) publish(F_Y + rb * 4 + ct, 0, epoch);
        return;
      }
      bar_arrive<BAR_PUB2>(160);
      bar_arrive<BAR_Z1>(256);
    }
    zero(acc);
    bar_sync<BAR_ORD1>(256);
    mainloop<160, 0, false, 0>(acc, sbase, grp, grp == 0 ? 52 : 30, grp == 0 ? NX : 64 - NX);
    if (grp == 0) mainloop<160, WOSW ? 1 : 2, true, 0>(acc, sbase, 0, 52 + NX, 12);
    const uint32_t slab = buf + w * (16 * 320);
    const uint32_t addr = slab + (((l >> 3) & 1) * 8 + (l & 7)) * 320 + (l >> 4) * 16;
    bar_sync<BAR_BUF>(160);
    mbar_wait(dep0 + 32, 0);
    drain(acc, sbase, grp, total - 1);
    TS(3, 12);
    #pragma unroll
    for (int mi = 0; mi < 2; mi++) {
      #pragma unroll
      for (int jj = 0; jj < 10; jj++) {
        const float* a = &acc[mi][8 * jj];
        stsm4(addr + mi * 20480 + jj * 32, pack_bf16(a[0], a[1]), pack_bf16(a[2], a[3]), pack_bf16(a[4], a[5]), pack_bf16(a[6], a[7]));
      }
      fence_async_smem();
      __syncwarp();
      if (l == 0) {
        tma_reduce_2d(&maps.m[M_OUT], slab + mi * 20480, ct * 160, rb * 128 + mi * 64 + w * 16);
        bulk_commit();
      }
    }
    TS(3, 13);
    if (l == 0) {
      bulk_wait_read();
      if (w == 0) atomicAdd(&g_done, 1u);
    }
    TS(3, 15);
  }
}

typedef CUresult (*EncodeFn)(CUtensorMap*, CUtensorMapDataType, cuuint32_t, void*, const cuuint64_t*, const cuuint64_t*,
                             const cuuint32_t*, const cuuint32_t*, CUtensorMapInterleave, CUtensorMapSwizzle,
                             CUtensorMapL2promotion, CUtensorMapFloatOOBfill);

void make2d(EncodeFn enc, CUtensorMap* m, const void* p, uint64_t cols, uint64_t rows, uint32_t bc, uint32_t br, bool swz = true) {
  cuuint64_t gd[2] = {cols, rows}, gs[1] = {cols * 2};
  cuuint32_t bd[2] = {bc, br}, es[2] = {1, 1};
  enc(m, CU_TENSOR_MAP_DATA_TYPE_BFLOAT16, 2, const_cast<void*>(p), gd, gs, bd, es, CU_TENSOR_MAP_INTERLEAVE_NONE,
      swz ? CU_TENSOR_MAP_SWIZZLE_128B : CU_TENSOR_MAP_SWIZZLE_NONE, PROMO, CU_TENSOR_MAP_FLOAT_OOB_FILL_NONE);
}
void make3d(EncodeFn enc, CUtensorMap* m, const void* p, uint64_t cols, uint64_t rows, uint32_t cw, uint32_t nc, uint32_t br = 64) {
  cuuint64_t gd[3] = {cw, rows, cols / cw}, gs[2] = {cols * 2, cw * 2};
  cuuint32_t bd[3] = {cw, br, nc}, es[3] = {1, 1, 1};
  enc(m, CU_TENSOR_MAP_DATA_TYPE_BFLOAT16, 3, const_cast<void*>(p), gd, gs, bd, es, CU_TENSOR_MAP_INTERLEAVE_NONE,
      cw == 64 ? CU_TENSOR_MAP_SWIZZLE_128B : CU_TENSOR_MAP_SWIZZLE_64B, PROMO, CU_TENSOR_MAP_FLOAT_OOB_FILL_NONE);
}

}

extern "C" void kernel_launch(void* const* d_in, const int* in_sizes, int n_in, void* d_out, int out_size) {
  const bf16* x = (const bf16*)d_in[0];
  const bf16* wsre = (const bf16*)d_in[1];
  const bf16* wsim = (const bf16*)d_in[2];
  const bf16* wdre = (const bf16*)d_in[3];
  const bf16* wdim = (const bf16*)d_in[4];
  const bf16* win = (const bf16*)d_in[6];
  const bf16* wsp = (const bf16*)d_in[7];
  const bf16* bsp = (const bf16*)d_in[8];
  const bf16* wout = (const bf16*)d_in[9];

  void* fn = nullptr;
  cudaDriverEntryPointQueryResult qr;
  cudaGetDriverEntryPoint("cuTensorMapEncodeTiled", &fn, cudaEnableDefault, &qr);
  EncodeFn enc = (EncodeFn)fn;
  void *abT, *z2, *h, *xn;
  cudaGetSymbolAddress(&xn, g_xn);
  cudaGetSymbolAddress(&abT, g_abT);
  cudaGetSymbolAddress(&z2, g_z2);
  cudaGetSymbolAddress(&h, g_h);

  Maps maps;
  make2d(enc, &maps.m[M_X], x, DM, SEQ, 64, 64);
  make2d(enc, &maps.m[M_XN], xn, DM, SEQ, 64, 64);
  make3d(enc, &maps.m[M_Z232], z2, FH, SEQ, 32, 3, 128);
  if (Z2SW) make2d(enc, &maps.m[M_WIN32], win, FF, DM, 64, 64); else make3d(enc, &maps.m[M_WIN32], win, FF, DM, 32, 3);
  make2d(enc, &maps.m[M_WSRE], wsre, SEQ, SEQ, 64, 64);
  make2d(enc, &maps.m[M_WSIM], wsim, SEQ, SEQ, 64, 64);
  make2d(enc, &maps.m[M_WSP], wsp, SEQ, SEQ, 64, 64);
  make2d(enc, &maps.m[M_H], h, FH, SEQ, 64, 64);
  make3d(enc, &maps.m[M_WIN3], win, FF, DM, 64, 3);
  make3d(enc, &maps.m[M_Z23], z2, FH, SEQ, 64, 3);
  make2d(enc, &maps.m[M_WDRE], wdre, DM, DM, 64, 160);
  make2d(enc, &maps.m[M_WDIM], wdim, DM, DM, 64, 160);
  make2d(enc, &maps.m[M_AB], abT, SEQ, 2 * DM, 64, 160);
  if (WOSW) make2d(enc, &maps.m[M_WOUT], wout, DM, FH, 64, 64); else make3d(enc, &maps.m[M_WOUT], wout, DM, FH, 32, 5);
  make2d(enc, &maps.m[M_HS], h, FH, SEQ, 64, 16);
  make2d(enc, &maps.m[M_ABS], abT, SEQ, 2 * DM, 64, 40);
  make2d(enc, &maps.m[M_OUT], d_out, DM, SEQ, 160, 16, false);

  cudaFuncSetAttribute(fused_kernel, cudaFuncAttributeMaxDynamicSharedMemorySize, SMEM_BYTES);
  fused_kernel<<<128, 384, SMEM_BYTES>>>(maps, x, win, bsp, (bf16*)d_out);
}
```

```cpp
#include <cuda_runtime.h>
#include <cuda_bf16.h>
#include <cuda.h>
#include <stdint.h>

namespace {

typedef __nv_bfloat16 bf16;

constexpr int SEQ = 2048, DM = 640, FF = 1536, FH = 768;
#define NXV 8
#define NOV 4
constexpr int NX = NXV;
constexpr int NO = NOV;
constexpr int NST_A = 4, NST_B = 5, MAXST = 5;
constexpr int A_BYTES = 16384;
constexpr int BAR_OFF = 0;
constexpr int READY_OFF = 128;
constexpr int COLSUM_OFF = 256;
constexpr int ROWSTAT_OFF = 1024;
constexpr int ZSTAT_OFF = 2048;
constexpr int RED_OFF = 3072;
constexpr int RING_OFF = 4096;
constexpr int STAGE_A = 40960, STAGE_B = 36864;
constexpr int SMEM_BYTES = RING_OFF + 5 * STAGE_B + 40960;
constexpr int KB_A = 52 + NX + 12 - NO;
constexpr int KB_B = 84 - NX + NO;
constexpr float LN_EPS = 1e-5f;
constexpr unsigned POLL_LIMIT = 100000;
#define POLL_NS 100
#define PF_D 8
#define WATCH_NS 40

constexpr int BAR_ORD1 = 1, BAR_ORD2 = 2, BAR_WG1 = 3, BAR_WG2 = 4, BAR_LN = 5, BAR_BUF = 6, BAR_Z1 = 7, BAR_PUB1 = 8, BAR_PUB2 = 9,
              BAR_STATS = 10, BAR_U = 11;

enum { M_X, M_XN, M_WSRE, M_WSIM, M_WSP, M_H, M_WIN3, M_Z23, M_WDRE, M_WDIM, M_AB, M_WOUT, M_OUT, M_HS, M_ZS, M_ABS, M_COUNT };
struct Maps { CUtensorMap m[M_COUNT]; };

__device__ __align__(1024) bf16 g_abT[2 * DM * SEQ];
__device__ __align__(1024) bf16 g_z2[SEQ * FH];
__device__ __align__(1024) bf16 g_h[SEQ * FH];
__device__ __align__(1024) bf16 g_xn[SEQ * DM];
__device__ __align__(16) uint2 g_xstat[SEQ];
__device__ __align__(16) uint2 g_csum[5 * FH + DM];
__device__ __align__(16) uint2 g_zstat[64 * 128];
__device__ __align__(256) unsigned char g_flags[108 * 256];
constexpr int F_A = 0, F_B = 4, F_Z = 8, F_H = 12, F_XN = 28, F_Y = 44;
__device__ unsigned g_done;
#define TS(role, ev)
#define TC(i)

extern __shared__ __align__(1024) uint8_t smem[];

__device__ __forceinline__ uint32_t smem_u32(const void* p) { return (uint32_t)__cvta_generic_to_shared(p); }
__device__ __forceinline__ void mbar_init(uint32_t bar, uint32_t cnt) { asm volatile("mbarrier.init.shared::cta.b64 [%0], %1;" :: "r"(bar), "r"(cnt)); }
__device__ __forceinline__ void mbar_expect_tx(uint32_t bar, uint32_t bytes) { asm volatile("mbarrier.arrive.expect_tx.shared::cta.b64 _, [%0], %1;" :: "r"(bar), "r"(bytes) : "memory"); }
__device__ __forceinline__ void mbar_arrive(uint32_t bar) { asm volatile("mbarrier.arrive.shared::cta.b64 _, [%0];" :: "r"(bar) : "memory"); }
__device__ __forceinline__ void mbar_arrive_cluster(uint32_t bar, uint32_t cta) {
  asm volatile("{\n.reg .b32 ra;\nmapa.shared::cluster.u32 ra, %0, %1;\nmbarrier.arrive.shared::cluster.b64 _, [ra];\n}" :: "r"(bar), "r"(cta) : "memory");
}
__device__ __forceinline__ void mbar_wait(uint32_t bar, uint32_t parity) {
  asm volatile("{\n.reg .pred p;\n.reg .u32 n;\nmov.u32 n, 0;\n"
               "LW: mbarrier.try_wait.parity.shared::cta.b64 p, [%0], %1, 2000;\n@p bra LD;\n"
               "add.u32 n, n, 1;\nsetp.lt.u32 p, n, 20000;\n@p bra LW;\nLD:\n}" :: "r"(bar), "r"(parity) : "memory");
}
__device__ __forceinline__ void tma_load_2d(uint32_t dst, const CUtensorMap* map, uint32_t bar, int c0, int c1) {
  asm volatile("cp.async.bulk.tensor.2d.shared::cluster.global.mbarrier::complete_tx::bytes [%0], [%1, {%3, %4}], [%2];"
    :: "r"(dst), "l"((uint64_t)map), "r"(bar), "r"(c0), "r"(c1) : "memory");
}
__device__ __forceinline__ void tma_load_3d(uint32_t dst, const CUtensorMap* map, uint32_t bar, int c0, int c1, int c2) {
  asm volatile("cp.async.bulk.tensor.3d.shared::cluster.global.mbarrier::complete_tx::bytes [%0], [%1, {%3, %4, %5}], [%2];"
    :: "r"(dst), "l"((uint64_t)map), "r"(bar), "r"(c0), "r"(c1), "r"(c2) : "memory");
}
__device__ __forceinline__ void tma_load_2d_mc(uint32_t dst, const CUtensorMap* map, uint32_t bar, int c0, int c1, uint16_t mask) {
  asm volatile("cp.async.bulk.tensor.2d.shared::cluster.global.mbarrier::complete_tx::bytes.multicast::cluster [%0], [%1, {%3, %4}], [%2], %5;"
    :: "r"(dst), "l"((uint64_t)map), "r"(bar), "r"(c0), "r"(c1), "h"(mask) : "memory");
}
__device__ __forceinline__ void tma_store_2d(const CUtensorMap* map, uint32_t src, int c0, int c1) {
  asm volatile("cp.async.bulk.tensor.2d.global.shared::cta.bulk_group [%0, {%2, %3}], [%1];"
    :: "l"((uint64_t)map), "r"(src), "r"(c0), "r"(c1) : "memory");
}
__device__ __forceinline__ void tma_store_3d(const CUtensorMap* map, uint32_t src, int c0, int c1, int c2) {
  asm volatile("cp.async.bulk.tensor.3d.global.shared::cta.bulk_group [%0, {%2, %3, %4}], [%1];"
    :: "l"((uint64_t)map), "r"(src), "r"(c0), "r"(c1), "r"(c2) : "memory");
}
__device__ __forceinline__ void tma_reduce_2d(const CUtensorMap* map, uint32_t src, int c0, int c1) {
  asm volatile("cp.reduce.async.bulk.tensor.2d.global.shared::cta.add.tile.bulk_group [%0, {%2, %3}], [%1];"
    :: "l"((uint64_t)map), "r"(src), "r"(c0), "r"(c1) : "memory");
}
__device__ __forceinline__ void bulk_wait_all() { asm volatile("cp.async.bulk.wait_group 0;" ::: "memory"); }
__device__ __forceinline__ void bulk_commit() { asm volatile("cp.async.bulk.commit_group;" ::: "memory"); }
__device__ __forceinline__ void bulk_wait_read() { asm volatile("cp.async.bulk.wait_group.read 0;" ::: "memory"); }
__device__ __forceinline__ void fence_async_smem() { asm volatile("fence.proxy.async.shared::cta;" ::: "memory"); }
__device__ __forceinline__ void fence_async_global() { asm volatile("fence.proxy.async.global;" ::: "memory"); }
__device__ __forceinline__ void wgmma_fence() { asm volatile("wgmma.fence.sync.aligned;" ::: "memory"); }
__device__ __forceinline__ void wgmma_commit() { asm volatile("wgmma.commit_group.sync.aligned;" ::: "memory"); }
template<int N> __device__ __forceinline__ void wgmma_wait() { asm volatile("wgmma.wait_group.sync.aligned %0;" :: "n"(N) : "memory"); }
template<int ID> __device__ __forceinline__ void bar_sync(int n) { asm volatile("bar.sync %0, %1;" :: "n"(ID), "r"(n) : "memory"); }
template<int ID> __device__ __forceinline__ void bar_arrive(int n) { asm volatile("bar.arrive %0, %1;" :: "n"(ID), "r"(n) : "memory"); }
__device__ __forceinline__ void cluster_wait() { asm volatile("barrier.cluster.wait.aligned;" ::: "memory"); }
__device__ __forceinline__ uint64_t desc64(uint32_t lo, uint32_t hi) { return (uint64_t)lo | ((uint64_t)hi << 32); }
__device__ __forceinline__ uint4 ld_vol4(const uint4* p) {
  uint4 v; asm volatile("ld.relaxed.gpu.global.v4.u32 {%0,%1,%2,%3}, [%4];" : "=r"(v.x), "=r"(v.y), "=r"(v.z), "=r"(v.w) : "l"(p) : "memory"); return v;
}
__device__ __forceinline__ uint2 ld_vol2(const uint2* p) {
  uint2 v; asm volatile("ld.relaxed.gpu.global.v2.u32 {%0,%1}, [%2];" : "=r"(v.x), "=r"(v.y) : "l"(p) : "memory"); return v;
}
__device__ __forceinline__ void st_vol4(uint4* p, uint32_t a, uint32_t b, uint32_t c, uint32_t d) {
  asm volatile("st.relaxed.gpu.global.v4.u32 [%0], {%1,%2,%3,%4};" :: "l"(p), "r"(a), "r"(b), "r"(c), "r"(d) : "memory");
}
__device__ __forceinline__ void st_vol2(uint2* p, uint32_t a, uint32_t b) {
  asm volatile("st.relaxed.gpu.global.v2.u32 [%0], {%1,%2};" :: "l"(p), "r"(a), "r"(b) : "memory");
}
__device__ __forceinline__ void stg128(void* p, uint4 v) {
  asm volatile("st.global.v4.u32 [%0], {%1,%2,%3,%4};" :: "l"(p), "r"(v.x), "r"(v.y), "r"(v.z), "r"(v.w));
}
__device__ __forceinline__ unsigned ld_relaxed(const unsigned* p) {
  unsigned v; asm volatile("ld.relaxed.gpu.global.u32 %0, [%1];" : "=r"(v) : "l"(p) : "memory"); return v;
}
__device__ __forceinline__ uint32_t pack_bf16(float lo, float hi) {
  uint32_t r; asm("cvt.rn.bf16x2.f32 %0, %1, %2;" : "=r"(r) : "f"(hi), "f"(lo)); return r;
}
__device__ __forceinline__ float bf_lo(uint32_t v) { return __uint_as_float(v << 16); }
__device__ __forceinline__ float bf_hi(uint32_t v) { return __uint_as_float(v & 0xFFFF0000u); }
__device__ __forceinline__ void stsm4(uint32_t addr, uint32_t a, uint32_t b, uint32_t c, uint32_t d) {
  asm volatile("stmatrix.sync.aligned.m8n8.x4.shared.b16 [%0], {%1,%2,%3,%4};" :: "r"(addr), "r"(a), "r"(b), "r"(c), "r"(d));
}
__device__ __forceinline__ void stsm4_t(uint32_t addr, uint32_t a, uint32_t b, uint32_t c, uint32_t d) {
  asm volatile("stmatrix.sync.aligned.m8n8.x4.trans.shared.b16 [%0], {%1,%2,%3,%4};" :: "r"(addr), "r"(a), "r"(b), "r"(c), "r"(d));
}
__device__ __forceinline__ void ldsm4(uint32_t addr, uint32_t& a, uint32_t& b, uint32_t& c, uint32_t& d) {
  asm volatile("ldmatrix.sync.aligned.m8n8.x4.shared.b16 {%0,%1,%2,%3}, [%4];" : "=r"(a), "=r"(b), "=r"(c), "=r"(d) : "r"(addr));
}
__device__ __forceinline__ uint4 lds128(uint32_t a) {
  uint4 v; asm volatile("ld.shared.v4.u32 {%0,%1,%2,%3}, [%4];" : "=r"(v.x), "=r"(v.y), "=r"(v.z), "=r"(v.w) : "r"(a)); return v;
}
__device__ __forceinline__ void sts128(uint32_t a, uint32_t x, uint32_t y, uint32_t z, uint32_t w) {
  asm volatile("st.shared.v4.u32 [%0], {%1,%2,%3,%4};" :: "r"(a), "r"(x), "r"(y), "r"(z), "r"(w));
}
__device__ __forceinline__ uint32_t hmul2_bf16(uint32_t a, uint32_t b) {
  uint32_t r; asm("mul.rn.bf16x2 %0, %1, %2;" : "=r"(r) : "r"(a), "r"(b)); return r;
}
__device__ __forceinline__ float gelu_tanh(float v) {
  float u = v * fmaf(0.0356774081f, v * v, 0.7978845608f);
  float t; asm("tanh.approx.f32 %0, %1;" : "=f"(t) : "f"(u));
  float hv = 0.5f * v;
  return fmaf(hv, t, hv);
}

template<int TB>
__device__ __forceinline__ void wgmma_n192(float (&d)[96], uint64_t da, uint64_t db, int scale_d) {
  asm volatile("{\n.reg .pred p;\nsetp.ne.b32 p, %98, 0;\n"
   "wgmma.mma_async.sync.aligned.m64n192k16.f32.bf16.bf16 {%0,%1,%2,%3,%4,%5,%6,%7,%8,%9,%10,%11,%12,%13,%14,%15,%16,%17,%18,%19,%20,%21,%22,%23,%24,%25,%26,%27,%28,%29,%30,%31,%32,%33,%34,%35,%36,%37,%38,%39,%40,%41,%42,%43,%44,%45,%46,%47,%48,%49,%50,%51,%52,%53,%54,%55,%56,%57,%58,%59,%60,%61,%62,%63,%64,%65,%66,%67,%68,%69,%70,%71,%72,%73,%74,%75,%76,%77,%78,%79,%80,%81,%82,%83,%84,%85,%86,%87,%88,%89,%90,%91,%92,%93,%94,%95}, %96, %97, p, 1, 1, 0, %99;\n}"
   : "+f"(d[0]),"+f"(d[1]),"+f"(d[2]),"+f"(d[3]),"+f"(d[4]),"+f"(d[5]),"+f"(d[6]),"+f"(d[7]),"+f"(d[8]),"+f"(d[9]),"+f"(d[10]),"+f"(d[11]),"+f"(d[12]),"+f"(d[13]),"+f"(d[14]),"+f"(d[15]),"+f"(d[16]),"+f"(d[17]),"+f"(d[18]),"+f"(d[19]),"+f"(d[20]),"+f"(d[21]),"+f"(d[22]),"+f"(d[23]),"+f"(d[24]),"+f"(d[25]),"+f"(d[26]),"+f"(d[27]),"+f"(d[28]),"+f"(d[29]),"+f"(d[30]),"+f"(d[31]),"+f"(d[32]),"+f"(d[33]),"+f"(d[34]),"+f"(d[35]),"+f"(d[36]),"+f"(d[37]),"+f"(d[38]),"+f"(d[39]),"+f"(d[40]),"+f"(d[41]),"+f"(d[42]),"+f"(d[43]),"+f"(d[44]),"+f"(d[45]),"+f"(d[46]),"+f"(d[47]),"+f"(d[48]),"+f"(d[49]),"+f"(d[50]),"+f"(d[51]),"+f"(d[52]),"+f"(d[53]),"+f"(d[54]),"+f"(d[55]),"+f"(d[56]),"+f"(d[57]),"+f"(d[58]),"+f"(d[59]),"+f"(d[60]),"+f"(d[61]),"+f"(d[62]),"+f"(d[63]),"+f"(d[64]),"+f"(d[65]),"+f"(d[66]),"+f"(d[67]),"+f"(d[68]),"+f"(d[69]),"+f"(d[70]),"+f"(d[71]),"+f"(d[72]),"+f"(d[73]),"+f"(d[74]),"+f"(d[75]),"+f"(d[76]),"+f"(d[77]),"+f"(d[78]),"+f"(d[79]),"+f"(d[80]),"+f"(d[81]),"+f"(d[82]),"+f"(d[83]),"+f"(d[84]),"+f"(d[85]),"+f"(d[86]),"+f"(d[87]),"+f"(d[88]),"+f"(d[89]),"+f"(d[90]),"+f"(d[91]),"+f"(d[92]),"+f"(d[93]),"+f"(d[94]),"+f"(d[95])
   : "l"(da), "l"(db), "r"(scale_d), "n"(TB));
}
template<int TB>
__device__ __forceinline__ void wgmma_n160(float (&d)[80], uint64_t da, uint64_t db, int scale_d) {
  asm volatile("{\n.reg .pred p;\nsetp.ne.b32 p, %82, 0;\n"
   "wgmma.mma_async.sync.aligned.m64n160k16.f32.bf16.bf16 {%0,%1,%2,%3,%4,%5,%6,%7,%8,%9,%10,%11,%12,%13,%14,%15,%16,%17,%18,%19,%20,%21,%22,%23,%24,%25,%26,%27,%28,%29,%30,%31,%32,%33,%34,%35,%36,%37,%38,%39,%40,%41,%42,%43,%44,%45,%46,%47,%48,%49,%50,%51,%52,%53,%54,%55,%56,%57,%58,%59,%60,%61,%62,%63,%64,%65,%66,%67,%68,%69,%70,%71,%72,%73,%74,%75,%76,%77,%78,%79}, %80, %81, p, 1, 1, 0, %83;\n}"
   : "+f"(d[0]),"+f"(d[1]),"+f"(d[2]),"+f"(d[3]),"+f"(d[4]),"+f"(d[5]),"+f"(d[6]),"+f"(d[7]),"+f"(d[8]),"+f"(d[9]),"+f"(d[10]),"+f"(d[11]),"+f"(d[12]),"+f"(d[13]),"+f"(d[14]),"+f"(d[15]),"+f"(d[16]),"+f"(d[17]),"+f"(d[18]),"+f"(d[19]),"+f"(d[20]),"+f"(d[21]),"+f"(d[22]),"+f"(d[23]),"+f"(d[24]),"+f"(d[25]),"+f"(d[26]),"+f"(d[27]),"+f"(d[28]),"+f"(d[29]),"+f"(d[30]),"+f"(d[31]),"+f"(d[32]),"+f"(d[33]),"+f"(d[34]),"+f"(d[35]),"+f"(d[36]),"+f"(d[37]),"+f"(d[38]),"+f"(d[39]),"+f"(d[40]),"+f"(d[41]),"+f"(d[42]),"+f"(d[43]),"+f"(d[44]),"+f"(d[45]),"+f"(d[46]),"+f"(d[47]),"+f"(d[48]),"+f"(d[49]),"+f"(d[50]),"+f"(d[51]),"+f"(d[52]),"+f"(d[53]),"+f"(d[54]),"+f"(d[55]),"+f"(d[56]),"+f"(d[57]),"+f"(d[58]),"+f"(d[59]),"+f"(d[60]),"+f"(d[61]),"+f"(d[62]),"+f"(d[63]),"+f"(d[64]),"+f"(d[65]),"+f"(d[66]),"+f"(d[67]),"+f"(d[68]),"+f"(d[69]),"+f"(d[70]),"+f"(d[71]),"+f"(d[72]),"+f"(d[73]),"+f"(d[74]),"+f"(d[75]),"+f"(d[76]),"+f"(d[77]),"+f"(d[78]),"+f"(d[79])
   : "l"(da), "l"(db), "r"(scale_d), "n"(TB));
}

template<int N, int TB>
__device__ __forceinline__ void wgmma_n(float (&d)[N / 2], uint64_t da, uint64_t db) {
  if constexpr (N == 192) wgmma_n192<TB>(d, da, db, 1); else wgmma_n160<TB>(d, da, db, 1);
}

template<int M, int R>
__device__ __forceinline__ void pin(float (&acc)[M][R]) {
  #pragma unroll
  for (int mi = 0; mi < M; mi++)
    #pragma unroll
    for (int i = 0; i < R; i++) asm volatile("" : "+f"(acc[mi][i]) :: "memory");
}
template<int M, int R>
__device__ __forceinline__ void zero(float (&acc)[M][R]) {
  #pragma unroll
  for (int mi = 0; mi < M; mi++)
    #pragma unroll
    for (int i = 0; i < R; i++) acc[mi][i] = 0.f;
  pin(acc);
}

template<int N, int M, int TB, bool CONT, int ORD_BAR>
__device__ __forceinline__ void mainloop(float (&acc)[M][N / 2], uint32_t sbase, int grp, int g0, int nk, int m0 = 0) {
  const uint32_t full0 = sbase + BAR_OFF, empty0 = full0 + 8 * MAXST, ring = sbase + RING_OFF;
  const int nst = grp == 0 ? NST_A : NST_B, total = grp == 0 ? KB_A : KB_B;
  const uint32_t sstep = (grp == 0 ? STAGE_A : STAGE_B) >> 4;
  const int t = threadIdx.x & 127;
  const uint32_t da0 = (((ring + m0 * 8192) & 0x3FFFF) >> 4) | 0x10000u;
  const uint32_t db0 = (((ring + A_BYTES) & 0x3FFFF) >> 4) | ((TB == 2 ? 256u : TB ? 512u : 1u) << 16);
  constexpr uint32_t HI_A = 0x40000040u, HI_B = TB == 2 ? 0x80000020u : 0x40000040u;
  int s = g0 % nst, ph = (g0 / nst) & 1, ps = s == 0 ? nst - 1 : s - 1;
  #pragma unroll 1
  for (int g = g0; g < g0 + nk; g++) {
    const uint32_t so = s * sstep;
    mbar_wait(full0 + 8 * s, ph);
    wgmma_fence();
    #pragma unroll
    for (int k = 0; k < 4; k++) {
      const uint64_t db = desc64(db0 + so + (TB == 2 ? k * 64 : TB ? k * 128 : k * 2), HI_B);
      #pragma unroll
      for (int mi = 0; mi < M; mi++) wgmma_n<N, TB != 0>(acc[mi], desc64(da0 + so + mi * 512 + k * 2, HI_A), db);
    }
    wgmma_commit();
    if (ORD_BAR != 0 && g == g0 + nk - 1) bar_arrive<ORD_BAR>(256);
    wgmma_wait<1>();
    if (t < 2 * M && (CONT || g > g0) && g - 1 + nst < total) mbar_arrive_cluster(empty0 + 8 * ps, t & 1);
    ps = s;
    if (++s == nst) { s = 0; ph ^= 1; }
  }
}
template<int M, int R>
__device__ __forceinline__ void drain(float (&acc)[M][R], uint32_t sbase, int grp, int glast) {
  wgmma_wait<0>();
  pin(acc);
  const int t = threadIdx.x & 127;
  const int nst = grp == 0 ? NST_A : NST_B, total = grp == 0 ? KB_A : KB_B;
  if (t < 2 * M && glast + nst < total) mbar_arrive_cluster(sbase + BAR_OFF + 8 * MAXST + 8 * (glast % nst), t & 1);
}

__device__ __forceinline__ void set_flag(int slot, int byte, unsigned epoch) {
  asm volatile("st.relaxed.gpu.global.u8 [%0], %1;" :: "l"(g_flags + slot * 256 + byte), "r"(epoch & 255u) : "memory");
}
__device__ __forceinline__ unsigned get_flag(int slot, int byte) {
  unsigned v; asm volatile("ld.relaxed.gpu.global.u8 %0, [%1];" : "=r"(v) : "l"(g_flags + slot * 256 + byte) : "memory"); return v;
}
__device__ __forceinline__ void publish(int slot, int byte, unsigned epoch) {
  asm volatile("fence.acq_rel.gpu;" ::: "memory");
  set_flag(slot, byte, epoch);
}
__device__ __forceinline__ float sum8(uint4 v) {
  return ((bf_lo(v.x) + bf_hi(v.x)) + (bf_lo(v.y) + bf_hi(v.y))) + ((bf_lo(v.z) + bf_hi(v.z)) + (bf_lo(v.w) + bf_hi(v.w)));
}
__device__ __forceinline__ uint4 ldg128(const void* p) {
  uint4 v; asm volatile("ld.global.nc.v4.u32 {%0,%1,%2,%3}, [%4];" : "=r"(v.x), "=r"(v.y), "=r"(v.z), "=r"(v.w) : "l"(p)); return v;
}

__device__ __forceinline__ void ln_rows(const uint4 (&rv)[5], int cta, unsigned epoch) {
  const int t = threadIdx.x - 128, row = cta * 16 + (t >> 4), c = t & 15;
  const float sh = __shfl_sync(0xffffffffu, bf_lo(rv[0].x), t & 16);
  float d[40], s = 0.f, q = 0.f;
  #pragma unroll
  for (int j = 0; j < 5; j++) {
    const uint32_t u[4] = {rv[j].x, rv[j].y, rv[j].z, rv[j].w};
    #pragma unroll
    for (int e = 0; e < 4; e++) {
      const float d0 = bf_lo(u[e]) - sh, d1 = bf_hi(u[e]) - sh;
      d[j * 8 + e * 2] = d0; d[j * 8 + e * 2 + 1] = d1;
      s += d0 + d1; q = fmaf(d0, d0, q); q = fmaf(d1, d1, q);
    }
  }
  #pragma unroll
  for (int o = 1; o < 16; o <<= 1) { s += __shfl_xor_sync(0xffffffffu, s, o); q += __shfl_xor_sync(0xffffffffu, q, o); }
  const float md = s * (1.f / DM);
  const float r = rsqrtf(fmaxf(fmaf(q, 1.f / DM, -md * md), 0.f) + LN_EPS), o = -md * r;
  if (c == 0) st_vol2(&g_xstat[row], __float_as_uint(r), (__float_as_uint(-(md + sh) * r) & ~255u) | (epoch & 255u));
  #pragma unroll
  for (int j = 0; j < 5; j++) {
    const float* a = &d[j * 8];
    stg128(reinterpret_cast<uint4*>(g_xn + (size_t)row * DM) + c + 16 * j, make_uint4(
           pack_bf16(fmaf(a[0], r, o), fmaf(a[1], r, o)), pack_bf16(fmaf(a[2], r, o), fmaf(a[3], r, o)),
           pack_bf16(fmaf(a[4], r, o), fmaf(a[5], r, o)), pack_bf16(fmaf(a[6], r, o), fmaf(a[7], r, o))));
  }
  bar_arrive<BAR_LN>(288);
}

__device__ __forceinline__ void weight_sums(const bf16* __restrict__ win, const bf16* __restrict__ wdre, int j, unsigned epoch) {
  const int t = threadIdx.x & 127, w = t >> 5, l = t & 31;
  const int cj = min(j, 59), cg = cj % 12, rg = cj / 12, wr = j * 10 + min(t >> 3, 9);
  uint4 cv[8], rv[10];
  #pragma unroll
  for (int i = 0; i < 8; i++) cv[i] = ldg128(reinterpret_cast<const uint4*>(win + (size_t)(rg * 128 + w * 32 + i * 4 + (l >> 3)) * FF + FH + cg * 64) + (l & 7));
  #pragma unroll
  for (int i = 0; i < 10; i++) rv[i] = ldg128(reinterpret_cast<const uint4*>(wdre + (size_t)wr * DM) + (l & 7) + 8 * i);
  float v[8];
  #pragma unroll
  for (int e = 0; e < 8; e++) v[e] = 0.f;
  #pragma unroll
  for (int i = 0; i < 8; i++) {
    v[0] += bf_lo(cv[i].x); v[1] += bf_hi(cv[i].x); v[2] += bf_lo(cv[i].y); v[3] += bf_hi(cv[i].y);
    v[4] += bf_lo(cv[i].z); v[5] += bf_hi(cv[i].z); v[6] += bf_lo(cv[i].w); v[7] += bf_hi(cv[i].w);
  }
  #pragma unroll
  for (int st = 0; st < 2; st++) {
    const int n = 4 >> st;
    const bool up = (l & (4 * n)) != 0;
    #pragma unroll
    for (int e = 0; e < 4; e++)
      if (e < n) { const float keep = up ? v[e + n] : v[e], send = up ? v[e] : v[e + n]; v[e] = keep + __shfl_xor_sync(0xffffffffu, send, 4 * n); }
  }
  float* red = reinterpret_cast<float*>(smem + RED_OFF);
  *reinterpret_cast<float2*>(red + w * 64 + (l & 7) * 8 + (l >> 3) * 2) = make_float2(v[0], v[1]);
  float s = 0.f;
  #pragma unroll
  for (int i = 0; i < 10; i++) s += sum8(rv[i]);
  #pragma unroll
  for (int o = 1; o < 8; o <<= 1) s += __shfl_xor_sync(0xffffffffu, s, o);
  if ((l & 7) == 0) st_vol2(&g_csum[5 * FH + wr], __float_as_uint(s), epoch);
  bar_sync<BAR_WG1>(128);
  if (t < 64) st_vol2(&g_csum[rg * FH + cg * 64 + t], __float_as_uint((red[t] + red[64 + t]) + (red[128 + t] + red[192 + t])), epoch);
}

__device__ __forceinline__ void a_entry(int g, int grp, int& mi, int& kb) {
  if (g < 10) { mi = M_X; kb = g; }
  else if (g < 20) { mi = M_XN; kb = g - 10; }
  else if (g < 52) { mi = grp == 0 ? M_WSP : M_WSRE; kb = g - 20; }
  else if (grp == 0) {
    if (g < 52 + NX) { mi = M_WSIM; kb = g - 52 + 32 - NX; }
    else { mi = M_H; kb = g - 52 - NX; }
  } else {
    if (g < 84 - NX) { mi = M_WSIM; kb = g - 52; }
    else { mi = M_H; kb = g - (84 - NX) + 12 - NO; }
  }
}

__global__ void __cluster_dims__(2, 1, 1) __launch_bounds__(384, 1)
fused_kernel(const __grid_constant__ Maps maps, const bf16* __restrict__ x, const bf16* __restrict__ win, const bf16* __restrict__ wdre,
             const bf16* __restrict__ bsp, bf16* __restrict__ out) {
  const uint32_t sbase = smem_u32(smem);
  const uint32_t full0 = sbase + BAR_OFF, empty0 = full0 + 8 * MAXST, dep0 = empty0 + 8 * MAXST, ring = sbase + RING_OFF;
  const int tid = threadIdx.x, wg = __shfl_sync(0xffffffffu, tid >> 7, 0);
  const int cta = blockIdx.x, rank = cta & 1, grp = (cta >> 1) & 1, rb = cta >> 3, ct = ((cta >> 2) & 1) * 2 + rank;
  const int total = grp == 0 ? KB_A : KB_B, gh = grp == 0 ? 52 + NX : 84 - NX;
  const uint32_t stage_bytes = grp == 0 ? STAGE_A : STAGE_B;
  const int nst = grp == 0 ? NST_A : NST_B;
  const uint32_t buf = ring + nst * stage_bytes;

  uint4 rv[5];
  if (wg != 0) {
    #pragma unroll
    for (int j = 0; j < 5; j++) rv[j] = ldg128(reinterpret_cast<const uint4*>(x + (size_t)(cta * 16 + ((tid - 128) >> 4)) * DM) + (tid & 15) + 16 * j);
  }
  const unsigned epoch = (ld_relaxed(&g_done) >> 7) + 1u;
  if (tid == 0) {
    TS(0, 0);
    for (int s = 0; s < MAXST; s++) { mbar_init(full0 + 8 * s, 2); mbar_init(empty0 + 8 * s, 4); mbar_init(dep0 + 8 * s, 1); }
    *reinterpret_cast<volatile int*>(smem + READY_OFF) = 0;
    asm volatile("fence.mbarrier_init.release.cluster;" ::: "memory");
  }
  __syncthreads();
  asm volatile("barrier.cluster.arrive.relaxed.aligned;" ::: "memory");

  if (wg == 0) {
    asm volatile("setmaxnreg.dec.sync.aligned.u32 40;");
    const int warp = tid >> 5, lane = tid & 31;
    if (warp == 0) {
      const int row = rb * 128;
      if (lane == 0) {
        for (int g = 0; g < nst; g++) {
          mbar_expect_tx(full0 + 8 * g, A_BYTES);
          tma_load_2d(ring + g * stage_bytes, &maps.m[M_X], full0 + 8 * g, g * 64, row);
          tma_load_2d(ring + g * stage_bytes + 8192, &maps.m[M_X], full0 + 8 * g, g * 64, row + 64);
        }
      }
      __syncwarp();
      cluster_wait();
      if (lane == 0) {
        int s = 0, ph = 0;
        #pragma unroll 1
        for (int g = nst; g < total; g++) {
          int mi, kb;
          a_entry(g, grp, mi, kb);
          if (g == 10 || g == gh) { TS(0, g > 10 ? 3 : 1); mbar_wait(dep0 + (g > 10 ? 24 : 0), 0); fence_async_global(); TS(0, g > 10 ? 4 : 2); }
          mbar_wait(empty0 + 8 * s, ph);
          mbar_expect_tx(full0 + 8 * s, A_BYTES);
          tma_load_2d_mc(ring + s * stage_bytes + rank * 8192, &maps.m[mi], full0 + 8 * s, kb * 64, row + rank * 64, 3);
          if (++s == nst) { s = 0; ph ^= 1; }
          if (g + PF_D < gh) {
            a_entry(g + PF_D, grp, mi, kb);
            if (mi >= M_WSRE && (kb & 1) == (ct >> 1))
              asm volatile("cp.async.bulk.prefetch.tensor.2d.L2.global.tile [%0, {%1, %2}];" :: "l"((uint64_t)&maps.m[mi]), "r"(kb * 64), "r"(row + rank * 64) : "memory");
          }
        }
        TS(0, 5);
      }
    } else if (warp == 1) {
      if (lane == 0) {
        int s = 0, ph = 1;
        int have = 0;
        #pragma unroll 1
        for (int g = 0; g < total; g++) {
          int mi, kb, c;
          a_entry(g, grp, mi, kb);
          const bool nmaj = g >= gh || (grp == 0 && g < 52);
          uint32_t bytes = 20480;
          if (g >= gh) { mi = M_WOUT; c = ct * 5; }
          else if (g >= 52) { mi = M_AB; c = DM + ct * 160; }
          else if (grp == 0) { mi = g < 20 ? M_WIN3 : M_Z23; c = 3 * ct + (g < 10 ? 12 : 0); bytes = 24576; }
          else { mi = g < 10 ? M_WDRE : g < 20 ? M_WDIM : M_AB; c = ct * 160; }
          if (g >= 20 && g < 52 && ((g - 20) >> 1) >= have) {
            if (g == 20) TS(1, 0);
            unsigned it = 0;
            while ((have = *reinterpret_cast<volatile int*>(smem + READY_OFF)) <= ((g - 20) >> 1) && ++it < 50 * POLL_LIMIT) {}
            fence_async_global();
            if (g == 20) { TS(1, 1); TC(1); }
          }
          if (g == 52) { TS(1, 2); mbar_wait(dep0 + 16, 0); fence_async_global(); TS(1, 3); TC(2); }
          const uint32_t dst = ring + s * stage_bytes + A_BYTES, fb = full0 + 8 * s;
          mbar_wait(empty0 + 8 * s, ph);
          if (++s == nst) { s = 0; ph ^= 1; }
          mbar_expect_tx(fb, bytes);
          if (nmaj) tma_load_3d(dst, &maps.m[mi], fb, 0, kb * 64, c);
          else tma_load_2d(dst, &maps.m[mi], fb, kb * 64, c);
        }
      }
      __syncwarp();
      cluster_wait();
    } else if (warp == 2) {
      if (lane < M_COUNT) asm volatile("prefetch.tensormap [%0];" :: "l"((uint64_t)&maps.m[lane]) : "memory");
      cluster_wait();
      {
        unsigned it = 0;
        uint2 v[4];
        while (true) {
          bool ok = true;
          #pragma unroll
          for (int i = 0; i < 4; i++) { v[i] = ld_vol2(&g_xstat[rb * 128 + i * 32 + lane]); ok = ok && ((v[i].y ^ epoch) & 255u) == 0; }
          if (ok || ++it > POLL_LIMIT) break;
          __nanosleep(POLL_NS);
        }
        #pragma unroll
        for (int i = 0; i < 4; i++) reinterpret_cast<uint2*>(smem + ROWSTAT_OFF)[i * 32 + lane] = make_uint2(v[i].x, v[i].y & ~255u);
        __syncwarp();
        TS(0, 6);
        if (grp == 0) bar_arrive<BAR_STATS>(320); else bar_arrive<BAR_STATS>(192);
      }
      #pragma unroll 1
      for (int i = 0; i < 5; i++) {
        const int d = i == 3 ? 4 : i == 4 ? 3 : i;
        const int slot = d == 0 ? F_XN + rb : d == 4 ? F_Y + rb * 4 + ct : d == 3 ? F_H + rb : d == 2 ? F_B + ct : grp == 0 ? F_Z + ct : F_A + ct;
        const int byte = d == 0 ? lane & 7 : d == 4 ? 0 : d == 3 ? lane & 3 : lane & 15;
        unsigned it = 0, m;
        while ((m = __ballot_sync(0xffffffffu, get_flag(slot, byte) != (epoch & 255u))) != 0 && ++it < POLL_LIMIT) {
          if (d == 1 && lane == 0) *reinterpret_cast<volatile int*>(smem + READY_OFF) = __ffs(m) - 1;
          __nanosleep(WATCH_NS);
        }
        if (d == 1 && lane == 0) *reinterpret_cast<volatile int*>(smem + READY_OFF) = 16;
        if (d < 4) TS(0, 8 + d * 2); else TS(0, 7);
        fence_async_global();
        __syncwarp();
        if (lane == 0 && d != 1) mbar_arrive(dep0 + 8 * d);
      }
    } else {
      cluster_wait();
      bar_sync<BAR_LN>(288);
      if (lane == 0) { TS(1, 5); publish(F_XN + rb, cta & 7, epoch); TS(1, 6); }
      __syncwarp();
      #pragma unroll 1
      for (int i = 0; i < 6 - grp; i++) {
        unsigned it = 0;
        const uint2* src = grp == 0 ? &g_csum[ct * 192 + i * 32 + lane] : &g_csum[5 * FH + ct * 160 + i * 32 + lane];
        while (true) {
          bool ok = true;
          float a = 0.f;
          #pragma unroll
          for (int p = 0; p < 5; p++) {
            if (p == 0 || grp == 0) { const uint2 u = ld_vol2(src + p * FH); ok = ok && u.y == epoch; a += __uint_as_float(u.x); }
          }
          reinterpret_cast<float*>(smem + COLSUM_OFF)[i * 32 + lane] = a;
          if (ok || ++it > POLL_LIMIT) break;
          __nanosleep(POLL_NS);
        }
      }
      __syncwarp();
      TS(1, 4);
      if (grp == 0) {
        bar_arrive<BAR_STATS>(320);
        bar_sync<BAR_PUB1>(160);
        if (lane == 0) set_flag(F_Z + ct, rb, epoch);
        TS(1, 8);
        __syncwarp();
        bar_arrive<BAR_BUF>(160);
      } else {
        bar_arrive<BAR_STATS>(192);
        bar_sync<BAR_PUB2>(160);
        if (lane == 0) set_flag(F_A + ct, rb, epoch);
        TS(1, 9);
        __syncwarp();
      }
      bar_sync<BAR_PUB1>(160);
      if (lane == 0) set_flag(grp == 0 ? F_H + rb : F_B + ct, grp == 0 ? ct : rb, epoch);
      TS(1, 10);
      __syncwarp();
      bar_arrive<BAR_BUF>(160);
    }
  } else {
    asm volatile("setmaxnreg.inc.sync.aligned.u32 232;");
    const int t = tid & 127, w = t >> 5, l = t & 31;
    ln_rows(rv, cta, epoch);
    TS(wg + 1, 0);
    cluster_wait();
    const uint32_t st_base = buf + (w * 16 + ((l >> 3) & 1) * 8 + (l & 7)) * 128;
    const uint32_t st_x = ((l >> 4) ^ (l & 7)) << 4;
    const float2* rs = reinterpret_cast<const float2*>(smem + ROWSTAT_OFF) + w * 16 + (l >> 2);
    const float2* cs = reinterpret_cast<const float2*>(smem + COLSUM_OFF) + (l & 3);
    if (grp == 0) {
      {
        const int mb = wg - 1;
        float acc[1][96];
        zero(acc);
        mainloop<192, 1, 1, false, 0>(acc, sbase, 0, 0, 10, mb);
        drain(acc, sbase, 0, 9);
        TS(wg + 1, 1);
        bar_sync<BAR_STATS>(320);
        const float2 s0 = rs[mb * 64], s1 = rs[mb * 64 + 8];
        float sm0 = 0.f, sm1 = 0.f, q0 = 0.f, q1 = 0.f;
        #pragma unroll
        for (int jj = 0; jj < 12; jj++) {
          float u[8];
          #pragma unroll
          for (int hf = 0; hf < 2; hf++) {
            const float2 c = cs[jj * 8 + hf * 4];
            const float* a = &acc[0][8 * jj + 4 * hf];
            u[4 * hf + 0] = gelu_tanh(fmaf(a[0], s0.x, s0.y * c.x)); u[4 * hf + 1] = gelu_tanh(fmaf(a[1], s0.x, s0.y * c.y));
            u[4 * hf + 2] = gelu_tanh(fmaf(a[2], s1.x, s1.y * c.x)); u[4 * hf + 3] = gelu_tanh(fmaf(a[3], s1.x, s1.y * c.y));
            sm0 += u[4 * hf] + u[4 * hf + 1]; q0 = fmaf(u[4 * hf], u[4 * hf], q0); q0 = fmaf(u[4 * hf + 1], u[4 * hf + 1], q0);
            sm1 += u[4 * hf + 2] + u[4 * hf + 3]; q1 = fmaf(u[4 * hf + 2], u[4 * hf + 2], q1); q1 = fmaf(u[4 * hf + 3], u[4 * hf + 3], q1);
          }
          stsm4(st_base + mb * 24576 + (jj >> 2) * 8192 + (st_x ^ ((jj & 3) << 5)),
                pack_bf16(u[0], u[1]), pack_bf16(u[2], u[3]), pack_bf16(u[4], u[5]), pack_bf16(u[6], u[7]));
        }
        #pragma unroll
        for (int o = 1; o < 4; o <<= 1) {
          sm0 += __shfl_xor_sync(0xffffffffu, sm0, o); q0 += __shfl_xor_sync(0xffffffffu, q0, o);
          sm1 += __shfl_xor_sync(0xffffffffu, sm1, o); q1 += __shfl_xor_sync(0xffffffffu, q1, o);
        }
        if ((l & 3) < 2) {
          const float sm = (l & 1) ? sm1 : sm0, sv = (l & 1) ? q1 : q0;
          const int row = mb * 64 + w * 16 + (l & 1) * 8 + (l >> 2);
          const float mu = sm * (1.f / 192), m2 = fmaxf(sv - sm * mu, 0.f);
          st_vol2(&g_zstat[(rb * 4 + ct) * 128 + row], __float_as_uint(mu), (__float_as_uint(m2) & ~255u) | (epoch & 255u));
          reinterpret_cast<float2*>(smem + ZSTAT_OFF)[row] = make_float2(mu, m2);
        }
        TS(wg + 1, 4);
      }
      float acc[2][96];
      if (wg == 1) {
        bar_sync<BAR_U>(256);
        uint2 v[3];
        unsigned n = 0;
        while (true) {
          bool ok = true;
          #pragma unroll
          for (int j = 0; j < 3; j++) { v[j] = ld_vol2(&g_zstat[(rb * 4 + ((ct + 1 + j) & 3)) * 128 + t]); ok = ok && ((v[j].y ^ epoch) & 255u) == 0; }
          if (ok || ++n > POLL_LIMIT) break;
          __nanosleep(POLL_NS);
        }
        const float2 own = reinterpret_cast<const float2*>(smem + ZSTAT_OFF)[t];
        const float m0 = __uint_as_float(v[0].x), m1 = __uint_as_float(v[1].x), m2 = __uint_as_float(v[2].x);
        const float mean = 0.25f * ((own.x + m0) + (m1 + m2));
        const float d = (own.x - mean) * (own.x - mean) + (m0 - mean) * (m0 - mean) + (m1 - mean) * (m1 - mean) + (m2 - mean) * (m2 - mean);
        const float var = fmaf(192.f, d, (own.y + __uint_as_float(v[0].y & ~255u)) + (__uint_as_float(v[1].y & ~255u) + __uint_as_float(v[2].y & ~255u)));
        const float r = rsqrtf(var * (1.f / FH) + LN_EPS), o = -mean * r;
        TS(2, 5);
        const uint32_t rbase = buf + (t >> 6) * 24576 + (t & 63) * 128;
        #pragma unroll 1
        for (int c = 0; c < 3; c++) {
          uint4 z[8];
          #pragma unroll
          for (int i = 0; i < 8; i++) z[i] = lds128(rbase + c * 8192 + (((i ^ l) & 7) << 4));
          #pragma unroll
          for (int i = 0; i < 8; i++)
            sts128(rbase + c * 8192 + (((i ^ l) & 7) << 4),
                   pack_bf16(fmaf(bf_lo(z[i].x), r, o), fmaf(bf_hi(z[i].x), r, o)), pack_bf16(fmaf(bf_lo(z[i].y), r, o), fmaf(bf_hi(z[i].y), r, o)),
                   pack_bf16(fmaf(bf_lo(z[i].z), r, o), fmaf(bf_hi(z[i].z), r, o)), pack_bf16(fmaf(bf_lo(z[i].w), r, o), fmaf(bf_hi(z[i].w), r, o)));
          fence_async_smem();
          __syncwarp();
          if (l < 2) {
            tma_store_2d(&maps.m[M_ZS], buf + (w >> 1) * 24576 + c * 8192 + ((w & 1) * 2 + l) * 2048, ct * 192 + c * 64, rb * 128 + w * 32 + l * 16);
            bulk_commit();
          }
        }
        TS(2, 6);
        if (l < 2) bulk_wait_all();
        __syncwarp();
        bar_arrive<BAR_PUB1>(160);
        {
          const bf16* bp = bsp + rb * 128 + w * 16 + (l >> 2);
          const float bb[4] = {__bfloat162float(bp[0]), __bfloat162float(bp[8]), __bfloat162float(bp[64]), __bfloat162float(bp[72])};
          #pragma unroll
          for (int i = 0; i < 96; i++) { acc[0][i] = bb[(i >> 1) & 1]; acc[1][i] = bb[2 + ((i >> 1) & 1)]; }
          pin(acc);
        }
        bar_sync<BAR_ORD2>(256);
        mainloop<192, 2, 1, false, BAR_ORD1>(acc, sbase, 0, 20, 32);
        bar_sync<BAR_Z1>(256);
        drain(acc, sbase, 0, 51);
        TS(2, 7);
        uint32_t z[2][4][4];
        #pragma unroll
        for (int i = 0; i < 4; i++) ldsm4(st_base + (st_x ^ (i << 5)), z[0][i][0], z[0][i][1], z[0][i][2], z[0][i][3]);
        #pragma unroll
        for (int bx = 0; bx < 6; bx++) {
          if (bx < 5) {
            #pragma unroll
            for (int i = 0; i < 4; i++)
              ldsm4(st_base + (bx + 1) * 8192 + (st_x ^ (i << 5)), z[(bx + 1) & 1][i][0], z[(bx + 1) & 1][i][1], z[(bx + 1) & 1][i][2], z[(bx + 1) & 1][i][3]);
          }
          #pragma unroll
          for (int i = 0; i < 4; i++) {
            const float* a = &acc[bx / 3][8 * ((bx % 3) * 4 + i)];
            const uint32_t* zz = z[bx & 1][i];
            stsm4(st_base + bx * 8192 + (st_x ^ (i << 5)),
                  hmul2_bf16(zz[0], pack_bf16(a[0], a[1])), hmul2_bf16(zz[1], pack_bf16(a[2], a[3])),
                  hmul2_bf16(zz[2], pack_bf16(a[4], a[5])), hmul2_bf16(zz[3], pack_bf16(a[6], a[7])));
          }
          if (bx % 3 == 2) {
            fence_async_smem();
            __syncwarp();
            if (l < 3) {
              tma_store_2d(&maps.m[M_HS], buf + (bx - 2 + l) * 8192 + w * 2048, ct * 192 + l * 64, rb * 128 + (bx / 3) * 64 + w * 16);
              bulk_commit();
            }
          }
        }
        TS(2, 8);
        if (l < 3) bulk_wait_all();
        __syncwarp();
        bar_arrive<BAR_PUB1>(160);
        TS(2, 9);
        return;
      }
      bar_arrive<BAR_U>(256);
      zero(acc);
      mainloop<192, 2, 1, false, BAR_ORD2>(acc, sbase, 0, 10, 10);
      drain(acc, sbase, 0, 19);
      TS(3, 2);
      bar_sync<BAR_BUF>(160);
      #pragma unroll
      for (int mi = 0; mi < 2; mi++)
        #pragma unroll
        for (int jj = 0; jj < 12; jj++) {
          const float* a = &acc[mi][8 * jj];
          stsm4(st_base + mi * 24576 + (jj >> 2) * 8192 + (st_x ^ ((jj & 3) << 5)),
                pack_bf16(a[0], a[1]), pack_bf16(a[2], a[3]), pack_bf16(a[4], a[5]), pack_bf16(a[6], a[7]));
        }
      __syncwarp();
      TS(3, 3);
      const uint32_t rbase = buf + (l >> 4) * 24576 + (w * 16 + (l & 15)) * 128;
      #pragma unroll 1
      for (int c2 = 0; c2 < 12; c2++) {
        const uint32_t ab = rbase + (c2 >> 2) * 8192;
        uint4 v[2];
        #pragma unroll
        for (int i = 0; i < 2; i++) v[i] = lds128(ab + (((((c2 & 3) * 2 + i) ^ l) & 7) << 4));
        #pragma unroll
        for (int i = 0; i < 2; i++)
          sts128(ab + (((((c2 & 3) * 2 + i) ^ l) & 7) << 4),
                 pack_bf16(gelu_tanh(bf_lo(v[i].x)), gelu_tanh(bf_hi(v[i].x))), pack_bf16(gelu_tanh(bf_lo(v[i].y)), gelu_tanh(bf_hi(v[i].y))),
                 pack_bf16(gelu_tanh(bf_lo(v[i].z)), gelu_tanh(bf_hi(v[i].z))), pack_bf16(gelu_tanh(bf_lo(v[i].w)), gelu_tanh(bf_hi(v[i].w))));
      }
      TS(3, 5);
      bar_arrive<BAR_Z1>(256);
    }
    float acc[2][80];
    if (grp == 1) {
      zero(acc);
      if (wg == 2) {
        mainloop<160, 2, 0, false, BAR_ORD2>(acc, sbase, 1, 0, 10);
      } else {
        weight_sums(win, wdre, rb * 4 + ct, epoch);
        TS(2, 1);
        bar_sync<BAR_ORD2>(256);
        mainloop<160, 2, 0, false, BAR_ORD1>(acc, sbase, 1, 10, 10);
      }
      drain(acc, sbase, 1, wg == 2 ? 9 : 19);
      TS(wg + 1, wg == 1 ? 7 : 2);
      if (wg == 1) bar_sync<BAR_Z1>(256); else bar_sync<BAR_STATS>(192);
      const uint32_t tb = buf + ((l >> 4) * 8 + (l & 7)) * 128 + (((w * 2 + ((l >> 3) & 1)) ^ (l & 7)) << 4);
      float2 st[4];
      #pragma unroll
      for (int r = 0; r < 4; r++) st[r] = wg == 2 ? rs[(r >> 1) * 64 + (r & 1) * 8] : make_float2(-1.f, 0.f);
      #pragma unroll
      for (int jj = 0; jj < 10; jj++) {
        const float2 c0 = cs[jj * 8], c1 = cs[jj * 8 + 4];
        #pragma unroll
        for (int mi = 0; mi < 2; mi++) {
          const float* a = &acc[mi][8 * jj];
          const float2 s0 = st[mi * 2], s1 = st[mi * 2 + 1];
          stsm4_t(tb + mi * 20480 + jj * 2048,
                  pack_bf16(fmaf(a[0], s0.x, s0.y * c0.x), fmaf(a[1], s0.x, s0.y * c0.y)), pack_bf16(fmaf(a[2], s1.x, s1.y * c0.x), fmaf(a[3], s1.x, s1.y * c0.y)),
                  pack_bf16(fmaf(a[4], s0.x, s0.y * c1.x), fmaf(a[5], s0.x, s0.y * c1.y)), pack_bf16(fmaf(a[6], s1.x, s1.y * c1.x), fmaf(a[7], s1.x, s1.y * c1.y)));
        }
      }
      fence_async_smem();
      if (wg == 1) bar_sync<BAR_WG1>(128); else bar_sync<BAR_WG2>(128);
      TS(wg + 1, wg == 1 ? 8 : 6);
      if (l < 2) {
        tma_store_2d(&maps.m[M_ABS], buf + l * 20480 + w * 5120, rb * 128 + l * 64, (2 - wg) * DM + ct * 160 + w * 40);
        bulk_commit();
        bulk_wait_all();
      }
      __syncwarp();
      TS(wg + 1, wg == 1 ? 9 : 10);
      if (wg == 1) {
        bar_arrive<BAR_PUB1>(160);
        #pragma unroll 1
        for (int i = 0; i < 4; i++) {
          uint4 v[5];
          #pragma unroll
          for (int j = 0; j < 5; j++) {
            const int e = (i * 5 + j) * 128 + t;
            v[j] = ldg128(x + (size_t)(rb * 128 + e / 20) * DM + ct * 160 + (e % 20) * 8);
          }
          #pragma unroll
          for (int j = 0; j < 5; j++) {
            const int e = (i * 5 + j) * 128 + t;
            stg128(out + (size_t)(rb * 128 + e / 20) * DM + ct * 160 + (e % 20) * 8, v[j]);
          }
        }
        bar_sync<BAR_WG1>(128);
        if (t == 0) publish(F_Y + rb * 4 + ct, 0, epoch);
        return;
      }
      bar_arrive<BAR_PUB2>(160);
      bar_arrive<BAR_Z1>(256);
    }
    zero(acc);
    bar_sync<BAR_ORD1>(256);
    mainloop<160, 2, 0, false, 0>(acc, sbase, grp, grp == 0 ? 52 : 20, grp == 0 ? NX : 64 - NX);
    mainloop<160, 2, 2, true, 0>(acc, sbase, grp, gh, total - gh);
    const uint32_t slab = buf + w * (16 * 320);
    const uint32_t addr = slab + (((l >> 3) & 1) * 8 + (l & 7)) * 320 + (l >> 4) * 16;
    bar_sync<BAR_BUF>(160);
    mbar_wait(dep0 + 32, 0);
    drain(acc, sbase, grp, total - 1);
    TS(3, 12);
    #pragma unroll
    for (int mi = 0; mi < 2; mi++) {
      #pragma unroll
      for (int jj = 0; jj < 10; jj++) {
        const float* a = &acc[mi][8 * jj];
        stsm4(addr + mi * 20480 + jj * 32, pack_bf16(a[0], a[1]), pack_bf16(a[2], a[3]), pack_bf16(a[4], a[5]), pack_bf16(a[6], a[7]));
      }
      fence_async_smem();
      __syncwarp();
      if (l == 0) {
        tma_reduce_2d(&maps.m[M_OUT], slab + mi * 20480, ct * 160, rb * 128 + mi * 64 + w * 16);
        bulk_commit();
      }
    }
    TS(3, 13);
    if (l == 0) {
      bulk_wait_read();
      if (w == 0) atomicAdd(&g_done, 1u);
    }
    TS(3, 15);
  }
}

typedef CUresult (*EncodeFn)(CUtensorMap*, CUtensorMapDataType, cuuint32_t, void*, const cuuint64_t*, const cuuint64_t*,
                             const cuuint32_t*, const cuuint32_t*, CUtensorMapInterleave, CUtensorMapSwizzle,
                             CUtensorMapL2promotion, CUtensorMapFloatOOBfill);

void make2d(EncodeFn enc, CUtensorMap* m, const void* p, uint64_t cols, uint64_t rows, uint32_t bc, uint32_t br, bool swz = true) {
  cuuint64_t gd[2] = {cols, rows}, gs[1] = {cols * 2};
  cuuint32_t bd[2] = {bc, br}, es[2] = {1, 1};
  enc(m, CU_TENSOR_MAP_DATA_TYPE_BFLOAT16, 2, const_cast<void*>(p), gd, gs, bd, es, CU_TENSOR_MAP_INTERLEAVE_NONE,
      swz ? CU_TENSOR_MAP_SWIZZLE_128B : CU_TENSOR_MAP_SWIZZLE_NONE, CU_TENSOR_MAP_L2_PROMOTION_L2_128B, CU_TENSOR_MAP_FLOAT_OOB_FILL_NONE);
}
void make3d(EncodeFn enc, CUtensorMap* m, const void* p, uint64_t cols, uint64_t rows, uint32_t cw, uint32_t nc, uint32_t br = 64) {
  cuuint64_t gd[3] = {cw, rows, cols / cw}, gs[2] = {cols * 2, cw * 2};
  cuuint32_t bd[3] = {cw, br, nc}, es[3] = {1, 1, 1};
  enc(m, CU_TENSOR_MAP_DATA_TYPE_BFLOAT16, 3, const_cast<void*>(p), gd, gs, bd, es, CU_TENSOR_MAP_INTERLEAVE_NONE,
      cw == 64 ? CU_TENSOR_MAP_SWIZZLE_128B : CU_TENSOR_MAP_SWIZZLE_64B, CU_TENSOR_MAP_L2_PROMOTION_L2_128B, CU_TENSOR_MAP_FLOAT_OOB_FILL_NONE);
}

}

extern "C" void kernel_launch(void* const* d_in, const int* in_sizes, int n_in, void* d_out, int out_size) {
  const bf16* x = (const bf16*)d_in[0];
  const bf16* wsre = (const bf16*)d_in[1];
  const bf16* wsim = (const bf16*)d_in[2];
  const bf16* wdre = (const bf16*)d_in[3];
  const bf16* wdim = (const bf16*)d_in[4];
  const bf16* win = (const bf16*)d_in[6];
  const bf16* wsp = (const bf16*)d_in[7];
  const bf16* bsp = (const bf16*)d_in[8];
  const bf16* wout = (const bf16*)d_in[9];

  void* fn = nullptr;
  cudaDriverEntryPointQueryResult qr;
  cudaGetDriverEntryPoint("cuTensorMapEncodeTiled", &fn, cudaEnableDefault, &qr);
  EncodeFn enc = (EncodeFn)fn;
  void *abT, *z2, *h, *xn;
  cudaGetSymbolAddress(&xn, g_xn);
  cudaGetSymbolAddress(&abT, g_abT);
  cudaGetSymbolAddress(&z2, g_z2);
  cudaGetSymbolAddress(&h, g_h);

  Maps maps;
  make2d(enc, &maps.m[M_X], x, DM, SEQ, 64, 64);
  make2d(enc, &maps.m[M_XN], xn, DM, SEQ, 64, 64);
  make2d(enc, &maps.m[M_WSRE], wsre, SEQ, SEQ, 64, 64);
  make2d(enc, &maps.m[M_WSIM], wsim, SEQ, SEQ, 64, 64);
  make2d(enc, &maps.m[M_WSP], wsp, SEQ, SEQ, 64, 64);
  make2d(enc, &maps.m[M_H], h, FH, SEQ, 64, 64);
  make3d(enc, &maps.m[M_WIN3], win, FF, DM, 64, 3);
  make3d(enc, &maps.m[M_Z23], z2, FH, SEQ, 64, 3);
  make2d(enc, &maps.m[M_WDRE], wdre, DM, DM, 64, 160);
  make2d(enc, &maps.m[M_WDIM], wdim, DM, DM, 64, 160);
  make2d(enc, &maps.m[M_AB], abT, SEQ, 2 * DM, 64, 160);
  make3d(enc, &maps.m[M_WOUT], wout, DM, FH, 32, 5);
  make2d(enc, &maps.m[M_HS], h, FH, SEQ, 64, 16);
  make2d(enc, &maps.m[M_ZS], z2, FH, SEQ, 64, 16);
  make2d(enc, &maps.m[M_ABS], abT, SEQ, 2 * DM, 64, 40);
  make2d(enc, &maps.m[M_OUT], d_out, DM, SEQ, 160, 16, false);

  cudaFuncSetAttribute(fused_kernel, cudaFuncAttributeMaxDynamicSharedMemorySize, SMEM_BYTES);
  fused_kernel<<<128, 384, SMEM_BYTES>>>(maps, x, win, wdre, bsp, (bf16*)d_out);
}
```

```cpp
#include <cuda_runtime.h>
#include <cuda_bf16.h>
#include <cuda.h>
#include <stdint.h>

namespace {

typedef __nv_bfloat16 bf16;

constexpr int SEQ = 2048, DM = 640, FF = 1536, FH = 768;
#define NXV 10
constexpr int NX = NXV;
#define NSTB 5
constexpr int NST_A = 4, NST_B = NSTB, MAXST = 5;
constexpr int A_BYTES = 16384;
constexpr int BAR_OFF = 512;
constexpr int READY_OFF = 640;
constexpr int ROWSTAT_OFF = 1024;
constexpr int COLSUM_OFF = 2048;
constexpr int RED_OFF = 2560;
constexpr int RING_OFF = 3072;
constexpr int STAGE_A = 40960, STAGE_B = 36864;
constexpr int SMEM_BYTES = RING_OFF + 5 * STAGE_B + 40960;
constexpr int KB_A = 20 + 32 + NX + 12;
constexpr int KB_B = 30 + 64 - NX;
constexpr float LN_EPS = 1e-5f;
constexpr unsigned POLL_LIMIT = 100000;
#define POLL_NS 100
#define PF_D 8
#define ROT 0
#define Z1_NS 0
#define INFL 2
#define LIM_G 1000
#define MAPV 0
#define PROMO CU_TENSOR_MAP_L2_PROMOTION_L2_128B
#define WATCH_NS 40
#define PF_COND (((g + PF_D) & 1) == (ct >> 1))
#define WPF 1
#define Z2SW 0
#define WOSW 0
#define HINT 1
#define PF_NS 150

constexpr int BAR_ORD1 = 1, BAR_ORD2 = 2, BAR_WG1 = 3, BAR_WG2 = 4, BAR_LN = 5, BAR_BUF = 6, BAR_Z1 = 7, BAR_PUB1 = 8, BAR_PUB2 = 9, BAR_STATS = 10;

enum { M_X, M_XN, M_WIN32, M_Z232, M_WSRE, M_WSIM, M_WSP, M_H, M_WIN3, M_Z23, M_WDRE, M_WDIM, M_AB, M_WOUT, M_OUT, M_HS, M_ABS, M_COUNT };
struct Maps { CUtensorMap m[M_COUNT]; };

__device__ __align__(1024) bf16 g_abT[2 * DM * SEQ];
__device__ __align__(1024) bf16 g_z2[SEQ * FH];
__device__ __align__(1024) bf16 g_h[SEQ * FH];
__device__ __align__(1024) bf16 g_xn[SEQ * DM];
__device__ __align__(16) uint2 g_xstat[SEQ];
__device__ __align__(16) uint2 g_csum[5 * FH];
__device__ __align__(16) uint2 g_zstat[128 * 128];
__device__ __align__(256) unsigned char g_flags[108 * 256];
constexpr int F_A = 0, F_B = 4, F_Z = 8, F_H = 12, F_XN = 28, F_Y = 44;
__device__ unsigned g_done;
#define TS(role, ev)
#define TC(i)

extern __shared__ __align__(1024) uint8_t smem[];

__device__ __forceinline__ uint32_t smem_u32(const void* p) { return (uint32_t)__cvta_generic_to_shared(p); }
__device__ __forceinline__ void mbar_init(uint32_t bar, uint32_t cnt) { asm volatile("mbarrier.init.shared::cta.b64 [%0], %1;" :: "r"(bar), "r"(cnt)); }
__device__ __forceinline__ void mbar_expect_tx(uint32_t bar, uint32_t bytes) { asm volatile("mbarrier.arrive.expect_tx.shared::cta.b64 _, [%0], %1;" :: "r"(bar), "r"(bytes) : "memory"); }
__device__ __forceinline__ void mbar_arrive(uint32_t bar) { asm volatile("mbarrier.arrive.shared::cta.b64 _, [%0];" :: "r"(bar) : "memory"); }
__device__ __forceinline__ void mbar_arrive_cluster(uint32_t bar, uint32_t cta) {
  asm volatile("{\n.reg .b32 ra;\nmapa.shared::cluster.u32 ra, %0, %1;\nmbarrier.arrive.shared::cluster.b64 _, [ra];\n}" :: "r"(bar), "r"(cta) : "memory");
}
__device__ __forceinline__ void mbar_wait(uint32_t bar, uint32_t parity) {
  asm volatile("{\n.reg .pred p;\n.reg .u32 n;\nmov.u32 n, 0;\n"
               "LW: mbarrier.try_wait.parity.shared::cta.b64 p, [%0], %1, 2000;\n@p bra LD;\n"
               "add.u32 n, n, 1;\nsetp.lt.u32 p, n, 20000;\n@p bra LW;\nLD:\n}" :: "r"(bar), "r"(parity) : "memory");
}
__device__ __forceinline__ void tma_load_2d(uint32_t dst, const CUtensorMap* map, uint32_t bar, int c0, int c1) {
  asm volatile("cp.async.bulk.tensor.2d.shared::cluster.global.mbarrier::complete_tx::bytes [%0], [%1, {%3, %4}], [%2];"
    :: "r"(dst), "l"((uint64_t)map), "r"(bar), "r"(c0), "r"(c1) : "memory");
}
__device__ __forceinline__ void tma_load_3d(uint32_t dst, const CUtensorMap* map, uint32_t bar, int c0, int c1, int c2) {
  asm volatile("cp.async.bulk.tensor.3d.shared::cluster.global.mbarrier::complete_tx::bytes [%0], [%1, {%3, %4, %5}], [%2];"
    :: "r"(dst), "l"((uint64_t)map), "r"(bar), "r"(c0), "r"(c1), "r"(c2) : "memory");
}
__device__ __forceinline__ void tma_load_2d_mc(uint32_t dst, const CUtensorMap* map, uint32_t bar, int c0, int c1, uint16_t mask) {
  asm volatile("cp.async.bulk.tensor.2d.shared::cluster.global.mbarrier::complete_tx::bytes.multicast::cluster [%0], [%1, {%3, %4}], [%2], %5;"
    :: "r"(dst), "l"((uint64_t)map), "r"(bar), "r"(c0), "r"(c1), "h"(mask) : "memory");
}
__device__ __forceinline__ void tma_store_2d(const CUtensorMap* map, uint32_t src, int c0, int c1) {
  asm volatile("cp.async.bulk.tensor.2d.global.shared::cta.bulk_group [%0, {%2, %3}], [%1];"
    :: "l"((uint64_t)map), "r"(src), "r"(c0), "r"(c1) : "memory");
}
__device__ __forceinline__ void tma_store_3d(const CUtensorMap* map, uint32_t src, int c0, int c1, int c2) {
  asm volatile("cp.async.bulk.tensor.3d.global.shared::cta.bulk_group [%0, {%2, %3, %4}], [%1];"
    :: "l"((uint64_t)map), "r"(src), "r"(c0), "r"(c1), "r"(c2) : "memory");
}
__device__ __forceinline__ void tma_reduce_2d(const CUtensorMap* map, uint32_t src, int c0, int c1) {
  asm volatile("cp.reduce.async.bulk.tensor.2d.global.shared::cta.add.tile.bulk_group [%0, {%2, %3}], [%1];"
    :: "l"((uint64_t)map), "r"(src), "r"(c0), "r"(c1) : "memory");
}
__device__ __forceinline__ void bulk_wait_all() { asm volatile("cp.async.bulk.wait_group 0;" ::: "memory"); }
__device__ __forceinline__ void bulk_commit() { asm volatile("cp.async.bulk.commit_group;" ::: "memory"); }
__device__ __forceinline__ void bulk_wait_read() { asm volatile("cp.async.bulk.wait_group.read 0;" ::: "memory"); }
__device__ __forceinline__ void fence_async_smem() { asm volatile("fence.proxy.async.shared::cta;" ::: "memory"); }
__device__ __forceinline__ void fence_async_global() { asm volatile("fence.proxy.async.global;" ::: "memory"); }
__device__ __forceinline__ void wgmma_fence() { asm volatile("wgmma.fence.sync.aligned;" ::: "memory"); }
__device__ __forceinline__ void wgmma_commit() { asm volatile("wgmma.commit_group.sync.aligned;" ::: "memory"); }
template<int N> __device__ __forceinline__ void wgmma_wait() { asm volatile("wgmma.wait_group.sync.aligned %0;" :: "n"(N) : "memory"); }
template<int ID> __device__ __forceinline__ void bar_sync(int n) { asm volatile("bar.sync %0, %1;" :: "n"(ID), "r"(n) : "memory"); }
template<int ID> __device__ __forceinline__ void bar_arrive(int n) { asm volatile("bar.arrive %0, %1;" :: "n"(ID), "r"(n) : "memory"); }
__device__ __forceinline__ void cluster_wait() { asm volatile("barrier.cluster.wait.aligned;" ::: "memory"); }
__device__ __forceinline__ uint64_t desc64(uint32_t lo, uint32_t hi) { return (uint64_t)lo | ((uint64_t)hi << 32); }
__device__ __forceinline__ uint4 ld_vol4(const uint4* p) {
  uint4 v; asm volatile("ld.relaxed.gpu.global.v4.u32 {%0,%1,%2,%3}, [%4];" : "=r"(v.x), "=r"(v.y), "=r"(v.z), "=r"(v.w) : "l"(p) : "memory"); return v;
}
__device__ __forceinline__ uint2 ld_vol2(const uint2* p) {
  uint2 v; asm volatile("ld.relaxed.gpu.global.v2.u32 {%0,%1}, [%2];" : "=r"(v.x), "=r"(v.y) : "l"(p) : "memory"); return v;
}
__device__ __forceinline__ void st_vol4(uint4* p, uint32_t a, uint32_t b, uint32_t c, uint32_t d) {
  asm volatile("st.relaxed.gpu.global.v4.u32 [%0], {%1,%2,%3,%4};" :: "l"(p), "r"(a), "r"(b), "r"(c), "r"(d) : "memory");
}
__device__ __forceinline__ void st_vol2(uint2* p, uint32_t a, uint32_t b) {
  asm volatile("st.relaxed.gpu.global.v2.u32 [%0], {%1,%2};" :: "l"(p), "r"(a), "r"(b) : "memory");
}
__device__ __forceinline__ void stg128(void* p, uint4 v) {
  asm volatile("st.global.v4.u32 [%0], {%1,%2,%3,%4};" :: "l"(p), "r"(v.x), "r"(v.y), "r"(v.z), "r"(v.w));
}
__device__ __forceinline__ unsigned ld_relaxed(const unsigned* p) {
  unsigned v; asm volatile("ld.relaxed.gpu.global.u32 %0, [%1];" : "=r"(v) : "l"(p) : "memory"); return v;
}
__device__ __forceinline__ uint32_t pack_bf16(float lo, float hi) {
  uint32_t r; asm("cvt.rn.bf16x2.f32 %0, %1, %2;" : "=r"(r) : "f"(hi), "f"(lo)); return r;
}
__device__ __forceinline__ float bf_lo(uint32_t v) { return __uint_as_float(v << 16); }
__device__ __forceinline__ float bf_hi(uint32_t v) { return __uint_as_float(v & 0xFFFF0000u); }
__device__ __forceinline__ void stsm4(uint32_t addr, uint32_t a, uint32_t b, uint32_t c, uint32_t d) {
  asm volatile("stmatrix.sync.aligned.m8n8.x4.shared.b16 [%0], {%1,%2,%3,%4};" :: "r"(addr), "r"(a), "r"(b), "r"(c), "r"(d));
}
__device__ __forceinline__ void stsm4_t(uint32_t addr, uint32_t a, uint32_t b, uint32_t c, uint32_t d) {
  asm volatile("stmatrix.sync.aligned.m8n8.x4.trans.shared.b16 [%0], {%1,%2,%3,%4};" :: "r"(addr), "r"(a), "r"(b), "r"(c), "r"(d));
}
__device__ __forceinline__ void ldsm4(uint32_t addr, uint32_t& a, uint32_t& b, uint32_t& c, uint32_t& d) {
  asm volatile("ldmatrix.sync.aligned.m8n8.x4.shared.b16 {%0,%1,%2,%3}, [%4];" : "=r"(a), "=r"(b), "=r"(c), "=r"(d) : "r"(addr));
}
__device__ __forceinline__ uint4 lds128(uint32_t a) {
  uint4 v; asm volatile("ld.shared.v4.u32 {%0,%1,%2,%3}, [%4];" : "=r"(v.x), "=r"(v.y), "=r"(v.z), "=r"(v.w) : "r"(a)); return v;
}
__device__ __forceinline__ void sts128(uint32_t a, uint32_t x, uint32_t y, uint32_t z, uint32_t w) {
  asm volatile("st.shared.v4.u32 [%0], {%1,%2,%3,%4};" :: "r"(a), "r"(x), "r"(y), "r"(z), "r"(w));
}
__device__ __forceinline__ uint32_t hmul2_bf16(uint32_t a, uint32_t b) {
  uint32_t r; asm("mul.rn.bf16x2 %0, %1, %2;" : "=r"(r) : "r"(a), "r"(b)); return r;
}
__device__ __forceinline__ float gelu_tanh(float v) {
  float u = v * fmaf(0.0356774081f, v * v, 0.7978845608f);
  float t; asm("tanh.approx.f32 %0, %1;" : "=f"(t) : "f"(u));
  float hv = 0.5f * v;
  return fmaf(hv, t, hv);
}

template<int TB>
__device__ __forceinline__ void wgmma_n192(float (&d)[96], uint64_t da, uint64_t db, int scale_d) {
  asm volatile("{\n.reg .pred p;\nsetp.ne.b32 p, %98, 0;\n"
   "wgmma.mma_async.sync.aligned.m64n192k16.f32.bf16.bf16 {%0,%1,%2,%3,%4,%5,%6,%7,%8,%9,%10,%11,%12,%13,%14,%15,%16,%17,%18,%19,%20,%21,%22,%23,%24,%25,%26,%27,%28,%29,%30,%31,%32,%33,%34,%35,%36,%37,%38,%39,%40,%41,%42,%43,%44,%45,%46,%47,%48,%49,%50,%51,%52,%53,%54,%55,%56,%57,%58,%59,%60,%61,%62,%63,%64,%65,%66,%67,%68,%69,%70,%71,%72,%73,%74,%75,%76,%77,%78,%79,%80,%81,%82,%83,%84,%85,%86,%87,%88,%89,%90,%91,%92,%93,%94,%95}, %96, %97, p, 1, 1, 0, %99;\n}"
   : "+f"(d[0]),"+f"(d[1]),"+f"(d[2]),"+f"(d[3]),"+f"(d[4]),"+f"(d[5]),"+f"(d[6]),"+f"(d[7]),"+f"(d[8]),"+f"(d[9]),"+f"(d[10]),"+f"(d[11]),"+f"(d[12]),"+f"(d[13]),"+f"(d[14]),"+f"(d[15]),"+f"(d[16]),"+f"(d[17]),"+f"(d[18]),"+f"(d[19]),"+f"(d[20]),"+f"(d[21]),"+f"(d[22]),"+f"(d[23]),"+f"(d[24]),"+f"(d[25]),"+f"(d[26]),"+f"(d[27]),"+f"(d[28]),"+f"(d[29]),"+f"(d[30]),"+f"(d[31]),"+f"(d[32]),"+f"(d[33]),"+f"(d[34]),"+f"(d[35]),"+f"(d[36]),"+f"(d[37]),"+f"(d[38]),"+f"(d[39]),"+f"(d[40]),"+f"(d[41]),"+f"(d[42]),"+f"(d[43]),"+f"(d[44]),"+f"(d[45]),"+f"(d[46]),"+f"(d[47]),"+f"(d[48]),"+f"(d[49]),"+f"(d[50]),"+f"(d[51]),"+f"(d[52]),"+f"(d[53]),"+f"(d[54]),"+f"(d[55]),"+f"(d[56]),"+f"(d[57]),"+f"(d[58]),"+f"(d[59]),"+f"(d[60]),"+f"(d[61]),"+f"(d[62]),"+f"(d[63]),"+f"(d[64]),"+f"(d[65]),"+f"(d[66]),"+f"(d[67]),"+f"(d[68]),"+f"(d[69]),"+f"(d[70]),"+f"(d[71]),"+f"(d[72]),"+f"(d[73]),"+f"(d[74]),"+f"(d[75]),"+f"(d[76]),"+f"(d[77]),"+f"(d[78]),"+f"(d[79]),"+f"(d[80]),"+f"(d[81]),"+f"(d[82]),"+f"(d[83]),"+f"(d[84]),"+f"(d[85]),"+f"(d[86]),"+f"(d[87]),"+f"(d[88]),"+f"(d[89]),"+f"(d[90]),"+f"(d[91]),"+f"(d[92]),"+f"(d[93]),"+f"(d[94]),"+f"(d[95])
   : "l"(da), "l"(db), "r"(scale_d), "n"(TB));
}
template<int TB>
__device__ __forceinline__ void wgmma_n160(float (&d)[80], uint64_t da, uint64_t db, int scale_d) {
  asm volatile("{\n.reg .pred p;\nsetp.ne.b32 p, %82, 0;\n"
   "wgmma.mma_async.sync.aligned.m64n160k16.f32.bf16.bf16 {%0,%1,%2,%3,%4,%5,%6,%7,%8,%9,%10,%11,%12,%13,%14,%15,%16,%17,%18,%19,%20,%21,%22,%23,%24,%25,%26,%27,%28,%29,%30,%31,%32,%33,%34,%35,%36,%37,%38,%39,%40,%41,%42,%43,%44,%45,%46,%47,%48,%49,%50,%51,%52,%53,%54,%55,%56,%57,%58,%59,%60,%61,%62,%63,%64,%65,%66,%67,%68,%69,%70,%71,%72,%73,%74,%75,%76,%77,%78,%79}, %80, %81, p, 1, 1, 0, %83;\n}"
   : "+f"(d[0]),"+f"(d[1]),"+f"(d[2]),"+f"(d[3]),"+f"(d[4]),"+f"(d[5]),"+f"(d[6]),"+f"(d[7]),"+f"(d[8]),"+f"(d[9]),"+f"(d[10]),"+f"(d[11]),"+f"(d[12]),"+f"(d[13]),"+f"(d[14]),"+f"(d[15]),"+f"(d[16]),"+f"(d[17]),"+f"(d[18]),"+f"(d[19]),"+f"(d[20]),"+f"(d[21]),"+f"(d[22]),"+f"(d[23]),"+f"(d[24]),"+f"(d[25]),"+f"(d[26]),"+f"(d[27]),"+f"(d[28]),"+f"(d[29]),"+f"(d[30]),"+f"(d[31]),"+f"(d[32]),"+f"(d[33]),"+f"(d[34]),"+f"(d[35]),"+f"(d[36]),"+f"(d[37]),"+f"(d[38]),"+f"(d[39]),"+f"(d[40]),"+f"(d[41]),"+f"(d[42]),"+f"(d[43]),"+f"(d[44]),"+f"(d[45]),"+f"(d[46]),"+f"(d[47]),"+f"(d[48]),"+f"(d[49]),"+f"(d[50]),"+f"(d[51]),"+f"(d[52]),"+f"(d[53]),"+f"(d[54]),"+f"(d[55]),"+f"(d[56]),"+f"(d[57]),"+f"(d[58]),"+f"(d[59]),"+f"(d[60]),"+f"(d[61]),"+f"(d[62]),"+f"(d[63]),"+f"(d[64]),"+f"(d[65]),"+f"(d[66]),"+f"(d[67]),"+f"(d[68]),"+f"(d[69]),"+f"(d[70]),"+f"(d[71]),"+f"(d[72]),"+f"(d[73]),"+f"(d[74]),"+f"(d[75]),"+f"(d[76]),"+f"(d[77]),"+f"(d[78]),"+f"(d[79])
   : "l"(da), "l"(db), "r"(scale_d), "n"(TB));
}
template<int TB>
__device__ __forceinline__ void wgmma_n96(float (&d)[48], uint64_t da, uint64_t db, int scale_d) {
  asm volatile("{\n.reg .pred p;\nsetp.ne.b32 p, %50, 0;\n"
   "wgmma.mma_async.sync.aligned.m64n96k16.f32.bf16.bf16 {%0,%1,%2,%3,%4,%5,%6,%7,%8,%9,%10,%11,%12,%13,%14,%15,%16,%17,%18,%19,%20,%21,%22,%23,%24,%25,%26,%27,%28,%29,%30,%31,%32,%33,%34,%35,%36,%37,%38,%39,%40,%41,%42,%43,%44,%45,%46,%47}, %48, %49, p, 1, 1, 0, %51;\n}"
   : "+f"(d[0]),"+f"(d[1]),"+f"(d[2]),"+f"(d[3]),"+f"(d[4]),"+f"(d[5]),"+f"(d[6]),"+f"(d[7]),"+f"(d[8]),"+f"(d[9]),"+f"(d[10]),"+f"(d[11]),"+f"(d[12]),"+f"(d[13]),"+f"(d[14]),"+f"(d[15]),"+f"(d[16]),"+f"(d[17]),"+f"(d[18]),"+f"(d[19]),"+f"(d[20]),"+f"(d[21]),"+f"(d[22]),"+f"(d[23]),"+f"(d[24]),"+f"(d[25]),"+f"(d[26]),"+f"(d[27]),"+f"(d[28]),"+f"(d[29]),"+f"(d[30]),"+f"(d[31]),"+f"(d[32]),"+f"(d[33]),"+f"(d[34]),"+f"(d[35]),"+f"(d[36]),"+f"(d[37]),"+f"(d[38]),"+f"(d[39]),"+f"(d[40]),"+f"(d[41]),"+f"(d[42]),"+f"(d[43]),"+f"(d[44]),"+f"(d[45]),"+f"(d[46]),"+f"(d[47])
   : "l"(da), "l"(db), "r"(scale_d), "n"(TB));
}

template<int N, int TB>
__device__ __forceinline__ void wgmma_n(float (&d)[N / 2], uint64_t da, uint64_t db) {
  if constexpr (N == 192) wgmma_n192<TB>(d, da, db, 1);
  else if constexpr (N == 160) wgmma_n160<TB>(d, da, db, 1);
  else wgmma_n96<TB>(d, da, db, 1);
}

template<int R>
__device__ __forceinline__ void pin(float (&acc)[2][R]) {
  #pragma unroll
  for (int mi = 0; mi < 2; mi++)
    #pragma unroll
    for (int i = 0; i < R; i++) asm volatile("" : "+f"(acc[mi][i]) :: "memory");
}
template<int R>
__device__ __forceinline__ void zero(float (&acc)[2][R]) {
  #pragma unroll
  for (int i = 0; i < R; i++) { acc[0][i] = 0.f; acc[1][i] = 0.f; }
  pin(acc);
}

template<int N, int TB, bool CONT, int ORD_BAR>
__device__ __forceinline__ void mainloop(float (&acc)[2][N / 2], uint32_t sbase, int grp, int g0, int nk) {
  const uint32_t full0 = sbase + BAR_OFF, empty0 = full0 + 8 * MAXST, ring = sbase + RING_OFF;
  const int nst = grp == 0 ? NST_A : NST_B, total = grp == 0 ? KB_A : KB_B;
  const uint32_t sstep = (grp == 0 ? STAGE_A : STAGE_B) >> 4;
  const int t = threadIdx.x & 127;
  const uint32_t da0 = ((ring & 0x3FFFF) >> 4) | 0x10000u;
  const uint32_t db0 = (((ring + A_BYTES) & 0x3FFFF) >> 4) | ((TB == 2 ? 256u : TB ? 512u : 1u) << 16);
  constexpr uint32_t HI_A = 0x40000040u, HI_B = TB == 2 ? 0x80000020u : 0x40000040u;
  int s = g0 % nst, ph = (g0 / nst) & 1, ps = s == 0 ? nst - 1 : s - 1;
  #pragma unroll 1
  for (int g = g0; g < g0 + nk; g++) {
    const uint32_t so = s * sstep;
    mbar_wait(full0 + 8 * s, ph);
    wgmma_fence();
    #pragma unroll
    for (int k = 0; k < 4; k++) {
      const uint64_t db = desc64(db0 + so + (TB == 2 ? k * 64 : TB ? k * 128 : k * 2), HI_B);
      wgmma_n<N, TB != 0>(acc[0], desc64(da0 + so + k * 2, HI_A), db);
      wgmma_n<N, TB != 0>(acc[1], desc64(da0 + so + 512 + k * 2, HI_A), db);
    }
    wgmma_commit();
    if (ORD_BAR != 0 && g == g0 + nk - 1) bar_arrive<ORD_BAR>(256);
    wgmma_wait<1>();
    if (t < 4 && (CONT || g > g0) && g - 1 + nst < total) mbar_arrive_cluster(empty0 + 8 * ps, t & 1);
    ps = s;
    if (++s == nst) { s = 0; ph ^= 1; }
  }
}
template<int R>
__device__ __forceinline__ void drain(float (&acc)[2][R], uint32_t sbase, int grp, int glast) {
  wgmma_wait<0>();
  pin(acc);
  const int t = threadIdx.x & 127;
  const int nst = grp == 0 ? NST_A : NST_B, total = grp == 0 ? KB_A : KB_B;
  if (t < 4 && glast + nst < total) mbar_arrive_cluster(sbase + BAR_OFF + 8 * MAXST + 8 * (glast % nst), t & 1);
}

__device__ __forceinline__ void yloop(float (&acc)[2][80], uint32_t sbase, int up) {
  const uint32_t full0 = sbase + BAR_OFF, empty0 = full0 + 8 * MAXST, ring = sbase + RING_OFF;
  const int t = threadIdx.x & 127;
  const uint32_t da0 = ((ring & 0x3FFFF) >> 4) | 0x10000u, db0 = (((ring + A_BYTES) & 0x3FFFF) >> 4) | 0x10000u;
  int sx = 30 % NST_B, px = (30 / NST_B) & 1, psx = 0, psy = 0;
  #pragma unroll 1
  for (int g = 30; g < KB_B; g += 2) {
    int sy = sx + 1, py = px;
    if (sy == NST_B) { sy = 0; py ^= 1; }
    mbar_wait(full0 + 8 * sx, px);
    if (up) mbar_wait(full0 + 8 * sy, py);
    const uint32_t da = da0 + (up ? sy : sx) * (STAGE_B >> 4), db = db0 + sx * (STAGE_B >> 4);
    wgmma_fence();
    #pragma unroll
    for (int k = 0; k < 4; k++) {
      wgmma_n<160, 0>(acc[0], desc64(da + k * 2, 0x40000040u), desc64(db + k * 2, 0x40000040u));
      wgmma_n<160, 0>(acc[1], desc64(da + 512 + k * 2, 0x40000040u), desc64(db + k * 2, 0x40000040u));
    }
    wgmma_commit();
    wgmma_wait<1>();
    if (g > 30 && t < 2 + 4 * up && g - 2 + (t >= 2) + NST_B < KB_B) mbar_arrive_cluster(empty0 + 8 * (t < 2 ? psx : psy), t & 1);
    psx = sx; psy = sy;
    sx = sy + 1; px = py;
    if (sx == NST_B) { sx = 0; px ^= 1; }
  }
}

__device__ __forceinline__ void set_flag(int slot, int byte, unsigned epoch) {
  asm volatile("st.relaxed.gpu.global.u8 [%0], %1;" :: "l"(g_flags + slot * 256 + byte), "r"(epoch & 255u) : "memory");
}
__device__ __forceinline__ unsigned get_flag(int slot, int byte) {
  unsigned v; asm volatile("ld.relaxed.gpu.global.u8 %0, [%1];" : "=r"(v) : "l"(g_flags + slot * 256 + byte) : "memory"); return v;
}
__device__ __forceinline__ void publish(int slot, int byte, unsigned epoch) {
  asm volatile("fence.acq_rel.gpu;" ::: "memory");
  set_flag(slot, byte, epoch);
}

__device__ __forceinline__ float sum8(uint4 v) {
  return ((bf_lo(v.x) + bf_hi(v.x)) + (bf_lo(v.y) + bf_hi(v.y))) + ((bf_lo(v.z) + bf_hi(v.z)) + (bf_lo(v.w) + bf_hi(v.w)));
}
__device__ __forceinline__ uint4 ldg128(const void* p) {
  uint4 v; asm volatile("ld.global.nc.v4.u32 {%0,%1,%2,%3}, [%4];" : "=r"(v.x), "=r"(v.y), "=r"(v.z), "=r"(v.w) : "l"(p)); return v;
}
__device__ __forceinline__ void ln_load(const bf16* __restrict__ x, int cta, uint4 (&rv)[5]) {
  const int t = threadIdx.x - 128, row = cta * 16 + (t >> 4), c = t & 15;
  #pragma unroll
  for (int j = 0; j < 5; j++) rv[j] = ldg128(reinterpret_cast<const uint4*>(x + (size_t)row * DM) + c + 16 * j);
}
__device__ __forceinline__ void ln_rows(const uint4 (&rv)[5], int cta, unsigned epoch) {
  const int t = threadIdx.x - 128, row = cta * 16 + (t >> 4), c = t & 15;
  const float sh = __shfl_sync(0xffffffffu, bf_lo(rv[0].x), t & 16);
  float d[40], s = 0.f, q = 0.f;
  #pragma unroll
  for (int j = 0; j < 5; j++) {
    const uint32_t u[4] = {rv[j].x, rv[j].y, rv[j].z, rv[j].w};
    #pragma unroll
    for (int e = 0; e < 4; e++) {
      const float d0 = bf_lo(u[e]) - sh, d1 = bf_hi(u[e]) - sh;
      d[j * 8 + e * 2] = d0; d[j * 8 + e * 2 + 1] = d1;
      s += d0 + d1; q = fmaf(d0, d0, q); q = fmaf(d1, d1, q);
    }
  }
  #pragma unroll
  for (int o = 1; o < 16; o <<= 1) { s += __shfl_xor_sync(0xffffffffu, s, o); q += __shfl_xor_sync(0xffffffffu, q, o); }
  const float md = s * (1.f / DM);
  const float r = rsqrtf(fmaxf(fmaf(q, 1.f / DM, -md * md), 0.f) + LN_EPS), o = -md * r;
  if (c == 0) st_vol2(&g_xstat[row], __float_as_uint(r), (__float_as_uint(-(md + sh) * r) & ~255u) | (epoch & 255u));
  #pragma unroll
  for (int j = 0; j < 5; j++) {
    const float* a = &d[j * 8];
    stg128(reinterpret_cast<uint4*>(g_xn + (size_t)row * DM) + c + 16 * j, make_uint4(
           pack_bf16(fmaf(a[0], r, o), fmaf(a[1], r, o)), pack_bf16(fmaf(a[2], r, o), fmaf(a[3], r, o)),
           pack_bf16(fmaf(a[4], r, o), fmaf(a[5], r, o)), pack_bf16(fmaf(a[6], r, o), fmaf(a[7], r, o))));
  }
  bar_arrive<BAR_LN>(288);
}
__device__ __forceinline__ void colsum_part(const bf16* __restrict__ win, int cta, unsigned epoch) {
  const int t = threadIdx.x & 127, w = t >> 5, l = t & 31;
  const int cj = min(cta, 119), cg = cj % 24, rg = cj / 24;
  uint4 cv[4];
  #pragma unroll
  for (int j = 0; j < 4; j++) cv[j] = ldg128(reinterpret_cast<const uint4*>(win + (size_t)(rg * 128 + w * 32 + j * 8 + (l >> 2)) * FF + FH + cg * 32) + (l & 3));
  float v[8];
  v[0] = (bf_lo(cv[0].x) + bf_lo(cv[1].x)) + (bf_lo(cv[2].x) + bf_lo(cv[3].x)); v[1] = (bf_hi(cv[0].x) + bf_hi(cv[1].x)) + (bf_hi(cv[2].x) + bf_hi(cv[3].x));
  v[2] = (bf_lo(cv[0].y) + bf_lo(cv[1].y)) + (bf_lo(cv[2].y) + bf_lo(cv[3].y)); v[3] = (bf_hi(cv[0].y) + bf_hi(cv[1].y)) + (bf_hi(cv[2].y) + bf_hi(cv[3].y));
  v[4] = (bf_lo(cv[0].z) + bf_lo(cv[1].z)) + (bf_lo(cv[2].z) + bf_lo(cv[3].z)); v[5] = (bf_hi(cv[0].z) + bf_hi(cv[1].z)) + (bf_hi(cv[2].z) + bf_hi(cv[3].z));
  v[6] = (bf_lo(cv[0].w) + bf_lo(cv[1].w)) + (bf_lo(cv[2].w) + bf_lo(cv[3].w)); v[7] = (bf_hi(cv[0].w) + bf_hi(cv[1].w)) + (bf_hi(cv[2].w) + bf_hi(cv[3].w));
  #pragma unroll
  for (int st = 0; st < 3; st++) {
    const int n = 4 >> st;
    const bool up = (l & (4 * n)) != 0;
    #pragma unroll
    for (int e = 0; e < 4; e++)
      if (e < n) { const float keep = up ? v[e + n] : v[e], send = up ? v[e] : v[e + n]; v[e] = keep + __shfl_xor_sync(0xffffffffu, send, 4 * n); }
  }
  float* red = reinterpret_cast<float*>(smem + RED_OFF);
  red[w * 32 + (l & 3) * 8 + (l >> 2)] = v[0];
  bar_sync<BAR_WG2>(128);
  if (t < 32) st_vol2(&g_csum[rg * FH + cg * 32 + t], __float_as_uint((red[t] + red[32 + t]) + (red[64 + t] + red[96 + t])), epoch);
}

__device__ __forceinline__ void a_entry(int g, int grp, int rb, int& mi, int& kb, int& row) {
  row = rb * 128;
  if (g < 10) { mi = M_X; kb = g; }
  else if (g < 20) { mi = M_XN; kb = g - 10; }
  else if (grp == 0) {
    if (g < 52) { mi = M_WSP; kb = g - 20; }
    else if (g < 52 + NX) { mi = M_WSIM; kb = g - 52 + 32 - NX; }
    else { mi = M_H; kb = g - 52 - NX; }
  } else if (g < 30) { mi = M_XN; kb = g - 20; }
  else {
    const int idx = ((g - 30) & ~1) + (rb & 1);
    mi = idx < 32 ? M_WSRE : M_WSIM; kb = idx & 31;
    row = (rb >> 1) * 256 + (g & 1) * 128;
  }
}

__global__ void __cluster_dims__(2, 1, 1) __launch_bounds__(384, 1)
fused_kernel(const __grid_constant__ Maps maps, const bf16* __restrict__ x, const bf16* __restrict__ win, const bf16* __restrict__ bsp,
             bf16* __restrict__ out) {
  const uint32_t sbase = smem_u32(smem);
  const uint32_t full0 = sbase + BAR_OFF, empty0 = full0 + 8 * MAXST, dep0 = empty0 + 8 * MAXST, ring = sbase + RING_OFF;
  const int tid = threadIdx.x, wg = __shfl_sync(0xffffffffu, tid >> 7, 0);
  const int rank = blockIdx.x & 1;
  const int grp = (blockIdx.x >> 1) & 1, half = (blockIdx.x >> 2) & 1, rb = blockIdx.x >> 3;
  const int ct = half * 2 + rank, c8 = grp * 4 + ct;
  const int cta = rb * 8 + half * 4 + grp * 2 + rank;
  const int total = grp == 0 ? KB_A : KB_B;
  const uint32_t stage_bytes = grp == 0 ? STAGE_A : STAGE_B;
  const int nst = grp == 0 ? NST_A : NST_B;
  const uint32_t buf = ring + nst * stage_bytes;

  uint4 rv[5];
  if (wg != 0) ln_load(x, cta, rv);
  if (wg == 2) {
    const int t = tid & 127;
    if (t < 60) asm volatile("prefetch.global.L2 [%0];" :: "l"(win + (size_t)(cta * 5 + t / 12) * FF + FH + (t % 12) * 64));
  }
  const unsigned epoch = (ld_relaxed(&g_done) >> 7) + 1u;
  if (tid == 0) {
    TS(0, 0);
    for (int s = 0; s < MAXST; s++) { mbar_init(full0 + 8 * s, 2); mbar_init(empty0 + 8 * s, 4); }
    for (int s = 0; s < 5; s++) mbar_init(dep0 + 8 * s, 1);
    *reinterpret_cast<volatile int*>(smem + READY_OFF) = 0;
    asm volatile("fence.mbarrier_init.release.cluster;" ::: "memory");
  }
  __syncthreads();
  asm volatile("barrier.cluster.arrive.relaxed.aligned;" ::: "memory");

  if (wg == 0) {
    asm volatile("setmaxnreg.dec.sync.aligned.u32 40;");
    const int warp = tid >> 5, lane = tid & 31;
    if (warp == 0) {
      const int row = rb * 128;
      if (lane == 0) {
        for (int g = 0; g < nst; g++) {
          mbar_expect_tx(full0 + 8 * g, A_BYTES);
          tma_load_2d(ring + g * stage_bytes, &maps.m[M_X], full0 + 8 * g, g * 64, row);
          tma_load_2d(ring + g * stage_bytes + 8192, &maps.m[M_X], full0 + 8 * g, g * 64, row + 64);
        }
      }
      __syncwarp();
      cluster_wait();
      if (lane == 0) {
        int s = 0, ph = 0;
        #pragma unroll 1
        for (int g = nst; g < total; g++) {
          int mi, kb, arow;
          a_entry(g, grp, rb, mi, kb, arow);
          if (g == 10 || (mi == M_H && kb == 0)) { TS(0, g > 10 ? 3 : 1); mbar_wait(dep0 + (g > 10 ? 24 : 0), 0); fence_async_global(); TS(0, g > 10 ? 4 : 2); }
          mbar_wait(empty0 + 8 * s, ph);
          mbar_expect_tx(full0 + 8 * s, A_BYTES);
          tma_load_2d_mc(ring + s * stage_bytes + rank * 8192, &maps.m[mi], full0 + 8 * s, kb * 64, arow + rank * 64, 3);
          if (++s == nst) { s = 0; ph ^= 1; }
          if (g + PF_D < total) {
            a_entry(g + PF_D, grp, rb, mi, kb, arow);
            if (mi >= M_WSRE && mi <= M_WSP && PF_COND)
              asm volatile("cp.async.bulk.prefetch.tensor.2d.L2.global.tile [%0, {%1, %2}];" :: "l"((uint64_t)&maps.m[mi]), "r"(kb * 64), "r"(arow + rank * 64) : "memory");
          }
        }
        TS(0, 5);
      }
    } else if (warp == 1) {
      if (lane == 0) {
        int s = 0, ph = 1;
        int have = 0;
        #pragma unroll 1
        for (int g = 0; g < total; g++) {
          int kind = 1, mi, kb, c, dep = 0, need = 0;
          uint32_t bytes = 20480;

          if (g < 10) { kind = 0; mi = M_WIN32; kb = g; c = 24 + 3 * c8; bytes = 12288; }
          else if (grp == 0) {
            if (g < 20) { kind = 0; mi = M_WIN3; kb = g - 10; c = 3 * ct; bytes = 24576; }
            else if (g < 52) { kind = 0; mi = M_Z23; kb = (g - 20); c = 3 * ct; bytes = 24576; need = ((g - 20) >> 1) + 1; }
            else if (g < 52 + NX) { mi = M_AB; kb = g - 52 + 32 - NX; c = DM + ct * 160; dep = g == 52 ? 2 : 0; }

            else { kind = 0; mi = M_WOUT; kb = g - 52 - NX; c = ct * 5; }
          } else {
            if (g < 30) { mi = g < 20 ? M_WDRE : M_WDIM; kb = g < 20 ? g - 10 : g - 20; c = ct * 160; }
            else {
              const int idx = g - 30 + (rb & 1);
              mi = M_AB; kb = idx & 31; c = ct * 160 + (idx < 32 ? 0 : DM);
              if (g & 1) kind = 2;
              else if (g < 62) need = ((g - 30) >> 1) + 1;
              else dep = g == 62 ? 2 : 0;
            }
          }
          if (need > have) {
            if (need == 1) TS(1, 0);
            unsigned it = 0;
            while ((have = *reinterpret_cast<volatile int*>(smem + READY_OFF)) < need && ++it < 50 * POLL_LIMIT) {}
            fence_async_global();
            if (need == 1) { TS(1, 1); TC(1); }
          }
          if (dep) { TS(1, dep * 2 - 2); mbar_wait(dep0 + 8 * dep, 0); fence_async_global(); TS(1, dep * 2 - 1); TC(dep); }
          const uint32_t dst = ring + s * stage_bytes + A_BYTES, fb = full0 + 8 * s;
          mbar_wait(empty0 + 8 * s, ph);
          if (++s == nst) { s = 0; ph ^= 1; }
          if (kind == 2) mbar_arrive(fb); else mbar_expect_tx(fb, bytes);
          if (kind == 0) tma_load_3d(dst, &maps.m[mi], fb, 0, kb * 64, c);
          else if (kind == 1) tma_load_2d(dst, &maps.m[mi], fb, kb * 64, c);
        }
      }
      __syncwarp();
      cluster_wait();
    } else if (warp == 2) {
      if (lane < M_COUNT) asm volatile("prefetch.tensormap [%0];" :: "l"((uint64_t)&maps.m[lane]) : "memory");
      cluster_wait();
      {
        unsigned it = 0;
        uint2 v[4];
        while (true) {
          bool ok = true;
          #pragma unroll
          for (int i = 0; i < 4; i++) { v[i] = ld_vol2(&g_xstat[rb * 128 + i * 32 + lane]); ok = ok && ((v[i].y ^ epoch) & 255u) == 0; }
          if (ok || ++it > POLL_LIMIT) break;
          __nanosleep(POLL_NS);
        }
        #pragma unroll
        for (int i = 0; i < 4; i++) reinterpret_cast<uint2*>(smem + ROWSTAT_OFF)[i * 32 + lane] = make_uint2(v[i].x, v[i].y & ~255u);
        __syncwarp();
        TS(0, 6);
        bar_arrive<BAR_STATS>(192);
      }
      #pragma unroll 1
      for (int d = 0; d < 5; d++) {
        if (d == 3 && grp == 1) continue;
        const int slot = d == 0 ? F_XN + rb : d == 4 ? F_Y + (rb >> 1) * 4 + ct : d == 3 ? F_H + rb : d == 2 ? F_B + ct : grp == 0 ? F_Z + ct : F_A + ct;
        const int byte = d == 0 ? lane & 7 : d == 4 ? lane & 1 : d == 3 ? lane & 3 : (d == 1 && grp == 0) ? lane : lane >> 1;
        unsigned it = 0, m;
        while ((m = __ballot_sync(0xffffffffu, get_flag(slot, byte) != (epoch & 255u))) != 0 && ++it < POLL_LIMIT) {
          if (d == 1 && lane == 0) *reinterpret_cast<volatile int*>(smem + READY_OFF) = (__ffs(m) - 1) >> 1;
          __nanosleep(WATCH_NS);
        }
        if (d == 1 && lane == 0) *reinterpret_cast<volatile int*>(smem + READY_OFF) = 16;
        if (d < 4) TS(0, 8 + d * 2); else TS(0, 7);
        fence_async_global();
        __syncwarp();
        if (lane == 0 && d != 1) mbar_arrive(dep0 + 8 * d);
      }
    } else {
      cluster_wait();
      bar_sync<BAR_LN>(288);
      if (lane == 0) { TS(1, 5); publish(F_XN + rb, cta & 7, epoch); TS(1, 6); }
      __syncwarp();
      {
        unsigned it = 0;
        while (true) {
          bool ok = true;
          uint2 u[15];
          #pragma unroll
          for (int i = 0; i < 15; i++) u[i] = ld_vol2(&g_csum[(i % 5) * FH + c8 * 96 + (i / 5) * 32 + lane]);
          #pragma unroll
          for (int i = 0; i < 15; i++) ok = ok && u[i].y == epoch;
          #pragma unroll
          for (int i = 0; i < 3; i++)
            reinterpret_cast<float*>(smem + COLSUM_OFF)[i * 32 + lane] = ((__uint_as_float(u[i * 5].x) + __uint_as_float(u[i * 5 + 1].x)) +
                (__uint_as_float(u[i * 5 + 2].x) + __uint_as_float(u[i * 5 + 3].x))) + __uint_as_float(u[i * 5 + 4].x);
          if (ok || ++it > POLL_LIMIT) break;
          __nanosleep(POLL_NS);
        }
      }
      __syncwarp();
      TS(1, 4);
      bar_arrive<BAR_STATS>(192);
      bar_sync<BAR_PUB1>(160);
      if (lane == 0) {
        TS(1, 7);
        tma_store_3d(&maps.m[M_Z232], buf, 0, rb * 128, 3 * c8);
        bulk_commit();
        bulk_wait_all();
        set_flag(F_Z + (c8 >> 1), rb * 2 + (c8 & 1), epoch);
        TS(1, 8);
      }
      __syncwarp();
      bar_arrive<BAR_BUF>(160);
      if (grp == 1) {
        bar_sync<BAR_PUB2>(160);
        if (lane == 0) set_flag(F_A + ct, rb, epoch);
        TS(1, 9);
        __syncwarp();
      }
      bar_sync<BAR_PUB1>(160);
      if (lane == 0) set_flag(grp == 0 ? F_H + rb : F_B + ct, grp == 0 ? ct : rb, epoch);
      TS(1, 10);
      __syncwarp();
      bar_arrive<BAR_BUF>(160);
    }
  } else {
    asm volatile("setmaxnreg.inc.sync.aligned.u32 232;");
    const int t = tid & 127, w = t >> 5, l = t & 31;
    ln_rows(rv, cta, epoch);
    if (wg == 2) colsum_part(win, cta, epoch);
    TS(wg + 1, 0);
    cluster_wait();
    const int rl = w * 16 + ((l >> 3) & 1) * 8 + (l & 7);
    const int gr = w * 16 + (l & 15);
    const uint32_t st_base = buf + rl * 128;
    const uint32_t st_x = ((l >> 4) ^ (l & 7)) << 4;
    if (wg == 1) {
      float acc[2][48];
      zero(acc);
      mainloop<96, 2, false, BAR_ORD1>(acc, sbase, grp, 0, 10);
      drain(acc, sbase, grp, 9);
      TS(2, 2);
      bar_sync<BAR_STATS>(192);
      const float2* rs = reinterpret_cast<const float2*>(smem + ROWSTAT_OFF) + w * 16 + (l >> 2);
      const float2* cs = reinterpret_cast<const float2*>(smem + COLSUM_OFF) + (l & 3);
      float sum[4], sq[4];
      #pragma unroll
      for (int r = 0; r < 4; r++) {
        const float2 st = rs[(r >> 1) * 64 + (r & 1) * 8];
        float s0 = 0.f, q0 = 0.f;
        #pragma unroll
        for (int j = 0; j < 12; j++) {
          const float2 c = cs[j * 4];
          float* a = &acc[r >> 1][4 * j + (r & 1) * 2];
          a[0] = gelu_tanh(fmaf(a[0], st.x, st.y * c.x));
          a[1] = gelu_tanh(fmaf(a[1], st.x, st.y * c.y));
          s0 += a[0] + a[1]; q0 = fmaf(a[0], a[0], q0); q0 = fmaf(a[1], a[1], q0);
        }
        s0 += __shfl_xor_sync(0xffffffffu, s0, 1); q0 += __shfl_xor_sync(0xffffffffu, q0, 1);
        s0 += __shfl_xor_sync(0xffffffffu, s0, 2); q0 += __shfl_xor_sync(0xffffffffu, q0, 2);
        sum[r] = s0; sq[r] = q0;
      }
      TS(2, 4);
      float rstd, off;
      {
        const int qd = l & 3;
        const float sm = qd == 0 ? sum[0] : qd == 1 ? sum[1] : qd == 2 ? sum[2] : sum[3];
        const float sv = qd == 0 ? sq[0] : qd == 1 ? sq[1] : qd == 2 ? sq[2] : sq[3];
        const int row = (qd >> 1) * 64 + w * 16 + (qd & 1) * 8 + (l >> 2);
        const float mu = sm * (1.f / 96), m2 = fmaxf(sv - sm * mu, 0.f);
        st_vol2(&g_zstat[(rb * 8 + c8) * 128 + row], __float_as_uint(mu), (__float_as_uint(m2) & ~255u) | (epoch & 255u));
        uint2 v[7];
        unsigned n = 0;
        while (true) {
          bool ok = true;
          #pragma unroll
          for (int j = 0; j < 7; j++) v[j] = ld_vol2(&g_zstat[(rb * 8 + ((c8 + 1 + j) & 7)) * 128 + row]);
          #pragma unroll
          for (int j = 0; j < 7; j++) ok = ok && ((v[j].y ^ epoch) & 255u) == 0;
          if (ok || ++n > POLL_LIMIT) break;
          __nanosleep(POLL_NS);
        }
        float mean = mu, var = m2;
        #pragma unroll
        for (int j = 0; j < 7; j++) { mean += __uint_as_float(v[j].x); var += __uint_as_float(v[j].y & ~255u); }
        mean *= 0.125f;
        float d = (mu - mean) * (mu - mean);
        #pragma unroll
        for (int j = 0; j < 7; j++) d = fmaf(__uint_as_float(v[j].x) - mean, __uint_as_float(v[j].x) - mean, d);
        rstd = rsqrtf(fmaf(96.f, d, var) * (1.f / FH) + LN_EPS); off = -mean * rstd;
        __syncwarp();
      }
      TS(2, 5);
      #pragma unroll
      for (int mi = 0; mi < 2; mi++) {
        const float r0 = __shfl_sync(0xffffffffu, rstd, (l & 28) + mi * 2), o0 = __shfl_sync(0xffffffffu, off, (l & 28) + mi * 2);
        const float r1 = __shfl_sync(0xffffffffu, rstd, (l & 28) + mi * 2 + 1), o1 = __shfl_sync(0xffffffffu, off, (l & 28) + mi * 2 + 1);
        #pragma unroll
        for (int jj = 0; jj < 6; jj++) {
          const float* a = &acc[mi][8 * jj];
          stsm4(buf + (jj >> 1) * 8192 + mi * 4096 + rl * 64 + ((((jj & 1) * 2 + (l >> 4)) ^ ((l >> 1) & 3)) << 4),
                pack_bf16(fmaf(a[0], r0, o0), fmaf(a[1], r0, o0)), pack_bf16(fmaf(a[2], r1, o1), fmaf(a[3], r1, o1)),
                pack_bf16(fmaf(a[4], r0, o0), fmaf(a[5], r0, o0)), pack_bf16(fmaf(a[6], r1, o1), fmaf(a[7], r1, o1)));
        }
      }
      fence_async_smem();
      bar_arrive<BAR_PUB1>(160);
      TS(2, 6);
      if (grp == 0) {
        float acc[2][96];
        {
          const bf16* bp = bsp + rb * 128 + w * 16 + (l >> 2);
          const float bb[4] = {__bfloat162float(bp[0]), __bfloat162float(bp[8]), __bfloat162float(bp[64]), __bfloat162float(bp[72])};
          #pragma unroll
          for (int i = 0; i < 96; i++) { acc[0][i] = bb[(i >> 1) & 1]; acc[1][i] = bb[2 + ((i >> 1) & 1)]; }
          pin(acc);
        }
        bar_sync<BAR_ORD2>(256);
        mainloop<192, 1, false, BAR_ORD1>(acc, sbase, 0, 20, 32);
        bar_sync<BAR_Z1>(256);
        drain(acc, sbase, 0, 51);
        TS(2, 7);
        {
          uint32_t z[2][4][4];
          #pragma unroll
          for (int i = 0; i < 4; i++) ldsm4(st_base + (st_x ^ (i << 5)), z[0][i][0], z[0][i][1], z[0][i][2], z[0][i][3]);
          #pragma unroll
          for (int bx = 0; bx < 6; bx++) {
            if (bx < 5) {
              #pragma unroll
              for (int i = 0; i < 4; i++)
                ldsm4(st_base + (bx + 1) * 8192 + (st_x ^ (i << 5)), z[(bx + 1) & 1][i][0], z[(bx + 1) & 1][i][1], z[(bx + 1) & 1][i][2], z[(bx + 1) & 1][i][3]);
            }
            #pragma unroll
            for (int i = 0; i < 4; i++) {
              const float* a = &acc[bx / 3][8 * ((bx % 3) * 4 + i)];
              const uint32_t* zz = z[bx & 1][i];
              stsm4(st_base + bx * 8192 + (st_x ^ (i << 5)),
                    hmul2_bf16(zz[0], pack_bf16(a[0], a[1])), hmul2_bf16(zz[1], pack_bf16(a[2], a[3])),
                    hmul2_bf16(zz[2], pack_bf16(a[4], a[5])), hmul2_bf16(zz[3], pack_bf16(a[6], a[7])));
            }
            if (bx % 3 == 2) {
              fence_async_smem();
              __syncwarp();
              if (l < 3) {
                tma_store_2d(&maps.m[M_HS], buf + (bx - 2 + l) * 8192 + w * 2048, ct * 192 + l * 64, rb * 128 + (bx / 3) * 64 + w * 16);
                bulk_commit();
              }
            }
          }
        }
        TS(2, 8);
        if (l < 3) bulk_wait_all();
        __syncwarp();
        bar_arrive<BAR_PUB1>(160);
        TS(2, 9);
        return;
      }
    } else {
      if (grp == 0) {
        float acc[2][96];
        zero(acc);
        bar_sync<BAR_ORD1>(256);
        mainloop<192, 1, false, BAR_ORD2>(acc, sbase, 0, 10, 10);
        drain(acc, sbase, 0, 19);
        TS(3, 2);
        bar_sync<BAR_BUF>(160);
        #pragma unroll
        for (int mi = 0; mi < 2; mi++)
          #pragma unroll
          for (int jj = 0; jj < 12; jj++) {
            const float* a = &acc[mi][8 * jj];
            stsm4(st_base + mi * 24576 + (jj >> 2) * 8192 + (st_x ^ ((jj & 3) << 5)),
                  pack_bf16(a[0], a[1]), pack_bf16(a[2], a[3]), pack_bf16(a[4], a[5]), pack_bf16(a[6], a[7]));
          }
        __syncwarp();
        TS(3, 3);
        const uint32_t rbase = buf + (l >> 4) * 24576 + gr * 128;
        #pragma unroll 1
        for (int c2 = 0; c2 < 12; c2++) {
          const uint32_t ab = rbase + (c2 >> 2) * 8192;
          uint4 v[2];
          #pragma unroll
          for (int i = 0; i < 2; i++) v[i] = lds128(ab + (((((c2 & 3) * 2 + i) ^ l) & 7) << 4));
          #pragma unroll
          for (int i = 0; i < 2; i++)
            sts128(ab + (((((c2 & 3) * 2 + i) ^ l) & 7) << 4),
                   pack_bf16(gelu_tanh(bf_lo(v[i].x)), gelu_tanh(bf_hi(v[i].x))), pack_bf16(gelu_tanh(bf_lo(v[i].y)), gelu_tanh(bf_hi(v[i].y))),
                   pack_bf16(gelu_tanh(bf_lo(v[i].z)), gelu_tanh(bf_hi(v[i].z))), pack_bf16(gelu_tanh(bf_lo(v[i].w)), gelu_tanh(bf_hi(v[i].w))));
        }
        TS(3, 4);
        bar_arrive<BAR_Z1>(256);
        #pragma unroll 1
        for (int i = 0; i < 4; i++) {
          uint4 v[5];
          #pragma unroll
          for (int j = 0; j < 5; j++) {
            const int e = (i * 5 + j) * 128 + t;
            v[j] = ldg128(x + (size_t)(rb * 128 + e / 20) * DM + ct * 160 + (e % 20) * 8);
          }
          #pragma unroll
          for (int j = 0; j < 5; j++) {
            const int e = (i * 5 + j) * 128 + t;
            stg128(out + (size_t)(rb * 128 + e / 20) * DM + ct * 160 + (e % 20) * 8, v[j]);
          }
        }
        bar_sync<BAR_WG2>(128);
        if (t == 0) publish(F_Y + (rb >> 1) * 4 + ct, rb & 1, epoch);
      }
    }
    float acc[2][80];
    if (grp == 1) {
      zero(acc);
      if (wg == 2) {
        bar_sync<BAR_ORD1>(256);
        mainloop<160, 0, false, BAR_ORD2>(acc, sbase, 1, 10, 10);
      } else {
        bar_sync<BAR_ORD2>(256);
        mainloop<160, 0, false, BAR_ORD1>(acc, sbase, 1, 20, 10);
      }
      drain(acc, sbase, 1, wg == 2 ? 19 : 29);
      TS(wg + 1, wg == 1 ? 7 : 2);
      if (wg == 1) bar_sync<BAR_Z1>(256); else bar_sync<BAR_BUF>(160);
      const uint32_t sg = wg == 1 ? 0x80008000u : 0u;
      const uint32_t tb = buf + ((l >> 4) * 8 + (l & 7)) * 128 + (((w * 2 + ((l >> 3) & 1)) ^ (l & 7)) << 4);
      #pragma unroll
      for (int mi = 0; mi < 2; mi++)
        #pragma unroll
        for (int jj = 0; jj < 10; jj++) {
          const float* a = &acc[mi][8 * jj];
          stsm4_t(tb + mi * 20480 + jj * 2048, pack_bf16(a[0], a[1]) ^ sg, pack_bf16(a[2], a[3]) ^ sg, pack_bf16(a[4], a[5]) ^ sg, pack_bf16(a[6], a[7]) ^ sg);
        }
      fence_async_smem();
      if (wg == 1) bar_sync<BAR_WG1>(128); else bar_sync<BAR_WG2>(128);
      TS(wg + 1, wg == 1 ? 8 : 6);
      if (l == 0) {
        #pragma unroll 1
        for (int i = 0; i < 2; i++) {
          tma_store_2d(&maps.m[M_ABS], buf + i * 20480 + w * 5120, rb * 128 + i * 64, (2 - wg) * DM + ct * 160 + w * 40);
          bulk_commit();
        }
        bulk_wait_all();
      }
      __syncwarp();
      TS(wg + 1, wg == 1 ? 9 : 10);
      if (wg == 1) {
        bar_arrive<BAR_PUB1>(160);
      } else {
        bar_arrive<BAR_PUB2>(160);
        bar_arrive<BAR_Z1>(256);
      }
    }
    zero(acc);
    if (wg == 2) bar_sync<BAR_ORD1>(256);
    if (grp == 0) {
      mainloop<160, 0, false, 0>(acc, sbase, 0, 52, NX);
      mainloop<160, 2, true, 0>(acc, sbase, 0, 52 + NX, 12);
    } else {
      yloop(acc, sbase, wg == 1);
    }
    const uint32_t slab0 = (wg == 2 ? buf : ring + ((KB_B - 1) % NST_B) * STAGE_B) + w * (16 * 320);
    const uint32_t slab1 = (wg == 2 ? buf + 20480 : ring + ((KB_B - 3) % NST_B) * STAGE_B) + w * (16 * 320);
    const uint32_t aoff = (((l >> 3) & 1) * 8 + (l & 7)) * 320 + (l >> 4) * 16;
    const int orow = (grp == 0 ? rb * 128 : (rb >> 1) * 256 + (2 - wg) * 128) + w * 16;
    if (wg == 2) bar_sync<BAR_BUF>(160);
    mbar_wait(dep0 + 32, 0);
    wgmma_wait<0>();
    pin(acc);
    if (wg == 1) bar_sync<BAR_WG1>(128);
    TS(wg + 1, 12);
    #pragma unroll
    for (int mi = 0; mi < 2; mi++) {
      const uint32_t slab = mi == 0 ? slab0 : slab1;
      #pragma unroll
      for (int jj = 0; jj < 10; jj++) {
        const float* a = &acc[mi][8 * jj];
        stsm4(slab + aoff + jj * 32, pack_bf16(a[0], a[1]), pack_bf16(a[2], a[3]), pack_bf16(a[4], a[5]), pack_bf16(a[6], a[7]));
      }
      fence_async_smem();
      __syncwarp();
      if (l == 0) {
        tma_reduce_2d(&maps.m[M_OUT], slab, ct * 160, orow + mi * 64);
        bulk_commit();
      }
    }
    TS(wg + 1, 13);
    if (l == 0) {
      bulk_wait_read();
      if (w == 0 && wg == 2) atomicAdd(&g_done, 1u);
    }
    TS(wg + 1, 15);
  }
}

typedef CUresult (*EncodeFn)(CUtensorMap*, CUtensorMapDataType, cuuint32_t, void*, const cuuint64_t*, const cuuint64_t*,
                             const cuuint32_t*, const cuuint32_t*, CUtensorMapInterleave, CUtensorMapSwizzle,
                             CUtensorMapL2promotion, CUtensorMapFloatOOBfill);

void make2d(EncodeFn enc, CUtensorMap* m, const void* p, uint64_t cols, uint64_t rows, uint32_t bc, uint32_t br, bool swz = true) {
  cuuint64_t gd[2] = {cols, rows}, gs[1] = {cols * 2};
  cuuint32_t bd[2] = {bc, br}, es[2] = {1, 1};
  enc(m, CU_TENSOR_MAP_DATA_TYPE_BFLOAT16, 2, const_cast<void*>(p), gd, gs, bd, es, CU_TENSOR_MAP_INTERLEAVE_NONE,
      swz ? CU_TENSOR_MAP_SWIZZLE_128B : CU_TENSOR_MAP_SWIZZLE_NONE, PROMO, CU_TENSOR_MAP_FLOAT_OOB_FILL_NONE);
}
void make3d(EncodeFn enc, CUtensorMap* m, const void* p, uint64_t cols, uint64_t rows, uint32_t cw, uint32_t nc, uint32_t br = 64) {
  cuuint64_t gd[3] = {cw, rows, cols / cw}, gs[2] = {cols * 2, cw * 2};
  cuuint32_t bd[3] = {cw, br, nc}, es[3] = {1, 1, 1};
  enc(m, CU_TENSOR_MAP_DATA_TYPE_BFLOAT16, 3, const_cast<void*>(p), gd, gs, bd, es, CU_TENSOR_MAP_INTERLEAVE_NONE,
      cw == 64 ? CU_TENSOR_MAP_SWIZZLE_128B : CU_TENSOR_MAP_SWIZZLE_64B, PROMO, CU_TENSOR_MAP_FLOAT_OOB_FILL_NONE);
}

}

extern "C" void kernel_launch(void* const* d_in, const int* in_sizes, int n_in, void* d_out, int out_size) {
  const bf16* x = (const bf16*)d_in[0];
  const bf16* wsre = (const bf16*)d_in[1];
  const bf16* wsim = (const bf16*)d_in[2];
  const bf16* wdre = (const bf16*)d_in[3];
  const bf16* wdim = (const bf16*)d_in[4];
  const bf16* win = (const bf16*)d_in[6];
  const bf16* wsp = (const bf16*)d_in[7];
  const bf16* bsp = (const bf16*)d_in[8];
  const bf16* wout = (const bf16*)d_in[9];

  void* fn = nullptr;
  cudaDriverEntryPointQueryResult qr;
  cudaGetDriverEntryPoint("cuTensorMapEncodeTiled", &fn, cudaEnableDefault, &qr);
  EncodeFn enc = (EncodeFn)fn;
  void *abT, *z2, *h, *xn;
  cudaGetSymbolAddress(&xn, g_xn);
  cudaGetSymbolAddress(&abT, g_abT);
  cudaGetSymbolAddress(&z2, g_z2);
  cudaGetSymbolAddress(&h, g_h);

  Maps maps;
  make2d(enc, &maps.m[M_X], x, DM, SEQ, 64, 64);
  make2d(enc, &maps.m[M_XN], xn, DM, SEQ, 64, 64);
  make3d(enc, &maps.m[M_Z232], z2, FH, SEQ, 32, 3, 128);
  make3d(enc, &maps.m[M_WIN32], win, FF, DM, 32, 3);
  make2d(enc, &maps.m[M_WSRE], wsre, SEQ, SEQ, 64, 64);
  make2d(enc, &maps.m[M_WSIM], wsim, SEQ, SEQ, 64, 64);
  make2d(enc, &maps.m[M_WSP], wsp, SEQ, SEQ, 64, 64);
  make2d(enc, &maps.m[M_H], h, FH, SEQ, 64, 64);
  make3d(enc, &maps.m[M_WIN3], win, FF, DM, 64, 3);
  make3d(enc, &maps.m[M_Z23], z2, FH, SEQ, 64, 3);
  make2d(enc, &maps.m[M_WDRE], wdre, DM, DM, 64, 160);
  make2d(enc, &maps.m[M_WDIM], wdim, DM, DM, 64, 160);
  make2d(enc, &maps.m[M_AB], abT, SEQ, 2 * DM, 64, 160);
  make3d(enc, &maps.m[M_WOUT], wout, DM, FH, 32, 5);
  make2d(enc, &maps.m[M_HS], h, FH, SEQ, 64, 16);
  make2d(enc, &maps.m[M_ABS], abT, SEQ, 2 * DM, 64, 40);
  make2d(enc, &maps.m[M_OUT], d_out, DM, SEQ, 160, 16, false);

  cudaFuncSetAttribute(fused_kernel, cudaFuncAttributeMaxDynamicSharedMemorySize, SMEM_BYTES);
  fused_kernel<<<128, 384, SMEM_BYTES>>>(maps, x, win, bsp, (bf16*)d_out);
}
```

```cpp
#include <cuda_runtime.h>
#include <cuda_bf16.h>
#include <cuda.h>
#include <stdint.h>

namespace {

typedef __nv_bfloat16 bf16;

constexpr int SEQ = 2048, DM = 640, FF = 1536, FH = 768;
#define NXV 10
constexpr int NX = NXV;
#define NSTB 5
constexpr int NST_A = 4, NST_B = NSTB, MAXST = 5;
constexpr int A_BYTES = 16384;
constexpr int BAR_OFF = 512;
constexpr int READY_OFF = 640;
constexpr int ROWSTAT_OFF = 1024;
constexpr int COLSUM_OFF = 2048;
constexpr int RED_OFF = 2560;
constexpr int RING_OFF = 3072;
constexpr int STAGE_A = 40960, STAGE_B = 36864;
constexpr int SMEM_BYTES = RING_OFF + 5 * STAGE_B + 40960;
constexpr int KB_A = 20 + 32 + NX + 12;
constexpr int KB_B = 30 + 64 - NX;
constexpr float LN_EPS = 1e-5f;
constexpr unsigned POLL_LIMIT = 100000;
#define POLL_NS 100
#define PF_D 8
#define ROT 0
#define Z1_NS 0
#define INFL 2
#define LIM_G 1000
#define MAPV 0
#define PROMO CU_TENSOR_MAP_L2_PROMOTION_L2_128B
#define WATCH_NS 40
#define PF_COND ((kb & 1) == (ct >> 1))
#define WPF 1
#define Z2SW 0
#define WOSW 0
#define HINT 1
#define WPF2 1
#define XNB 1
#define PF_NS 150

constexpr int BAR_ORD1 = 1, BAR_ORD2 = 2, BAR_WG1 = 3, BAR_WG2 = 4, BAR_LN = 5, BAR_BUF = 6, BAR_Z1 = 7, BAR_PUB1 = 8, BAR_PUB2 = 9, BAR_STATS = 10;

enum { M_X, M_XN, M_WIN32, M_Z232, M_WSRE, M_WSIM, M_WSP, M_H, M_WIN3, M_Z23, M_WDRE, M_WDIM, M_AB, M_WOUT, M_OUT, M_HS, M_ABS, M_COUNT };
struct Maps { CUtensorMap m[M_COUNT]; };

__device__ __align__(1024) bf16 g_abT[2 * DM * SEQ];
__device__ __align__(1024) bf16 g_z2[SEQ * FH];
__device__ __align__(1024) bf16 g_h[SEQ * FH];
__device__ __align__(1024) bf16 g_xn[SEQ * DM];
__device__ __align__(16) uint2 g_xstat[SEQ];
__device__ __align__(16) uint2 g_csum[5 * FH];
__device__ __align__(16) uint2 g_zstat[128 * 128];
__device__ __align__(256) unsigned char g_flags[108 * 256];
constexpr int F_A = 0, F_B = 4, F_Z = 8, F_H = 12, F_XN = 28, F_Y = 44;
__device__ unsigned g_done;
#define TS(role, ev)
#define TC(i)

extern __shared__ __align__(1024) uint8_t smem[];

__device__ __forceinline__ uint32_t smem_u32(const void* p) { return (uint32_t)__cvta_generic_to_shared(p); }
__device__ __forceinline__ void mbar_init(uint32_t bar, uint32_t cnt) { asm volatile("mbarrier.init.shared::cta.b64 [%0], %1;" :: "r"(bar), "r"(cnt)); }
__device__ __forceinline__ void mbar_expect_tx(uint32_t bar, uint32_t bytes) { asm volatile("mbarrier.arrive.expect_tx.shared::cta.b64 _, [%0], %1;" :: "r"(bar), "r"(bytes) : "memory"); }
__device__ __forceinline__ void mbar_arrive(uint32_t bar) { asm volatile("mbarrier.arrive.shared::cta.b64 _, [%0];" :: "r"(bar) : "memory"); }
__device__ __forceinline__ void mbar_arrive_cluster(uint32_t bar, uint32_t cta) {
  asm volatile("{\n.reg .b32 ra;\nmapa.shared::cluster.u32 ra, %0, %1;\nmbarrier.arrive.shared::cluster.b64 _, [ra];\n}" :: "r"(bar), "r"(cta) : "memory");
}
__device__ __forceinline__ void mbar_wait(uint32_t bar, uint32_t parity) {
  asm volatile("{\n.reg .pred p;\n.reg .u32 n;\nmov.u32 n, 0;\n"
               "LW: mbarrier.try_wait.parity.shared::cta.b64 p, [%0], %1, 2000;\n@p bra LD;\n"
               "add.u32 n, n, 1;\nsetp.lt.u32 p, n, 20000;\n@p bra LW;\nLD:\n}" :: "r"(bar), "r"(parity) : "memory");
}
__device__ __forceinline__ void tma_load_2d(uint32_t dst, const CUtensorMap* map, uint32_t bar, int c0, int c1) {
  asm volatile("cp.async.bulk.tensor.2d.shared::cluster.global.mbarrier::complete_tx::bytes [%0], [%1, {%3, %4}], [%2];"
    :: "r"(dst), "l"((uint64_t)map), "r"(bar), "r"(c0), "r"(c1) : "memory");
}
__device__ __forceinline__ void tma_load_3d(uint32_t dst, const CUtensorMap* map, uint32_t bar, int c0, int c1, int c2) {
  asm volatile("cp.async.bulk.tensor.3d.shared::cluster.global.mbarrier::complete_tx::bytes [%0], [%1, {%3, %4, %5}], [%2];"
    :: "r"(dst), "l"((uint64_t)map), "r"(bar), "r"(c0), "r"(c1), "r"(c2) : "memory");
}
__device__ __forceinline__ void tma_load_2d_mc(uint32_t dst, const CUtensorMap* map, uint32_t bar, int c0, int c1, uint16_t mask) {
  asm volatile("cp.async.bulk.tensor.2d.shared::cluster.global.mbarrier::complete_tx::bytes.multicast::cluster [%0], [%1, {%3, %4}], [%2], %5;"
    :: "r"(dst), "l"((uint64_t)map), "r"(bar), "r"(c0), "r"(c1), "h"(mask) : "memory");
}
__device__ __forceinline__ void tma_store_2d(const CUtensorMap* map, uint32_t src, int c0, int c1) {
  asm volatile("cp.async.bulk.tensor.2d.global.shared::cta.bulk_group [%0, {%2, %3}], [%1];"
    :: "l"((uint64_t)map), "r"(src), "r"(c0), "r"(c1) : "memory");
}
__device__ __forceinline__ void tma_store_3d(const CUtensorMap* map, uint32_t src, int c0, int c1, int c2) {
  asm volatile("cp.async.bulk.tensor.3d.global.shared::cta.bulk_group [%0, {%2, %3, %4}], [%1];"
    :: "l"((uint64_t)map), "r"(src), "r"(c0), "r"(c1), "r"(c2) : "memory");
}
__device__ __forceinline__ void tma_reduce_2d(const CUtensorMap* map, uint32_t src, int c0, int c1) {
  asm volatile("cp.reduce.async.bulk.tensor.2d.global.shared::cta.add.tile.bulk_group [%0, {%2, %3}], [%1];"
    :: "l"((uint64_t)map), "r"(src), "r"(c0), "r"(c1) : "memory");
}
__device__ __forceinline__ void bulk_wait_all() { asm volatile("cp.async.bulk.wait_group 0;" ::: "memory"); }
__device__ __forceinline__ void bulk_commit() { asm volatile("cp.async.bulk.commit_group;" ::: "memory"); }
__device__ __forceinline__ void bulk_wait_read() { asm volatile("cp.async.bulk.wait_group.read 0;" ::: "memory"); }
__device__ __forceinline__ void fence_async_smem() { asm volatile("fence.proxy.async.shared::cta;" ::: "memory"); }
__device__ __forceinline__ void fence_async_global() { asm volatile("fence.proxy.async.global;" ::: "memory"); }
__device__ __forceinline__ void wgmma_fence() { asm volatile("wgmma.fence.sync.aligned;" ::: "memory"); }
__device__ __forceinline__ void wgmma_commit() { asm volatile("wgmma.commit_group.sync.aligned;" ::: "memory"); }
template<int N> __device__ __forceinline__ void wgmma_wait() { asm volatile("wgmma.wait_group.sync.aligned %0;" :: "n"(N) : "memory"); }
template<int ID> __device__ __forceinline__ void bar_sync(int n) { asm volatile("bar.sync %0, %1;" :: "n"(ID), "r"(n) : "memory"); }
template<int ID> __device__ __forceinline__ void bar_arrive(int n) { asm volatile("bar.arrive %0, %1;" :: "n"(ID), "r"(n) : "memory"); }
__device__ __forceinline__ void cluster_wait() { asm volatile("barrier.cluster.wait.aligned;" ::: "memory"); }
__device__ __forceinline__ uint64_t desc64(uint32_t lo, uint32_t hi) { return (uint64_t)lo | ((uint64_t)hi << 32); }
__device__ __forceinline__ uint4 ld_vol4(const uint4* p) {
  uint4 v; asm volatile("ld.relaxed.gpu.global.v4.u32 {%0,%1,%2,%3}, [%4];" : "=r"(v.x), "=r"(v.y), "=r"(v.z), "=r"(v.w) : "l"(p) : "memory"); return v;
}
__device__ __forceinline__ uint2 ld_vol2(const uint2* p) {
  uint2 v; asm volatile("ld.relaxed.gpu.global.v2.u32 {%0,%1}, [%2];" : "=r"(v.x), "=r"(v.y) : "l"(p) : "memory"); return v;
}
__device__ __forceinline__ void st_vol4(uint4* p, uint32_t a, uint32_t b, uint32_t c, uint32_t d) {
  asm volatile("st.relaxed.gpu.global.v4.u32 [%0], {%1,%2,%3,%4};" :: "l"(p), "r"(a), "r"(b), "r"(c), "r"(d) : "memory");
}
__device__ __forceinline__ void st_vol2(uint2* p, uint32_t a, uint32_t b) {
  asm volatile("st.relaxed.gpu.global.v2.u32 [%0], {%1,%2};" :: "l"(p), "r"(a), "r"(b) : "memory");
}
__device__ __forceinline__ void stg128(void* p, uint4 v) {
  asm volatile("st.global.v4.u32 [%0], {%1,%2,%3,%4};" :: "l"(p), "r"(v.x), "r"(v.y), "r"(v.z), "r"(v.w));
}
__device__ __forceinline__ unsigned ld_relaxed(const unsigned* p) {
  unsigned v; asm volatile("ld.relaxed.gpu.global.u32 %0, [%1];" : "=r"(v) : "l"(p) : "memory"); return v;
}
__device__ __forceinline__ uint32_t pack_bf16(float lo, float hi) {
  uint32_t r; asm("cvt.rn.bf16x2.f32 %0, %1, %2;" : "=r"(r) : "f"(hi), "f"(lo)); return r;
}
__device__ __forceinline__ float bf_lo(uint32_t v) { return __uint_as_float(v << 16); }
__device__ __forceinline__ float bf_hi(uint32_t v) { return __uint_as_float(v & 0xFFFF0000u); }
__device__ __forceinline__ void stsm4(uint32_t addr, uint32_t a, uint32_t b, uint32_t c, uint32_t d) {
  asm volatile("stmatrix.sync.aligned.m8n8.x4.shared.b16 [%0], {%1,%2,%3,%4};" :: "r"(addr), "r"(a), "r"(b), "r"(c), "r"(d));
}
__device__ __forceinline__ void stsm4_t(uint32_t addr, uint32_t a, uint32_t b, uint32_t c, uint32_t d) {
  asm volatile("stmatrix.sync.aligned.m8n8.x4.trans.shared.b16 [%0], {%1,%2,%3,%4};" :: "r"(addr), "r"(a), "r"(b), "r"(c), "r"(d));
}
__device__ __forceinline__ void ldsm4(uint32_t addr, uint32_t& a, uint32_t& b, uint32_t& c, uint32_t& d) {
  asm volatile("ldmatrix.sync.aligned.m8n8.x4.shared.b16 {%0,%1,%2,%3}, [%4];" : "=r"(a), "=r"(b), "=r"(c), "=r"(d) : "r"(addr));
}
__device__ __forceinline__ uint4 lds128(uint32_t a) {
  uint4 v; asm volatile("ld.shared.v4.u32 {%0,%1,%2,%3}, [%4];" : "=r"(v.x), "=r"(v.y), "=r"(v.z), "=r"(v.w) : "r"(a)); return v;
}
__device__ __forceinline__ void sts128(uint32_t a, uint32_t x, uint32_t y, uint32_t z, uint32_t w) {
  asm volatile("st.shared.v4.u32 [%0], {%1,%2,%3,%4};" :: "r"(a), "r"(x), "r"(y), "r"(z), "r"(w));
}
__device__ __forceinline__ uint32_t hmul2_bf16(uint32_t a, uint32_t b) {
  uint32_t r; asm("mul.rn.bf16x2 %0, %1, %2;" : "=r"(r) : "r"(a), "r"(b)); return r;
}
__device__ __forceinline__ float gelu_tanh(float v) {
  float u = v * fmaf(0.0356774081f, v * v, 0.7978845608f);
  float t; asm("tanh.approx.f32 %0, %1;" : "=f"(t) : "f"(u));
  float hv = 0.5f * v;
  return fmaf(hv, t, hv);
}

template<int TB>
__device__ __forceinline__ void wgmma_n192(float (&d)[96], uint64_t da, uint64_t db, int scale_d) {
  asm volatile("{\n.reg .pred p;\nsetp.ne.b32 p, %98, 0;\n"
   "wgmma.mma_async.sync.aligned.m64n192k16.f32.bf16.bf16 {%0,%1,%2,%3,%4,%5,%6,%7,%8,%9,%10,%11,%12,%13,%14,%15,%16,%17,%18,%19,%20,%21,%22,%23,%24,%25,%26,%27,%28,%29,%30,%31,%32,%33,%34,%35,%36,%37,%38,%39,%40,%41,%42,%43,%44,%45,%46,%47,%48,%49,%50,%51,%52,%53,%54,%55,%56,%57,%58,%59,%60,%61,%62,%63,%64,%65,%66,%67,%68,%69,%70,%71,%72,%73,%74,%75,%76,%77,%78,%79,%80,%81,%82,%83,%84,%85,%86,%87,%88,%89,%90,%91,%92,%93,%94,%95}, %96, %97, p, 1, 1, 0, %99;\n}"
   : "+f"(d[0]),"+f"(d[1]),"+f"(d[2]),"+f"(d[3]),"+f"(d[4]),"+f"(d[5]),"+f"(d[6]),"+f"(d[7]),"+f"(d[8]),"+f"(d[9]),"+f"(d[10]),"+f"(d[11]),"+f"(d[12]),"+f"(d[13]),"+f"(d[14]),"+f"(d[15]),"+f"(d[16]),"+f"(d[17]),"+f"(d[18]),"+f"(d[19]),"+f"(d[20]),"+f"(d[21]),"+f"(d[22]),"+f"(d[23]),"+f"(d[24]),"+f"(d[25]),"+f"(d[26]),"+f"(d[27]),"+f"(d[28]),"+f"(d[29]),"+f"(d[30]),"+f"(d[31]),"+f"(d[32]),"+f"(d[33]),"+f"(d[34]),"+f"(d[35]),"+f"(d[36]),"+f"(d[37]),"+f"(d[38]),"+f"(d[39]),"+f"(d[40]),"+f"(d[41]),"+f"(d[42]),"+f"(d[43]),"+f"(d[44]),"+f"(d[45]),"+f"(d[46]),"+f"(d[47]),"+f"(d[48]),"+f"(d[49]),"+f"(d[50]),"+f"(d[51]),"+f"(d[52]),"+f"(d[53]),"+f"(d[54]),"+f"(d[55]),"+f"(d[56]),"+f"(d[57]),"+f"(d[58]),"+f"(d[59]),"+f"(d[60]),"+f"(d[61]),"+f"(d[62]),"+f"(d[63]),"+f"(d[64]),"+f"(d[65]),"+f"(d[66]),"+f"(d[67]),"+f"(d[68]),"+f"(d[69]),"+f"(d[70]),"+f"(d[71]),"+f"(d[72]),"+f"(d[73]),"+f"(d[74]),"+f"(d[75]),"+f"(d[76]),"+f"(d[77]),"+f"(d[78]),"+f"(d[79]),"+f"(d[80]),"+f"(d[81]),"+f"(d[82]),"+f"(d[83]),"+f"(d[84]),"+f"(d[85]),"+f"(d[86]),"+f"(d[87]),"+f"(d[88]),"+f"(d[89]),"+f"(d[90]),"+f"(d[91]),"+f"(d[92]),"+f"(d[93]),"+f"(d[94]),"+f"(d[95])
   : "l"(da), "l"(db), "r"(scale_d), "n"(TB));
}
template<int TB>
__device__ __forceinline__ void wgmma_n160(float (&d)[80], uint64_t da, uint64_t db, int scale_d) {
  asm volatile("{\n.reg .pred p;\nsetp.ne.b32 p, %82, 0;\n"
   "wgmma.mma_async.sync.aligned.m64n160k16.f32.bf16.bf16 {%0,%1,%2,%3,%4,%5,%6,%7,%8,%9,%10,%11,%12,%13,%14,%15,%16,%17,%18,%19,%20,%21,%22,%23,%24,%25,%26,%27,%28,%29,%30,%31,%32,%33,%34,%35,%36,%37,%38,%39,%40,%41,%42,%43,%44,%45,%46,%47,%48,%49,%50,%51,%52,%53,%54,%55,%56,%57,%58,%59,%60,%61,%62,%63,%64,%65,%66,%67,%68,%69,%70,%71,%72,%73,%74,%75,%76,%77,%78,%79}, %80, %81, p, 1, 1, 0, %83;\n}"
   : "+f"(d[0]),"+f"(d[1]),"+f"(d[2]),"+f"(d[3]),"+f"(d[4]),"+f"(d[5]),"+f"(d[6]),"+f"(d[7]),"+f"(d[8]),"+f"(d[9]),"+f"(d[10]),"+f"(d[11]),"+f"(d[12]),"+f"(d[13]),"+f"(d[14]),"+f"(d[15]),"+f"(d[16]),"+f"(d[17]),"+f"(d[18]),"+f"(d[19]),"+f"(d[20]),"+f"(d[21]),"+f"(d[22]),"+f"(d[23]),"+f"(d[24]),"+f"(d[25]),"+f"(d[26]),"+f"(d[27]),"+f"(d[28]),"+f"(d[29]),"+f"(d[30]),"+f"(d[31]),"+f"(d[32]),"+f"(d[33]),"+f"(d[34]),"+f"(d[35]),"+f"(d[36]),"+f"(d[37]),"+f"(d[38]),"+f"(d[39]),"+f"(d[40]),"+f"(d[41]),"+f"(d[42]),"+f"(d[43]),"+f"(d[44]),"+f"(d[45]),"+f"(d[46]),"+f"(d[47]),"+f"(d[48]),"+f"(d[49]),"+f"(d[50]),"+f"(d[51]),"+f"(d[52]),"+f"(d[53]),"+f"(d[54]),"+f"(d[55]),"+f"(d[56]),"+f"(d[57]),"+f"(d[58]),"+f"(d[59]),"+f"(d[60]),"+f"(d[61]),"+f"(d[62]),"+f"(d[63]),"+f"(d[64]),"+f"(d[65]),"+f"(d[66]),"+f"(d[67]),"+f"(d[68]),"+f"(d[69]),"+f"(d[70]),"+f"(d[71]),"+f"(d[72]),"+f"(d[73]),"+f"(d[74]),"+f"(d[75]),"+f"(d[76]),"+f"(d[77]),"+f"(d[78]),"+f"(d[79])
   : "l"(da), "l"(db), "r"(scale_d), "n"(TB));
}
template<int TB>
__device__ __forceinline__ void wgmma_n96(float (&d)[48], uint64_t da, uint64_t db, int scale_d) {
  asm volatile("{\n.reg .pred p;\nsetp.ne.b32 p, %50, 0;\n"
   "wgmma.mma_async.sync.aligned.m64n96k16.f32.bf16.bf16 {%0,%1,%2,%3,%4,%5,%6,%7,%8,%9,%10,%11,%12,%13,%14,%15,%16,%17,%18,%19,%20,%21,%22,%23,%24,%25,%26,%27,%28,%29,%30,%31,%32,%33,%34,%35,%36,%37,%38,%39,%40,%41,%42,%43,%44,%45,%46,%47}, %48, %49, p, 1, 1, 0, %51;\n}"
   : "+f"(d[0]),"+f"(d[1]),"+f"(d[2]),"+f"(d[3]),"+f"(d[4]),"+f"(d[5]),"+f"(d[6]),"+f"(d[7]),"+f"(d[8]),"+f"(d[9]),"+f"(d[10]),"+f"(d[11]),"+f"(d[12]),"+f"(d[13]),"+f"(d[14]),"+f"(d[15]),"+f"(d[16]),"+f"(d[17]),"+f"(d[18]),"+f"(d[19]),"+f"(d[20]),"+f"(d[21]),"+f"(d[22]),"+f"(d[23]),"+f"(d[24]),"+f"(d[25]),"+f"(d[26]),"+f"(d[27]),"+f"(d[28]),"+f"(d[29]),"+f"(d[30]),"+f"(d[31]),"+f"(d[32]),"+f"(d[33]),"+f"(d[34]),"+f"(d[35]),"+f"(d[36]),"+f"(d[37]),"+f"(d[38]),"+f"(d[39]),"+f"(d[40]),"+f"(d[41]),"+f"(d[42]),"+f"(d[43]),"+f"(d[44]),"+f"(d[45]),"+f"(d[46]),"+f"(d[47])
   : "l"(da), "l"(db), "r"(scale_d), "n"(TB));
}

template<int N, int TB>
__device__ __forceinline__ void wgmma_n(float (&d)[N / 2], uint64_t da, uint64_t db) {
  if constexpr (N == 192) wgmma_n192<TB>(d, da, db, 1);
  else if constexpr (N == 160) wgmma_n160<TB>(d, da, db, 1);
  else wgmma_n96<TB>(d, da, db, 1);
}

template<int R>
__device__ __forceinline__ void pin(float (&acc)[2][R]) {
  #pragma unroll
  for (int mi = 0; mi < 2; mi++)
    #pragma unroll
    for (int i = 0; i < R; i++) asm volatile("" : "+f"(acc[mi][i]) :: "memory");
}
template<int R>
__device__ __forceinline__ void zero(float (&acc)[2][R]) {
  #pragma unroll
  for (int i = 0; i < R; i++) { acc[0][i] = 0.f; acc[1][i] = 0.f; }
  pin(acc);
}

template<int N, int TB, bool CONT, int ORD_BAR>
__device__ __forceinline__ void mainloop(float (&acc)[2][N / 2], uint32_t sbase, int grp, int g0, int nk) {
  const uint32_t full0 = sbase + BAR_OFF, empty0 = full0 + 8 * MAXST, ring = sbase + RING_OFF;
  const int nst = grp == 0 ? NST_A : NST_B, total = grp == 0 ? KB_A : KB_B;
  const uint32_t sstep = (grp == 0 ? STAGE_A : STAGE_B) >> 4;
  const int t = threadIdx.x & 127;
  const uint32_t da0 = ((ring & 0x3FFFF) >> 4) | 0x10000u;
  const uint32_t db0 = (((ring + A_BYTES) & 0x3FFFF) >> 4) | ((TB == 2 ? 256u : TB ? 512u : 1u) << 16);
  constexpr uint32_t HI_A = 0x40000040u, HI_B = TB == 2 ? 0x80000020u : 0x40000040u;
  int s = g0 % nst, ph = (g0 / nst) & 1, ps = s == 0 ? nst - 1 : s - 1;
  #pragma unroll 1
  for (int g = g0; g < g0 + nk; g++) {
    const uint32_t so = s * sstep;
    mbar_wait(full0 + 8 * s, ph);
    wgmma_fence();
    #pragma unroll
    for (int k = 0; k < 4; k++) {
      const uint64_t db = desc64(db0 + so + (TB == 2 ? k * 64 : TB ? k * 128 : k * 2), HI_B);
      wgmma_n<N, TB != 0>(acc[0], desc64(da0 + so + k * 2, HI_A), db);
      wgmma_n<N, TB != 0>(acc[1], desc64(da0 + so + 512 + k * 2, HI_A), db);
    }
    wgmma_commit();
    if (ORD_BAR != 0 && g == g0 + nk - 1) bar_arrive<ORD_BAR>(256);
    wgmma_wait<1>();
    if (t < 2 && (CONT || g > g0) && g - 1 + nst < total) mbar_arrive_cluster(empty0 + 8 * ps, t);
    ps = s;
    if (++s == nst) { s = 0; ph ^= 1; }
  }
}
template<int R>
__device__ __forceinline__ void drain(float (&acc)[2][R], uint32_t sbase, int grp, int glast) {
  wgmma_wait<0>();
  pin(acc);
  const int t = threadIdx.x & 127;
  const int nst = grp == 0 ? NST_A : NST_B, total = grp == 0 ? KB_A : KB_B;
  if (t < 2 && glast + nst < total) mbar_arrive_cluster(sbase + BAR_OFF + 8 * MAXST + 8 * (glast % nst), t);
}

__device__ __forceinline__ void set_flag(int slot, int byte, unsigned epoch) {
  asm volatile("st.relaxed.gpu.global.u8 [%0], %1;" :: "l"(g_flags + slot * 256 + byte), "r"(epoch & 255u) : "memory");
}
__device__ __forceinline__ unsigned get_flag(int slot, int byte) {
  unsigned v; asm volatile("ld.relaxed.gpu.global.u8 %0, [%1];" : "=r"(v) : "l"(g_flags + slot * 256 + byte) : "memory"); return v;
}
__device__ __forceinline__ void publish(int slot, int byte, unsigned epoch) {
  asm volatile("fence.acq_rel.gpu;" ::: "memory");
  set_flag(slot, byte, epoch);
}

__device__ __forceinline__ float sum8(uint4 v) {
  return ((bf_lo(v.x) + bf_hi(v.x)) + (bf_lo(v.y) + bf_hi(v.y))) + ((bf_lo(v.z) + bf_hi(v.z)) + (bf_lo(v.w) + bf_hi(v.w)));
}
__device__ __forceinline__ uint4 ldg128(const void* p) {
  uint4 v; asm volatile("ld.global.nc.v4.u32 {%0,%1,%2,%3}, [%4];" : "=r"(v.x), "=r"(v.y), "=r"(v.z), "=r"(v.w) : "l"(p)); return v;
}
__device__ __forceinline__ void ln_load(const bf16* __restrict__ x, int cta, uint4 (&rv)[5]) {
  const int t = threadIdx.x - 128, row = cta * 16 + (t >> 4), c = t & 15;
  #pragma unroll
  for (int j = 0; j < 5; j++) rv[j] = ldg128(reinterpret_cast<const uint4*>(x + (size_t)row * DM) + c + 16 * j);
}
__device__ __forceinline__ void ln_rows(const uint4 (&rv)[5], uint32_t buf, int cta, unsigned epoch) {
  const int t = threadIdx.x - 128, row = cta * 16 + (t >> 4), c = t & 15;
  const float sh = __shfl_sync(0xffffffffu, bf_lo(rv[0].x), t & 16);
  float d[40], s = 0.f, q = 0.f;
  #pragma unroll
  for (int j = 0; j < 5; j++) {
    const uint32_t u[4] = {rv[j].x, rv[j].y, rv[j].z, rv[j].w};
    #pragma unroll
    for (int e = 0; e < 4; e++) {
      const float d0 = bf_lo(u[e]) - sh, d1 = bf_hi(u[e]) - sh;
      d[j * 8 + e * 2] = d0; d[j * 8 + e * 2 + 1] = d1;
      s += d0 + d1; q = fmaf(d0, d0, q); q = fmaf(d1, d1, q);
    }
  }
  #pragma unroll
  for (int o = 1; o < 16; o <<= 1) { s += __shfl_xor_sync(0xffffffffu, s, o); q += __shfl_xor_sync(0xffffffffu, q, o); }
  const float md = s * (1.f / DM);
  const float r = rsqrtf(fmaxf(fmaf(q, 1.f / DM, -md * md), 0.f) + LN_EPS), o = -md * r;
  if (c == 0) st_vol2(&g_xstat[row], __float_as_uint(r), (__float_as_uint(-(md + sh) * r) & ~255u) | (epoch & 255u));
  #pragma unroll
  for (int j = 0; j < 5; j++) {
    const float* a = &d[j * 8];
    sts128(buf + (t >> 4) * 1280 + (c + 16 * j) * 16,
           pack_bf16(fmaf(a[0], r, o), fmaf(a[1], r, o)), pack_bf16(fmaf(a[2], r, o), fmaf(a[3], r, o)),
           pack_bf16(fmaf(a[4], r, o), fmaf(a[5], r, o)), pack_bf16(fmaf(a[6], r, o), fmaf(a[7], r, o)));
  }
  fence_async_smem();
  bar_arrive<BAR_LN>(288);
}
__device__ __forceinline__ void colsum_part(const bf16* __restrict__ win, int cta, unsigned epoch) {
  const int t = threadIdx.x & 127, w = t >> 5, l = t & 31;
  const int cj = min(cta, 119), cg = cj % 24, rg = cj / 24;
  uint4 cv[4];
  #pragma unroll
  for (int j = 0; j < 4; j++) cv[j] = ldg128(reinterpret_cast<const uint4*>(win + (size_t)(rg * 128 + w * 32 + j * 8 + (l >> 2)) * FF + FH + cg * 32) + (l & 3));
  float v[8];
  v[0] = (bf_lo(cv[0].x) + bf_lo(cv[1].x)) + (bf_lo(cv[2].x) + bf_lo(cv[3].x)); v[1] = (bf_hi(cv[0].x) + bf_hi(cv[1].x)) + (bf_hi(cv[2].x) + bf_hi(cv[3].x));
  v[2] = (bf_lo(cv[0].y) + bf_lo(cv[1].y)) + (bf_lo(cv[2].y) + bf_lo(cv[3].y)); v[3] = (bf_hi(cv[0].y) + bf_hi(cv[1].y)) + (bf_hi(cv[2].y) + bf_hi(cv[3].y));
  v[4] = (bf_lo(cv[0].z) + bf_lo(cv[1].z)) + (bf_lo(cv[2].z) + bf_lo(cv[3].z)); v[5] = (bf_hi(cv[0].z) + bf_hi(cv[1].z)) + (bf_hi(cv[2].z) + bf_hi(cv[3].z));
  v[6] = (bf_lo(cv[0].w) + bf_lo(cv[1].w)) + (bf_lo(cv[2].w) + bf_lo(cv[3].w)); v[7] = (bf_hi(cv[0].w) + bf_hi(cv[1].w)) + (bf_hi(cv[2].w) + bf_hi(cv[3].w));
  #pragma unroll
  for (int st = 0; st < 3; st++) {
    const int n = 4 >> st;
    const bool up = (l & (4 * n)) != 0;
    #pragma unroll
    for (int e = 0; e < 4; e++)
      if (e < n) { const float keep = up ? v[e + n] : v[e], send = up ? v[e] : v[e + n]; v[e] = keep + __shfl_xor_sync(0xffffffffu, send, 4 * n); }
  }
  float* red = reinterpret_cast<float*>(smem + RED_OFF);
  red[w * 32 + (l & 3) * 8 + (l >> 2)] = v[0];
  bar_sync<BAR_WG2>(128);
  if (t < 32) st_vol2(&g_csum[rg * FH + cg * 32 + t], __float_as_uint((red[t] + red[32 + t]) + (red[64 + t] + red[96 + t])), epoch);
}

__device__ __forceinline__ void a_entry(int g, int grp, int rb, int& mi, int& kb) {
  if (g < 10) { mi = M_X; kb = g; }
  else if (g < 20) { mi = M_XN; kb = g - 10; }
  else if (grp == 0) {
    if (g < 52) { mi = M_WSP; kb = (g - 20); }
    else if (g < 52 + NX) { mi = M_WSIM; kb = g - 52 + 32 - NX; }
    else { mi = M_H; kb = g - 52 - NX; }
  } else {
    if (g < 30) { mi = M_XN; kb = g - 20; }
    else if (g < 62) { mi = M_WSRE; kb = (g - 30); }
    else { mi = M_WSIM; kb = g - 62; }
  }
}

__global__ void __cluster_dims__(2, 1, 1) __launch_bounds__(384, 1)
fused_kernel(const __grid_constant__ Maps maps, const bf16* __restrict__ x, const bf16* __restrict__ win, const bf16* __restrict__ bsp,
             const bf16* __restrict__ wdre, const bf16* __restrict__ wdim, bf16* __restrict__ out) {
  const uint32_t sbase = smem_u32(smem);
  const uint32_t full0 = sbase + BAR_OFF, empty0 = full0 + 8 * MAXST, dep0 = empty0 + 8 * MAXST, ring = sbase + RING_OFF;
  const int tid = threadIdx.x, wg = __shfl_sync(0xffffffffu, tid >> 7, 0);
  const int rank = blockIdx.x & 1;
  const int grp = (blockIdx.x >> 1) & 1, half = (blockIdx.x >> 2) & 1, rb = blockIdx.x >> 3;
  const int ct = half * 2 + rank, c8 = grp * 4 + ct;
  const int cta = rb * 8 + half * 4 + grp * 2 + rank;
  const int total = grp == 0 ? KB_A : KB_B;
  const uint32_t stage_bytes = grp == 0 ? STAGE_A : STAGE_B;
  const int nst = grp == 0 ? NST_A : NST_B;
  const uint32_t buf = ring + nst * stage_bytes;

  uint4 rv[5];
  if (wg != 0) ln_load(x, cta, rv);
  if (wg == 2) {
    const int t = tid & 127;
    if (t < 60) asm volatile("prefetch.global.L2 [%0];" :: "l"(win + (size_t)(cta * 5 + t / 12) * FF + FH + (t % 12) * 64));
  }
  const unsigned epoch = (ld_relaxed(&g_done) >> 7) + 1u;
  if (tid == 0) {
    TS(0, 0);
    for (int s = 0; s < MAXST; s++) { mbar_init(full0 + 8 * s, 2); mbar_init(empty0 + 8 * s, 2); }
    for (int s = 0; s < 5; s++) mbar_init(dep0 + 8 * s, 1);
    *reinterpret_cast<volatile int*>(smem + READY_OFF) = 0;
    asm volatile("fence.mbarrier_init.release.cluster;" ::: "memory");
  }
  __syncthreads();
  asm volatile("barrier.cluster.arrive.relaxed.aligned;" ::: "memory");

  if (wg == 0) {
    asm volatile("setmaxnreg.dec.sync.aligned.u32 40;");
    const int warp = tid >> 5, lane = tid & 31;
    if (warp == 0) {
      const int row = rb * 128;
      if (lane == 0) {
        for (int g = 0; g < nst; g++) {
          mbar_expect_tx(full0 + 8 * g, A_BYTES);
          tma_load_2d(ring + g * stage_bytes, &maps.m[M_X], full0 + 8 * g, g * 64, row);
          tma_load_2d(ring + g * stage_bytes + 8192, &maps.m[M_X], full0 + 8 * g, g * 64, row + 64);
        }
      }
      __syncwarp();
      cluster_wait();
      if (lane == 0) {
        int s = 0, ph = 0;
        #pragma unroll 1
        for (int g = nst; g < total; g++) {
          int mi, kb;
          a_entry(g, grp, rb, mi, kb);
          if (g == 10 || (mi == M_H && kb == 0)) { TS(0, g > 10 ? 3 : 1); mbar_wait(dep0 + (g > 10 ? 24 : 0), 0); fence_async_global(); TS(0, g > 10 ? 4 : 2); }
          mbar_wait(empty0 + 8 * s, ph);
          mbar_expect_tx(full0 + 8 * s, A_BYTES);
          tma_load_2d_mc(ring + s * stage_bytes + rank * 8192, &maps.m[mi], full0 + 8 * s, kb * 64, row + rank * 64, 3);
          if (++s == nst) { s = 0; ph ^= 1; }
          if (g + PF_D < total) {
            a_entry(g + PF_D, grp, rb, mi, kb);
            if (mi >= M_WSRE && mi <= M_WSP && PF_COND)
              asm volatile("cp.async.bulk.prefetch.tensor.2d.L2.global.tile [%0, {%1, %2}];" :: "l"((uint64_t)&maps.m[mi]), "r"(kb * 64), "r"(row + rank * 64) : "memory");
          }
        }
        TS(0, 5);
      }
    } else if (warp == 1) {
      if (lane == 0) {
        int s = 0, ph = 1;
        int have = 0;
        #pragma unroll 1
        for (int g = 0; g < total; g++) {
          int kind = 1, mi, kb, c, dep = 0, need = 0;
          uint32_t bytes = 20480;

          if (g < 10) { kind = 0; mi = M_WIN32; kb = g; c = 24 + 3 * c8; bytes = 12288; }
          else if (grp == 0) {
            if (g < 20) { kind = 0; mi = M_WIN3; kb = g - 10; c = 3 * ct; bytes = 24576; }
            else if (g < 52) { kind = 0; mi = M_Z23; kb = (g - 20); c = 3 * ct; bytes = 24576; need = ((g - 20) >> 1) + 1; }
            else if (g < 52 + NX) { mi = M_AB; kb = g - 52 + 32 - NX; c = DM + ct * 160; dep = g == 52 ? 2 : 0; }

            else { kind = 0; mi = M_WOUT; kb = g - 52 - NX; c = ct * 5; }
          } else {
            if (g < 30) { mi = g < 20 ? M_WDRE : M_WDIM; kb = g < 20 ? g - 10 : g - 20; c = ct * 160; }
            else if (g < 62) { mi = M_AB; kb = (g - 30); c = ct * 160; need = ((g - 30) >> 1) + 1; }
            else { mi = M_AB; kb = g - 62; c = ct * 160 + DM; dep = g == 62 ? 2 : 0; }
          }
          if (need > have) {
            if (need == 1) TS(1, 0);
            unsigned it = 0;
            while ((have = *reinterpret_cast<volatile int*>(smem + READY_OFF)) < need && ++it < 50 * POLL_LIMIT) {}
            fence_async_global();
            if (need == 1) { TS(1, 1); TC(1); }
          }
          if (dep) { TS(1, dep * 2 - 2); mbar_wait(dep0 + 8 * dep, 0); fence_async_global(); TS(1, dep * 2 - 1); TC(dep); }
          const uint32_t dst = ring + s * stage_bytes + A_BYTES, fb = full0 + 8 * s;
          mbar_wait(empty0 + 8 * s, ph);
          if (++s == nst) { s = 0; ph ^= 1; }
          mbar_expect_tx(fb, bytes);
          if (kind == 0) tma_load_3d(dst, &maps.m[mi], fb, 0, kb * 64, c);
          else if (kind == 1) tma_load_2d(dst, &maps.m[mi], fb, kb * 64, c);
          else {
            #pragma unroll 1
            for (uint32_t o = 0; o < bytes; o += 8192) tma_load_2d(dst + o, &maps.m[mi], fb, c + (o >> 7), kb * 64);
          }
        }
      }
      __syncwarp();
      cluster_wait();
    } else if (warp == 2) {
      if (lane < M_COUNT) asm volatile("prefetch.tensormap [%0];" :: "l"((uint64_t)&maps.m[lane]) : "memory");
      cluster_wait();
      {
        unsigned it = 0;
        uint2 v[4];
        while (true) {
          bool ok = true;
          #pragma unroll
          for (int i = 0; i < 4; i++) { v[i] = ld_vol2(&g_xstat[rb * 128 + i * 32 + lane]); ok = ok && ((v[i].y ^ epoch) & 255u) == 0; }
          if (ok || ++it > POLL_LIMIT) break;
          __nanosleep(POLL_NS);
        }
        #pragma unroll
        for (int i = 0; i < 4; i++) reinterpret_cast<uint2*>(smem + ROWSTAT_OFF)[i * 32 + lane] = make_uint2(v[i].x, v[i].y & ~255u);
        __syncwarp();
        TS(0, 6);
        bar_arrive<BAR_STATS>(192);
      }
      #pragma unroll 1
      for (int d = 0; d < 5; d++) {
        if (d == 3 && grp == 1) continue;
        const int slot = d == 0 ? F_XN + rb : d == 4 ? F_Y + rb * 4 + ct : d == 3 ? F_H + rb : d == 2 ? F_B + ct : grp == 0 ? F_Z + ct : F_A + ct;
        const int byte = d == 0 ? lane & 7 : d == 4 ? 0 : d == 3 ? lane & 3 : (d == 1 && grp == 0) ? lane : lane >> 1;
        unsigned it = 0, m;
        while ((m = __ballot_sync(0xffffffffu, get_flag(slot, byte) != (epoch & 255u))) != 0 && ++it < POLL_LIMIT) {
          if (d == 1 && lane == 0) *reinterpret_cast<volatile int*>(smem + READY_OFF) = (__ffs(m) - 1) >> 1;
          __nanosleep(WATCH_NS);
        }
        if (d == 1 && lane == 0) *reinterpret_cast<volatile int*>(smem + READY_OFF) = 16;
        if (d < 4) TS(0, 8 + d * 2); else TS(0, 7);
        fence_async_global();
        __syncwarp();
        if (lane == 0 && d != 1) mbar_arrive(dep0 + 8 * d);
      }
    } else {
      cluster_wait();
      bar_sync<BAR_LN>(288);
      if (lane == 0) {
        TS(1, 5);
        asm volatile("cp.async.bulk.global.shared::cta.bulk_group [%0], [%1], 20480;" :: "l"(g_xn + (size_t)cta * 16 * DM), "r"(buf) : "memory");
        bulk_commit();
        bulk_wait_all();
        set_flag(F_XN + rb, cta & 7, epoch);
        TS(1, 6);
      }
      __syncwarp();
      {
        unsigned it = 0;
        while (true) {
          bool ok = true;
          uint2 u[15];
          #pragma unroll
          for (int i = 0; i < 15; i++) u[i] = ld_vol2(&g_csum[(i % 5) * FH + c8 * 96 + (i / 5) * 32 + lane]);
          #pragma unroll
          for (int i = 0; i < 15; i++) ok = ok && u[i].y == epoch;
          #pragma unroll
          for (int i = 0; i < 3; i++)
            reinterpret_cast<float*>(smem + COLSUM_OFF)[i * 32 + lane] = ((__uint_as_float(u[i * 5].x) + __uint_as_float(u[i * 5 + 1].x)) +
                (__uint_as_float(u[i * 5 + 2].x) + __uint_as_float(u[i * 5 + 3].x))) + __uint_as_float(u[i * 5 + 4].x);
          if (ok || ++it > POLL_LIMIT) break;
          __nanosleep(POLL_NS);
        }
      }
      __syncwarp();
      TS(1, 4);
      bar_arrive<BAR_STATS>(192);
      bar_sync<BAR_PUB1>(160);
      if (lane == 0) {
        TS(1, 7);
        tma_store_3d(&maps.m[M_Z232], buf, 0, rb * 128, 3 * c8);
        bulk_commit();
        bulk_wait_all();
        set_flag(F_Z + (c8 >> 1), rb * 2 + (c8 & 1), epoch);
        TS(1, 8);
      }
      __syncwarp();
      bar_arrive<BAR_BUF>(160);
      if (grp == 1) {
        bar_sync<BAR_PUB2>(160);
        if (lane == 0) set_flag(F_A + ct, rb, epoch);
        TS(1, 9);
        __syncwarp();
      }
      bar_sync<BAR_PUB1>(160);
      if (lane == 0) set_flag(grp == 0 ? F_H + rb : F_B + ct, grp == 0 ? ct : rb, epoch);
      TS(1, 10);
      __syncwarp();
      bar_arrive<BAR_BUF>(160);
    }
  } else {
    asm volatile("setmaxnreg.inc.sync.aligned.u32 232;");
    const int t = tid & 127, w = t >> 5, l = t & 31;
    ln_rows(rv, buf, cta, epoch);
    if (wg == 2) {
      const bf16* p = t < 60 ? win + (size_t)(cta * 5 + t / 12) * FF + (t % 12) * 64
                             : (t < 110 ? wdre : wdim) + (size_t)cta * 5 * DM + ((t - 60) % 50) * 64;
      asm volatile("prefetch.global.L2 [%0];" :: "l"(p));
      if (t < 32) asm volatile("prefetch.global.L2 [%0];" :: "l"(wdim + (size_t)cta * 5 * DM + (18 + t) * 64));
      colsum_part(win, cta, epoch);
    }
    TS(wg + 1, 0);
    cluster_wait();
    const int rl = w * 16 + ((l >> 3) & 1) * 8 + (l & 7);
    const int gr = w * 16 + (l & 15);
    const uint32_t st_base = buf + rl * 128;
    const uint32_t st_x = ((l >> 4) ^ (l & 7)) << 4;
    if (wg == 1) {
      float acc[2][48];
      zero(acc);
      mainloop<96, Z2SW ? 1 : 2, false, BAR_ORD1>(acc, sbase, grp, 0, 10);
      drain(acc, sbase, grp, 9);
      TS(2, 2);
      bar_sync<BAR_STATS>(192);
      const float2* rs = reinterpret_cast<const float2*>(smem + ROWSTAT_OFF) + w * 16 + (l >> 2);
      const float2* cs = reinterpret_cast<const float2*>(smem + COLSUM_OFF) + (l & 3);
      float sum[4], sq[4];
      #pragma unroll
      for (int r = 0; r < 4; r++) {
        const float2 st = rs[(r >> 1) * 64 + (r & 1) * 8];
        float s0 = 0.f, q0 = 0.f;
        #pragma unroll
        for (int j = 0; j < 12; j++) {
          const float2 c = cs[j * 4];
          float* a = &acc[r >> 1][4 * j + (r & 1) * 2];
          a[0] = gelu_tanh(fmaf(a[0], st.x, st.y * c.x));
          a[1] = gelu_tanh(fmaf(a[1], st.x, st.y * c.y));
          s0 += a[0] + a[1]; q0 = fmaf(a[0], a[0], q0); q0 = fmaf(a[1], a[1], q0);
        }
        s0 += __shfl_xor_sync(0xffffffffu, s0, 1); q0 += __shfl_xor_sync(0xffffffffu, q0, 1);
        s0 += __shfl_xor_sync(0xffffffffu, s0, 2); q0 += __shfl_xor_sync(0xffffffffu, q0, 2);
        sum[r] = s0; sq[r] = q0;
      }
      TS(2, 4);
      float rstd, off;
      {
        const int qd = l & 3;
        const float sm = qd == 0 ? sum[0] : qd == 1 ? sum[1] : qd == 2 ? sum[2] : sum[3];
        const float sv = qd == 0 ? sq[0] : qd == 1 ? sq[1] : qd == 2 ? sq[2] : sq[3];
        const int row = (qd >> 1) * 64 + w * 16 + (qd & 1) * 8 + (l >> 2);
        const float mu = sm * (1.f / 96), m2 = fmaxf(sv - sm * mu, 0.f);
        st_vol2(&g_zstat[(rb * 8 + c8) * 128 + row], __float_as_uint(mu), (__float_as_uint(m2) & ~255u) | (epoch & 255u));
        uint2 v[7];
        unsigned n = 0;
        while (true) {
          bool ok = true;
          #pragma unroll
          for (int j = 0; j < 7; j++) v[j] = ld_vol2(&g_zstat[(rb * 8 + ((c8 + 1 + j) & 7)) * 128 + row]);
          #pragma unroll
          for (int j = 0; j < 7; j++) ok = ok && ((v[j].y ^ epoch) & 255u) == 0;
          if (ok || ++n > POLL_LIMIT) break;
          __nanosleep(POLL_NS);
        }
        float mean = mu, var = m2;
        #pragma unroll
        for (int j = 0; j < 7; j++) { mean += __uint_as_float(v[j].x); var += __uint_as_float(v[j].y & ~255u); }
        mean *= 0.125f;
        float d = (mu - mean) * (mu - mean);
        #pragma unroll
        for (int j = 0; j < 7; j++) d = fmaf(__uint_as_float(v[j].x) - mean, __uint_as_float(v[j].x) - mean, d);
        rstd = rsqrtf(fmaf(96.f, d, var) * (1.f / FH) + LN_EPS); off = -mean * rstd;
        __syncwarp();
      }
      TS(2, 5);
      #pragma unroll
      for (int mi = 0; mi < 2; mi++) {
        const float r0 = __shfl_sync(0xffffffffu, rstd, (l & 28) + mi * 2), o0 = __shfl_sync(0xffffffffu, off, (l & 28) + mi * 2);
        const float r1 = __shfl_sync(0xffffffffu, rstd, (l & 28) + mi * 2 + 1), o1 = __shfl_sync(0xffffffffu, off, (l & 28) + mi * 2 + 1);
        #pragma unroll
        for (int jj = 0; jj < 6; jj++) {
          const float* a = &acc[mi][8 * jj];
          stsm4(buf + (jj >> 1) * 8192 + mi * 4096 + rl * 64 + ((((jj & 1) * 2 + (l >> 4)) ^ ((l >> 1) & 3)) << 4),
                pack_bf16(fmaf(a[0], r0, o0), fmaf(a[1], r0, o0)), pack_bf16(fmaf(a[2], r1, o1), fmaf(a[3], r1, o1)),
                pack_bf16(fmaf(a[4], r0, o0), fmaf(a[5], r0, o0)), pack_bf16(fmaf(a[6], r1, o1), fmaf(a[7], r1, o1)));
        }
      }
      fence_async_smem();
      bar_arrive<BAR_PUB1>(160);
      TS(2, 6);
      if (grp == 0) {
        float acc[2][96];
        {
          const bf16* bp = bsp + rb * 128 + w * 16 + (l >> 2);
          const float bb[4] = {__bfloat162float(bp[0]), __bfloat162float(bp[8]), __bfloat162float(bp[64]), __bfloat162float(bp[72])};
          #pragma unroll
          for (int i = 0; i < 96; i++) { acc[0][i] = bb[(i >> 1) & 1]; acc[1][i] = bb[2 + ((i >> 1) & 1)]; }
          pin(acc);
        }
        bar_sync<BAR_ORD2>(256);
        mainloop<192, 1, false, BAR_ORD1>(acc, sbase, 0, 20, 32);
        bar_sync<BAR_Z1>(256);
        drain(acc, sbase, 0, 51);
        TS(2, 7);
        {
          uint32_t z[2][4][4];
          #pragma unroll
          for (int i = 0; i < 4; i++) ldsm4(st_base + (st_x ^ (i << 5)), z[0][i][0], z[0][i][1], z[0][i][2], z[0][i][3]);
          #pragma unroll
          for (int bx = 0; bx < 6; bx++) {
            if (bx < 5) {
              #pragma unroll
              for (int i = 0; i < 4; i++)
                ldsm4(st_base + (bx + 1) * 8192 + (st_x ^ (i << 5)), z[(bx + 1) & 1][i][0], z[(bx + 1) & 1][i][1], z[(bx + 1) & 1][i][2], z[(bx + 1) & 1][i][3]);
            }
            #pragma unroll
            for (int i = 0; i < 4; i++) {
              const float* a = &acc[bx / 3][8 * ((bx % 3) * 4 + i)];
              const uint32_t* zz = z[bx & 1][i];
              stsm4(st_base + bx * 8192 + (st_x ^ (i << 5)),
                    hmul2_bf16(zz[0], pack_bf16(a[0], a[1])), hmul2_bf16(zz[1], pack_bf16(a[2], a[3])),
                    hmul2_bf16(zz[2], pack_bf16(a[4], a[5])), hmul2_bf16(zz[3], pack_bf16(a[6], a[7])));
            }
            if (bx % 3 == 2) {
              fence_async_smem();
              __syncwarp();
              if (l < 3) {
                tma_store_2d(&maps.m[M_HS], buf + (bx - 2 + l) * 8192 + w * 2048, ct * 192 + l * 64, rb * 128 + (bx / 3) * 64 + w * 16);
                bulk_commit();
              }
            }
          }
        }
        TS(2, 8);
        if (l < 3) bulk_wait_all();
        __syncwarp();
        bar_arrive<BAR_PUB1>(160);
        TS(2, 9);
        return;
      }
    } else {
      if (grp == 0) {
        float acc[2][96];
        zero(acc);
        bar_sync<BAR_ORD1>(256);
        mainloop<192, 1, false, BAR_ORD2>(acc, sbase, 0, 10, 10);
        drain(acc, sbase, 0, 19);
        TS(3, 2);
        bar_sync<BAR_BUF>(160);
        #pragma unroll
        for (int mi = 0; mi < 2; mi++)
          #pragma unroll
          for (int jj = 0; jj < 12; jj++) {
            const float* a = &acc[mi][8 * jj];
            stsm4(st_base + mi * 24576 + (jj >> 2) * 8192 + (st_x ^ ((jj & 3) << 5)),
                  pack_bf16(a[0], a[1]), pack_bf16(a[2], a[3]), pack_bf16(a[4], a[5]), pack_bf16(a[6], a[7]));
          }
        __syncwarp();
        TS(3, 3);
        const uint32_t rbase = buf + (l >> 4) * 24576 + gr * 128;
        #pragma unroll 1
        for (int c2 = 0; c2 < 12; c2++) {
          const uint32_t ab = rbase + (c2 >> 2) * 8192;
          uint4 v[2];
          #pragma unroll
          for (int i = 0; i < 2; i++) v[i] = lds128(ab + (((((c2 & 3) * 2 + i) ^ l) & 7) << 4));
          #pragma unroll
          for (int i = 0; i < 2; i++)
            sts128(ab + (((((c2 & 3) * 2 + i) ^ l) & 7) << 4),
                   pack_bf16(gelu_tanh(bf_lo(v[i].x)), gelu_tanh(bf_hi(v[i].x))), pack_bf16(gelu_tanh(bf_lo(v[i].y)), gelu_tanh(bf_hi(v[i].y))),
                   pack_bf16(gelu_tanh(bf_lo(v[i].z)), gelu_tanh(bf_hi(v[i].z))), pack_bf16(gelu_tanh(bf_lo(v[i].w)), gelu_tanh(bf_hi(v[i].w))));
        }
        TS(3, 4);
        bar_arrive<BAR_Z1>(256);
      }
    }
    float acc[2][80];
    if (grp == 1) {
      zero(acc);
      if (wg == 2) {
        bar_sync<BAR_ORD1>(256);
        mainloop<160, 0, false, BAR_ORD2>(acc, sbase, 1, 10, 10);
      } else {
        bar_sync<BAR_ORD2>(256);
        mainloop<160, 0, false, BAR_ORD1>(acc, sbase, 1, 20, 10);
      }
      drain(acc, sbase, 1, wg == 2 ? 19 : 29);
      TS(wg + 1, wg == 1 ? 7 : 2);
      if (wg == 1) bar_sync<BAR_Z1>(256); else bar_sync<BAR_BUF>(160);
      const uint32_t sg = wg == 1 ? 0x80008000u : 0u;
      const uint32_t tb = buf + ((l >> 4) * 8 + (l & 7)) * 128 + (((w * 2 + ((l >> 3) & 1)) ^ (l & 7)) << 4);
      #pragma unroll
      for (int mi = 0; mi < 2; mi++)
        #pragma unroll
        for (int jj = 0; jj < 10; jj++) {
          const float* a = &acc[mi][8 * jj];
          stsm4_t(tb + mi * 20480 + jj * 2048, pack_bf16(a[0], a[1]) ^ sg, pack_bf16(a[2], a[3]) ^ sg, pack_bf16(a[4], a[5]) ^ sg, pack_bf16(a[6], a[7]) ^ sg);
        }
      fence_async_smem();
      if (wg == 1) bar_sync<BAR_WG1>(128); else bar_sync<BAR_WG2>(128);
      TS(wg + 1, wg == 1 ? 8 : 6);
      if (l == 0) {
        #pragma unroll 1
        for (int i = 0; i < 2; i++) {
          tma_store_2d(&maps.m[M_ABS], buf + i * 20480 + w * 5120, rb * 128 + i * 64, (2 - wg) * DM + ct * 160 + w * 40);
          bulk_commit();
        }
        bulk_wait_all();
      }
      __syncwarp();
      TS(wg + 1, wg == 1 ? 9 : 10);
      if (wg == 1) {
        bar_arrive<BAR_PUB1>(160);
        #pragma unroll 1
        for (int i = 0; i < 4; i++) {
          uint4 v[5];
          #pragma unroll
          for (int j = 0; j < 5; j++) {
            const int e = (i * 5 + j) * 128 + t;
            v[j] = ldg128(x + (size_t)(rb * 128 + e / 20) * DM + ct * 160 + (e % 20) * 8);
          }
          #pragma unroll
          for (int j = 0; j < 5; j++) {
            const int e = (i * 5 + j) * 128 + t;
            stg128(out + (size_t)(rb * 128 + e / 20) * DM + ct * 160 + (e % 20) * 8, v[j]);
          }
        }
        bar_sync<BAR_WG1>(128);
        if (t == 0) publish(F_Y + rb * 4 + ct, 0, epoch);
        return;
      }
      bar_arrive<BAR_PUB2>(160);
      bar_arrive<BAR_Z1>(256);
    }
    zero(acc);
    bar_sync<BAR_ORD1>(256);
    mainloop<160, 0, false, 0>(acc, sbase, grp, grp == 0 ? 52 : 30, grp == 0 ? NX : 64 - NX);
    if (grp == 0) mainloop<160, WOSW ? 1 : 2, true, 0>(acc, sbase, 0, 52 + NX, 12);
    const uint32_t slab = buf + w * (16 * 320);
    const uint32_t addr = slab + (((l >> 3) & 1) * 8 + (l & 7)) * 320 + (l >> 4) * 16;
    bar_sync<BAR_BUF>(160);
    mbar_wait(dep0 + 32, 0);
    drain(acc, sbase, grp, total - 1);
    TS(3, 12);
    #pragma unroll
    for (int mi = 0; mi < 2; mi++) {
      #pragma unroll
      for (int jj = 0; jj < 10; jj++) {
        const float* a = &acc[mi][8 * jj];
        stsm4(addr + mi * 20480 + jj * 32, pack_bf16(a[0], a[1]), pack_bf16(a[2], a[3]), pack_bf16(a[4], a[5]), pack_bf16(a[6], a[7]));
      }
      fence_async_smem();
      __syncwarp();
      if (l == 0) {
        tma_reduce_2d(&maps.m[M_OUT], slab + mi * 20480, ct * 160, rb * 128 + mi * 64 + w * 16);
        bulk_commit();
      }
    }
    TS(3, 13);
    if (l == 0) {
      bulk_wait_read();
      if (w == 0) atomicAdd(&g_done, 1u);
    }
    TS(3, 15);
  }
}

typedef CUresult (*EncodeFn)(CUtensorMap*, CUtensorMapDataType, cuuint32_t, void*, const cuuint64_t*, const cuuint64_t*,
                             const cuuint32_t*, const cuuint32_t*, CUtensorMapInterleave, CUtensorMapSwizzle,
                             CUtensorMapL2promotion, CUtensorMapFloatOOBfill);

void make2d(EncodeFn enc, CUtensorMap* m, const void* p, uint64_t cols, uint64_t rows, uint32_t bc, uint32_t br, bool swz = true) {
  cuuint64_t gd[2] = {cols, rows}, gs[1] = {cols * 2};
  cuuint32_t bd[2] = {bc, br}, es[2] = {1, 1};
  enc(m, CU_TENSOR_MAP_DATA_TYPE_BFLOAT16, 2, const_cast<void*>(p), gd, gs, bd, es, CU_TENSOR_MAP_INTERLEAVE_NONE,
      swz ? CU_TENSOR_MAP_SWIZZLE_128B : CU_TENSOR_MAP_SWIZZLE_NONE, PROMO, CU_TENSOR_MAP_FLOAT_OOB_FILL_NONE);
}
void make3d(EncodeFn enc, CUtensorMap* m, const void* p, uint64_t cols, uint64_t rows, uint32_t cw, uint32_t nc, uint32_t br = 64) {
  cuuint64_t gd[3] = {cw, rows, cols / cw}, gs[2] = {cols * 2, cw * 2};
  cuuint32_t bd[3] = {cw, br, nc}, es[3] = {1, 1, 1};
  enc(m, CU_TENSOR_MAP_DATA_TYPE_BFLOAT16, 3, const_cast<void*>(p), gd, gs, bd, es, CU_TENSOR_MAP_INTERLEAVE_NONE,
      cw == 64 ? CU_TENSOR_MAP_SWIZZLE_128B : CU_TENSOR_MAP_SWIZZLE_64B, PROMO, CU_TENSOR_MAP_FLOAT_OOB_FILL_NONE);
}

}

extern "C" void kernel_launch(void* const* d_in, const int* in_sizes, int n_in, void* d_out, int out_size) {
  const bf16* x = (const bf16*)d_in[0];
  const bf16* wsre = (const bf16*)d_in[1];
  const bf16* wsim = (const bf16*)d_in[2];
  const bf16* wdre = (const bf16*)d_in[3];
  const bf16* wdim = (const bf16*)d_in[4];
  const bf16* win = (const bf16*)d_in[6];
  const bf16* wsp = (const bf16*)d_in[7];
  const bf16* bsp = (const bf16*)d_in[8];
  const bf16* wout = (const bf16*)d_in[9];

  void* fn = nullptr;
  cudaDriverEntryPointQueryResult qr;
  cudaGetDriverEntryPoint("cuTensorMapEncodeTiled", &fn, cudaEnableDefault, &qr);
  EncodeFn enc = (EncodeFn)fn;
  void *abT, *z2, *h, *xn;
  cudaGetSymbolAddress(&xn, g_xn);
  cudaGetSymbolAddress(&abT, g_abT);
  cudaGetSymbolAddress(&z2, g_z2);
  cudaGetSymbolAddress(&h, g_h);

  Maps maps;
  make2d(enc, &maps.m[M_X], x, DM, SEQ, 64, 64);
  make2d(enc, &maps.m[M_XN], xn, DM, SEQ, 64, 64);
  make3d(enc, &maps.m[M_Z232], z2, FH, SEQ, 32, 3, 128);
  if (Z2SW) make2d(enc, &maps.m[M_WIN32], win, FF, DM, 64, 64); else make3d(enc, &maps.m[M_WIN32], win, FF, DM, 32, 3);
  make2d(enc, &maps.m[M_WSRE], wsre, SEQ, SEQ, 64, 64);
  make2d(enc, &maps.m[M_WSIM], wsim, SEQ, SEQ, 64, 64);
  make2d(enc, &maps.m[M_WSP], wsp, SEQ, SEQ, 64, 64);
  make2d(enc, &maps.m[M_H], h, FH, SEQ, 64, 64);
  make3d(enc, &maps.m[M_WIN3], win, FF, DM, 64, 3);
  make3d(enc, &maps.m[M_Z23], z2, FH, SEQ, 64, 3);
  make2d(enc, &maps.m[M_WDRE], wdre, DM, DM, 64, 160);
  make2d(enc, &maps.m[M_WDIM], wdim, DM, DM, 64, 160);
  make2d(enc, &maps.m[M_AB], abT, SEQ, 2 * DM, 64, 160);
  if (WOSW) make2d(enc, &maps.m[M_WOUT], wout, DM, FH, 64, 64); else make3d(enc, &maps.m[M_WOUT], wout, DM, FH, 32, 5);
  make2d(enc, &maps.m[M_HS], h, FH, SEQ, 64, 16);
  make2d(enc, &maps.m[M_ABS], abT, SEQ, 2 * DM, 64, 40);
  make2d(enc, &maps.m[M_OUT], d_out, DM, SEQ, 160, 16, false);

  cudaFuncSetAttribute(fused_kernel, cudaFuncAttributeMaxDynamicSharedMemorySize, SMEM_BYTES);
  fused_kernel<<<128, 384, SMEM_BYTES>>>(maps, x, win, bsp, wdre, wdim, (bf16*)d_out);
}
```

```cpp
#include <cuda_runtime.h>
#include <cuda_bf16.h>
#include <cuda.h>
#include <stdint.h>

namespace {

typedef __nv_bfloat16 bf16;

constexpr int SEQ = 2048, DM = 640, FF = 1536, FH = 768;
#define NXV 6
#define NOV 6
constexpr int NX = NXV;
constexpr int NO = NOV;
#define NSTB 5
#define PFB 1
constexpr int NST_A = 4, NST_B = NSTB, MAXST = 5;
constexpr int A_BYTES = 16384;
constexpr int BAR_OFF = 0;
constexpr int READY_OFF = 128;
constexpr int COLSUM_OFF = 256;
constexpr int ROWSTAT_OFF = 1024;
constexpr int ZSTAT_OFF = 2048;
constexpr int RED_OFF = 3072;
constexpr int RING_OFF = 4096;
constexpr int STAGE_A = 40960, STAGE_B = 36864;
constexpr int SMEM_BYTES = RING_OFF + 5 * STAGE_B + 40960;
constexpr int KB_A = 52 + NX + 12 - NO;
constexpr int KB_B = 84 - NX + NO;
constexpr float LN_EPS = 1e-5f;
constexpr unsigned POLL_LIMIT = 100000;
#define POLL_NS 100
#define PF_D 8
#define NORM2 1
#define Z1_NS 0
#define WATCH_NS 40

constexpr int BAR_ORD1 = 1, BAR_ORD2 = 2, BAR_WG1 = 3, BAR_WG2 = 4, BAR_LN = 5, BAR_BUF = 6, BAR_Z1 = 7, BAR_PUB1 = 8, BAR_PUB2 = 9,
              BAR_STATS = 10, BAR_U = 11;

enum { M_X, M_XN, M_WSRE, M_WSIM, M_WSP, M_H, M_WIN3, M_Z23, M_WDRE, M_WDIM, M_AB, M_WOUT, M_OUT, M_HS, M_ZS, M_ABS, M_COUNT };
struct Maps { CUtensorMap m[M_COUNT]; };

__device__ __align__(1024) bf16 g_abT[2 * DM * SEQ];
__device__ __align__(1024) bf16 g_z2[SEQ * FH];
__device__ __align__(1024) bf16 g_h[SEQ * FH];
__device__ __align__(1024) bf16 g_xn[SEQ * DM];
__device__ __align__(16) uint2 g_xstat[SEQ];
__device__ __align__(16) uint2 g_csum[5 * FH + DM];
__device__ __align__(16) uint2 g_zstat[64 * 128];
__device__ __align__(256) unsigned char g_flags[108 * 256];
constexpr int F_A = 0, F_B = 4, F_Z = 8, F_H = 12, F_XN = 28, F_Y = 44;
__device__ unsigned g_done;
#define TS(role, ev)
#define TC(i)

extern __shared__ __align__(1024) uint8_t smem[];

__device__ __forceinline__ uint32_t smem_u32(const void* p) { return (uint32_t)__cvta_generic_to_shared(p); }
__device__ __forceinline__ void mbar_init(uint32_t bar, uint32_t cnt) { asm volatile("mbarrier.init.shared::cta.b64 [%0], %1;" :: "r"(bar), "r"(cnt)); }
__device__ __forceinline__ void mbar_expect_tx(uint32_t bar, uint32_t bytes) { asm volatile("mbarrier.arrive.expect_tx.shared::cta.b64 _, [%0], %1;" :: "r"(bar), "r"(bytes) : "memory"); }
__device__ __forceinline__ void mbar_arrive(uint32_t bar) { asm volatile("mbarrier.arrive.shared::cta.b64 _, [%0];" :: "r"(bar) : "memory"); }
__device__ __forceinline__ void mbar_arrive_cluster(uint32_t bar, uint32_t cta) {
  asm volatile("{\n.reg .b32 ra;\nmapa.shared::cluster.u32 ra, %0, %1;\nmbarrier.arrive.shared::cluster.b64 _, [ra];\n}" :: "r"(bar), "r"(cta) : "memory");
}
__device__ __forceinline__ void mbar_wait(uint32_t bar, uint32_t parity) {
  asm volatile("{\n.reg .pred p;\n.reg .u32 n;\nmov.u32 n, 0;\n"
               "LW: mbarrier.try_wait.parity.shared::cta.b64 p, [%0], %1, 2000;\n@p bra LD;\n"
               "add.u32 n, n, 1;\nsetp.lt.u32 p, n, 20000;\n@p bra LW;\nLD:\n}" :: "r"(bar), "r"(parity) : "memory");
}
__device__ __forceinline__ void tma_load_2d(uint32_t dst, const CUtensorMap* map, uint32_t bar, int c0, int c1) {
  asm volatile("cp.async.bulk.tensor.2d.shared::cluster.global.mbarrier::complete_tx::bytes [%0], [%1, {%3, %4}], [%2];"
    :: "r"(dst), "l"((uint64_t)map), "r"(bar), "r"(c0), "r"(c1) : "memory");
}
__device__ __forceinline__ void tma_load_3d(uint32_t dst, const CUtensorMap* map, uint32_t bar, int c0, int c1, int c2) {
  asm volatile("cp.async.bulk.tensor.3d.shared::cluster.global.mbarrier::complete_tx::bytes [%0], [%1, {%3, %4, %5}], [%2];"
    :: "r"(dst), "l"((uint64_t)map), "r"(bar), "r"(c0), "r"(c1), "r"(c2) : "memory");
}
__device__ __forceinline__ void tma_load_2d_mc(uint32_t dst, const CUtensorMap* map, uint32_t bar, int c0, int c1, uint16_t mask) {
  asm volatile("cp.async.bulk.tensor.2d.shared::cluster.global.mbarrier::complete_tx::bytes.multicast::cluster [%0], [%1, {%3, %4}], [%2], %5;"
    :: "r"(dst), "l"((uint64_t)map), "r"(bar), "r"(c0), "r"(c1), "h"(mask) : "memory");
}
__device__ __forceinline__ void tma_store_2d(const CUtensorMap* map, uint32_t src, int c0, int c1) {
  asm volatile("cp.async.bulk.tensor.2d.global.shared::cta.bulk_group [%0, {%2, %3}], [%1];"
    :: "l"((uint64_t)map), "r"(src), "r"(c0), "r"(c1) : "memory");
}
__device__ __forceinline__ void tma_store_3d(const CUtensorMap* map, uint32_t src, int c0, int c1, int c2) {
  asm volatile("cp.async.bulk.tensor.3d.global.shared::cta.bulk_group [%0, {%2, %3, %4}], [%1];"
    :: "l"((uint64_t)map), "r"(src), "r"(c0), "r"(c1), "r"(c2) : "memory");
}
__device__ __forceinline__ void tma_reduce_2d(const CUtensorMap* map, uint32_t src, int c0, int c1) {
  asm volatile("cp.reduce.async.bulk.tensor.2d.global.shared::cta.add.tile.bulk_group [%0, {%2, %3}], [%1];"
    :: "l"((uint64_t)map), "r"(src), "r"(c0), "r"(c1) : "memory");
}
__device__ __forceinline__ void bulk_wait_all() { asm volatile("cp.async.bulk.wait_group 0;" ::: "memory"); }
__device__ __forceinline__ void bulk_commit() { asm volatile("cp.async.bulk.commit_group;" ::: "memory"); }
__device__ __forceinline__ void bulk_wait_read() { asm volatile("cp.async.bulk.wait_group.read 0;" ::: "memory"); }
__device__ __forceinline__ void fence_async_smem() { asm volatile("fence.proxy.async.shared::cta;" ::: "memory"); }
__device__ __forceinline__ void fence_async_global() { asm volatile("fence.proxy.async.global;" ::: "memory"); }
__device__ __forceinline__ void wgmma_fence() { asm volatile("wgmma.fence.sync.aligned;" ::: "memory"); }
__device__ __forceinline__ void wgmma_commit() { asm volatile("wgmma.commit_group.sync.aligned;" ::: "memory"); }
template<int N> __device__ __forceinline__ void wgmma_wait() { asm volatile("wgmma.wait_group.sync.aligned %0;" :: "n"(N) : "memory"); }
template<int ID> __device__ __forceinline__ void bar_sync(int n) { asm volatile("bar.sync %0, %1;" :: "n"(ID), "r"(n) : "memory"); }
template<int ID> __device__ __forceinline__ void bar_arrive(int n) { asm volatile("bar.arrive %0, %1;" :: "n"(ID), "r"(n) : "memory"); }
__device__ __forceinline__ void cluster_wait() { asm volatile("barrier.cluster.wait.aligned;" ::: "memory"); }
__device__ __forceinline__ uint64_t desc64(uint32_t lo, uint32_t hi) { return (uint64_t)lo | ((uint64_t)hi << 32); }
__device__ __forceinline__ uint4 ld_vol4(const uint4* p) {
  uint4 v; asm volatile("ld.relaxed.gpu.global.v4.u32 {%0,%1,%2,%3}, [%4];" : "=r"(v.x), "=r"(v.y), "=r"(v.z), "=r"(v.w) : "l"(p) : "memory"); return v;
}
__device__ __forceinline__ uint2 ld_vol2(const uint2* p) {
  uint2 v; asm volatile("ld.relaxed.gpu.global.v2.u32 {%0,%1}, [%2];" : "=r"(v.x), "=r"(v.y) : "l"(p) : "memory"); return v;
}
__device__ __forceinline__ void st_vol4(uint4* p, uint32_t a, uint32_t b, uint32_t c, uint32_t d) {
  asm volatile("st.relaxed.gpu.global.v4.u32 [%0], {%1,%2,%3,%4};" :: "l"(p), "r"(a), "r"(b), "r"(c), "r"(d) : "memory");
}
__device__ __forceinline__ void st_vol2(uint2* p, uint32_t a, uint32_t b) {
  asm volatile("st.relaxed.gpu.global.v2.u32 [%0], {%1,%2};" :: "l"(p), "r"(a), "r"(b) : "memory");
}
__device__ __forceinline__ void stg128(void* p, uint4 v) {
  asm volatile("st.global.v4.u32 [%0], {%1,%2,%3,%4};" :: "l"(p), "r"(v.x), "r"(v.y), "r"(v.z), "r"(v.w));
}
__device__ __forceinline__ unsigned ld_relaxed(const unsigned* p) {
  unsigned v; asm volatile("ld.relaxed.gpu.global.u32 %0, [%1];" : "=r"(v) : "l"(p) : "memory"); return v;
}
__device__ __forceinline__ uint32_t pack_bf16(float lo, float hi) {
  uint32_t r; asm("cvt.rn.bf16x2.f32 %0, %1, %2;" : "=r"(r) : "f"(hi), "f"(lo)); return r;
}
__device__ __forceinline__ float bf_lo(uint32_t v) { return __uint_as_float(v << 16); }
__device__ __forceinline__ float bf_hi(uint32_t v) { return __uint_as_float(v & 0xFFFF0000u); }
__device__ __forceinline__ void stsm4(uint32_t addr, uint32_t a, uint32_t b, uint32_t c, uint32_t d) {
  asm volatile("stmatrix.sync.aligned.m8n8.x4.shared.b16 [%0], {%1,%2,%3,%4};" :: "r"(addr), "r"(a), "r"(b), "r"(c), "r"(d));
}
__device__ __forceinline__ void stsm4_t(uint32_t addr, uint32_t a, uint32_t b, uint32_t c, uint32_t d) {
  asm volatile("stmatrix.sync.aligned.m8n8.x4.trans.shared.b16 [%0], {%1,%2,%3,%4};" :: "r"(addr), "r"(a), "r"(b), "r"(c), "r"(d));
}
__device__ __forceinline__ void ldsm4(uint32_t addr, uint32_t& a, uint32_t& b, uint32_t& c, uint32_t& d) {
  asm volatile("ldmatrix.sync.aligned.m8n8.x4.shared.b16 {%0,%1,%2,%3}, [%4];" : "=r"(a), "=r"(b), "=r"(c), "=r"(d) : "r"(addr));
}
__device__ __forceinline__ uint4 lds128(uint32_t a) {
  uint4 v; asm volatile("ld.shared.v4.u32 {%0,%1,%2,%3}, [%4];" : "=r"(v.x), "=r"(v.y), "=r"(v.z), "=r"(v.w) : "r"(a)); return v;
}
__device__ __forceinline__ void sts128(uint32_t a, uint32_t x, uint32_t y, uint32_t z, uint32_t w) {
  asm volatile("st.shared.v4.u32 [%0], {%1,%2,%3,%4};" :: "r"(a), "r"(x), "r"(y), "r"(z), "r"(w));
}
__device__ __forceinline__ uint32_t hmul2_bf16(uint32_t a, uint32_t b) {
  uint32_t r; asm("mul.rn.bf16x2 %0, %1, %2;" : "=r"(r) : "r"(a), "r"(b)); return r;
}
__device__ __forceinline__ uint32_t hadd2_bf16(uint32_t a, uint32_t b) {
  uint32_t r; asm("add.rn.bf16x2 %0, %1, %2;" : "=r"(r) : "r"(a), "r"(b)); return r;
}
__device__ __forceinline__ uint32_t hfma2_bf16(uint32_t a, uint32_t b, uint32_t c) {
  uint32_t r; asm("fma.rn.bf16x2 %0, %1, %2, %3;" : "=r"(r) : "r"(a), "r"(b), "r"(c)); return r;
}
__device__ __forceinline__ float gelu_tanh(float v) {
  float u = v * fmaf(0.0356774081f, v * v, 0.7978845608f);
  float t; asm("tanh.approx.f32 %0, %1;" : "=f"(t) : "f"(u));
  float hv = 0.5f * v;
  return fmaf(hv, t, hv);
}

template<int TB>
__device__ __forceinline__ void wgmma_n192(float (&d)[96], uint64_t da, uint64_t db, int scale_d) {
  asm volatile("{\n.reg .pred p;\nsetp.ne.b32 p, %98, 0;\n"
   "wgmma.mma_async.sync.aligned.m64n192k16.f32.bf16.bf16 {%0,%1,%2,%3,%4,%5,%6,%7,%8,%9,%10,%11,%12,%13,%14,%15,%16,%17,%18,%19,%20,%21,%22,%23,%24,%25,%26,%27,%28,%29,%30,%31,%32,%33,%34,%35,%36,%37,%38,%39,%40,%41,%42,%43,%44,%45,%46,%47,%48,%49,%50,%51,%52,%53,%54,%55,%56,%57,%58,%59,%60,%61,%62,%63,%64,%65,%66,%67,%68,%69,%70,%71,%72,%73,%74,%75,%76,%77,%78,%79,%80,%81,%82,%83,%84,%85,%86,%87,%88,%89,%90,%91,%92,%93,%94,%95}, %96, %97, p, 1, 1, 0, %99;\n}"
   : "+f"(d[0]),"+f"(d[1]),"+f"(d[2]),"+f"(d[3]),"+f"(d[4]),"+f"(d[5]),"+f"(d[6]),"+f"(d[7]),"+f"(d[8]),"+f"(d[9]),"+f"(d[10]),"+f"(d[11]),"+f"(d[12]),"+f"(d[13]),"+f"(d[14]),"+f"(d[15]),"+f"(d[16]),"+f"(d[17]),"+f"(d[18]),"+f"(d[19]),"+f"(d[20]),"+f"(d[21]),"+f"(d[22]),"+f"(d[23]),"+f"(d[24]),"+f"(d[25]),"+f"(d[26]),"+f"(d[27]),"+f"(d[28]),"+f"(d[29]),"+f"(d[30]),"+f"(d[31]),"+f"(d[32]),"+f"(d[33]),"+f"(d[34]),"+f"(d[35]),"+f"(d[36]),"+f"(d[37]),"+f"(d[38]),"+f"(d[39]),"+f"(d[40]),"+f"(d[41]),"+f"(d[42]),"+f"(d[43]),"+f"(d[44]),"+f"(d[45]),"+f"(d[46]),"+f"(d[47]),"+f"(d[48]),"+f"(d[49]),"+f"(d[50]),"+f"(d[51]),"+f"(d[52]),"+f"(d[53]),"+f"(d[54]),"+f"(d[55]),"+f"(d[56]),"+f"(d[57]),"+f"(d[58]),"+f"(d[59]),"+f"(d[60]),"+f"(d[61]),"+f"(d[62]),"+f"(d[63]),"+f"(d[64]),"+f"(d[65]),"+f"(d[66]),"+f"(d[67]),"+f"(d[68]),"+f"(d[69]),"+f"(d[70]),"+f"(d[71]),"+f"(d[72]),"+f"(d[73]),"+f"(d[74]),"+f"(d[75]),"+f"(d[76]),"+f"(d[77]),"+f"(d[78]),"+f"(d[79]),"+f"(d[80]),"+f"(d[81]),"+f"(d[82]),"+f"(d[83]),"+f"(d[84]),"+f"(d[85]),"+f"(d[86]),"+f"(d[87]),"+f"(d[88]),"+f"(d[89]),"+f"(d[90]),"+f"(d[91]),"+f"(d[92]),"+f"(d[93]),"+f"(d[94]),"+f"(d[95])
   : "l"(da), "l"(db), "r"(scale_d), "n"(TB));
}
template<int TB>
__device__ __forceinline__ void wgmma_n160(float (&d)[80], uint64_t da, uint64_t db, int scale_d) {
  asm volatile("{\n.reg .pred p;\nsetp.ne.b32 p, %82, 0;\n"
   "wgmma.mma_async.sync.aligned.m64n160k16.f32.bf16.bf16 {%0,%1,%2,%3,%4,%5,%6,%7,%8,%9,%10,%11,%12,%13,%14,%15,%16,%17,%18,%19,%20,%21,%22,%23,%24,%25,%26,%27,%28,%29,%30,%31,%32,%33,%34,%35,%36,%37,%38,%39,%40,%41,%42,%43,%44,%45,%46,%47,%48,%49,%50,%51,%52,%53,%54,%55,%56,%57,%58,%59,%60,%61,%62,%63,%64,%65,%66,%67,%68,%69,%70,%71,%72,%73,%74,%75,%76,%77,%78,%79}, %80, %81, p, 1, 1, 0, %83;\n}"
   : "+f"(d[0]),"+f"(d[1]),"+f"(d[2]),"+f"(d[3]),"+f"(d[4]),"+f"(d[5]),"+f"(d[6]),"+f"(d[7]),"+f"(d[8]),"+f"(d[9]),"+f"(d[10]),"+f"(d[11]),"+f"(d[12]),"+f"(d[13]),"+f"(d[14]),"+f"(d[15]),"+f"(d[16]),"+f"(d[17]),"+f"(d[18]),"+f"(d[19]),"+f"(d[20]),"+f"(d[21]),"+f"(d[22]),"+f"(d[23]),"+f"(d[24]),"+f"(d[25]),"+f"(d[26]),"+f"(d[27]),"+f"(d[28]),"+f"(d[29]),"+f"(d[30]),"+f"(d[31]),"+f"(d[32]),"+f"(d[33]),"+f"(d[34]),"+f"(d[35]),"+f"(d[36]),"+f"(d[37]),"+f"(d[38]),"+f"(d[39]),"+f"(d[40]),"+f"(d[41]),"+f"(d[42]),"+f"(d[43]),"+f"(d[44]),"+f"(d[45]),"+f"(d[46]),"+f"(d[47]),"+f"(d[48]),"+f"(d[49]),"+f"(d[50]),"+f"(d[51]),"+f"(d[52]),"+f"(d[53]),"+f"(d[54]),"+f"(d[55]),"+f"(d[56]),"+f"(d[57]),"+f"(d[58]),"+f"(d[59]),"+f"(d[60]),"+f"(d[61]),"+f"(d[62]),"+f"(d[63]),"+f"(d[64]),"+f"(d[65]),"+f"(d[66]),"+f"(d[67]),"+f"(d[68]),"+f"(d[69]),"+f"(d[70]),"+f"(d[71]),"+f"(d[72]),"+f"(d[73]),"+f"(d[74]),"+f"(d[75]),"+f"(d[76]),"+f"(d[77]),"+f"(d[78]),"+f"(d[79])
   : "l"(da), "l"(db), "r"(scale_d), "n"(TB));
}

template<int N, int TB>
__device__ __forceinline__ void wgmma_n(float (&d)[N / 2], uint64_t da, uint64_t db) {
  if constexpr (N == 192) wgmma_n192<TB>(d, da, db, 1); else wgmma_n160<TB>(d, da, db, 1);
}

template<int M, int R>
__device__ __forceinline__ void pin(float (&acc)[M][R]) {
  #pragma unroll
  for (int mi = 0; mi < M; mi++)
    #pragma unroll
    for (int i = 0; i < R; i++) asm volatile("" : "+f"(acc[mi][i]) :: "memory");
}
template<int M, int R>
__device__ __forceinline__ void zero(float (&acc)[M][R]) {
  #pragma unroll
  for (int mi = 0; mi < M; mi++)
    #pragma unroll
    for (int i = 0; i < R; i++) acc[mi][i] = 0.f;
  pin(acc);
}

template<int N, int M, int TB, bool CONT, int ORD_BAR>
__device__ __forceinline__ void mainloop(float (&acc)[M][N / 2], uint32_t sbase, int grp, int g0, int nk, int m0 = 0) {
  const uint32_t full0 = sbase + BAR_OFF, empty0 = full0 + 8 * MAXST, ring = sbase + RING_OFF;
  const int nst = grp == 0 ? NST_A : NST_B, total = grp == 0 ? KB_A : KB_B;
  const uint32_t sstep = (grp == 0 ? STAGE_A : STAGE_B) >> 4;
  const int t = threadIdx.x & 127;
  const uint32_t da0 = (((ring + m0 * 8192) & 0x3FFFF) >> 4) | 0x10000u;
  const uint32_t db0 = (((ring + A_BYTES) & 0x3FFFF) >> 4) | ((TB == 2 ? 256u : TB ? 512u : 1u) << 16);
  constexpr uint32_t HI_A = 0x40000040u, HI_B = TB == 2 ? 0x80000020u : 0x40000040u;
  int s = g0 % nst, ph = (g0 / nst) & 1, ps = s == 0 ? nst - 1 : s - 1;
  #pragma unroll 1
  for (int g = g0; g < g0 + nk; g++) {
    const uint32_t so = s * sstep;
    mbar_wait(full0 + 8 * s, ph);
    wgmma_fence();
    #pragma unroll
    for (int k = 0; k < 4; k++) {
      const uint64_t db = desc64(db0 + so + (TB == 2 ? k * 64 : TB ? k * 128 : k * 2), HI_B);
      #pragma unroll
      for (int mi = 0; mi < M; mi++) wgmma_n<N, TB != 0>(acc[mi], desc64(da0 + so + mi * 512 + k * 2, HI_A), db);
    }
    wgmma_commit();
    if (ORD_BAR != 0 && g == g0 + nk - 1) bar_arrive<ORD_BAR>(256);
    wgmma_wait<1>();
    if (t < 2 * M && (CONT || g > g0) && g - 1 + nst < total) mbar_arrive_cluster(empty0 + 8 * ps, t & 1);
    ps = s;
    if (++s == nst) { s = 0; ph ^= 1; }
  }
}
template<int M, int R>
__device__ __forceinline__ void drain(float (&acc)[M][R], uint32_t sbase, int grp, int glast) {
  wgmma_wait<0>();
  pin(acc);
  const int t = threadIdx.x & 127;
  const int nst = grp == 0 ? NST_A : NST_B, total = grp == 0 ? KB_A : KB_B;
  if (t < 2 * M && glast + nst < total) mbar_arrive_cluster(sbase + BAR_OFF + 8 * MAXST + 8 * (glast % nst), t & 1);
}

__device__ __forceinline__ void set_flag(int slot, int byte, unsigned epoch) {
  asm volatile("st.relaxed.gpu.global.u8 [%0], %1;" :: "l"(g_flags + slot * 256 + byte), "r"(epoch & 255u) : "memory");
}
__device__ __forceinline__ unsigned get_flag(int slot, int byte) {
  unsigned v; asm volatile("ld.relaxed.gpu.global.u8 %0, [%1];" : "=r"(v) : "l"(g_flags + slot * 256 + byte) : "memory"); return v;
}
__device__ __forceinline__ void publish(int slot, int byte, unsigned epoch) {
  asm volatile("fence.acq_rel.gpu;" ::: "memory");
  set_flag(slot, byte, epoch);
}
__device__ __forceinline__ float sum8(uint4 v) {
  return ((bf_lo(v.x) + bf_hi(v.x)) + (bf_lo(v.y) + bf_hi(v.y))) + ((bf_lo(v.z) + bf_hi(v.z)) + (bf_lo(v.w) + bf_hi(v.w)));
}
__device__ __forceinline__ uint4 ldg128(const void* p) {
  uint4 v; asm volatile("ld.global.nc.v4.u32 {%0,%1,%2,%3}, [%4];" : "=r"(v.x), "=r"(v.y), "=r"(v.z), "=r"(v.w) : "l"(p)); return v;
}

__device__ __forceinline__ void ln_rows(const uint4 (&rv)[5], uint32_t buf, int cta, unsigned epoch) {
  const int t = threadIdx.x - 128, row = cta * 16 + (t >> 4), c = t & 15;
  const float sh = __shfl_sync(0xffffffffu, bf_lo(rv[0].x), t & 16);
  float d[40], s = 0.f, q = 0.f;
  #pragma unroll
  for (int j = 0; j < 5; j++) {
    const uint32_t u[4] = {rv[j].x, rv[j].y, rv[j].z, rv[j].w};
    #pragma unroll
    for (int e = 0; e < 4; e++) {
      const float d0 = bf_lo(u[e]) - sh, d1 = bf_hi(u[e]) - sh;
      d[j * 8 + e * 2] = d0; d[j * 8 + e * 2 + 1] = d1;
      s += d0 + d1; q = fmaf(d0, d0, q); q = fmaf(d1, d1, q);
    }
  }
  #pragma unroll
  for (int o = 1; o < 16; o <<= 1) { s += __shfl_xor_sync(0xffffffffu, s, o); q += __shfl_xor_sync(0xffffffffu, q, o); }
  const float md = s * (1.f / DM);
  const float r = rsqrtf(fmaxf(fmaf(q, 1.f / DM, -md * md), 0.f) + LN_EPS), o = -md * r;
  if (c == 0) st_vol2(&g_xstat[row], __float_as_uint(r), (__float_as_uint(-(md + sh) * r) & ~255u) | (epoch & 255u));
  #pragma unroll
  for (int j = 0; j < 5; j++) {
    const float* a = &d[j * 8];
    sts128(buf + (t >> 4) * 1280 + (c + 16 * j) * 16,
           pack_bf16(fmaf(a[0], r, o), fmaf(a[1], r, o)), pack_bf16(fmaf(a[2], r, o), fmaf(a[3], r, o)),
           pack_bf16(fmaf(a[4], r, o), fmaf(a[5], r, o)), pack_bf16(fmaf(a[6], r, o), fmaf(a[7], r, o)));
  }
  fence_async_smem();
  bar_arrive<BAR_LN>(288);
}

__device__ __forceinline__ void weight_sums(const bf16* __restrict__ win, const bf16* __restrict__ wdre, int j, unsigned epoch) {
  const int t = threadIdx.x & 127, w = t >> 5, l = t & 31;
  const int cj = min(j, 59), cg = cj % 12, rg = cj / 12, wr = j * 10 + min(t >> 3, 9);
  uint4 cv[8], rv[10];
  #pragma unroll
  for (int i = 0; i < 8; i++) cv[i] = ldg128(reinterpret_cast<const uint4*>(win + (size_t)(rg * 128 + w * 32 + i * 4 + (l >> 3)) * FF + FH + cg * 64) + (l & 7));
  #pragma unroll
  for (int i = 0; i < 10; i++) rv[i] = ldg128(reinterpret_cast<const uint4*>(wdre + (size_t)wr * DM) + (l & 7) + 8 * i);
  float v[8];
  #pragma unroll
  for (int e = 0; e < 8; e++) v[e] = 0.f;
  #pragma unroll
  for (int i = 0; i < 8; i++) {
    v[0] += bf_lo(cv[i].x); v[1] += bf_hi(cv[i].x); v[2] += bf_lo(cv[i].y); v[3] += bf_hi(cv[i].y);
    v[4] += bf_lo(cv[i].z); v[5] += bf_hi(cv[i].z); v[6] += bf_lo(cv[i].w); v[7] += bf_hi(cv[i].w);
  }
  #pragma unroll
  for (int st = 0; st < 2; st++) {
    const int n = 4 >> st;
    const bool up = (l & (4 * n)) != 0;
    #pragma unroll
    for (int e = 0; e < 4; e++)
      if (e < n) { const float keep = up ? v[e + n] : v[e], send = up ? v[e] : v[e + n]; v[e] = keep + __shfl_xor_sync(0xffffffffu, send, 4 * n); }
  }
  float* red = reinterpret_cast<float*>(smem + RED_OFF);
  *reinterpret_cast<float2*>(red + w * 64 + (l & 7) * 8 + (l >> 3) * 2) = make_float2(v[0], v[1]);
  float s = 0.f;
  #pragma unroll
  for (int i = 0; i < 10; i++) s += sum8(rv[i]);
  #pragma unroll
  for (int o = 1; o < 8; o <<= 1) s += __shfl_xor_sync(0xffffffffu, s, o);
  if ((l & 7) == 0) st_vol2(&g_csum[5 * FH + wr], __float_as_uint(s), epoch);
  bar_sync<BAR_WG1>(128);
  if (t < 64) st_vol2(&g_csum[rg * FH + cg * 64 + t], __float_as_uint((red[t] + red[64 + t]) + (red[128 + t] + red[192 + t])), epoch);
}

__device__ __forceinline__ void gather96(const uint2* src, float* dst, unsigned epoch) {
  unsigned it = 0;
  while (true) {
    bool ok = true;
    uint2 u[15];
    #pragma unroll
    for (int j = 0; j < 15; j++) u[j] = ld_vol2(src + (j % 5) * FH + (j / 5) * 32);
    #pragma unroll
    for (int j = 0; j < 15; j++) ok = ok && u[j].y == epoch;
    #pragma unroll
    for (int j = 0; j < 3; j++)
      dst[j * 32] = ((__uint_as_float(u[j * 5].x) + __uint_as_float(u[j * 5 + 1].x)) + (__uint_as_float(u[j * 5 + 2].x) + __uint_as_float(u[j * 5 + 3].x))) + __uint_as_float(u[j * 5 + 4].x);
    if (ok || ++it > POLL_LIMIT) break;
    __nanosleep(2 * POLL_NS);
  }
}

__device__ __forceinline__ void a_entry(int g, int grp, int& mi, int& kb) {
  if (g < 10) { mi = M_X; kb = g; }
  else if (g < 20) { mi = M_XN; kb = g - 10; }
  else if (g < 52) { mi = grp == 0 ? M_WSP : M_WSRE; kb = g - 20; }
  else if (grp == 0) {
    if (g < 52 + NX) { mi = M_WSIM; kb = g - 52 + 32 - NX; }
    else { mi = M_H; kb = g - 52 - NX; }
  } else {
    if (g < 84 - NX) { mi = M_WSIM; kb = g - 52; }
    else { mi = M_H; kb = g - (84 - NX) + 12 - NO; }
  }
}

__global__ void __cluster_dims__(2, 1, 1) __launch_bounds__(384, 1)
fused_kernel(const __grid_constant__ Maps maps, const bf16* __restrict__ x, const bf16* __restrict__ win, const bf16* __restrict__ wdre,
             const bf16* __restrict__ bsp, bf16* __restrict__ out) {
  const uint32_t sbase = smem_u32(smem);
  const uint32_t full0 = sbase + BAR_OFF, empty0 = full0 + 8 * MAXST, dep0 = empty0 + 8 * MAXST, ring = sbase + RING_OFF;
  const int tid = threadIdx.x, wg = __shfl_sync(0xffffffffu, tid >> 7, 0);
  const int cta = blockIdx.x, rank = cta & 1, grp = (cta >> 1) & 1, rb = cta >> 3, ct = ((cta >> 2) & 1) * 2 + rank;
  const int total = grp == 0 ? KB_A : KB_B, gh = grp == 0 ? 52 + NX : 84 - NX;
  const uint32_t stage_bytes = grp == 0 ? STAGE_A : STAGE_B;
  const int nst = grp == 0 ? NST_A : NST_B;
  const uint32_t buf = ring + nst * stage_bytes;

  uint4 rv[5];
  if (wg != 0) {
    #pragma unroll
    for (int j = 0; j < 5; j++) rv[j] = ldg128(reinterpret_cast<const uint4*>(x + (size_t)(cta * 16 + ((tid - 128) >> 4)) * DM) + (tid & 15) + 16 * j);
  }
  const unsigned epoch = (ld_relaxed(&g_done) >> 7) + 1u;
  if (tid == 0) {
    TS(0, 0);
    for (int s = 0; s < MAXST; s++) { mbar_init(full0 + 8 * s, 2); mbar_init(empty0 + 8 * s, 4); mbar_init(dep0 + 8 * s, 1); }
    *reinterpret_cast<volatile int*>(smem + READY_OFF) = 0;
    asm volatile("fence.mbarrier_init.release.cluster;" ::: "memory");
  }
  __syncthreads();
  asm volatile("barrier.cluster.arrive.relaxed.aligned;" ::: "memory");

  if (wg == 0) {
    asm volatile("setmaxnreg.dec.sync.aligned.u32 40;");
    const int warp = tid >> 5, lane = tid & 31;
    if (warp == 0) {
      const int row = rb * 128;
      if (lane == 0) {
        for (int g = 0; g < nst; g++) {
          mbar_expect_tx(full0 + 8 * g, A_BYTES);
          tma_load_2d(ring + g * stage_bytes, &maps.m[M_X], full0 + 8 * g, g * 64, row);
          tma_load_2d(ring + g * stage_bytes + 8192, &maps.m[M_X], full0 + 8 * g, g * 64, row + 64);
        }
      }
      __syncwarp();
      cluster_wait();
      if (lane == 0) {
        int s = 0, ph = 0;
        #pragma unroll 1
        for (int g = nst; g < total; g++) {
          int mi, kb;
          a_entry(g, grp, mi, kb);
          if (g == 10 || g == gh) { TS(0, g > 10 ? 3 : 1); mbar_wait(dep0 + (g > 10 ? 24 : 0), 0); fence_async_global(); TS(0, g > 10 ? 4 : 2); }
          mbar_wait(empty0 + 8 * s, ph);
          mbar_expect_tx(full0 + 8 * s, A_BYTES);
          tma_load_2d_mc(ring + s * stage_bytes + rank * 8192, &maps.m[mi], full0 + 8 * s, kb * 64, row + rank * 64, 3);
          if (++s == nst) { s = 0; ph ^= 1; }
          if (g + PF_D < gh && (PFB || grp == 0)) {
            a_entry(g + PF_D, grp, mi, kb);
            if (mi >= M_WSRE && (kb & 1) == (ct >> 1))
              asm volatile("cp.async.bulk.prefetch.tensor.2d.L2.global.tile [%0, {%1, %2}];" :: "l"((uint64_t)&maps.m[mi]), "r"(kb * 64), "r"(row + rank * 64) : "memory");
          }
        }
        TS(0, 5);
      }
    } else if (warp == 1) {
      if (lane == 0) {
        int s = 0, ph = 1;
        int have = 0;
        #pragma unroll 1
        for (int g = 0; g < total; g++) {
          int mi, kb, c;
          a_entry(g, grp, mi, kb);
          const bool nmaj = g >= gh || (grp == 0 && g < 52);
          uint32_t bytes = 20480;
          if (g >= gh) { mi = M_WOUT; c = ct * 5; }
          else if (g >= 52) { mi = M_AB; c = DM + ct * 160; }
          else if (grp == 0) { mi = g < 20 ? M_WIN3 : M_Z23; c = 3 * ct + (g < 10 ? 12 : 0); bytes = 24576; }
          else { mi = g < 10 ? M_WDRE : g < 20 ? M_WDIM : M_AB; c = ct * 160; }
          if (g >= 20 && g < 52 && ((g - 20) >> 1) >= have) {
            if (g == 20) TS(1, 0);
            unsigned it = 0;
            while ((have = *reinterpret_cast<volatile int*>(smem + READY_OFF)) <= ((g - 20) >> 1) && ++it < 50 * POLL_LIMIT) {}
            fence_async_global();
            if (g == 20) { TS(1, 1); TC(1); }
          }
          if (g == 52) { TS(1, 2); mbar_wait(dep0 + 16, 0); fence_async_global(); TS(1, 3); TC(2); }
          const uint32_t dst = ring + s * stage_bytes + A_BYTES, fb = full0 + 8 * s;
          mbar_wait(empty0 + 8 * s, ph);
          if (++s == nst) { s = 0; ph ^= 1; }
          mbar_expect_tx(fb, bytes);
          if (nmaj) tma_load_3d(dst, &maps.m[mi], fb, 0, kb * 64, c);
          else tma_load_2d(dst, &maps.m[mi], fb, kb * 64, c);
        }
      }
      __syncwarp();
      cluster_wait();
    } else if (warp == 2) {
      if (lane < M_COUNT) asm volatile("prefetch.tensormap [%0];" :: "l"((uint64_t)&maps.m[lane]) : "memory");
      cluster_wait();
      {
        unsigned it = 0;
        uint2 v[4];
        while (true) {
          bool ok = true;
          #pragma unroll
          for (int i = 0; i < 4; i++) { v[i] = ld_vol2(&g_xstat[rb * 128 + i * 32 + lane]); ok = ok && ((v[i].y ^ epoch) & 255u) == 0; }
          if (ok || ++it > POLL_LIMIT) break;
          __nanosleep(POLL_NS);
        }
        #pragma unroll
        for (int i = 0; i < 4; i++) reinterpret_cast<uint2*>(smem + ROWSTAT_OFF)[i * 32 + lane] = make_uint2(v[i].x, v[i].y & ~255u);
        __syncwarp();
        TS(0, 6);
        if (grp == 0) bar_arrive<BAR_STATS>(320); else bar_arrive<BAR_STATS>(192);
      }
      #pragma unroll 1
      for (int i = 0; i < 5; i++) {
        const int d = i == 3 ? 4 : i == 4 ? 3 : i;
        const int slot = d == 0 ? F_XN + rb : d == 4 ? F_Y + rb * 4 + ct : d == 3 ? F_H + rb : d == 2 ? F_B + ct : grp == 0 ? F_Z + ct : F_A + ct;
        const int byte = d == 0 ? lane & 7 : d == 4 ? 0 : d == 3 ? lane & 3 : lane & 15;
        unsigned it = 0, m;
        while ((m = __ballot_sync(0xffffffffu, get_flag(slot, byte) != (epoch & 255u))) != 0 && ++it < POLL_LIMIT) {
          if (d == 1 && lane == 0) *reinterpret_cast<volatile int*>(smem + READY_OFF) = __ffs(m) - 1;
          __nanosleep(WATCH_NS);
        }
        if (d == 1 && lane == 0) *reinterpret_cast<volatile int*>(smem + READY_OFF) = 16;
        if (d < 4) TS(0, 8 + d * 2); else TS(0, 7);
        fence_async_global();
        __syncwarp();
        if (lane == 0 && d != 1) mbar_arrive(dep0 + 8 * d);
      }
    } else {
      cluster_wait();
      bar_sync<BAR_LN>(288);
      if (lane == 0) {
        TS(1, 5);
        asm volatile("cp.async.bulk.global.shared::cta.bulk_group [%0], [%1], 20480;" :: "l"(g_xn + (size_t)cta * 16 * DM), "r"(buf) : "memory");
        bulk_commit();
        bulk_wait_all();
        set_flag(F_XN + rb, cta & 7, epoch);
        TS(1, 6);
      }
      __syncwarp();
      if (grp == 0) {
        #pragma unroll 1
        for (int i = 0; i < 2; i++) gather96(&g_csum[ct * 192 + i * 96 + lane], reinterpret_cast<float*>(smem + COLSUM_OFF) + i * 96 + lane, epoch);
      } else {
        unsigned it = 0;
        while (true) {
          bool ok = true;
          #pragma unroll
          for (int j = 0; j < 5; j++) {
            const uint2 u = ld_vol2(&g_csum[5 * FH + ct * 160 + j * 32 + lane]);
            ok = ok && u.y == epoch;
            reinterpret_cast<uint32_t*>(smem + COLSUM_OFF)[j * 32 + lane] = u.x;
          }
          if (ok || ++it > POLL_LIMIT) break;
          __nanosleep(2 * POLL_NS);
        }
      }
      __syncwarp();
      TS(1, 4);
      if (grp == 0) {
        bar_arrive<BAR_STATS>(320);
        bar_sync<BAR_PUB1>(160);
        if (lane == 0) set_flag(F_Z + ct, rb, epoch);
        TS(1, 8);
        __syncwarp();
        bar_arrive<BAR_BUF>(160);
      } else {
        bar_arrive<BAR_STATS>(192);
        bar_sync<BAR_PUB2>(160);
        if (lane == 0) set_flag(F_A + ct, rb, epoch);
        TS(1, 9);
        __syncwarp();
      }
      bar_sync<BAR_PUB1>(160);
      if (lane == 0) set_flag(grp == 0 ? F_H + rb : F_B + ct, grp == 0 ? ct : rb, epoch);
      TS(1, 10);
      __syncwarp();
      bar_arrive<BAR_BUF>(160);
    }
  } else {
    asm volatile("setmaxnreg.inc.sync.aligned.u32 232;");
    const int t = tid & 127, w = t >> 5, l = t & 31;
    ln_rows(rv, buf, cta, epoch);
    TS(wg + 1, 0);
    cluster_wait();
    const uint32_t st_base = buf + (w * 16 + ((l >> 3) & 1) * 8 + (l & 7)) * 128;
    const uint32_t st_x = ((l >> 4) ^ (l & 7)) << 4;
    const float2* rs = reinterpret_cast<const float2*>(smem + ROWSTAT_OFF) + w * 16 + (l >> 2);
    const float2* cs = reinterpret_cast<const float2*>(smem + COLSUM_OFF) + (l & 3);
    if (grp == 0) {
      {
        const int mb = wg - 1;
        float acc[1][96];
        zero(acc);
        mainloop<192, 1, 1, false, 0>(acc, sbase, 0, 0, 10, mb);
        drain(acc, sbase, 0, 9);
        TS(wg + 1, 1);
        bar_sync<BAR_STATS>(320);
        const float2 s0 = rs[mb * 64], s1 = rs[mb * 64 + 8];
        const float nm[2] = {s0.y / s0.x, s1.y / s1.x}, hr[2] = {0.5f * s0.x, 0.5f * s1.x};
        const float k1[2] = {0.7978845608f * s0.x, 0.7978845608f * s1.x};
        const float k2[2] = {0.0356774081f * s0.x * s0.x * s0.x, 0.0356774081f * s1.x * s1.x * s1.x};
        float sm0 = 0.f, sm1 = 0.f, q0 = 0.f, q1 = 0.f;
        #pragma unroll
        for (int jj = 0; jj < 12; jj++) {
          float u[8];
          #pragma unroll
          for (int hf = 0; hf < 2; hf++) {
            const float2 c = cs[jj * 8 + hf * 4];
            #pragma unroll
            for (int e = 0; e < 4; e++) {
              const float wv = fmaf(nm[e >> 1], (e & 1) ? c.y : c.x, acc[0][8 * jj + 4 * hf + e]);
              float th; asm("tanh.approx.f32 %0, %1;" : "=f"(th) : "f"(wv * fmaf(k2[e >> 1], wv * wv, k1[e >> 1])));
              const float hv = hr[e >> 1] * wv;
              u[4 * hf + e] = fmaf(hv, th, hv);
            }
            sm0 += u[4 * hf] + u[4 * hf + 1]; q0 = fmaf(u[4 * hf], u[4 * hf], q0); q0 = fmaf(u[4 * hf + 1], u[4 * hf + 1], q0);
            sm1 += u[4 * hf + 2] + u[4 * hf + 3]; q1 = fmaf(u[4 * hf + 2], u[4 * hf + 2], q1); q1 = fmaf(u[4 * hf + 3], u[4 * hf + 3], q1);
          }
          stsm4(st_base + mb * 24576 + (jj >> 2) * 8192 + (st_x ^ ((jj & 3) << 5)),
                pack_bf16(u[0], u[1]), pack_bf16(u[2], u[3]), pack_bf16(u[4], u[5]), pack_bf16(u[6], u[7]));
        }
        #pragma unroll
        for (int o = 1; o < 4; o <<= 1) {
          sm0 += __shfl_xor_sync(0xffffffffu, sm0, o); q0 += __shfl_xor_sync(0xffffffffu, q0, o);
          sm1 += __shfl_xor_sync(0xffffffffu, sm1, o); q1 += __shfl_xor_sync(0xffffffffu, q1, o);
        }
        if ((l & 3) < 2) {
          const float sm = (l & 1) ? sm1 : sm0, sv = (l & 1) ? q1 : q0;
          const int row = mb * 64 + w * 16 + (l & 1) * 8 + (l >> 2);
          const float mu = sm * (1.f / 192), m2 = fmaxf(sv - sm * mu, 0.f);
          st_vol2(&g_zstat[(rb * 4 + ct) * 128 + row], __float_as_uint(mu), (__float_as_uint(m2) & ~255u) | (epoch & 255u));
          reinterpret_cast<float2*>(smem + ZSTAT_OFF)[row] = make_float2(mu, m2);
        }
        TS(wg + 1, 4);
      }
      float acc[2][96];
      if (wg == 1) {
        bar_sync<BAR_U>(256);
        uint2 v[3];
        unsigned n = 0;
        while (true) {
          bool ok = true;
          #pragma unroll
          for (int j = 0; j < 3; j++) { v[j] = ld_vol2(&g_zstat[(rb * 4 + ((ct + 1 + j) & 3)) * 128 + t]); ok = ok && ((v[j].y ^ epoch) & 255u) == 0; }
          if (ok || ++n > POLL_LIMIT) break;
          __nanosleep(POLL_NS);
        }
        const float2 own = reinterpret_cast<const float2*>(smem + ZSTAT_OFF)[t];
        const float m0 = __uint_as_float(v[0].x), m1 = __uint_as_float(v[1].x), m3 = __uint_as_float(v[2].x);
        const float mean = 0.25f * ((own.x + m0) + (m1 + m3));
        const float d = (own.x - mean) * (own.x - mean) + (m0 - mean) * (m0 - mean) + (m1 - mean) * (m1 - mean) + (m3 - mean) * (m3 - mean);
        const float var = fmaf(192.f, d, (own.y + __uint_as_float(v[0].y & ~255u)) + (__uint_as_float(v[1].y & ~255u) + __uint_as_float(v[2].y & ~255u)));
        const float r = rsqrtf(var * (1.f / FH) + LN_EPS), o = -mean * r;
        TS(2, 5);
        const uint32_t rbase = buf + (t >> 6) * 24576 + (t & 63) * 128;
        const uint32_t m2 = pack_bf16(-mean, -mean), r2 = pack_bf16(r, r);
        const float res = (-mean - bf_lo(m2)) * r;
        const uint32_t e2 = pack_bf16(res, res);
        #pragma unroll 1
        for (int c = 0; c < 3; c++) {
          uint4 z[8];
          #pragma unroll
          for (int i = 0; i < 8; i++) z[i] = lds128(rbase + c * 8192 + (((i ^ l) & 7) << 4));
          #pragma unroll
          for (int i = 0; i < 8; i++)
            sts128(rbase + c * 8192 + (((i ^ l) & 7) << 4), hfma2_bf16(hadd2_bf16(z[i].x, m2), r2, e2), hfma2_bf16(hadd2_bf16(z[i].y, m2), r2, e2),
                   hfma2_bf16(hadd2_bf16(z[i].z, m2), r2, e2), hfma2_bf16(hadd2_bf16(z[i].w, m2), r2, e2));
          fence_async_smem();
          __syncwarp();
          if (l == 0) {
            tma_store_2d(&maps.m[M_ZS], buf + (w >> 1) * 24576 + c * 8192 + (w & 1) * 4096, ct * 192 + c * 64, rb * 128 + w * 32);
            bulk_commit();
          }
        }
        TS(2, 6);
        if (l == 0) bulk_wait_all();
        __syncwarp();
        bar_arrive<BAR_PUB1>(160);
        {
          const bf16* bp = bsp + rb * 128 + w * 16 + (l >> 2);
          const float bb[4] = {__bfloat162float(bp[0]), __bfloat162float(bp[8]), __bfloat162float(bp[64]), __bfloat162float(bp[72])};
          #pragma unroll
          for (int i = 0; i < 96; i++) { acc[0][i] = bb[(i >> 1) & 1]; acc[1][i] = bb[2 + ((i >> 1) & 1)]; }
          pin(acc);
        }
        bar_sync<BAR_ORD2>(256);
        mainloop<192, 2, 1, false, BAR_ORD1>(acc, sbase, 0, 20, 32);
        bar_sync<BAR_Z1>(256);
        drain(acc, sbase, 0, 51);
        TS(2, 7);
        uint32_t z[2][4][4];
        #pragma unroll
        for (int i = 0; i < 4; i++) ldsm4(st_base + (st_x ^ (i << 5)), z[0][i][0], z[0][i][1], z[0][i][2], z[0][i][3]);
        #pragma unroll
        for (int bx = 0; bx < 6; bx++) {
          if (bx < 5) {
            #pragma unroll
            for (int i = 0; i < 4; i++)
              ldsm4(st_base + (bx + 1) * 8192 + (st_x ^ (i << 5)), z[(bx + 1) & 1][i][0], z[(bx + 1) & 1][i][1], z[(bx + 1) & 1][i][2], z[(bx + 1) & 1][i][3]);
          }
          #pragma unroll
          for (int i = 0; i < 4; i++) {
            const float* a = &acc[bx / 3][8 * ((bx % 3) * 4 + i)];
            const uint32_t* zz = z[bx & 1][i];
            stsm4(st_base + bx * 8192 + (st_x ^ (i << 5)),
                  hmul2_bf16(zz[0], pack_bf16(a[0], a[1])), hmul2_bf16(zz[1], pack_bf16(a[2], a[3])),
                  hmul2_bf16(zz[2], pack_bf16(a[4], a[5])), hmul2_bf16(zz[3], pack_bf16(a[6], a[7])));
          }
          if (bx % 3 == 2) {
            fence_async_smem();
            __syncwarp();
            if (l < 3) {
              tma_store_2d(&maps.m[M_HS], buf + (bx - 2 + l) * 8192 + w * 2048, ct * 192 + l * 64, rb * 128 + (bx / 3) * 64 + w * 16);
              bulk_commit();
            }
          }
        }
        TS(2, 8);
        if (l < 3) bulk_wait_all();
        __syncwarp();
        bar_arrive<BAR_PUB1>(160);
        TS(2, 9);
        return;
      }
      bar_arrive<BAR_U>(256);
      zero(acc);
      mainloop<192, 2, 1, false, BAR_ORD2>(acc, sbase, 0, 10, 10);
      drain(acc, sbase, 0, 19);
      TS(3, 2);
      bar_sync<BAR_BUF>(160);
      #pragma unroll
      for (int mi = 0; mi < 2; mi++)
        #pragma unroll
        for (int jj = 0; jj < 12; jj++) {
          const float* a = &acc[mi][8 * jj];
          stsm4(st_base + mi * 24576 + (jj >> 2) * 8192 + (st_x ^ ((jj & 3) << 5)),
                pack_bf16(a[0], a[1]), pack_bf16(a[2], a[3]), pack_bf16(a[4], a[5]), pack_bf16(a[6], a[7]));
        }
      __syncwarp();
      TS(3, 3);
      const uint32_t rbase = buf + (l >> 4) * 24576 + (w * 16 + (l & 15)) * 128;
      #pragma unroll 1
      for (int c2 = 0; c2 < 12; c2++) {
        const uint32_t ab = rbase + (c2 >> 2) * 8192;
        uint4 v[2];
        #pragma unroll
        for (int i = 0; i < 2; i++) v[i] = lds128(ab + (((((c2 & 3) * 2 + i) ^ l) & 7) << 4));
        #pragma unroll
        for (int i = 0; i < 2; i++)
          sts128(ab + (((((c2 & 3) * 2 + i) ^ l) & 7) << 4),
                 pack_bf16(gelu_tanh(bf_lo(v[i].x)), gelu_tanh(bf_hi(v[i].x))), pack_bf16(gelu_tanh(bf_lo(v[i].y)), gelu_tanh(bf_hi(v[i].y))),
                 pack_bf16(gelu_tanh(bf_lo(v[i].z)), gelu_tanh(bf_hi(v[i].z))), pack_bf16(gelu_tanh(bf_lo(v[i].w)), gelu_tanh(bf_hi(v[i].w))));
      }
      TS(3, 5);
      bar_arrive<BAR_Z1>(256);
    }
    float acc[2][80];
    if (grp == 1) {
      zero(acc);
      if (wg == 2) {
        mainloop<160, 2, 0, false, BAR_ORD2>(acc, sbase, 1, 0, 10);
      } else {
        weight_sums(win, wdre, rb * 4 + ct, epoch);
        TS(2, 1);
        bar_sync<BAR_ORD2>(256);
        mainloop<160, 2, 0, false, BAR_ORD1>(acc, sbase, 1, 10, 10);
      }
      drain(acc, sbase, 1, wg == 2 ? 9 : 19);
      TS(wg + 1, wg == 1 ? 7 : 2);
      if (wg == 1) bar_sync<BAR_Z1>(256); else bar_sync<BAR_STATS>(192);
      const uint32_t tb = buf + ((l >> 4) * 8 + (l & 7)) * 128 + (((w * 2 + ((l >> 3) & 1)) ^ (l & 7)) << 4);
      float2 st[4];
      #pragma unroll
      for (int r = 0; r < 4; r++) st[r] = wg == 2 ? rs[(r >> 1) * 64 + (r & 1) * 8] : make_float2(-1.f, 0.f);
      #pragma unroll
      for (int jj = 0; jj < 10; jj++) {
        const float2 c0 = cs[jj * 8], c1 = cs[jj * 8 + 4];
        #pragma unroll
        for (int mi = 0; mi < 2; mi++) {
          const float* a = &acc[mi][8 * jj];
          const float2 s0 = st[mi * 2], s1 = st[mi * 2 + 1];
          stsm4_t(tb + mi * 20480 + jj * 2048,
                  pack_bf16(fmaf(a[0], s0.x, s0.y * c0.x), fmaf(a[1], s0.x, s0.y * c0.y)), pack_bf16(fmaf(a[2], s1.x, s1.y * c0.x), fmaf(a[3], s1.x, s1.y * c0.y)),
                  pack_bf16(fmaf(a[4], s0.x, s0.y * c1.x), fmaf(a[5], s0.x, s0.y * c1.y)), pack_bf16(fmaf(a[6], s1.x, s1.y * c1.x), fmaf(a[7], s1.x, s1.y * c1.y)));
        }
      }
      fence_async_smem();
      if (wg == 1) bar_sync<BAR_WG1>(128); else bar_sync<BAR_WG2>(128);
      TS(wg + 1, wg == 1 ? 8 : 6);
      if (l < 2) {
        tma_store_2d(&maps.m[M_ABS], buf + l * 20480 + w * 5120, rb * 128 + l * 64, (2 - wg) * DM + ct * 160 + w * 40);
        bulk_commit();
        bulk_wait_all();
      }
      __syncwarp();
      TS(wg + 1, wg == 1 ? 9 : 10);
      if (wg == 1) {
        bar_arrive<BAR_PUB1>(160);
        #pragma unroll 1
        for (int i = 0; i < 4; i++) {
          uint4 v[5];
          #pragma unroll
          for (int j = 0; j < 5; j++) {
            const int e = (i * 5 + j) * 128 + t;
            v[j] = ldg128(x + (size_t)(rb * 128 + e / 20) * DM + ct * 160 + (e % 20) * 8);
          }
          #pragma unroll
          for (int j = 0; j < 5; j++) {
            const int e = (i * 5 + j) * 128 + t;
            stg128(out + (size_t)(rb * 128 + e / 20) * DM + ct * 160 + (e % 20) * 8, v[j]);
          }
        }
        bar_sync<BAR_WG1>(128);
        if (t == 0) publish(F_Y + rb * 4 + ct, 0, epoch);
        return;
      }
      bar_arrive<BAR_PUB2>(160);
      bar_arrive<BAR_Z1>(256);
    }
    zero(acc);
    bar_sync<BAR_ORD1>(256);
    mainloop<160, 2, 0, false, 0>(acc, sbase, grp, grp == 0 ? 52 : 20, grp == 0 ? NX : 64 - NX);
    mainloop<160, 2, 2, true, 0>(acc, sbase, grp, gh, total - gh);
    const uint32_t slab = buf + w * (16 * 320);
    const uint32_t addr = slab + (((l >> 3) & 1) * 8 + (l & 7)) * 320 + (l >> 4) * 16;
    bar_sync<BAR_BUF>(160);
    mbar_wait(dep0 + 32, 0);
    drain(acc, sbase, grp, total - 1);
    TS(3, 12);
    #pragma unroll
    for (int mi = 0; mi < 2; mi++) {
      #pragma unroll
      for (int jj = 0; jj < 10; jj++) {
        const float* a = &acc[mi][8 * jj];
        stsm4(addr + mi * 20480 + jj * 32, pack_bf16(a[0], a[1]), pack_bf16(a[2], a[3]), pack_bf16(a[4], a[5]), pack_bf16(a[6], a[7]));
      }
      fence_async_smem();
      __syncwarp();
      if (l == 0) {
        tma_reduce_2d(&maps.m[M_OUT], slab + mi * 20480, ct * 160, rb * 128 + mi * 64 + w * 16);
        bulk_commit();
      }
    }
    TS(3, 13);
    if (l == 0) {
      bulk_wait_read();
      if (w == 0) atomicAdd(&g_done, 1u);
    }
    TS(3, 15);
  }
}

typedef CUresult (*EncodeFn)(CUtensorMap*, CUtensorMapDataType, cuuint32_t, void*, const cuuint64_t*, const cuuint64_t*,
                             const cuuint32_t*, const cuuint32_t*, CUtensorMapInterleave, CUtensorMapSwizzle,
                             CUtensorMapL2promotion, CUtensorMapFloatOOBfill);

void make2d(EncodeFn enc, CUtensorMap* m, const void* p, uint64_t cols, uint64_t rows, uint32_t bc, uint32_t br, bool swz = true) {
  cuuint64_t gd[2] = {cols, rows}, gs[1] = {cols * 2};
  cuuint32_t bd[2] = {bc, br}, es[2] = {1, 1};
  enc(m, CU_TENSOR_MAP_DATA_TYPE_BFLOAT16, 2, const_cast<void*>(p), gd, gs, bd, es, CU_TENSOR_MAP_INTERLEAVE_NONE,
      swz ? CU_TENSOR_MAP_SWIZZLE_128B : CU_TENSOR_MAP_SWIZZLE_NONE, CU_TENSOR_MAP_L2_PROMOTION_L2_128B, CU_TENSOR_MAP_FLOAT_OOB_FILL_NONE);
}
void make3d(EncodeFn enc, CUtensorMap* m, const void* p, uint64_t cols, uint64_t rows, uint32_t cw, uint32_t nc, uint32_t br = 64) {
  cuuint64_t gd[3] = {cw, rows, cols / cw}, gs[2] = {cols * 2, cw * 2};
  cuuint32_t bd[3] = {cw, br, nc}, es[3] = {1, 1, 1};
  enc(m, CU_TENSOR_MAP_DATA_TYPE_BFLOAT16, 3, const_cast<void*>(p), gd, gs, bd, es, CU_TENSOR_MAP_INTERLEAVE_NONE,
      cw == 64 ? CU_TENSOR_MAP_SWIZZLE_128B : CU_TENSOR_MAP_SWIZZLE_64B, CU_TENSOR_MAP_L2_PROMOTION_L2_128B, CU_TENSOR_MAP_FLOAT_OOB_FILL_NONE);
}

}

extern "C" void kernel_launch(void* const* d_in, const int* in_sizes, int n_in, void* d_out, int out_size) {
  const bf16* x = (const bf16*)d_in[0];
  const bf16* wsre = (const bf16*)d_in[1];
  const bf16* wsim = (const bf16*)d_in[2];
  const bf16* wdre = (const bf16*)d_in[3];
  const bf16* wdim = (const bf16*)d_in[4];
  const bf16* win = (const bf16*)d_in[6];
  const bf16* wsp = (const bf16*)d_in[7];
  const bf16* bsp = (const bf16*)d_in[8];
  const bf16* wout = (const bf16*)d_in[9];

  void* fn = nullptr;
  cudaDriverEntryPointQueryResult qr;
  cudaGetDriverEntryPoint("cuTensorMapEncodeTiled", &fn, cudaEnableDefault, &qr);
  EncodeFn enc = (EncodeFn)fn;
  void *abT, *z2, *h, *xn;
  cudaGetSymbolAddress(&xn, g_xn);
  cudaGetSymbolAddress(&abT, g_abT);
  cudaGetSymbolAddress(&z2, g_z2);
  cudaGetSymbolAddress(&h, g_h);

  Maps maps;
  make2d(enc, &maps.m[M_X], x, DM, SEQ, 64, 64);
  make2d(enc, &maps.m[M_XN], xn, DM, SEQ, 64, 64);
  make2d(enc, &maps.m[M_WSRE], wsre, SEQ, SEQ, 64, 64);
  make2d(enc, &maps.m[M_WSIM], wsim, SEQ, SEQ, 64, 64);
  make2d(enc, &maps.m[M_WSP], wsp, SEQ, SEQ, 64, 64);
  make2d(enc, &maps.m[M_H], h, FH, SEQ, 64, 64);
  make3d(enc, &maps.m[M_WIN3], win, FF, DM, 64, 3);
  make3d(enc, &maps.m[M_Z23], z2, FH, SEQ, 64, 3);
  make2d(enc, &maps.m[M_WDRE], wdre, DM, DM, 64, 160);
  make2d(enc, &maps.m[M_WDIM], wdim, DM, DM, 64, 160);
  make2d(enc, &maps.m[M_AB], abT, SEQ, 2 * DM, 64, 160);
  make3d(enc, &maps.m[M_WOUT], wout, DM, FH, 32, 5);
  make2d(enc, &maps.m[M_HS], h, FH, SEQ, 64, 16);
  make2d(enc, &maps.m[M_ZS], z2, FH, SEQ, 64, 32);
  make2d(enc, &maps.m[M_ABS], abT, SEQ, 2 * DM, 64, 40);
  make2d(enc, &maps.m[M_OUT], d_out, DM, SEQ, 160, 16, false);

  cudaFuncSetAttribute(fused_kernel, cudaFuncAttributeMaxDynamicSharedMemorySize, SMEM_BYTES);
  fused_kernel<<<128, 384, SMEM_BYTES>>>(maps, x, win, wdre, bsp, (bf16*)d_out);
}
```

```cpp
#include <cuda_runtime.h>
#include <cuda_bf16.h>
#include <cuda.h>
#include <stdint.h>

namespace {

typedef __nv_bfloat16 bf16;

constexpr int SEQ = 2048, DM = 640, FF = 1536, FH = 768;
#define NXV 6
#define NOV 6
constexpr int NX = NXV;
constexpr int NO = NOV;
#define NSTB 5
#define PFB 1
constexpr int NST_A = 4, NST_B = NSTB, MAXST = 5;
constexpr int A_BYTES = 16384;
constexpr int BAR_OFF = 0;
constexpr int READY_OFF = 128;
constexpr int COLSUM_OFF = 256;
constexpr int ROWSTAT_OFF = 1024;
constexpr int ZSTAT_OFF = 2048;
constexpr int RED_OFF = 3072;
constexpr int RING_OFF = 4096;
constexpr int STAGE_A = 40960, STAGE_B = 36864;
constexpr int SMEM_BYTES = RING_OFF + 5 * STAGE_B + 40960;
constexpr int KB_A = 52 + NX + 12 - NO;
constexpr int KB_B = 84 - NX + NO;
constexpr float LN_EPS = 1e-5f;
constexpr unsigned POLL_LIMIT = 100000;
#define POLL_NS 100
#define PF_D 8
#define NORM2 1
#define Z1_NS 600
#define WATCH_NS 40

constexpr int BAR_ORD1 = 1, BAR_ORD2 = 2, BAR_WG1 = 3, BAR_WG2 = 4, BAR_LN = 5, BAR_BUF = 6, BAR_Z1 = 7, BAR_PUB1 = 8, BAR_PUB2 = 9,
              BAR_STATS = 10, BAR_U = 11;

enum { M_X, M_XN, M_WSRE, M_WSIM, M_WSP, M_H, M_WIN3, M_Z23, M_WDRE, M_WDIM, M_AB, M_WOUT, M_OUT, M_HS, M_ZS, M_ABS, M_COUNT };
struct Maps { CUtensorMap m[M_COUNT]; };

__device__ __align__(1024) bf16 g_abT[2 * DM * SEQ];
__device__ __align__(1024) bf16 g_z2[SEQ * FH];
__device__ __align__(1024) bf16 g_h[SEQ * FH];
__device__ __align__(1024) bf16 g_xn[SEQ * DM];
__device__ __align__(16) uint2 g_xstat[SEQ];
__device__ __align__(16) uint2 g_csum[5 * FH + DM];
__device__ __align__(16) uint2 g_zstat[64 * 128];
__device__ __align__(256) unsigned char g_flags[108 * 256];
constexpr int F_A = 0, F_B = 4, F_Z = 8, F_H = 12, F_XN = 28, F_Y = 44;
__device__ unsigned g_done;
#define TS(role, ev)
#define TC(i)

extern __shared__ __align__(1024) uint8_t smem[];

__device__ __forceinline__ uint32_t smem_u32(const void* p) { return (uint32_t)__cvta_generic_to_shared(p); }
__device__ __forceinline__ void mbar_init(uint32_t bar, uint32_t cnt) { asm volatile("mbarrier.init.shared::cta.b64 [%0], %1;" :: "r"(bar), "r"(cnt)); }
__device__ __forceinline__ void mbar_expect_tx(uint32_t bar, uint32_t bytes) { asm volatile("mbarrier.arrive.expect_tx.shared::cta.b64 _, [%0], %1;" :: "r"(bar), "r"(bytes) : "memory"); }
__device__ __forceinline__ void mbar_arrive(uint32_t bar) { asm volatile("mbarrier.arrive.shared::cta.b64 _, [%0];" :: "r"(bar) : "memory"); }
__device__ __forceinline__ void mbar_arrive_cluster(uint32_t bar, uint32_t cta) {
  asm volatile("{\n.reg .b32 ra;\nmapa.shared::cluster.u32 ra, %0, %1;\nmbarrier.arrive.shared::cluster.b64 _, [ra];\n}" :: "r"(bar), "r"(cta) : "memory");
}
__device__ __forceinline__ void mbar_wait(uint32_t bar, uint32_t parity) {
  asm volatile("{\n.reg .pred p;\n.reg .u32 n;\nmov.u32 n, 0;\n"
               "LW: mbarrier.try_wait.parity.shared::cta.b64 p, [%0], %1, 2000;\n@p bra LD;\n"
               "add.u32 n, n, 1;\nsetp.lt.u32 p, n, 20000;\n@p bra LW;\nLD:\n}" :: "r"(bar), "r"(parity) : "memory");
}
__device__ __forceinline__ void tma_load_2d(uint32_t dst, const CUtensorMap* map, uint32_t bar, int c0, int c1) {
  asm volatile("cp.async.bulk.tensor.2d.shared::cluster.global.mbarrier::complete_tx::bytes [%0], [%1, {%3, %4}], [%2];"
    :: "r"(dst), "l"((uint64_t)map), "r"(bar), "r"(c0), "r"(c1) : "memory");
}
__device__ __forceinline__ void tma_load_3d(uint32_t dst, const CUtensorMap* map, uint32_t bar, int c0, int c1, int c2) {
  asm volatile("cp.async.bulk.tensor.3d.shared::cluster.global.mbarrier::complete_tx::bytes [%0], [%1, {%3, %4, %5}], [%2];"
    :: "r"(dst), "l"((uint64_t)map), "r"(bar), "r"(c0), "r"(c1), "r"(c2) : "memory");
}
__device__ __forceinline__ void tma_load_2d_mc(uint32_t dst, const CUtensorMap* map, uint32_t bar, int c0, int c1, uint16_t mask) {
  asm volatile("cp.async.bulk.tensor.2d.shared::cluster.global.mbarrier::complete_tx::bytes.multicast::cluster [%0], [%1, {%3, %4}], [%2], %5;"
    :: "r"(dst), "l"((uint64_t)map), "r"(bar), "r"(c0), "r"(c1), "h"(mask) : "memory");
}
__device__ __forceinline__ void tma_store_2d(const CUtensorMap* map, uint32_t src, int c0, int c1) {
  asm volatile("cp.async.bulk.tensor.2d.global.shared::cta.bulk_group [%0, {%2, %3}], [%1];"
    :: "l"((uint64_t)map), "r"(src), "r"(c0), "r"(c1) : "memory");
}
__device__ __forceinline__ void tma_store_3d(const CUtensorMap* map, uint32_t src, int c0, int c1, int c2) {
  asm volatile("cp.async.bulk.tensor.3d.global.shared::cta.bulk_group [%0, {%2, %3, %4}], [%1];"
    :: "l"((uint64_t)map), "r"(src), "r"(c0), "r"(c1), "r"(c2) : "memory");
}
__device__ __forceinline__ void tma_reduce_2d(const CUtensorMap* map, uint32_t src, int c0, int c1) {
  asm volatile("cp.reduce.async.bulk.tensor.2d.global.shared::cta.add.tile.bulk_group [%0, {%2, %3}], [%1];"
    :: "l"((uint64_t)map), "r"(src), "r"(c0), "r"(c1) : "memory");
}
__device__ __forceinline__ void bulk_wait_all() { asm volatile("cp.async.bulk.wait_group 0;" ::: "memory"); }
__device__ __forceinline__ void bulk_commit() { asm volatile("cp.async.bulk.commit_group;" ::: "memory"); }
__device__ __forceinline__ void bulk_wait_read() { asm volatile("cp.async.bulk.wait_group.read 0;" ::: "memory"); }
__device__ __forceinline__ void fence_async_smem() { asm volatile("fence.proxy.async.shared::cta;" ::: "memory"); }
__device__ __forceinline__ void fence_async_global() { asm volatile("fence.proxy.async.global;" ::: "memory"); }
__device__ __forceinline__ void wgmma_fence() { asm volatile("wgmma.fence.sync.aligned;" ::: "memory"); }
__device__ __forceinline__ void wgmma_commit() { asm volatile("wgmma.commit_group.sync.aligned;" ::: "memory"); }
template<int N> __device__ __forceinline__ void wgmma_wait() { asm volatile("wgmma.wait_group.sync.aligned %0;" :: "n"(N) : "memory"); }
template<int ID> __device__ __forceinline__ void bar_sync(int n) { asm volatile("bar.sync %0, %1;" :: "n"(ID), "r"(n) : "memory"); }
template<int ID> __device__ __forceinline__ void bar_arrive(int n) { asm volatile("bar.arrive %0, %1;" :: "n"(ID), "r"(n) : "memory"); }
__device__ __forceinline__ void cluster_wait() { asm volatile("barrier.cluster.wait.aligned;" ::: "memory"); }
__device__ __forceinline__ uint64_t desc64(uint32_t lo, uint32_t hi) { return (uint64_t)lo | ((uint64_t)hi << 32); }
__device__ __forceinline__ uint4 ld_vol4(const uint4* p) {
  uint4 v; asm volatile("ld.relaxed.gpu.global.v4.u32 {%0,%1,%2,%3}, [%4];" : "=r"(v.x), "=r"(v.y), "=r"(v.z), "=r"(v.w) : "l"(p) : "memory"); return v;
}
__device__ __forceinline__ uint2 ld_vol2(const uint2* p) {
  uint2 v; asm volatile("ld.relaxed.gpu.global.v2.u32 {%0,%1}, [%2];" : "=r"(v.x), "=r"(v.y) : "l"(p) : "memory"); return v;
}
__device__ __forceinline__ void st_vol4(uint4* p, uint32_t a, uint32_t b, uint32_t c, uint32_t d) {
  asm volatile("st.relaxed.gpu.global.v4.u32 [%0], {%1,%2,%3,%4};" :: "l"(p), "r"(a), "r"(b), "r"(c), "r"(d) : "memory");
}
__device__ __forceinline__ void st_vol2(uint2* p, uint32_t a, uint32_t b) {
  asm volatile("st.relaxed.gpu.global.v2.u32 [%0], {%1,%2};" :: "l"(p), "r"(a), "r"(b) : "memory");
}
__device__ __forceinline__ void stg128(void* p, uint4 v) {
  asm volatile("st.global.v4.u32 [%0], {%1,%2,%3,%4};" :: "l"(p), "r"(v.x), "r"(v.y), "r"(v.z), "r"(v.w));
}
__device__ __forceinline__ unsigned ld_relaxed(const unsigned* p) {
  unsigned v; asm volatile("ld.relaxed.gpu.global.u32 %0, [%1];" : "=r"(v) : "l"(p) : "memory"); return v;
}
__device__ __forceinline__ uint32_t pack_bf16(float lo, float hi) {
  uint32_t r; asm("cvt.rn.bf16x2.f32 %0, %1, %2;" : "=r"(r) : "f"(hi), "f"(lo)); return r;
}
__device__ __forceinline__ float bf_lo(uint32_t v) { return __uint_as_float(v << 16); }
__device__ __forceinline__ float bf_hi(uint32_t v) { return __uint_as_float(v & 0xFFFF0000u); }
__device__ __forceinline__ void stsm4(uint32_t addr, uint32_t a, uint32_t b, uint32_t c, uint32_t d) {
  asm volatile("stmatrix.sync.aligned.m8n8.x4.shared.b16 [%0], {%1,%2,%3,%4};" :: "r"(addr), "r"(a), "r"(b), "r"(c), "r"(d));
}
__device__ __forceinline__ void stsm4_t(uint32_t addr, uint32_t a, uint32_t b, uint32_t c, uint32_t d) {
  asm volatile("stmatrix.sync.aligned.m8n8.x4.trans.shared.b16 [%0], {%1,%2,%3,%4};" :: "r"(addr), "r"(a), "r"(b), "r"(c), "r"(d));
}
__device__ __forceinline__ void ldsm4(uint32_t addr, uint32_t& a, uint32_t& b, uint32_t& c, uint32_t& d) {
  asm volatile("ldmatrix.sync.aligned.m8n8.x4.shared.b16 {%0,%1,%2,%3}, [%4];" : "=r"(a), "=r"(b), "=r"(c), "=r"(d) : "r"(addr));
}
__device__ __forceinline__ uint4 lds128(uint32_t a) {
  uint4 v; asm volatile("ld.shared.v4.u32 {%0,%1,%2,%3}, [%4];" : "=r"(v.x), "=r"(v.y), "=r"(v.z), "=r"(v.w) : "r"(a)); return v;
}
__device__ __forceinline__ void sts128(uint32_t a, uint32_t x, uint32_t y, uint32_t z, uint32_t w) {
  asm volatile("st.shared.v4.u32 [%0], {%1,%2,%3,%4};" :: "r"(a), "r"(x), "r"(y), "r"(z), "r"(w));
}
__device__ __forceinline__ uint32_t hmul2_bf16(uint32_t a, uint32_t b) {
  uint32_t r; asm("mul.rn.bf16x2 %0, %1, %2;" : "=r"(r) : "r"(a), "r"(b)); return r;
}
__device__ __forceinline__ uint32_t hadd2_bf16(uint32_t a, uint32_t b) {
  uint32_t r; asm("add.rn.bf16x2 %0, %1, %2;" : "=r"(r) : "r"(a), "r"(b)); return r;
}
__device__ __forceinline__ uint32_t hfma2_bf16(uint32_t a, uint32_t b, uint32_t c) {
  uint32_t r; asm("fma.rn.bf16x2 %0, %1, %2, %3;" : "=r"(r) : "r"(a), "r"(b), "r"(c)); return r;
}
__device__ __forceinline__ float gelu_tanh(float v) {
  float u = v * fmaf(0.0356774081f, v * v, 0.7978845608f);
  float t; asm("tanh.approx.f32 %0, %1;" : "=f"(t) : "f"(u));
  float hv = 0.5f * v;
  return fmaf(hv, t, hv);
}

template<int TB>
__device__ __forceinline__ void wgmma_n192(float (&d)[96], uint64_t da, uint64_t db, int scale_d) {
  asm volatile("{\n.reg .pred p;\nsetp.ne.b32 p, %98, 0;\n"
   "wgmma.mma_async.sync.aligned.m64n192k16.f32.bf16.bf16 {%0,%1,%2,%3,%4,%5,%6,%7,%8,%9,%10,%11,%12,%13,%14,%15,%16,%17,%18,%19,%20,%21,%22,%23,%24,%25,%26,%27,%28,%29,%30,%31,%32,%33,%34,%35,%36,%37,%38,%39,%40,%41,%42,%43,%44,%45,%46,%47,%48,%49,%50,%51,%52,%53,%54,%55,%56,%57,%58,%59,%60,%61,%62,%63,%64,%65,%66,%67,%68,%69,%70,%71,%72,%73,%74,%75,%76,%77,%78,%79,%80,%81,%82,%83,%84,%85,%86,%87,%88,%89,%90,%91,%92,%93,%94,%95}, %96, %97, p, 1, 1, 0, %99;\n}"
   : "+f"(d[0]),"+f"(d[1]),"+f"(d[2]),"+f"(d[3]),"+f"(d[4]),"+f"(d[5]),"+f"(d[6]),"+f"(d[7]),"+f"(d[8]),"+f"(d[9]),"+f"(d[10]),"+f"(d[11]),"+f"(d[12]),"+f"(d[13]),"+f"(d[14]),"+f"(d[15]),"+f"(d[16]),"+f"(d[17]),"+f"(d[18]),"+f"(d[19]),"+f"(d[20]),"+f"(d[21]),"+f"(d[22]),"+f"(d[23]),"+f"(d[24]),"+f"(d[25]),"+f"(d[26]),"+f"(d[27]),"+f"(d[28]),"+f"(d[29]),"+f"(d[30]),"+f"(d[31]),"+f"(d[32]),"+f"(d[33]),"+f"(d[34]),"+f"(d[35]),"+f"(d[36]),"+f"(d[37]),"+f"(d[38]),"+f"(d[39]),"+f"(d[40]),"+f"(d[41]),"+f"(d[42]),"+f"(d[43]),"+f"(d[44]),"+f"(d[45]),"+f"(d[46]),"+f"(d[47]),"+f"(d[48]),"+f"(d[49]),"+f"(d[50]),"+f"(d[51]),"+f"(d[52]),"+f"(d[53]),"+f"(d[54]),"+f"(d[55]),"+f"(d[56]),"+f"(d[57]),"+f"(d[58]),"+f"(d[59]),"+f"(d[60]),"+f"(d[61]),"+f"(d[62]),"+f"(d[63]),"+f"(d[64]),"+f"(d[65]),"+f"(d[66]),"+f"(d[67]),"+f"(d[68]),"+f"(d[69]),"+f"(d[70]),"+f"(d[71]),"+f"(d[72]),"+f"(d[73]),"+f"(d[74]),"+f"(d[75]),"+f"(d[76]),"+f"(d[77]),"+f"(d[78]),"+f"(d[79]),"+f"(d[80]),"+f"(d[81]),"+f"(d[82]),"+f"(d[83]),"+f"(d[84]),"+f"(d[85]),"+f"(d[86]),"+f"(d[87]),"+f"(d[88]),"+f"(d[89]),"+f"(d[90]),"+f"(d[91]),"+f"(d[92]),"+f"(d[93]),"+f"(d[94]),"+f"(d[95])
   : "l"(da), "l"(db), "r"(scale_d), "n"(TB));
}
template<int TB>
__device__ __forceinline__ void wgmma_n160(float (&d)[80], uint64_t da, uint64_t db, int scale_d) {
  asm volatile("{\n.reg .pred p;\nsetp.ne.b32 p, %82, 0;\n"
   "wgmma.mma_async.sync.aligned.m64n160k16.f32.bf16.bf16 {%0,%1,%2,%3,%4,%5,%6,%7,%8,%9,%10,%11,%12,%13,%14,%15,%16,%17,%18,%19,%20,%21,%22,%23,%24,%25,%26,%27,%28,%29,%30,%31,%32,%33,%34,%35,%36,%37,%38,%39,%40,%41,%42,%43,%44,%45,%46,%47,%48,%49,%50,%51,%52,%53,%54,%55,%56,%57,%58,%59,%60,%61,%62,%63,%64,%65,%66,%67,%68,%69,%70,%71,%72,%73,%74,%75,%76,%77,%78,%79}, %80, %81, p, 1, 1, 0, %83;\n}"
   : "+f"(d[0]),"+f"(d[1]),"+f"(d[2]),"+f"(d[3]),"+f"(d[4]),"+f"(d[5]),"+f"(d[6]),"+f"(d[7]),"+f"(d[8]),"+f"(d[9]),"+f"(d[10]),"+f"(d[11]),"+f"(d[12]),"+f"(d[13]),"+f"(d[14]),"+f"(d[15]),"+f"(d[16]),"+f"(d[17]),"+f"(d[18]),"+f"(d[19]),"+f"(d[20]),"+f"(d[21]),"+f"(d[22]),"+f"(d[23]),"+f"(d[24]),"+f"(d[25]),"+f"(d[26]),"+f"(d[27]),"+f"(d[28]),"+f"(d[29]),"+f"(d[30]),"+f"(d[31]),"+f"(d[32]),"+f"(d[33]),"+f"(d[34]),"+f"(d[35]),"+f"(d[36]),"+f"(d[37]),"+f"(d[38]),"+f"(d[39]),"+f"(d[40]),"+f"(d[41]),"+f"(d[42]),"+f"(d[43]),"+f"(d[44]),"+f"(d[45]),"+f"(d[46]),"+f"(d[47]),"+f"(d[48]),"+f"(d[49]),"+f"(d[50]),"+f"(d[51]),"+f"(d[52]),"+f"(d[53]),"+f"(d[54]),"+f"(d[55]),"+f"(d[56]),"+f"(d[57]),"+f"(d[58]),"+f"(d[59]),"+f"(d[60]),"+f"(d[61]),"+f"(d[62]),"+f"(d[63]),"+f"(d[64]),"+f"(d[65]),"+f"(d[66]),"+f"(d[67]),"+f"(d[68]),"+f"(d[69]),"+f"(d[70]),"+f"(d[71]),"+f"(d[72]),"+f"(d[73]),"+f"(d[74]),"+f"(d[75]),"+f"(d[76]),"+f"(d[77]),"+f"(d[78]),"+f"(d[79])
   : "l"(da), "l"(db), "r"(scale_d), "n"(TB));
}

template<int N, int TB>
__device__ __forceinline__ void wgmma_n(float (&d)[N / 2], uint64_t da, uint64_t db) {
  if constexpr (N == 192) wgmma_n192<TB>(d, da, db, 1); else wgmma_n160<TB>(d, da, db, 1);
}

template<int M, int R>
__device__ __forceinline__ void pin(float (&acc)[M][R]) {
  #pragma unroll
  for (int mi = 0; mi < M; mi++)
    #pragma unroll
    for (int i = 0; i < R; i++) asm volatile("" : "+f"(acc[mi][i]) :: "memory");
}
template<int M, int R>
__device__ __forceinline__ void zero(float (&acc)[M][R]) {
  #pragma unroll
  for (int mi = 0; mi < M; mi++)
    #pragma unroll
    for (int i = 0; i < R; i++) acc[mi][i] = 0.f;
  pin(acc);
}

template<int N, int M, int TB, bool CONT, int ORD_BAR>
__device__ __forceinline__ void mainloop(float (&acc)[M][N / 2], uint32_t sbase, int grp, int g0, int nk, int m0 = 0) {
  const uint32_t full0 = sbase + BAR_OFF, empty0 = full0 + 8 * MAXST, ring = sbase + RING_OFF;
  const int nst = grp == 0 ? NST_A : NST_B, total = grp == 0 ? KB_A : KB_B;
  const uint32_t sstep = (grp == 0 ? STAGE_A : STAGE_B) >> 4;
  const int t = threadIdx.x & 127;
  const uint32_t da0 = (((ring + m0 * 8192) & 0x3FFFF) >> 4) | 0x10000u;
  const uint32_t db0 = (((ring + A_BYTES) & 0x3FFFF) >> 4) | ((TB == 2 ? 256u : TB ? 512u : 1u) << 16);
  constexpr uint32_t HI_A = 0x40000040u, HI_B = TB == 2 ? 0x80000020u : 0x40000040u;
  int s = g0 % nst, ph = (g0 / nst) & 1, ps = s == 0 ? nst - 1 : s - 1;
  #pragma unroll 1
  for (int g = g0; g < g0 + nk; g++) {
    const uint32_t so = s * sstep;
    mbar_wait(full0 + 8 * s, ph);
    wgmma_fence();
    #pragma unroll
    for (int k = 0; k < 4; k++) {
      const uint64_t db = desc64(db0 + so + (TB == 2 ? k * 64 : TB ? k * 128 : k * 2), HI_B);
      #pragma unroll
      for (int mi = 0; mi < M; mi++) wgmma_n<N, TB != 0>(acc[mi], desc64(da0 + so + mi * 512 + k * 2, HI_A), db);
    }
    wgmma_commit();
    if (ORD_BAR != 0 && g == g0 + nk - 1) bar_arrive<ORD_BAR>(256);
    wgmma_wait<1>();
    if (t < 2 * M && (CONT || g > g0) && g - 1 + nst < total) mbar_arrive_cluster(empty0 + 8 * ps, t & 1);
    ps = s;
    if (++s == nst) { s = 0; ph ^= 1; }
  }
}
template<int M, int R>
__device__ __forceinline__ void drain(float (&acc)[M][R], uint32_t sbase, int grp, int glast) {
  wgmma_wait<0>();
  pin(acc);
  const int t = threadIdx.x & 127;
  const int nst = grp == 0 ? NST_A : NST_B, total = grp == 0 ? KB_A : KB_B;
  if (t < 2 * M && glast + nst < total) mbar_arrive_cluster(sbase + BAR_OFF + 8 * MAXST + 8 * (glast % nst), t & 1);
}

__device__ __forceinline__ void set_flag(int slot, int byte, unsigned epoch) {
  asm volatile("st.relaxed.gpu.global.u8 [%0], %1;" :: "l"(g_flags + slot * 256 + byte), "r"(epoch & 255u) : "memory");
}
__device__ __forceinline__ unsigned get_flag(int slot, int byte) {
  unsigned v; asm volatile("ld.relaxed.gpu.global.u8 %0, [%1];" : "=r"(v) : "l"(g_flags + slot * 256 + byte) : "memory"); return v;
}
__device__ __forceinline__ void publish(int slot, int byte, unsigned epoch) {
  asm volatile("fence.acq_rel.gpu;" ::: "memory");
  set_flag(slot, byte, epoch);
}
__device__ __forceinline__ float sum8(uint4 v) {
  return ((bf_lo(v.x) + bf_hi(v.x)) + (bf_lo(v.y) + bf_hi(v.y))) + ((bf_lo(v.z) + bf_hi(v.z)) + (bf_lo(v.w) + bf_hi(v.w)));
}
__device__ __forceinline__ uint4 ldg128(const void* p) {
  uint4 v; asm volatile("ld.global.nc.v4.u32 {%0,%1,%2,%3}, [%4];" : "=r"(v.x), "=r"(v.y), "=r"(v.z), "=r"(v.w) : "l"(p)); return v;
}

__device__ __forceinline__ void ln_rows(const uint4 (&rv)[5], uint32_t buf, int cta, unsigned epoch) {
  const int t = threadIdx.x - 128, row = cta * 16 + (t >> 4), c = t & 15;
  const float sh = __shfl_sync(0xffffffffu, bf_lo(rv[0].x), t & 16);
  float d[40], s = 0.f, q = 0.f;
  #pragma unroll
  for (int j = 0; j < 5; j++) {
    const uint32_t u[4] = {rv[j].x, rv[j].y, rv[j].z, rv[j].w};
    #pragma unroll
    for (int e = 0; e < 4; e++) {
      const float d0 = bf_lo(u[e]) - sh, d1 = bf_hi(u[e]) - sh;
      d[j * 8 + e * 2] = d0; d[j * 8 + e * 2 + 1] = d1;
      s += d0 + d1; q = fmaf(d0, d0, q); q = fmaf(d1, d1, q);
    }
  }
  #pragma unroll
  for (int o = 1; o < 16; o <<= 1) { s += __shfl_xor_sync(0xffffffffu, s, o); q += __shfl_xor_sync(0xffffffffu, q, o); }
  const float md = s * (1.f / DM);
  const float r = rsqrtf(fmaxf(fmaf(q, 1.f / DM, -md * md), 0.f) + LN_EPS), o = -md * r;
  if (c == 0) st_vol2(&g_xstat[row], __float_as_uint(r), (__float_as_uint(-(md + sh) * r) & ~255u) | (epoch & 255u));
  #pragma unroll
  for (int j = 0; j < 5; j++) {
    const float* a = &d[j * 8];
    sts128(buf + (t >> 4) * 1280 + (c + 16 * j) * 16,
           pack_bf16(fmaf(a[0], r, o), fmaf(a[1], r, o)), pack_bf16(fmaf(a[2], r, o), fmaf(a[3], r, o)),
           pack_bf16(fmaf(a[4], r, o), fmaf(a[5], r, o)), pack_bf16(fmaf(a[6], r, o), fmaf(a[7], r, o)));
  }
  fence_async_smem();
  bar_arrive<BAR_LN>(288);
}

__device__ __forceinline__ void weight_sums(const bf16* __restrict__ win, const bf16* __restrict__ wdre, int j, unsigned epoch) {
  const int t = threadIdx.x & 127, w = t >> 5, l = t & 31;
  const int cj = min(j, 59), cg = cj % 12, rg = cj / 12, wr = j * 10 + min(t >> 3, 9);
  uint4 cv[8], rv[10];
  #pragma unroll
  for (int i = 0; i < 8; i++) cv[i] = ldg128(reinterpret_cast<const uint4*>(win + (size_t)(rg * 128 + w * 32 + i * 4 + (l >> 3)) * FF + FH + cg * 64) + (l & 7));
  #pragma unroll
  for (int i = 0; i < 10; i++) rv[i] = ldg128(reinterpret_cast<const uint4*>(wdre + (size_t)wr * DM) + (l & 7) + 8 * i);
  float v[8];
  #pragma unroll
  for (int e = 0; e < 8; e++) v[e] = 0.f;
  #pragma unroll
  for (int i = 0; i < 8; i++) {
    v[0] += bf_lo(cv[i].x); v[1] += bf_hi(cv[i].x); v[2] += bf_lo(cv[i].y); v[3] += bf_hi(cv[i].y);
    v[4] += bf_lo(cv[i].z); v[5] += bf_hi(cv[i].z); v[6] += bf_lo(cv[i].w); v[7] += bf_hi(cv[i].w);
  }
  #pragma unroll
  for (int st = 0; st < 2; st++) {
    const int n = 4 >> st;
    const bool up = (l & (4 * n)) != 0;
    #pragma unroll
    for (int e = 0; e < 4; e++)
      if (e < n) { const float keep = up ? v[e + n] : v[e], send = up ? v[e] : v[e + n]; v[e] = keep + __shfl_xor_sync(0xffffffffu, send, 4 * n); }
  }
  float* red = reinterpret_cast<float*>(smem + RED_OFF);
  *reinterpret_cast<float2*>(red + w * 64 + (l & 7) * 8 + (l >> 3) * 2) = make_float2(v[0], v[1]);
  float s = 0.f;
  #pragma unroll
  for (int i = 0; i < 10; i++) s += sum8(rv[i]);
  #pragma unroll
  for (int o = 1; o < 8; o <<= 1) s += __shfl_xor_sync(0xffffffffu, s, o);
  if ((l & 7) == 0) st_vol2(&g_csum[5 * FH + wr], __float_as_uint(s), epoch);
  bar_sync<BAR_WG1>(128);
  if (t < 64) st_vol2(&g_csum[rg * FH + cg * 64 + t], __float_as_uint((red[t] + red[64 + t]) + (red[128 + t] + red[192 + t])), epoch);
}

__device__ __forceinline__ void gather96(const uint2* src, float* dst, unsigned epoch) {
  unsigned it = 0;
  while (true) {
    bool ok = true;
    uint2 u[15];
    #pragma unroll
    for (int j = 0; j < 15; j++) u[j] = ld_vol2(src + (j % 5) * FH + (j / 5) * 32);
    #pragma unroll
    for (int j = 0; j < 15; j++) ok = ok && u[j].y == epoch;
    #pragma unroll
    for (int j = 0; j < 3; j++)
      dst[j * 32] = ((__uint_as_float(u[j * 5].x) + __uint_as_float(u[j * 5 + 1].x)) + (__uint_as_float(u[j * 5 + 2].x) + __uint_as_float(u[j * 5 + 3].x))) + __uint_as_float(u[j * 5 + 4].x);
    if (ok || ++it > POLL_LIMIT) break;
    __nanosleep(2 * POLL_NS);
  }
}

__device__ __forceinline__ void a_entry(int g, int grp, int& mi, int& kb) {
  if (g < 10) { mi = M_X; kb = g; }
  else if (g < 20) { mi = M_XN; kb = g - 10; }
  else if (g < 52) { mi = grp == 0 ? M_WSP : M_WSRE; kb = g - 20; }
  else if (grp == 0) {
    if (g < 52 + NX) { mi = M_WSIM; kb = g - 52 + 32 - NX; }
    else { mi = M_H; kb = g - 52 - NX; }
  } else {
    if (g < 84 - NX) { mi = M_WSIM; kb = g - 52; }
    else { mi = M_H; kb = g - (84 - NX) + 12 - NO; }
  }
}

__global__ void __cluster_dims__(2, 1, 1) __launch_bounds__(384, 1)
fused_kernel(const __grid_constant__ Maps maps, const bf16* __restrict__ x, const bf16* __restrict__ win, const bf16* __restrict__ wdre,
             const bf16* __restrict__ bsp, bf16* __restrict__ out) {
  const uint32_t sbase = smem_u32(smem);
  const uint32_t full0 = sbase + BAR_OFF, empty0 = full0 + 8 * MAXST, dep0 = empty0 + 8 * MAXST, ring = sbase + RING_OFF;
  const int tid = threadIdx.x, wg = __shfl_sync(0xffffffffu, tid >> 7, 0);
  const int cta = blockIdx.x, rank = cta & 1, grp = (cta >> 1) & 1, rb = cta >> 3, ct = ((cta >> 2) & 1) * 2 + rank;
  const int total = grp == 0 ? KB_A : KB_B, gh = grp == 0 ? 52 + NX : 84 - NX;
  const uint32_t stage_bytes = grp == 0 ? STAGE_A : STAGE_B;
  const int nst = grp == 0 ? NST_A : NST_B;
  const uint32_t buf = ring + nst * stage_bytes;

  uint4 rv[5];
  if (wg != 0) {
    #pragma unroll
    for (int j = 0; j < 5; j++) rv[j] = ldg128(reinterpret_cast<const uint4*>(x + (size_t)(cta * 16 + ((tid - 128) >> 4)) * DM) + (tid & 15) + 16 * j);
  }
  const unsigned epoch = (ld_relaxed(&g_done) >> 7) + 1u;
  if (tid == 0) {
    TS(0, 0);
    for (int s = 0; s < MAXST; s++) { mbar_init(full0 + 8 * s, 2); mbar_init(empty0 + 8 * s, 4); mbar_init(dep0 + 8 * s, 1); }
    *reinterpret_cast<volatile int*>(smem + READY_OFF) = 0;
    asm volatile("fence.mbarrier_init.release.cluster;" ::: "memory");
  }
  __syncthreads();
  asm volatile("barrier.cluster.arrive.relaxed.aligned;" ::: "memory");

  if (wg == 0) {
    asm volatile("setmaxnreg.dec.sync.aligned.u32 40;");
    const int warp = tid >> 5, lane = tid & 31;
    if (warp == 0) {
      const int row = rb * 128;
      if (lane == 0) {
        for (int g = 0; g < nst; g++) {
          mbar_expect_tx(full0 + 8 * g, A_BYTES);
          tma_load_2d(ring + g * stage_bytes, &maps.m[M_X], full0 + 8 * g, g * 64, row);
          tma_load_2d(ring + g * stage_bytes + 8192, &maps.m[M_X], full0 + 8 * g, g * 64, row + 64);
        }
      }
      __syncwarp();
      cluster_wait();
      if (lane == 0) {
        int s = 0, ph = 0;
        #pragma unroll 1
        for (int g = nst; g < total; g++) {
          int mi, kb;
          a_entry(g, grp, mi, kb);
          if (g == 10 || g == gh) { TS(0, g > 10 ? 3 : 1); mbar_wait(dep0 + (g > 10 ? 24 : 0), 0); fence_async_global(); TS(0, g > 10 ? 4 : 2); }
          mbar_wait(empty0 + 8 * s, ph);
          mbar_expect_tx(full0 + 8 * s, A_BYTES);
          tma_load_2d_mc(ring + s * stage_bytes + rank * 8192, &maps.m[mi], full0 + 8 * s, kb * 64, row + rank * 64, 3);
          if (++s == nst) { s = 0; ph ^= 1; }
          if (g + PF_D < gh && (PFB || grp == 0)) {
            a_entry(g + PF_D, grp, mi, kb);
            if (mi >= M_WSRE && (kb & 1) == (ct >> 1))
              asm volatile("cp.async.bulk.prefetch.tensor.2d.L2.global.tile [%0, {%1, %2}];" :: "l"((uint64_t)&maps.m[mi]), "r"(kb * 64), "r"(row + rank * 64) : "memory");
          }
        }
        TS(0, 5);
      }
    } else if (warp == 1) {
      if (lane == 0) {
        int s = 0, ph = 1;
        int have = 0;
        #pragma unroll 1
        for (int g = 0; g < total; g++) {
          int mi, kb, c;
          a_entry(g, grp, mi, kb);
          const bool nmaj = g >= gh || (grp == 0 && g < 52);
          uint32_t bytes = 20480;
          if (g >= gh) { mi = M_WOUT; c = ct * 5; }
          else if (g >= 52) { mi = M_AB; c = DM + ct * 160; }
          else if (grp == 0) { mi = g < 20 ? M_WIN3 : M_Z23; c = 3 * ct + (g < 10 ? 12 : 0); bytes = 24576; }
          else { mi = g < 10 ? M_WDRE : g < 20 ? M_WDIM : M_AB; c = ct * 160; }
          if (g >= 20 && g < 52 && ((g - 20) >> 1) >= have) {
            if (g == 20) TS(1, 0);
            unsigned it = 0;
            while ((have = *reinterpret_cast<volatile int*>(smem + READY_OFF)) <= ((g - 20) >> 1) && ++it < 50 * POLL_LIMIT) {}
            fence_async_global();
            if (g == 20) { TS(1, 1); TC(1); }
          }
          if (g == 52) { TS(1, 2); mbar_wait(dep0 + 16, 0); fence_async_global(); TS(1, 3); TC(2); }
          const uint32_t dst = ring + s * stage_bytes + A_BYTES, fb = full0 + 8 * s;
          mbar_wait(empty0 + 8 * s, ph);
          if (++s == nst) { s = 0; ph ^= 1; }
          mbar_expect_tx(fb, bytes);
          if (nmaj) tma_load_3d(dst, &maps.m[mi], fb, 0, kb * 64, c);
          else tma_load_2d(dst, &maps.m[mi], fb, kb * 64, c);
        }
      }
      __syncwarp();
      cluster_wait();
    } else if (warp == 2) {
      if (lane < M_COUNT) asm volatile("prefetch.tensormap [%0];" :: "l"((uint64_t)&maps.m[lane]) : "memory");
      cluster_wait();
      {
        unsigned it = 0;
        uint2 v[4];
        while (true) {
          bool ok = true;
          #pragma unroll
          for (int i = 0; i < 4; i++) { v[i] = ld_vol2(&g_xstat[rb * 128 + i * 32 + lane]); ok = ok && ((v[i].y ^ epoch) & 255u) == 0; }
          if (ok || ++it > POLL_LIMIT) break;
          __nanosleep(POLL_NS);
        }
        #pragma unroll
        for (int i = 0; i < 4; i++) reinterpret_cast<uint2*>(smem + ROWSTAT_OFF)[i * 32 + lane] = make_uint2(v[i].x, v[i].y & ~255u);
        __syncwarp();
        TS(0, 6);
        if (grp == 0) bar_arrive<BAR_STATS>(320); else bar_arrive<BAR_STATS>(192);
      }
      #pragma unroll 1
      for (int i = 0; i < 5; i++) {
        const int d = i == 3 ? 4 : i == 4 ? 3 : i;
        const int slot = d == 0 ? F_XN + rb : d == 4 ? F_Y + rb * 4 + ct : d == 3 ? F_H + rb : d == 2 ? F_B + ct : grp == 0 ? F_Z + ct : F_A + ct;
        const int byte = d == 0 ? lane & 7 : d == 4 ? 0 : d == 3 ? lane & 3 : lane & 15;
        unsigned it = 0, m;
        while ((m = __ballot_sync(0xffffffffu, get_flag(slot, byte) != (epoch & 255u))) != 0 && ++it < POLL_LIMIT) {
          if (d == 1 && lane == 0) *reinterpret_cast<volatile int*>(smem + READY_OFF) = __ffs(m) - 1;
          __nanosleep(WATCH_NS);
        }
        if (d == 1 && lane == 0) *reinterpret_cast<volatile int*>(smem + READY_OFF) = 16;
        if (d < 4) TS(0, 8 + d * 2); else TS(0, 7);
        fence_async_global();
        __syncwarp();
        if (lane == 0 && d != 1) mbar_arrive(dep0 + 8 * d);
      }
    } else {
      cluster_wait();
      bar_sync<BAR_LN>(288);
      if (lane == 0) {
        TS(1, 5);
        asm volatile("cp.async.bulk.global.shared::cta.bulk_group [%0], [%1], 20480;" :: "l"(g_xn + (size_t)cta * 16 * DM), "r"(buf) : "memory");
        bulk_commit();
        bulk_wait_all();
        set_flag(F_XN + rb, cta & 7, epoch);
        TS(1, 6);
      }
      __syncwarp();
      if (grp == 0) {
        #pragma unroll 1
        for (int i = 0; i < 2; i++) gather96(&g_csum[ct * 192 + i * 96 + lane], reinterpret_cast<float*>(smem + COLSUM_OFF) + i * 96 + lane, epoch);
      } else {
        unsigned it = 0;
        while (true) {
          bool ok = true;
          #pragma unroll
          for (int j = 0; j < 5; j++) {
            const uint2 u = ld_vol2(&g_csum[5 * FH + ct * 160 + j * 32 + lane]);
            ok = ok && u.y == epoch;
            reinterpret_cast<uint32_t*>(smem + COLSUM_OFF)[j * 32 + lane] = u.x;
          }
          if (ok || ++it > POLL_LIMIT) break;
          __nanosleep(2 * POLL_NS);
        }
      }
      __syncwarp();
      TS(1, 4);
      if (grp == 0) {
        bar_arrive<BAR_STATS>(320);
        bar_sync<BAR_PUB1>(160);
        if (lane == 0) set_flag(F_Z + ct, rb, epoch);
        TS(1, 8);
        __syncwarp();
        bar_arrive<BAR_BUF>(160);
      } else {
        bar_arrive<BAR_STATS>(192);
        bar_sync<BAR_PUB2>(160);
        if (lane == 0) set_flag(F_A + ct, rb, epoch);
        TS(1, 9);
        __syncwarp();
      }
      bar_sync<BAR_PUB1>(160);
      if (lane == 0) set_flag(grp == 0 ? F_H + rb : F_B + ct, grp == 0 ? ct : rb, epoch);
      TS(1, 10);
      __syncwarp();
      bar_arrive<BAR_BUF>(160);
    }
  } else {
    asm volatile("setmaxnreg.inc.sync.aligned.u32 232;");
    const int t = tid & 127, w = t >> 5, l = t & 31;
    ln_rows(rv, buf, cta, epoch);
    TS(wg + 1, 0);
    cluster_wait();
    const uint32_t st_base = buf + (w * 16 + ((l >> 3) & 1) * 8 + (l & 7)) * 128;
    const uint32_t st_x = ((l >> 4) ^ (l & 7)) << 4;
    const float2* rs = reinterpret_cast<const float2*>(smem + ROWSTAT_OFF) + w * 16 + (l >> 2);
    const float2* cs = reinterpret_cast<const float2*>(smem + COLSUM_OFF) + (l & 3);
    if (grp == 0) {
      {
        const int mb = wg - 1;
        float acc[1][96];
        zero(acc);
        mainloop<192, 1, 1, false, 0>(acc, sbase, 0, 0, 10, mb);
        drain(acc, sbase, 0, 9);
        TS(wg + 1, 1);
        bar_sync<BAR_STATS>(320);
        const float2 s0 = rs[mb * 64], s1 = rs[mb * 64 + 8];
        const float nm[2] = {s0.y / s0.x, s1.y / s1.x}, hr[2] = {0.5f * s0.x, 0.5f * s1.x};
        const float k1[2] = {0.7978845608f * s0.x, 0.7978845608f * s1.x};
        const float k2[2] = {0.0356774081f * s0.x * s0.x * s0.x, 0.0356774081f * s1.x * s1.x * s1.x};
        float sm0 = 0.f, sm1 = 0.f, q0 = 0.f, q1 = 0.f;
        #pragma unroll
        for (int jj = 0; jj < 12; jj++) {
          float u[8];
          #pragma unroll
          for (int hf = 0; hf < 2; hf++) {
            const float2 c = cs[jj * 8 + hf * 4];
            #pragma unroll
            for (int e = 0; e < 4; e++) {
              const float wv = fmaf(nm[e >> 1], (e & 1) ? c.y : c.x, acc[0][8 * jj + 4 * hf + e]);
              float th; asm("tanh.approx.f32 %0, %1;" : "=f"(th) : "f"(wv * fmaf(k2[e >> 1], wv * wv, k1[e >> 1])));
              const float hv = hr[e >> 1] * wv;
              u[4 * hf + e] = fmaf(hv, th, hv);
            }
            sm0 += u[4 * hf] + u[4 * hf + 1]; q0 = fmaf(u[4 * hf], u[4 * hf], q0); q0 = fmaf(u[4 * hf + 1], u[4 * hf + 1], q0);
            sm1 += u[4 * hf + 2] + u[4 * hf + 3]; q1 = fmaf(u[4 * hf + 2], u[4 * hf + 2], q1); q1 = fmaf(u[4 * hf + 3], u[4 * hf + 3], q1);
          }
          stsm4(st_base + mb * 24576 + (jj >> 2) * 8192 + (st_x ^ ((jj & 3) << 5)),
                pack_bf16(u[0], u[1]), pack_bf16(u[2], u[3]), pack_bf16(u[4], u[5]), pack_bf16(u[6], u[7]));
        }
        #pragma unroll
        for (int o = 1; o < 4; o <<= 1) {
          sm0 += __shfl_xor_sync(0xffffffffu, sm0, o); q0 += __shfl_xor_sync(0xffffffffu, q0, o);
          sm1 += __shfl_xor_sync(0xffffffffu, sm1, o); q1 += __shfl_xor_sync(0xffffffffu, q1, o);
        }
        if ((l & 3) < 2) {
          const float sm = (l & 1) ? sm1 : sm0, sv = (l & 1) ? q1 : q0;
          const int row = mb * 64 + w * 16 + (l & 1) * 8 + (l >> 2);
          const float mu = sm * (1.f / 192), m2 = fmaxf(sv - sm * mu, 0.f);
          st_vol2(&g_zstat[(rb * 4 + ct) * 128 + row], __float_as_uint(mu), (__float_as_uint(m2) & ~255u) | (epoch & 255u));
          reinterpret_cast<float2*>(smem + ZSTAT_OFF)[row] = make_float2(mu, m2);
        }
        TS(wg + 1, 4);
      }
      float acc[2][96];
      if (wg == 1) {
        bar_sync<BAR_U>(256);
        uint2 v[3];
        unsigned n = 0;
        while (true) {
          bool ok = true;
          #pragma unroll
          for (int j = 0; j < 3; j++) { v[j] = ld_vol2(&g_zstat[(rb * 4 + ((ct + 1 + j) & 3)) * 128 + t]); ok = ok && ((v[j].y ^ epoch) & 255u) == 0; }
          if (ok || ++n > POLL_LIMIT) break;
          __nanosleep(POLL_NS);
        }
        const float2 own = reinterpret_cast<const float2*>(smem + ZSTAT_OFF)[t];
        const float m0 = __uint_as_float(v[0].x), m1 = __uint_as_float(v[1].x), m3 = __uint_as_float(v[2].x);
        const float mean = 0.25f * ((own.x + m0) + (m1 + m3));
        const float d = (own.x - mean) * (own.x - mean) + (m0 - mean) * (m0 - mean) + (m1 - mean) * (m1 - mean) + (m3 - mean) * (m3 - mean);
        const float var = fmaf(192.f, d, (own.y + __uint_as_float(v[0].y & ~255u)) + (__uint_as_float(v[1].y & ~255u) + __uint_as_float(v[2].y & ~255u)));
        const float r = rsqrtf(var * (1.f / FH) + LN_EPS), o = -mean * r;
        TS(2, 5);
        const uint32_t rbase = buf + (t >> 6) * 24576 + (t & 63) * 128;
        const uint32_t m2 = pack_bf16(-mean, -mean), r2 = pack_bf16(r, r);
        const float res = (-mean - bf_lo(m2)) * r;
        const uint32_t e2 = pack_bf16(res, res);
        #pragma unroll 1
        for (int c = 0; c < 3; c++) {
          uint4 z[8];
          #pragma unroll
          for (int i = 0; i < 8; i++) z[i] = lds128(rbase + c * 8192 + (((i ^ l) & 7) << 4));
          #pragma unroll
          for (int i = 0; i < 8; i++)
            sts128(rbase + c * 8192 + (((i ^ l) & 7) << 4), hfma2_bf16(hadd2_bf16(z[i].x, m2), r2, e2), hfma2_bf16(hadd2_bf16(z[i].y, m2), r2, e2),
                   hfma2_bf16(hadd2_bf16(z[i].z, m2), r2, e2), hfma2_bf16(hadd2_bf16(z[i].w, m2), r2, e2));
          fence_async_smem();
          __syncwarp();
          if (l == 0) {
            tma_store_2d(&maps.m[M_ZS], buf + (w >> 1) * 24576 + c * 8192 + (w & 1) * 4096, ct * 192 + c * 64, rb * 128 + w * 32);
            bulk_commit();
          }
        }
        TS(2, 6);
        if (l == 0) bulk_wait_all();
        __syncwarp();
        bar_arrive<BAR_PUB1>(160);
        {
          const bf16* bp = bsp + rb * 128 + w * 16 + (l >> 2);
          const float bb[4] = {__bfloat162float(bp[0]), __bfloat162float(bp[8]), __bfloat162float(bp[64]), __bfloat162float(bp[72])};
          #pragma unroll
          for (int i = 0; i < 96; i++) { acc[0][i] = bb[(i >> 1) & 1]; acc[1][i] = bb[2 + ((i >> 1) & 1)]; }
          pin(acc);
        }
        bar_sync<BAR_ORD2>(256);
        mainloop<192, 2, 1, false, BAR_ORD1>(acc, sbase, 0, 20, 32);
        bar_sync<BAR_Z1>(256);
        drain(acc, sbase, 0, 51);
        TS(2, 7);
        uint32_t z[2][4][4];
        #pragma unroll
        for (int i = 0; i < 4; i++) ldsm4(st_base + (st_x ^ (i << 5)), z[0][i][0], z[0][i][1], z[0][i][2], z[0][i][3]);
        #pragma unroll
        for (int bx = 0; bx < 6; bx++) {
          if (bx < 5) {
            #pragma unroll
            for (int i = 0; i < 4; i++)
              ldsm4(st_base + (bx + 1) * 8192 + (st_x ^ (i << 5)), z[(bx + 1) & 1][i][0], z[(bx + 1) & 1][i][1], z[(bx + 1) & 1][i][2], z[(bx + 1) & 1][i][3]);
          }
          #pragma unroll
          for (int i = 0; i < 4; i++) {
            const float* a = &acc[bx / 3][8 * ((bx % 3) * 4 + i)];
            const uint32_t* zz = z[bx & 1][i];
            stsm4(st_base + bx * 8192 + (st_x ^ (i << 5)),
                  hmul2_bf16(zz[0], pack_bf16(a[0], a[1])), hmul2_bf16(zz[1], pack_bf16(a[2], a[3])),
                  hmul2_bf16(zz[2], pack_bf16(a[4], a[5])), hmul2_bf16(zz[3], pack_bf16(a[6], a[7])));
          }
          if (bx % 3 == 2) {
            fence_async_smem();
            __syncwarp();
            if (l < 3) {
              tma_store_2d(&maps.m[M_HS], buf + (bx - 2 + l) * 8192 + w * 2048, ct * 192 + l * 64, rb * 128 + (bx / 3) * 64 + w * 16);
              bulk_commit();
            }
          }
        }
        TS(2, 8);
        if (l < 3) bulk_wait_all();
        __syncwarp();
        bar_arrive<BAR_PUB1>(160);
        TS(2, 9);
        return;
      }
      bar_arrive<BAR_U>(256);
      zero(acc);
      mainloop<192, 2, 1, false, BAR_ORD2>(acc, sbase, 0, 10, 10);
      drain(acc, sbase, 0, 19);
      TS(3, 2);
      bar_sync<BAR_BUF>(160);
      #pragma unroll
      for (int mi = 0; mi < 2; mi++)
        #pragma unroll
        for (int jj = 0; jj < 12; jj++) {
          const float* a = &acc[mi][8 * jj];
          stsm4(st_base + mi * 24576 + (jj >> 2) * 8192 + (st_x ^ ((jj & 3) << 5)),
                pack_bf16(a[0], a[1]), pack_bf16(a[2], a[3]), pack_bf16(a[4], a[5]), pack_bf16(a[6], a[7]));
        }
      __syncwarp();
      TS(3, 3);
      const uint32_t rbase = buf + (l >> 4) * 24576 + (w * 16 + (l & 15)) * 128;
      #pragma unroll 1
      for (int c2 = 0; c2 < 12; c2++) {
        const uint32_t ab = rbase + (c2 >> 2) * 8192;
        uint4 v[2];
        #pragma unroll
        for (int i = 0; i < 2; i++) v[i] = lds128(ab + (((((c2 & 3) * 2 + i) ^ l) & 7) << 4));
        #pragma unroll
        for (int i = 0; i < 2; i++)
          sts128(ab + (((((c2 & 3) * 2 + i) ^ l) & 7) << 4),
                 pack_bf16(gelu_tanh(bf_lo(v[i].x)), gelu_tanh(bf_hi(v[i].x))), pack_bf16(gelu_tanh(bf_lo(v[i].y)), gelu_tanh(bf_hi(v[i].y))),
                 pack_bf16(gelu_tanh(bf_lo(v[i].z)), gelu_tanh(bf_hi(v[i].z))), pack_bf16(gelu_tanh(bf_lo(v[i].w)), gelu_tanh(bf_hi(v[i].w))));
        __nanosleep(Z1_NS);
      }
      TS(3, 5);
      bar_arrive<BAR_Z1>(256);
    }
    float acc[2][80];
    if (grp == 1) {
      zero(acc);
      if (wg == 2) {
        mainloop<160, 2, 0, false, BAR_ORD2>(acc, sbase, 1, 0, 10);
      } else {
        weight_sums(win, wdre, rb * 4 + ct, epoch);
        TS(2, 1);
        bar_sync<BAR_ORD2>(256);
        mainloop<160, 2, 0, false, BAR_ORD1>(acc, sbase, 1, 10, 10);
      }
      drain(acc, sbase, 1, wg == 2 ? 9 : 19);
      TS(wg + 1, wg == 1 ? 7 : 2);
      if (wg == 1) bar_sync<BAR_Z1>(256); else bar_sync<BAR_STATS>(192);
      const uint32_t tb = buf + ((l >> 4) * 8 + (l & 7)) * 128 + (((w * 2 + ((l >> 3) & 1)) ^ (l & 7)) << 4);
      float2 st[4];
      #pragma unroll
      for (int r = 0; r < 4; r++) st[r] = wg == 2 ? rs[(r >> 1) * 64 + (r & 1) * 8] : make_float2(-1.f, 0.f);
      #pragma unroll
      for (int jj = 0; jj < 10; jj++) {
        const float2 c0 = cs[jj * 8], c1 = cs[jj * 8 + 4];
        #pragma unroll
        for (int mi = 0; mi < 2; mi++) {
          const float* a = &acc[mi][8 * jj];
          const float2 s0 = st[mi * 2], s1 = st[mi * 2 + 1];
          stsm4_t(tb + mi * 20480 + jj * 2048,
                  pack_bf16(fmaf(a[0], s0.x, s0.y * c0.x), fmaf(a[1], s0.x, s0.y * c0.y)), pack_bf16(fmaf(a[2], s1.x, s1.y * c0.x), fmaf(a[3], s1.x, s1.y * c0.y)),
                  pack_bf16(fmaf(a[4], s0.x, s0.y * c1.x), fmaf(a[5], s0.x, s0.y * c1.y)), pack_bf16(fmaf(a[6], s1.x, s1.y * c1.x), fmaf(a[7], s1.x, s1.y * c1.y)));
        }
      }
      fence_async_smem();
      if (wg == 1) bar_sync<BAR_WG1>(128); else bar_sync<BAR_WG2>(128);
      TS(wg + 1, wg == 1 ? 8 : 6);
      if (l < 2) {
        tma_store_2d(&maps.m[M_ABS], buf + l * 20480 + w * 5120, rb * 128 + l * 64, (2 - wg) * DM + ct * 160 + w * 40);
        bulk_commit();
        bulk_wait_all();
      }
      __syncwarp();
      TS(wg + 1, wg == 1 ? 9 : 10);
      if (wg == 1) {
        bar_arrive<BAR_PUB1>(160);
        #pragma unroll 1
        for (int i = 0; i < 4; i++) {
          uint4 v[5];
          #pragma unroll
          for (int j = 0; j < 5; j++) {
            const int e = (i * 5 + j) * 128 + t;
            v[j] = ldg128(x + (size_t)(rb * 128 + e / 20) * DM + ct * 160 + (e % 20) * 8);
          }
          #pragma unroll
          for (int j = 0; j < 5; j++) {
            const int e = (i * 5 + j) * 128 + t;
            stg128(out + (size_t)(rb * 128 + e / 20) * DM + ct * 160 + (e % 20) * 8, v[j]);
          }
        }
        bar_sync<BAR_WG1>(128);
        if (t == 0) publish(F_Y + rb * 4 + ct, 0, epoch);
        return;
      }
      bar_arrive<BAR_PUB2>(160);
      bar_arrive<BAR_Z1>(256);
    }
    zero(acc);
    bar_sync<BAR_ORD1>(256);
    mainloop<160, 2, 0, false, 0>(acc, sbase, grp, grp == 0 ? 52 : 20, grp == 0 ? NX : 64 - NX);
    mainloop<160, 2, 2, true, 0>(acc, sbase, grp, gh, total - gh);
    const uint32_t slab = buf + w * (16 * 320);
    const uint32_t addr = slab + (((l >> 3) & 1) * 8 + (l & 7)) * 80;
    const bool hi = l >= 16;
    bar_sync<BAR_BUF>(160);
    mbar_wait(dep0 + 32, 0);
    drain(acc, sbase, grp, total - 1);
    TS(3, 12);
    #pragma unroll
    for (int mi = 0; mi < 2; mi++) {
      #pragma unroll
      for (int jj = 0; jj < 10; jj++) {
        const float* a = &acc[mi][8 * jj];
        const int o0 = ((2 * jj) / 5) * 1280 + ((2 * jj) % 5) * 16, o1 = ((2 * jj + 1) / 5) * 1280 + ((2 * jj + 1) % 5) * 16;
        stsm4(addr + mi * 20480 + (hi ? o1 : o0), pack_bf16(a[0], a[1]), pack_bf16(a[2], a[3]), pack_bf16(a[4], a[5]), pack_bf16(a[6], a[7]));
      }
      fence_async_smem();
      __syncwarp();
      if (l == 0) {
        asm volatile("cp.reduce.async.bulk.tensor.3d.global.shared::cta.add.tile.bulk_group [%0, {%2, %3, %4}], [%1];"
          :: "l"((uint64_t)&maps.m[M_OUT]), "r"(slab + mi * 20480), "r"(0), "r"(rb * 128 + mi * 64 + w * 16), "r"(ct * 4) : "memory");
        bulk_commit();
      }
    }
    TS(3, 13);
    if (l == 0) {
      bulk_wait_read();
      if (w == 0) atomicAdd(&g_done, 1u);
    }
    TS(3, 15);
  }
}

typedef CUresult (*EncodeFn)(CUtensorMap*, CUtensorMapDataType, cuuint32_t, void*, const cuuint64_t*, const cuuint64_t*,
                             const cuuint32_t*, const cuuint32_t*, CUtensorMapInterleave, CUtensorMapSwizzle,
                             CUtensorMapL2promotion, CUtensorMapFloatOOBfill);

void make2d(EncodeFn enc, CUtensorMap* m, const void* p, uint64_t cols, uint64_t rows, uint32_t bc, uint32_t br, bool swz = true) {
  cuuint64_t gd[2] = {cols, rows}, gs[1] = {cols * 2};
  cuuint32_t bd[2] = {bc, br}, es[2] = {1, 1};
  enc(m, CU_TENSOR_MAP_DATA_TYPE_BFLOAT16, 2, const_cast<void*>(p), gd, gs, bd, es, CU_TENSOR_MAP_INTERLEAVE_NONE,
      swz ? CU_TENSOR_MAP_SWIZZLE_128B : CU_TENSOR_MAP_SWIZZLE_NONE, CU_TENSOR_MAP_L2_PROMOTION_L2_128B, CU_TENSOR_MAP_FLOAT_OOB_FILL_NONE);
}
void make3d(EncodeFn enc, CUtensorMap* m, const void* p, uint64_t cols, uint64_t rows, uint32_t cw, uint32_t nc, uint32_t br = 64) {
  cuuint64_t gd[3] = {cw, rows, cols / cw}, gs[2] = {cols * 2, cw * 2};
  cuuint32_t bd[3] = {cw, br, nc}, es[3] = {1, 1, 1};
  enc(m, CU_TENSOR_MAP_DATA_TYPE_BFLOAT16, 3, const_cast<void*>(p), gd, gs, bd, es, CU_TENSOR_MAP_INTERLEAVE_NONE,
      cw == 64 ? CU_TENSOR_MAP_SWIZZLE_128B : cw == 32 ? CU_TENSOR_MAP_SWIZZLE_64B : CU_TENSOR_MAP_SWIZZLE_NONE, CU_TENSOR_MAP_L2_PROMOTION_L2_128B, CU_TENSOR_MAP_FLOAT_OOB_FILL_NONE);
}

}

extern "C" void kernel_launch(void* const* d_in, const int* in_sizes, int n_in, void* d_out, int out_size) {
  const bf16* x = (const bf16*)d_in[0];
  const bf16* wsre = (const bf16*)d_in[1];
  const bf16* wsim = (const bf16*)d_in[2];
  const bf16* wdre = (const bf16*)d_in[3];
  const bf16* wdim = (const bf16*)d_in[4];
  const bf16* win = (const bf16*)d_in[6];
  const bf16* wsp = (const bf16*)d_in[7];
  const bf16* bsp = (const bf16*)d_in[8];
  const bf16* wout = (const bf16*)d_in[9];

  void* fn = nullptr;
  cudaDriverEntryPointQueryResult qr;
  cudaGetDriverEntryPoint("cuTensorMapEncodeTiled", &fn, cudaEnableDefault, &qr);
  EncodeFn enc = (EncodeFn)fn;
  void *abT, *z2, *h, *xn;
  cudaGetSymbolAddress(&xn, g_xn);
  cudaGetSymbolAddress(&abT, g_abT);
  cudaGetSymbolAddress(&z2, g_z2);
  cudaGetSymbolAddress(&h, g_h);

  Maps maps;
  make2d(enc, &maps.m[M_X], x, DM, SEQ, 64, 64);
  make2d(enc, &maps.m[M_XN], xn, DM, SEQ, 64, 64);
  make2d(enc, &maps.m[M_WSRE], wsre, SEQ, SEQ, 64, 64);
  make2d(enc, &maps.m[M_WSIM], wsim, SEQ, SEQ, 64, 64);
  make2d(enc, &maps.m[M_WSP], wsp, SEQ, SEQ, 64, 64);
  make2d(enc, &maps.m[M_H], h, FH, SEQ, 64, 64);
  make3d(enc, &maps.m[M_WIN3], win, FF, DM, 64, 3);
  make3d(enc, &maps.m[M_Z23], z2, FH, SEQ, 64, 3);
  make2d(enc, &maps.m[M_WDRE], wdre, DM, DM, 64, 160);
  make2d(enc, &maps.m[M_WDIM], wdim, DM, DM, 64, 160);
  make2d(enc, &maps.m[M_AB], abT, SEQ, 2 * DM, 64, 160);
  make3d(enc, &maps.m[M_WOUT], wout, DM, FH, 32, 5);
  make2d(enc, &maps.m[M_HS], h, FH, SEQ, 64, 16);
  make2d(enc, &maps.m[M_ZS], z2, FH, SEQ, 64, 32);
  make2d(enc, &maps.m[M_ABS], abT, SEQ, 2 * DM, 64, 40);
  make3d(enc, &maps.m[M_OUT], d_out, DM, SEQ, 40, 4, 16);

  cudaFuncSetAttribute(fused_kernel, cudaFuncAttributeMaxDynamicSharedMemorySize, SMEM_BYTES);
  fused_kernel<<<128, 384, SMEM_BYTES>>>(maps, x, win, wdre, bsp, (bf16*)d_out);
}
```

```cpp
#include <cuda_runtime.h>
#include <cuda_bf16.h>
#include <cuda.h>
#include <stdint.h>

namespace {

typedef __nv_bfloat16 bf16;

constexpr int SEQ = 2048, DM = 640, FF = 1536, FH = 768;
#define NXV 6
#define NOV 4
constexpr int NX = NXV;
constexpr int NO = NOV;
#define NSTB 5
#define PFB 1
constexpr int NST_A = 4, NST_B = NSTB, MAXST = 5;
constexpr int A_BYTES = 16384;
constexpr int BAR_OFF = 0;
constexpr int READY_OFF = 128;
constexpr int COLSUM_OFF = 256;
constexpr int ROWSTAT_OFF = 1024;
constexpr int ZSTAT_OFF = 2048;
constexpr int RED_OFF = 3072;
constexpr int RING_OFF = 4096;
constexpr int STAGE_A = 40960, STAGE_B = 36864;
constexpr int SMEM_BYTES = RING_OFF + 5 * STAGE_B + 40960;
constexpr int KB_A = 52 + NX + 12 - NO;
constexpr int KB_B = 84 - NX + NO;
constexpr float LN_EPS = 1e-5f;
constexpr unsigned POLL_LIMIT = 100000;
#define POLL_NS 100
#define PF_D 8
#define NORM2 1
#define Z1_NS 600
#define WATCH_NS 40

constexpr int BAR_ORD1 = 1, BAR_ORD2 = 2, BAR_WG1 = 3, BAR_WG2 = 4, BAR_LN = 5, BAR_BUF = 6, BAR_Z1 = 7, BAR_PUB1 = 8, BAR_PUB2 = 9,
              BAR_STATS = 10, BAR_U = 11;

enum { M_X, M_XN, M_WSRE, M_WSIM, M_WSP, M_H, M_WIN3, M_Z23, M_WDRE, M_WDIM, M_AB, M_WOUT, M_OUT, M_HS, M_ZS, M_ABS, M_COUNT };
struct Maps { CUtensorMap m[M_COUNT]; };

__device__ __align__(1024) bf16 g_abT[2 * DM * SEQ];
__device__ __align__(1024) bf16 g_z2[SEQ * FH];
__device__ __align__(1024) bf16 g_h[SEQ * FH];
__device__ __align__(1024) bf16 g_xn[SEQ * DM];
__device__ __align__(16) uint2 g_xstat[SEQ];
__device__ __align__(16) uint2 g_csum[5 * FH + DM];
__device__ __align__(16) uint2 g_zstat[64 * 128];
__device__ __align__(256) unsigned char g_flags[108 * 256];
constexpr int F_A = 0, F_B = 4, F_Z = 8, F_H = 12, F_XN = 28, F_Y = 44;
__device__ unsigned g_done;
#define TS(role, ev)
#define TC(i)

extern __shared__ __align__(1024) uint8_t smem[];

__device__ __forceinline__ uint32_t smem_u32(const void* p) { return (uint32_t)__cvta_generic_to_shared(p); }
__device__ __forceinline__ void mbar_init(uint32_t bar, uint32_t cnt) { asm volatile("mbarrier.init.shared::cta.b64 [%0], %1;" :: "r"(bar), "r"(cnt)); }
__device__ __forceinline__ void mbar_expect_tx(uint32_t bar, uint32_t bytes) { asm volatile("mbarrier.arrive.expect_tx.shared::cta.b64 _, [%0], %1;" :: "r"(bar), "r"(bytes) : "memory"); }
__device__ __forceinline__ void mbar_arrive(uint32_t bar) { asm volatile("mbarrier.arrive.shared::cta.b64 _, [%0];" :: "r"(bar) : "memory"); }
__device__ __forceinline__ void mbar_arrive_cluster(uint32_t bar, uint32_t cta) {
  asm volatile("{\n.reg .b32 ra;\nmapa.shared::cluster.u32 ra, %0, %1;\nmbarrier.arrive.shared::cluster.b64 _, [ra];\n}" :: "r"(bar), "r"(cta) : "memory");
}
__device__ __forceinline__ void mbar_wait(uint32_t bar, uint32_t parity) {
  asm volatile("{\n.reg .pred p;\n.reg .u32 n;\nmov.u32 n, 0;\n"
               "LW: mbarrier.try_wait.parity.shared::cta.b64 p, [%0], %1, 2000;\n@p bra LD;\n"
               "add.u32 n, n, 1;\nsetp.lt.u32 p, n, 20000;\n@p bra LW;\nLD:\n}" :: "r"(bar), "r"(parity) : "memory");
}
__device__ __forceinline__ void tma_load_2d(uint32_t dst, const CUtensorMap* map, uint32_t bar, int c0, int c1) {
  asm volatile("cp.async.bulk.tensor.2d.shared::cluster.global.mbarrier::complete_tx::bytes [%0], [%1, {%3, %4}], [%2];"
    :: "r"(dst), "l"((uint64_t)map), "r"(bar), "r"(c0), "r"(c1) : "memory");
}
__device__ __forceinline__ void tma_load_3d(uint32_t dst, const CUtensorMap* map, uint32_t bar, int c0, int c1, int c2) {
  asm volatile("cp.async.bulk.tensor.3d.shared::cluster.global.mbarrier::complete_tx::bytes [%0], [%1, {%3, %4, %5}], [%2];"
    :: "r"(dst), "l"((uint64_t)map), "r"(bar), "r"(c0), "r"(c1), "r"(c2) : "memory");
}
__device__ __forceinline__ void tma_load_2d_mc(uint32_t dst, const CUtensorMap* map, uint32_t bar, int c0, int c1, uint16_t mask) {
  asm volatile("cp.async.bulk.tensor.2d.shared::cluster.global.mbarrier::complete_tx::bytes.multicast::cluster [%0], [%1, {%3, %4}], [%2], %5;"
    :: "r"(dst), "l"((uint64_t)map), "r"(bar), "r"(c0), "r"(c1), "h"(mask) : "memory");
}
__device__ __forceinline__ void tma_store_2d(const CUtensorMap* map, uint32_t src, int c0, int c1) {
  asm volatile("cp.async.bulk.tensor.2d.global.shared::cta.bulk_group [%0, {%2, %3}], [%1];"
    :: "l"((uint64_t)map), "r"(src), "r"(c0), "r"(c1) : "memory");
}
__device__ __forceinline__ void tma_store_3d(const CUtensorMap* map, uint32_t src, int c0, int c1, int c2) {
  asm volatile("cp.async.bulk.tensor.3d.global.shared::cta.bulk_group [%0, {%2, %3, %4}], [%1];"
    :: "l"((uint64_t)map), "r"(src), "r"(c0), "r"(c1), "r"(c2) : "memory");
}
__device__ __forceinline__ void tma_reduce_2d(const CUtensorMap* map, uint32_t src, int c0, int c1) {
  asm volatile("cp.reduce.async.bulk.tensor.2d.global.shared::cta.add.tile.bulk_group [%0, {%2, %3}], [%1];"
    :: "l"((uint64_t)map), "r"(src), "r"(c0), "r"(c1) : "memory");
}
__device__ __forceinline__ void bulk_wait_all() { asm volatile("cp.async.bulk.wait_group 0;" ::: "memory"); }
__device__ __forceinline__ void bulk_commit() { asm volatile("cp.async.bulk.commit_group;" ::: "memory"); }
__device__ __forceinline__ void bulk_wait_read() { asm volatile("cp.async.bulk.wait_group.read 0;" ::: "memory"); }
__device__ __forceinline__ void fence_async_smem() { asm volatile("fence.proxy.async.shared::cta;" ::: "memory"); }
__device__ __forceinline__ void fence_async_global() { asm volatile("fence.proxy.async.global;" ::: "memory"); }
__device__ __forceinline__ void wgmma_fence() { asm volatile("wgmma.fence.sync.aligned;" ::: "memory"); }
__device__ __forceinline__ void wgmma_commit() { asm volatile("wgmma.commit_group.sync.aligned;" ::: "memory"); }
template<int N> __device__ __forceinline__ void wgmma_wait() { asm volatile("wgmma.wait_group.sync.aligned %0;" :: "n"(N) : "memory"); }
template<int ID> __device__ __forceinline__ void bar_sync(int n) { asm volatile("bar.sync %0, %1;" :: "n"(ID), "r"(n) : "memory"); }
template<int ID> __device__ __forceinline__ void bar_arrive(int n) { asm volatile("bar.arrive %0, %1;" :: "n"(ID), "r"(n) : "memory"); }
__device__ __forceinline__ void cluster_wait() { asm volatile("barrier.cluster.wait.aligned;" ::: "memory"); }
__device__ __forceinline__ uint64_t desc64(uint32_t lo, uint32_t hi) { return (uint64_t)lo | ((uint64_t)hi << 32); }
__device__ __forceinline__ uint4 ld_vol4(const uint4* p) {
  uint4 v; asm volatile("ld.relaxed.gpu.global.v4.u32 {%0,%1,%2,%3}, [%4];" : "=r"(v.x), "=r"(v.y), "=r"(v.z), "=r"(v.w) : "l"(p) : "memory"); return v;
}
__device__ __forceinline__ uint2 ld_vol2(const uint2* p) {
  uint2 v; asm volatile("ld.relaxed.gpu.global.v2.u32 {%0,%1}, [%2];" : "=r"(v.x), "=r"(v.y) : "l"(p) : "memory"); return v;
}
__device__ __forceinline__ void st_vol4(uint4* p, uint32_t a, uint32_t b, uint32_t c, uint32_t d) {
  asm volatile("st.relaxed.gpu.global.v4.u32 [%0], {%1,%2,%3,%4};" :: "l"(p), "r"(a), "r"(b), "r"(c), "r"(d) : "memory");
}
__device__ __forceinline__ void st_vol2(uint2* p, uint32_t a, uint32_t b) {
  asm volatile("st.relaxed.gpu.global.v2.u32 [%0], {%1,%2};" :: "l"(p), "r"(a), "r"(b) : "memory");
}
__device__ __forceinline__ void stg128(void* p, uint4 v) {
  asm volatile("st.global.v4.u32 [%0], {%1,%2,%3,%4};" :: "l"(p), "r"(v.x), "r"(v.y), "r"(v.z), "r"(v.w));
}
__device__ __forceinline__ unsigned ld_relaxed(const unsigned* p) {
  unsigned v; asm volatile("ld.relaxed.gpu.global.u32 %0, [%1];" : "=r"(v) : "l"(p) : "memory"); return v;
}
__device__ __forceinline__ uint32_t pack_bf16(float lo, float hi) {
  uint32_t r; asm("cvt.rn.bf16x2.f32 %0, %1, %2;" : "=r"(r) : "f"(hi), "f"(lo)); return r;
}
__device__ __forceinline__ float bf_lo(uint32_t v) { return __uint_as_float(v << 16); }
__device__ __forceinline__ float bf_hi(uint32_t v) { return __uint_as_float(v & 0xFFFF0000u); }
__device__ __forceinline__ void stsm4(uint32_t addr, uint32_t a, uint32_t b, uint32_t c, uint32_t d) {
  asm volatile("stmatrix.sync.aligned.m8n8.x4.shared.b16 [%0], {%1,%2,%3,%4};" :: "r"(addr), "r"(a), "r"(b), "r"(c), "r"(d));
}
__device__ __forceinline__ void stsm4_t(uint32_t addr, uint32_t a, uint32_t b, uint32_t c, uint32_t d) {
  asm volatile("stmatrix.sync.aligned.m8n8.x4.trans.shared.b16 [%0], {%1,%2,%3,%4};" :: "r"(addr), "r"(a), "r"(b), "r"(c), "r"(d));
}
__device__ __forceinline__ void ldsm4(uint32_t addr, uint32_t& a, uint32_t& b, uint32_t& c, uint32_t& d) {
  asm volatile("ldmatrix.sync.aligned.m8n8.x4.shared.b16 {%0,%1,%2,%3}, [%4];" : "=r"(a), "=r"(b), "=r"(c), "=r"(d) : "r"(addr));
}
__device__ __forceinline__ uint4 lds128(uint32_t a) {
  uint4 v; asm volatile("ld.shared.v4.u32 {%0,%1,%2,%3}, [%4];" : "=r"(v.x), "=r"(v.y), "=r"(v.z), "=r"(v.w) : "r"(a)); return v;
}
__device__ __forceinline__ void sts128(uint32_t a, uint32_t x, uint32_t y, uint32_t z, uint32_t w) {
  asm volatile("st.shared.v4.u32 [%0], {%1,%2,%3,%4};" :: "r"(a), "r"(x), "r"(y), "r"(z), "r"(w));
}
__device__ __forceinline__ uint32_t hmul2_bf16(uint32_t a, uint32_t b) {
  uint32_t r; asm("mul.rn.bf16x2 %0, %1, %2;" : "=r"(r) : "r"(a), "r"(b)); return r;
}
__device__ __forceinline__ uint32_t hadd2_bf16(uint32_t a, uint32_t b) {
  uint32_t r; asm("add.rn.bf16x2 %0, %1, %2;" : "=r"(r) : "r"(a), "r"(b)); return r;
}
__device__ __forceinline__ uint32_t hfma2_bf16(uint32_t a, uint32_t b, uint32_t c) {
  uint32_t r; asm("fma.rn.bf16x2 %0, %1, %2, %3;" : "=r"(r) : "r"(a), "r"(b), "r"(c)); return r;
}
__device__ __forceinline__ float gelu_tanh(float v) {
  float u = v * fmaf(0.0356774081f, v * v, 0.7978845608f);
  float t; asm("tanh.approx.f32 %0, %1;" : "=f"(t) : "f"(u));
  float hv = 0.5f * v;
  return fmaf(hv, t, hv);
}

template<int TB>
__device__ __forceinline__ void wgmma_n192(float (&d)[96], uint64_t da, uint64_t db, int scale_d) {
  asm volatile("{\n.reg .pred p;\nsetp.ne.b32 p, %98, 0;\n"
   "wgmma.mma_async.sync.aligned.m64n192k16.f32.bf16.bf16 {%0,%1,%2,%3,%4,%5,%6,%7,%8,%9,%10,%11,%12,%13,%14,%15,%16,%17,%18,%19,%20,%21,%22,%23,%24,%25,%26,%27,%28,%29,%30,%31,%32,%33,%34,%35,%36,%37,%38,%39,%40,%41,%42,%43,%44,%45,%46,%47,%48,%49,%50,%51,%52,%53,%54,%55,%56,%57,%58,%59,%60,%61,%62,%63,%64,%65,%66,%67,%68,%69,%70,%71,%72,%73,%74,%75,%76,%77,%78,%79,%80,%81,%82,%83,%84,%85,%86,%87,%88,%89,%90,%91,%92,%93,%94,%95}, %96, %97, p, 1, 1, 0, %99;\n}"
   : "+f"(d[0]),"+f"(d[1]),"+f"(d[2]),"+f"(d[3]),"+f"(d[4]),"+f"(d[5]),"+f"(d[6]),"+f"(d[7]),"+f"(d[8]),"+f"(d[9]),"+f"(d[10]),"+f"(d[11]),"+f"(d[12]),"+f"(d[13]),"+f"(d[14]),"+f"(d[15]),"+f"(d[16]),"+f"(d[17]),"+f"(d[18]),"+f"(d[19]),"+f"(d[20]),"+f"(d[21]),"+f"(d[22]),"+f"(d[23]),"+f"(d[24]),"+f"(d[25]),"+f"(d[26]),"+f"(d[27]),"+f"(d[28]),"+f"(d[29]),"+f"(d[30]),"+f"(d[31]),"+f"(d[32]),"+f"(d[33]),"+f"(d[34]),"+f"(d[35]),"+f"(d[36]),"+f"(d[37]),"+f"(d[38]),"+f"(d[39]),"+f"(d[40]),"+f"(d[41]),"+f"(d[42]),"+f"(d[43]),"+f"(d[44]),"+f"(d[45]),"+f"(d[46]),"+f"(d[47]),"+f"(d[48]),"+f"(d[49]),"+f"(d[50]),"+f"(d[51]),"+f"(d[52]),"+f"(d[53]),"+f"(d[54]),"+f"(d[55]),"+f"(d[56]),"+f"(d[57]),"+f"(d[58]),"+f"(d[59]),"+f"(d[60]),"+f"(d[61]),"+f"(d[62]),"+f"(d[63]),"+f"(d[64]),"+f"(d[65]),"+f"(d[66]),"+f"(d[67]),"+f"(d[68]),"+f"(d[69]),"+f"(d[70]),"+f"(d[71]),"+f"(d[72]),"+f"(d[73]),"+f"(d[74]),"+f"(d[75]),"+f"(d[76]),"+f"(d[77]),"+f"(d[78]),"+f"(d[79]),"+f"(d[80]),"+f"(d[81]),"+f"(d[82]),"+f"(d[83]),"+f"(d[84]),"+f"(d[85]),"+f"(d[86]),"+f"(d[87]),"+f"(d[88]),"+f"(d[89]),"+f"(d[90]),"+f"(d[91]),"+f"(d[92]),"+f"(d[93]),"+f"(d[94]),"+f"(d[95])
   : "l"(da), "l"(db), "r"(scale_d), "n"(TB));
}
template<int TB>
__device__ __forceinline__ void wgmma_n160(float (&d)[80], uint64_t da, uint64_t db, int scale_d) {
  asm volatile("{\n.reg .pred p;\nsetp.ne.b32 p, %82, 0;\n"
   "wgmma.mma_async.sync.aligned.m64n160k16.f32.bf16.bf16 {%0,%1,%2,%3,%4,%5,%6,%7,%8,%9,%10,%11,%12,%13,%14,%15,%16,%17,%18,%19,%20,%21,%22,%23,%24,%25,%26,%27,%28,%29,%30,%31,%32,%33,%34,%35,%36,%37,%38,%39,%40,%41,%42,%43,%44,%45,%46,%47,%48,%49,%50,%51,%52,%53,%54,%55,%56,%57,%58,%59,%60,%61,%62,%63,%64,%65,%66,%67,%68,%69,%70,%71,%72,%73,%74,%75,%76,%77,%78,%79}, %80, %81, p, 1, 1, 0, %83;\n}"
   : "+f"(d[0]),"+f"(d[1]),"+f"(d[2]),"+f"(d[3]),"+f"(d[4]),"+f"(d[5]),"+f"(d[6]),"+f"(d[7]),"+f"(d[8]),"+f"(d[9]),"+f"(d[10]),"+f"(d[11]),"+f"(d[12]),"+f"(d[13]),"+f"(d[14]),"+f"(d[15]),"+f"(d[16]),"+f"(d[17]),"+f"(d[18]),"+f"(d[19]),"+f"(d[20]),"+f"(d[21]),"+f"(d[22]),"+f"(d[23]),"+f"(d[24]),"+f"(d[25]),"+f"(d[26]),"+f"(d[27]),"+f"(d[28]),"+f"(d[29]),"+f"(d[30]),"+f"(d[31]),"+f"(d[32]),"+f"(d[33]),"+f"(d[34]),"+f"(d[35]),"+f"(d[36]),"+f"(d[37]),"+f"(d[38]),"+f"(d[39]),"+f"(d[40]),"+f"(d[41]),"+f"(d[42]),"+f"(d[43]),"+f"(d[44]),"+f"(d[45]),"+f"(d[46]),"+f"(d[47]),"+f"(d[48]),"+f"(d[49]),"+f"(d[50]),"+f"(d[51]),"+f"(d[52]),"+f"(d[53]),"+f"(d[54]),"+f"(d[55]),"+f"(d[56]),"+f"(d[57]),"+f"(d[58]),"+f"(d[59]),"+f"(d[60]),"+f"(d[61]),"+f"(d[62]),"+f"(d[63]),"+f"(d[64]),"+f"(d[65]),"+f"(d[66]),"+f"(d[67]),"+f"(d[68]),"+f"(d[69]),"+f"(d[70]),"+f"(d[71]),"+f"(d[72]),"+f"(d[73]),"+f"(d[74]),"+f"(d[75]),"+f"(d[76]),"+f"(d[77]),"+f"(d[78]),"+f"(d[79])
   : "l"(da), "l"(db), "r"(scale_d), "n"(TB));
}

template<int N, int TB>
__device__ __forceinline__ void wgmma_n(float (&d)[N / 2], uint64_t da, uint64_t db) {
  if constexpr (N == 192) wgmma_n192<TB>(d, da, db, 1); else wgmma_n160<TB>(d, da, db, 1);
}

template<int M, int R>
__device__ __forceinline__ void pin(float (&acc)[M][R]) {
  #pragma unroll
  for (int mi = 0; mi < M; mi++)
    #pragma unroll
    for (int i = 0; i < R; i++) asm volatile("" : "+f"(acc[mi][i]) :: "memory");
}
template<int M, int R>
__device__ __forceinline__ void zero(float (&acc)[M][R]) {
  #pragma unroll
  for (int mi = 0; mi < M; mi++)
    #pragma unroll
    for (int i = 0; i < R; i++) acc[mi][i] = 0.f;
  pin(acc);
}

template<int N, int M, int TB, bool CONT, int ORD_BAR, bool AOWN = false>
__device__ __forceinline__ void mainloop(float (&acc)[M][N / 2], uint32_t sbase, int grp, int g0, int nk, int m0 = 0) {
  const uint32_t full0 = sbase + BAR_OFF, empty0 = full0 + 8 * MAXST, ring = sbase + RING_OFF;
  const int nst = grp == 0 ? NST_A : NST_B, total = grp == 0 ? KB_A : KB_B;
  const uint32_t sstep = (grp == 0 ? STAGE_A : STAGE_B) >> 4;
  const int t = threadIdx.x & 127;
  const uint32_t da0 = (((ring + m0 * 8192) & 0x3FFFF) >> 4) | 0x10000u;
  const uint32_t db0 = (((ring + A_BYTES) & 0x3FFFF) >> 4) | ((TB == 2 ? 256u : TB ? 512u : 1u) << 16);
  constexpr uint32_t HI_A = 0x40000040u, HI_B = TB == 2 ? 0x80000020u : 0x40000040u;
  int s = g0 % nst, ph = (g0 / nst) & 1, ps = s == 0 ? nst - 1 : s - 1;
  #pragma unroll 1
  for (int g = g0; g < g0 + nk; g++) {
    const uint32_t so = s * sstep;
    mbar_wait(full0 + 8 * s, ph);
    wgmma_fence();
    #pragma unroll
    for (int k = 0; k < 4; k++) {
      const uint64_t db = desc64(db0 + so + (TB == 2 ? k * 64 : TB ? k * 128 : k * 2), HI_B);
      #pragma unroll
      for (int mi = 0; mi < M; mi++)
        wgmma_n<N, TB != 0>(acc[mi], desc64(AOWN ? da0 + ((NST_A * STAGE_A) >> 4) + (g - g0) * 512 + mi * 1536 + k * 2 : da0 + so + mi * 512 + k * 2, HI_A), db);
    }
    wgmma_commit();
    if (ORD_BAR != 0 && g == g0 + nk - 1) bar_arrive<ORD_BAR>(256);
    wgmma_wait<1>();
    if (t < 2 * M && (CONT || g > g0) && g - 1 + nst < total) mbar_arrive_cluster(empty0 + 8 * ps, t & 1);
    ps = s;
    if (++s == nst) { s = 0; ph ^= 1; }
  }
}
template<int M, int R>
__device__ __forceinline__ void drain(float (&acc)[M][R], uint32_t sbase, int grp, int glast) {
  wgmma_wait<0>();
  pin(acc);
  const int t = threadIdx.x & 127;
  const int nst = grp == 0 ? NST_A : NST_B, total = grp == 0 ? KB_A : KB_B;
  if (t < 2 * M && glast + nst < total) mbar_arrive_cluster(sbase + BAR_OFF + 8 * MAXST + 8 * (glast % nst), t & 1);
}

__device__ __forceinline__ void set_flag(int slot, int byte, unsigned epoch) {
  asm volatile("st.relaxed.gpu.global.u8 [%0], %1;" :: "l"(g_flags + slot * 256 + byte), "r"(epoch & 255u) : "memory");
}
__device__ __forceinline__ unsigned get_flag(int slot, int byte) {
  unsigned v; asm volatile("ld.relaxed.gpu.global.u8 %0, [%1];" : "=r"(v) : "l"(g_flags + slot * 256 + byte) : "memory"); return v;
}
__device__ __forceinline__ void publish(int slot, int byte, unsigned epoch) {
  asm volatile("fence.acq_rel.gpu;" ::: "memory");
  set_flag(slot, byte, epoch);
}
__device__ __forceinline__ float sum8(uint4 v) {
  return ((bf_lo(v.x) + bf_hi(v.x)) + (bf_lo(v.y) + bf_hi(v.y))) + ((bf_lo(v.z) + bf_hi(v.z)) + (bf_lo(v.w) + bf_hi(v.w)));
}
__device__ __forceinline__ uint4 ldg128(const void* p) {
  uint4 v; asm volatile("ld.global.nc.v4.u32 {%0,%1,%2,%3}, [%4];" : "=r"(v.x), "=r"(v.y), "=r"(v.z), "=r"(v.w) : "l"(p)); return v;
}

__device__ __forceinline__ void ln_rows(const uint4 (&rv)[5], uint32_t buf, int cta, unsigned epoch) {
  const int t = threadIdx.x - 128, row = cta * 16 + (t >> 4), c = t & 15;
  const float sh = __shfl_sync(0xffffffffu, bf_lo(rv[0].x), t & 16);
  float d[40], s = 0.f, q = 0.f;
  #pragma unroll
  for (int j = 0; j < 5; j++) {
    const uint32_t u[4] = {rv[j].x, rv[j].y, rv[j].z, rv[j].w};
    #pragma unroll
    for (int e = 0; e < 4; e++) {
      const float d0 = bf_lo(u[e]) - sh, d1 = bf_hi(u[e]) - sh;
      d[j * 8 + e * 2] = d0; d[j * 8 + e * 2 + 1] = d1;
      s += d0 + d1; q = fmaf(d0, d0, q); q = fmaf(d1, d1, q);
    }
  }
  #pragma unroll
  for (int o = 1; o < 16; o <<= 1) { s += __shfl_xor_sync(0xffffffffu, s, o); q += __shfl_xor_sync(0xffffffffu, q, o); }
  const float md = s * (1.f / DM);
  const float r = rsqrtf(fmaxf(fmaf(q, 1.f / DM, -md * md), 0.f) + LN_EPS), o = -md * r;
  if (c == 0) st_vol2(&g_xstat[row], __float_as_uint(r), (__float_as_uint(-(md + sh) * r) & ~255u) | (epoch & 255u));
  #pragma unroll
  for (int j = 0; j < 5; j++) {
    const float* a = &d[j * 8];
    sts128(buf + (t >> 4) * 1280 + (c + 16 * j) * 16,
           pack_bf16(fmaf(a[0], r, o), fmaf(a[1], r, o)), pack_bf16(fmaf(a[2], r, o), fmaf(a[3], r, o)),
           pack_bf16(fmaf(a[4], r, o), fmaf(a[5], r, o)), pack_bf16(fmaf(a[6], r, o), fmaf(a[7], r, o)));
  }
  fence_async_smem();
  bar_arrive<BAR_LN>(288);
}

__device__ __forceinline__ void weight_sums(const bf16* __restrict__ win, const bf16* __restrict__ wdre, int j, unsigned epoch) {
  const int t = threadIdx.x & 127, w = t >> 5, l = t & 31;
  const int cj = min(j, 59), cg = cj % 12, rg = cj / 12, wr = j * 10 + min(t >> 3, 9);
  uint4 cv[8], rv[10];
  #pragma unroll
  for (int i = 0; i < 8; i++) cv[i] = ldg128(reinterpret_cast<const uint4*>(win + (size_t)(rg * 128 + w * 32 + i * 4 + (l >> 3)) * FF + FH + cg * 64) + (l & 7));
  #pragma unroll
  for (int i = 0; i < 10; i++) rv[i] = ldg128(reinterpret_cast<const uint4*>(wdre + (size_t)wr * DM) + (l & 7) + 8 * i);
  float v[8];
  #pragma unroll
  for (int e = 0; e < 8; e++) v[e] = 0.f;
  #pragma unroll
  for (int i = 0; i < 8; i++) {
    v[0] += bf_lo(cv[i].x); v[1] += bf_hi(cv[i].x); v[2] += bf_lo(cv[i].y); v[3] += bf_hi(cv[i].y);
    v[4] += bf_lo(cv[i].z); v[5] += bf_hi(cv[i].z); v[6] += bf_lo(cv[i].w); v[7] += bf_hi(cv[i].w);
  }
  #pragma unroll
  for (int st = 0; st < 2; st++) {
    const int n = 4 >> st;
    const bool up = (l & (4 * n)) != 0;
    #pragma unroll
    for (int e = 0; e < 4; e++)
      if (e < n) { const float keep = up ? v[e + n] : v[e], send = up ? v[e] : v[e + n]; v[e] = keep + __shfl_xor_sync(0xffffffffu, send, 4 * n); }
  }
  float* red = reinterpret_cast<float*>(smem + RED_OFF);
  *reinterpret_cast<float2*>(red + w * 64 + (l & 7) * 8 + (l >> 3) * 2) = make_float2(v[0], v[1]);
  float s = 0.f;
  #pragma unroll
  for (int i = 0; i < 10; i++) s += sum8(rv[i]);
  #pragma unroll
  for (int o = 1; o < 8; o <<= 1) s += __shfl_xor_sync(0xffffffffu, s, o);
  if ((l & 7) == 0) st_vol2(&g_csum[5 * FH + wr], __float_as_uint(s), epoch);
  bar_sync<BAR_WG1>(128);
  if (t < 64) st_vol2(&g_csum[rg * FH + cg * 64 + t], __float_as_uint((red[t] + red[64 + t]) + (red[128 + t] + red[192 + t])), epoch);
}

__device__ __forceinline__ void gather96(const uint2* src, float* dst, unsigned epoch) {
  unsigned it = 0;
  while (true) {
    bool ok = true;
    uint2 u[15];
    #pragma unroll
    for (int j = 0; j < 15; j++) u[j] = ld_vol2(src + (j % 5) * FH + (j / 5) * 32);
    #pragma unroll
    for (int j = 0; j < 15; j++) ok = ok && u[j].y == epoch;
    #pragma unroll
    for (int j = 0; j < 3; j++)
      dst[j * 32] = ((__uint_as_float(u[j * 5].x) + __uint_as_float(u[j * 5 + 1].x)) + (__uint_as_float(u[j * 5 + 2].x) + __uint_as_float(u[j * 5 + 3].x))) + __uint_as_float(u[j * 5 + 4].x);
    if (ok || ++it > POLL_LIMIT) break;
    __nanosleep(2 * POLL_NS);
  }
}

__device__ __forceinline__ void a_entry(int g, int grp, int ct, int& mi, int& kb) {
  if (g < 10) { mi = M_X; kb = g; }
  else if (g < 20) { mi = M_XN; kb = g - 10; }
  else if (g < 52) { mi = grp == 0 ? M_WSP : M_WSRE; kb = g - 20; }
  else if (grp == 0) {
    if (g < 52 + NX) { mi = M_WSIM; kb = g - 52 + 32 - NX; }
    else {
      const int i = g - 52 - NX;
      mi = M_H; kb = i < 3 ? ct * 3 + i : i < 6 ? (ct ^ 1) * 3 + i - 3 : ((ct >> 1) ^ 1) * 6 + i - 6;
    }
  } else {
    if (g < 84 - NX) { mi = M_WSIM; kb = g - 52; }
    else { mi = M_H; kb = ((ct >> 1) ^ 1) * 6 + g - (84 - NX) + 6 - NO; }
  }
}

__global__ void __cluster_dims__(2, 1, 1) __launch_bounds__(384, 1)
fused_kernel(const __grid_constant__ Maps maps, const bf16* __restrict__ x, const bf16* __restrict__ win, const bf16* __restrict__ wdre,
             const bf16* __restrict__ bsp, bf16* __restrict__ out) {
  const uint32_t sbase = smem_u32(smem);
  const uint32_t full0 = sbase + BAR_OFF, empty0 = full0 + 8 * MAXST, dep0 = empty0 + 8 * MAXST, ring = sbase + RING_OFF;
  const int tid = threadIdx.x, wg = __shfl_sync(0xffffffffu, tid >> 7, 0);
  const int cta = blockIdx.x, rank = cta & 1, grp = (cta >> 1) & 1, rb = cta >> 3, ct = ((cta >> 2) & 1) * 2 + rank;
  const int total = grp == 0 ? KB_A : KB_B, gh = grp == 0 ? 52 + NX : 84 - NX;
  const uint32_t stage_bytes = grp == 0 ? STAGE_A : STAGE_B;
  const int nst = grp == 0 ? NST_A : NST_B;
  const uint32_t buf = ring + nst * stage_bytes;

  uint4 rv[5];
  if (wg != 0) {
    #pragma unroll
    for (int j = 0; j < 5; j++) rv[j] = ldg128(reinterpret_cast<const uint4*>(x + (size_t)(cta * 16 + ((tid - 128) >> 4)) * DM) + (tid & 15) + 16 * j);
  }
  const unsigned epoch = (ld_relaxed(&g_done) >> 7) + 1u;
  if (tid == 0) {
    TS(0, 0);
    for (int s = 0; s < MAXST; s++) { mbar_init(full0 + 8 * s, 2); mbar_init(empty0 + 8 * s, 4); mbar_init(dep0 + 8 * s, 1); }
    *reinterpret_cast<volatile int*>(smem + READY_OFF) = 0;
    asm volatile("fence.mbarrier_init.release.cluster;" ::: "memory");
  }
  __syncthreads();
  asm volatile("barrier.cluster.arrive.relaxed.aligned;" ::: "memory");

  if (wg == 0) {
    asm volatile("setmaxnreg.dec.sync.aligned.u32 40;");
    const int warp = tid >> 5, lane = tid & 31;
    if (warp == 0) {
      const int row = rb * 128;
      if (lane == 0) {
        for (int g = 0; g < nst; g++) {
          mbar_expect_tx(full0 + 8 * g, A_BYTES);
          tma_load_2d(ring + g * stage_bytes, &maps.m[M_X], full0 + 8 * g, g * 64, row);
          tma_load_2d(ring + g * stage_bytes + 8192, &maps.m[M_X], full0 + 8 * g, g * 64, row + 64);
        }
      }
      __syncwarp();
      cluster_wait();
      if (lane == 0) {
        int s = 0, ph = 0;
        #pragma unroll 1
        for (int g = nst; g < total; g++) {
          int mi, kb;
          a_entry(g, grp, ct, mi, kb);
          if (g == 10 || g == gh + 3 - 3 * grp) { TS(0, g > 10 ? 3 : 1); mbar_wait(dep0 + (g > 10 ? 24 : 0), 0); fence_async_global(); TS(0, g > 10 ? 4 : 2); }
          mbar_wait(empty0 + 8 * s, ph);
          if (grp == 0 && g >= gh && g < gh + 6) {
            if (g < gh + 3) {
              mbar_arrive(full0 + 8 * s);
            } else {
              mbar_expect_tx(full0 + 8 * s, A_BYTES);
              tma_load_2d(ring + s * stage_bytes, &maps.m[mi], full0 + 8 * s, kb * 64, row);
              tma_load_2d(ring + s * stage_bytes + 8192, &maps.m[mi], full0 + 8 * s, kb * 64, row + 64);
            }
          } else {
            mbar_expect_tx(full0 + 8 * s, A_BYTES);
            tma_load_2d_mc(ring + s * stage_bytes + rank * 8192, &maps.m[mi], full0 + 8 * s, kb * 64, row + rank * 64, 3);
          }
          if (++s == nst) { s = 0; ph ^= 1; }
          if (g + PF_D < gh && (PFB || grp == 0)) {
            a_entry(g + PF_D, grp, ct, mi, kb);
            if (mi >= M_WSRE && (kb & 1) == (ct >> 1))
              asm volatile("cp.async.bulk.prefetch.tensor.2d.L2.global.tile [%0, {%1, %2}];" :: "l"((uint64_t)&maps.m[mi]), "r"(kb * 64), "r"(row + rank * 64) : "memory");
          }
        }
        TS(0, 5);
      }
    } else if (warp == 1) {
      if (lane == 0) {
        int s = 0, ph = 1;
        int have = 0;
        #pragma unroll 1
        for (int g = 0; g < total; g++) {
          int mi, kb, c;
          a_entry(g, grp, ct, mi, kb);
          const bool nmaj = g >= gh || (grp == 0 && g < 52);
          uint32_t bytes = 20480;
          if (g >= gh) { mi = M_WOUT; c = ct * 5; }
          else if (g >= 52) { mi = M_AB; c = DM + ct * 160; }
          else if (grp == 0) { mi = g < 20 ? M_WIN3 : M_Z23; c = 3 * ct + (g < 10 ? 12 : 0); bytes = 24576; }
          else { mi = g < 10 ? M_WDRE : g < 20 ? M_WDIM : M_AB; c = ct * 160; }
          if (g >= 20 && g < 52 && ((g - 20) >> 1) >= have) {
            if (g == 20) TS(1, 0);
            unsigned it = 0;
            while ((have = *reinterpret_cast<volatile int*>(smem + READY_OFF)) <= ((g - 20) >> 1) && ++it < 50 * POLL_LIMIT) {}
            fence_async_global();
            if (g == 20) { TS(1, 1); TC(1); }
          }
          if (g == 52) { TS(1, 2); mbar_wait(dep0 + 16, 0); fence_async_global(); TS(1, 3); TC(2); }
          const uint32_t dst = ring + s * stage_bytes + A_BYTES, fb = full0 + 8 * s;
          mbar_wait(empty0 + 8 * s, ph);
          if (++s == nst) { s = 0; ph ^= 1; }
          mbar_expect_tx(fb, bytes);
          if (nmaj) tma_load_3d(dst, &maps.m[mi], fb, 0, kb * 64, c);
          else tma_load_2d(dst, &maps.m[mi], fb, kb * 64, c);
        }
      }
      __syncwarp();
      cluster_wait();
    } else if (warp == 2) {
      if (lane < M_COUNT) asm volatile("prefetch.tensormap [%0];" :: "l"((uint64_t)&maps.m[lane]) : "memory");
      cluster_wait();
      {
        unsigned it = 0;
        uint2 v[4];
        while (true) {
          bool ok = true;
          #pragma unroll
          for (int i = 0; i < 4; i++) { v[i] = ld_vol2(&g_xstat[rb * 128 + i * 32 + lane]); ok = ok && ((v[i].y ^ epoch) & 255u) == 0; }
          if (ok || ++it > POLL_LIMIT) break;
          __nanosleep(POLL_NS);
        }
        #pragma unroll
        for (int i = 0; i < 4; i++) reinterpret_cast<uint2*>(smem + ROWSTAT_OFF)[i * 32 + lane] = make_uint2(v[i].x, v[i].y & ~255u);
        __syncwarp();
        TS(0, 6);
        if (grp == 0) bar_arrive<BAR_STATS>(320); else bar_arrive<BAR_STATS>(192);
      }
      #pragma unroll 1
      for (int i = 0; i < 5; i++) {
        const int d = i == 3 ? 4 : i == 4 ? 3 : i;
        const int slot = d == 0 ? F_XN + rb : d == 4 ? F_Y + rb * 4 + ct : d == 3 ? F_H + rb : d == 2 ? F_B + ct : grp == 0 ? F_Z + ct : F_A + ct;
        const int byte = d == 0 ? lane & 7 : d == 4 ? 0 : d == 3 ? lane & 3 : lane & 15;
        unsigned it = 0, m;
        while ((m = __ballot_sync(0xffffffffu, get_flag(slot, byte) != (epoch & 255u))) != 0 && ++it < POLL_LIMIT) {
          if (d == 1 && lane == 0) *reinterpret_cast<volatile int*>(smem + READY_OFF) = __ffs(m) - 1;
          __nanosleep(WATCH_NS);
        }
        if (d == 1 && lane == 0) *reinterpret_cast<volatile int*>(smem + READY_OFF) = 16;
        if (d < 4) TS(0, 8 + d * 2); else TS(0, 7);
        fence_async_global();
        __syncwarp();
        if (lane == 0 && d != 1) mbar_arrive(dep0 + 8 * d);
      }
    } else {
      cluster_wait();
      bar_sync<BAR_LN>(288);
      if (lane == 0) {
        TS(1, 5);
        asm volatile("cp.async.bulk.global.shared::cta.bulk_group [%0], [%1], 20480;" :: "l"(g_xn + (size_t)cta * 16 * DM), "r"(buf) : "memory");
        bulk_commit();
        bulk_wait_all();
        set_flag(F_XN + rb, cta & 7, epoch);
        TS(1, 6);
      }
      __syncwarp();
      if (grp == 0) {
        #pragma unroll 1
        for (int i = 0; i < 2; i++) gather96(&g_csum[ct * 192 + i * 96 + lane], reinterpret_cast<float*>(smem + COLSUM_OFF) + i * 96 + lane, epoch);
      } else {
        unsigned it = 0;
        while (true) {
          bool ok = true;
          #pragma unroll
          for (int j = 0; j < 5; j++) {
            const uint2 u = ld_vol2(&g_csum[5 * FH + ct * 160 + j * 32 + lane]);
            ok = ok && u.y == epoch;
            reinterpret_cast<uint32_t*>(smem + COLSUM_OFF)[j * 32 + lane] = u.x;
          }
          if (ok || ++it > POLL_LIMIT) break;
          __nanosleep(2 * POLL_NS);
        }
      }
      __syncwarp();
      TS(1, 4);
      if (grp == 0) {
        bar_arrive<BAR_STATS>(320);
        bar_sync<BAR_PUB1>(160);
        if (lane == 0) set_flag(F_Z + ct, rb, epoch);
        TS(1, 8);
        __syncwarp();
        bar_arrive<BAR_BUF>(160);
      } else {
        bar_arrive<BAR_STATS>(192);
        bar_sync<BAR_PUB2>(160);
        if (lane == 0) set_flag(F_A + ct, rb, epoch);
        TS(1, 9);
        __syncwarp();
      }
      bar_sync<BAR_PUB1>(160);
      if (lane == 0) set_flag(grp == 0 ? F_H + rb : F_B + ct, grp == 0 ? ct : rb, epoch);
      TS(1, 10);
      __syncwarp();
      bar_arrive<BAR_BUF>(160);
    }
  } else {
    asm volatile("setmaxnreg.inc.sync.aligned.u32 232;");
    const int t = tid & 127, w = t >> 5, l = t & 31;
    ln_rows(rv, buf, cta, epoch);
    TS(wg + 1, 0);
    cluster_wait();
    const uint32_t st_base = buf + (w * 16 + ((l >> 3) & 1) * 8 + (l & 7)) * 128;
    const uint32_t st_x = ((l >> 4) ^ (l & 7)) << 4;
    const float2* rs = reinterpret_cast<const float2*>(smem + ROWSTAT_OFF) + w * 16 + (l >> 2);
    const float2* cs = reinterpret_cast<const float2*>(smem + COLSUM_OFF) + (l & 3);
    if (grp == 0) {
      {
        const int mb = wg - 1;
        float acc[1][96];
        zero(acc);
        mainloop<192, 1, 1, false, 0>(acc, sbase, 0, 0, 10, mb);
        drain(acc, sbase, 0, 9);
        TS(wg + 1, 1);
        bar_sync<BAR_STATS>(320);
        const float2 s0 = rs[mb * 64], s1 = rs[mb * 64 + 8];
        const float nm[2] = {s0.y / s0.x, s1.y / s1.x}, hr[2] = {0.5f * s0.x, 0.5f * s1.x};
        const float k1[2] = {0.7978845608f * s0.x, 0.7978845608f * s1.x};
        const float k2[2] = {0.0356774081f * s0.x * s0.x * s0.x, 0.0356774081f * s1.x * s1.x * s1.x};
        float sm0 = 0.f, sm1 = 0.f, q0 = 0.f, q1 = 0.f;
        #pragma unroll
        for (int jj = 0; jj < 12; jj++) {
          float u[8];
          #pragma unroll
          for (int hf = 0; hf < 2; hf++) {
            const float2 c = cs[jj * 8 + hf * 4];
            #pragma unroll
            for (int e = 0; e < 4; e++) {
              const float wv = fmaf(nm[e >> 1], (e & 1) ? c.y : c.x, acc[0][8 * jj + 4 * hf + e]);
              float th; asm("tanh.approx.f32 %0, %1;" : "=f"(th) : "f"(wv * fmaf(k2[e >> 1], wv * wv, k1[e >> 1])));
              const float hv = hr[e >> 1] * wv;
              u[4 * hf + e] = fmaf(hv, th, hv);
            }
            sm0 += u[4 * hf] + u[4 * hf + 1]; q0 = fmaf(u[4 * hf], u[4 * hf], q0); q0 = fmaf(u[4 * hf + 1], u[4 * hf + 1], q0);
            sm1 += u[4 * hf + 2] + u[4 * hf + 3]; q1 = fmaf(u[4 * hf + 2], u[4 * hf + 2], q1); q1 = fmaf(u[4 * hf + 3], u[4 * hf + 3], q1);
          }
          stsm4(st_base + mb * 24576 + (jj >> 2) * 8192 + (st_x ^ ((jj & 3) << 5)),
                pack_bf16(u[0], u[1]), pack_bf16(u[2], u[3]), pack_bf16(u[4], u[5]), pack_bf16(u[6], u[7]));
        }
        #pragma unroll
        for (int o = 1; o < 4; o <<= 1) {
          sm0 += __shfl_xor_sync(0xffffffffu, sm0, o); q0 += __shfl_xor_sync(0xffffffffu, q0, o);
          sm1 += __shfl_xor_sync(0xffffffffu, sm1, o); q1 += __shfl_xor_sync(0xffffffffu, q1, o);
        }
        if ((l & 3) < 2) {
          const float sm = (l & 1) ? sm1 : sm0, sv = (l & 1) ? q1 : q0;
          const int row = mb * 64 + w * 16 + (l & 1) * 8 + (l >> 2);
          const float mu = sm * (1.f / 192), m2 = fmaxf(sv - sm * mu, 0.f);
          st_vol2(&g_zstat[(rb * 4 + ct) * 128 + row], __float_as_uint(mu), (__float_as_uint(m2) & ~255u) | (epoch & 255u));
          reinterpret_cast<float2*>(smem + ZSTAT_OFF)[row] = make_float2(mu, m2);
        }
        TS(wg + 1, 4);
      }
      float acc[2][96];
      if (wg == 1) {
        bar_sync<BAR_U>(256);
        uint2 v[3];
        unsigned n = 0;
        while (true) {
          bool ok = true;
          #pragma unroll
          for (int j = 0; j < 3; j++) { v[j] = ld_vol2(&g_zstat[(rb * 4 + ((ct + 1 + j) & 3)) * 128 + t]); ok = ok && ((v[j].y ^ epoch) & 255u) == 0; }
          if (ok || ++n > POLL_LIMIT) break;
          __nanosleep(POLL_NS);
        }
        const float2 own = reinterpret_cast<const float2*>(smem + ZSTAT_OFF)[t];
        const float m0 = __uint_as_float(v[0].x), m1 = __uint_as_float(v[1].x), m3 = __uint_as_float(v[2].x);
        const float mean = 0.25f * ((own.x + m0) + (m1 + m3));
        const float d = (own.x - mean) * (own.x - mean) + (m0 - mean) * (m0 - mean) + (m1 - mean) * (m1 - mean) + (m3 - mean) * (m3 - mean);
        const float var = fmaf(192.f, d, (own.y + __uint_as_float(v[0].y & ~255u)) + (__uint_as_float(v[1].y & ~255u) + __uint_as_float(v[2].y & ~255u)));
        const float r = rsqrtf(var * (1.f / FH) + LN_EPS), o = -mean * r;
        TS(2, 5);
        const uint32_t rbase = buf + (t >> 6) * 24576 + (t & 63) * 128;
        const uint32_t m2 = pack_bf16(-mean, -mean), r2 = pack_bf16(r, r);
        const float res = (-mean - bf_lo(m2)) * r;
        const uint32_t e2 = pack_bf16(res, res);
        #pragma unroll 1
        for (int c = 0; c < 3; c++) {
          uint4 z[8];
          #pragma unroll
          for (int i = 0; i < 8; i++) z[i] = lds128(rbase + c * 8192 + (((i ^ l) & 7) << 4));
          #pragma unroll
          for (int i = 0; i < 8; i++)
            sts128(rbase + c * 8192 + (((i ^ l) & 7) << 4), hfma2_bf16(hadd2_bf16(z[i].x, m2), r2, e2), hfma2_bf16(hadd2_bf16(z[i].y, m2), r2, e2),
                   hfma2_bf16(hadd2_bf16(z[i].z, m2), r2, e2), hfma2_bf16(hadd2_bf16(z[i].w, m2), r2, e2));
          fence_async_smem();
          __syncwarp();
          if (l == 0) {
            tma_store_2d(&maps.m[M_ZS], buf + (w >> 1) * 24576 + c * 8192 + (w & 1) * 4096, ct * 192 + c * 64, rb * 128 + w * 32);
            bulk_commit();
          }
        }
        TS(2, 6);
        if (l == 0) bulk_wait_all();
        __syncwarp();
        bar_arrive<BAR_PUB1>(160);
        {
          const bf16* bp = bsp + rb * 128 + w * 16 + (l >> 2);
          const float bb[4] = {__bfloat162float(bp[0]), __bfloat162float(bp[8]), __bfloat162float(bp[64]), __bfloat162float(bp[72])};
          #pragma unroll
          for (int i = 0; i < 96; i++) { acc[0][i] = bb[(i >> 1) & 1]; acc[1][i] = bb[2 + ((i >> 1) & 1)]; }
          pin(acc);
        }
        bar_sync<BAR_ORD2>(256);
        mainloop<192, 2, 1, false, BAR_ORD1>(acc, sbase, 0, 20, 32);
        bar_sync<BAR_Z1>(256);
        drain(acc, sbase, 0, 51);
        TS(2, 7);
        uint32_t z[2][4][4];
        #pragma unroll
        for (int i = 0; i < 4; i++) ldsm4(st_base + (st_x ^ (i << 5)), z[0][i][0], z[0][i][1], z[0][i][2], z[0][i][3]);
        #pragma unroll
        for (int bx = 0; bx < 6; bx++) {
          if (bx < 5) {
            #pragma unroll
            for (int i = 0; i < 4; i++)
              ldsm4(st_base + (bx + 1) * 8192 + (st_x ^ (i << 5)), z[(bx + 1) & 1][i][0], z[(bx + 1) & 1][i][1], z[(bx + 1) & 1][i][2], z[(bx + 1) & 1][i][3]);
          }
          #pragma unroll
          for (int i = 0; i < 4; i++) {
            const float* a = &acc[bx / 3][8 * ((bx % 3) * 4 + i)];
            const uint32_t* zz = z[bx & 1][i];
            stsm4(st_base + bx * 8192 + (st_x ^ (i << 5)),
                  hmul2_bf16(zz[0], pack_bf16(a[0], a[1])), hmul2_bf16(zz[1], pack_bf16(a[2], a[3])),
                  hmul2_bf16(zz[2], pack_bf16(a[4], a[5])), hmul2_bf16(zz[3], pack_bf16(a[6], a[7])));
          }
          if (bx % 3 == 2) {
            fence_async_smem();
            __syncwarp();
            if (l < 3) {
              tma_store_2d(&maps.m[M_HS], buf + (bx - 2 + l) * 8192 + w * 2048, ct * 192 + l * 64, rb * 128 + (bx / 3) * 64 + w * 16);
              bulk_commit();
            }
          }
        }
        bar_arrive<BAR_U>(256);
        TS(2, 8);
        if (l < 3) bulk_wait_all();
        __syncwarp();
        bar_arrive<BAR_PUB1>(160);
        TS(2, 9);
        return;
      }
      bar_arrive<BAR_U>(256);
      zero(acc);
      mainloop<192, 2, 1, false, BAR_ORD2>(acc, sbase, 0, 10, 10);
      drain(acc, sbase, 0, 19);
      TS(3, 2);
      bar_sync<BAR_BUF>(160);
      #pragma unroll
      for (int mi = 0; mi < 2; mi++)
        #pragma unroll
        for (int jj = 0; jj < 12; jj++) {
          const float* a = &acc[mi][8 * jj];
          stsm4(st_base + mi * 24576 + (jj >> 2) * 8192 + (st_x ^ ((jj & 3) << 5)),
                pack_bf16(a[0], a[1]), pack_bf16(a[2], a[3]), pack_bf16(a[4], a[5]), pack_bf16(a[6], a[7]));
        }
      __syncwarp();
      TS(3, 3);
      const uint32_t rbase = buf + (l >> 4) * 24576 + (w * 16 + (l & 15)) * 128;
      #pragma unroll 1
      for (int c2 = 0; c2 < 12; c2++) {
        const uint32_t ab = rbase + (c2 >> 2) * 8192;
        uint4 v[2];
        #pragma unroll
        for (int i = 0; i < 2; i++) v[i] = lds128(ab + (((((c2 & 3) * 2 + i) ^ l) & 7) << 4));
        #pragma unroll
        for (int i = 0; i < 2; i++)
          sts128(ab + (((((c2 & 3) * 2 + i) ^ l) & 7) << 4),
                 pack_bf16(gelu_tanh(bf_lo(v[i].x)), gelu_tanh(bf_hi(v[i].x))), pack_bf16(gelu_tanh(bf_lo(v[i].y)), gelu_tanh(bf_hi(v[i].y))),
                 pack_bf16(gelu_tanh(bf_lo(v[i].z)), gelu_tanh(bf_hi(v[i].z))), pack_bf16(gelu_tanh(bf_lo(v[i].w)), gelu_tanh(bf_hi(v[i].w))));
        __nanosleep(Z1_NS);
      }
      TS(3, 5);
      bar_arrive<BAR_Z1>(256);
    }
    float acc[2][80];
    if (grp == 1) {
      zero(acc);
      if (wg == 2) {
        mainloop<160, 2, 0, false, BAR_ORD2>(acc, sbase, 1, 0, 10);
      } else {
        weight_sums(win, wdre, rb * 4 + ct, epoch);
        TS(2, 1);
        bar_sync<BAR_ORD2>(256);
        mainloop<160, 2, 0, false, BAR_ORD1>(acc, sbase, 1, 10, 10);
      }
      drain(acc, sbase, 1, wg == 2 ? 9 : 19);
      TS(wg + 1, wg == 1 ? 7 : 2);
      if (wg == 1) bar_sync<BAR_Z1>(256); else bar_sync<BAR_STATS>(192);
      const uint32_t tb = buf + ((l >> 4) * 8 + (l & 7)) * 128 + (((w * 2 + ((l >> 3) & 1)) ^ (l & 7)) << 4);
      float2 st[4];
      #pragma unroll
      for (int r = 0; r < 4; r++) st[r] = wg == 2 ? rs[(r >> 1) * 64 + (r & 1) * 8] : make_float2(-1.f, 0.f);
      #pragma unroll
      for (int jj = 0; jj < 10; jj++) {
        const float2 c0 = cs[jj * 8], c1 = cs[jj * 8 + 4];
        #pragma unroll
        for (int mi = 0; mi < 2; mi++) {
          const float* a = &acc[mi][8 * jj];
          const float2 s0 = st[mi * 2], s1 = st[mi * 2 + 1];
          stsm4_t(tb + mi * 20480 + jj * 2048,
                  pack_bf16(fmaf(a[0], s0.x, s0.y * c0.x), fmaf(a[1], s0.x, s0.y * c0.y)), pack_bf16(fmaf(a[2], s1.x, s1.y * c0.x), fmaf(a[3], s1.x, s1.y * c0.y)),
                  pack_bf16(fmaf(a[4], s0.x, s0.y * c1.x), fmaf(a[5], s0.x, s0.y * c1.y)), pack_bf16(fmaf(a[6], s1.x, s1.y * c1.x), fmaf(a[7], s1.x, s1.y * c1.y)));
        }
      }
      fence_async_smem();
      if (wg == 1) bar_sync<BAR_WG1>(128); else bar_sync<BAR_WG2>(128);
      TS(wg + 1, wg == 1 ? 8 : 6);
      if (l < 2) {
        tma_store_2d(&maps.m[M_ABS], buf + l * 20480 + w * 5120, rb * 128 + l * 64, (2 - wg) * DM + ct * 160 + w * 40);
        bulk_commit();
        bulk_wait_all();
      }
      __syncwarp();
      TS(wg + 1, wg == 1 ? 9 : 10);
      if (wg == 1) {
        bar_arrive<BAR_PUB1>(160);
        #pragma unroll 1
        for (int i = 0; i < 4; i++) {
          uint4 v[5];
          #pragma unroll
          for (int j = 0; j < 5; j++) {
            const int e = (i * 5 + j) * 128 + t;
            v[j] = ldg128(x + (size_t)(rb * 128 + e / 20) * DM + ct * 160 + (e % 20) * 8);
          }
          #pragma unroll
          for (int j = 0; j < 5; j++) {
            const int e = (i * 5 + j) * 128 + t;
            stg128(out + (size_t)(rb * 128 + e / 20) * DM + ct * 160 + (e % 20) * 8, v[j]);
          }
        }
        bar_sync<BAR_WG1>(128);
        if (t == 0) publish(F_Y + rb * 4 + ct, 0, epoch);
        return;
      }
      bar_arrive<BAR_PUB2>(160);
      bar_arrive<BAR_Z1>(256);
    }
    zero(acc);
    bar_sync<BAR_ORD1>(256);
    mainloop<160, 2, 0, false, 0>(acc, sbase, grp, grp == 0 ? 52 : 20, grp == 0 ? NX : 64 - NX);
    if (grp == 0) {
      bar_sync<BAR_U>(256);
      mainloop<160, 2, 2, true, 0, true>(acc, sbase, 0, 52 + NX, 3);
    }
    mainloop<160, 2, 2, true, 0>(acc, sbase, grp, gh + 3 - 3 * grp, total - gh - 3 + 3 * grp);
    const uint32_t slab = buf + w * (16 * 320);
    const uint32_t addr = slab + (((l >> 3) & 1) * 8 + (l & 7)) * 320 + (l >> 4) * 16;
    bar_sync<BAR_BUF>(160);
    mbar_wait(dep0 + 32, 0);
    drain(acc, sbase, grp, total - 1);
    TS(3, 12);
    #pragma unroll
    for (int mi = 0; mi < 2; mi++) {
      #pragma unroll
      for (int jj = 0; jj < 10; jj++) {
        const float* a = &acc[mi][8 * jj];
        stsm4(addr + mi * 20480 + jj * 32, pack_bf16(a[0], a[1]), pack_bf16(a[2], a[3]), pack_bf16(a[4], a[5]), pack_bf16(a[6], a[7]));
      }
      fence_async_smem();
      __syncwarp();
      if (l == 0) {
        tma_reduce_2d(&maps.m[M_OUT], slab + mi * 20480, ct * 160, rb * 128 + mi * 64 + w * 16);
        bulk_commit();
      }
    }
    TS(3, 13);
    if (l == 0) {
      bulk_wait_read();
      if (w == 0) atomicAdd(&g_done, 1u);
    }
    TS(3, 15);
  }
}

typedef CUresult (*EncodeFn)(CUtensorMap*, CUtensorMapDataType, cuuint32_t, void*, const cuuint64_t*, const cuuint64_t*,
                             const cuuint32_t*, const cuuint32_t*, CUtensorMapInterleave, CUtensorMapSwizzle,
                             CUtensorMapL2promotion, CUtensorMapFloatOOBfill);

void make2d(EncodeFn enc, CUtensorMap* m, const void* p, uint64_t cols, uint64_t rows, uint32_t bc, uint32_t br, bool swz = true) {
  cuuint64_t gd[2] = {cols, rows}, gs[1] = {cols * 2};
  cuuint32_t bd[2] = {bc, br}, es[2] = {1, 1};
  enc(m, CU_TENSOR_MAP_DATA_TYPE_BFLOAT16, 2, const_cast<void*>(p), gd, gs, bd, es, CU_TENSOR_MAP_INTERLEAVE_NONE,
      swz ? CU_TENSOR_MAP_SWIZZLE_128B : CU_TENSOR_MAP_SWIZZLE_NONE, CU_TENSOR_MAP_L2_PROMOTION_L2_128B, CU_TENSOR_MAP_FLOAT_OOB_FILL_NONE);
}
void make3d(EncodeFn enc, CUtensorMap* m, const void* p, uint64_t cols, uint64_t rows, uint32_t cw, uint32_t nc, uint32_t br = 64) {
  cuuint64_t gd[3] = {cw, rows, cols / cw}, gs[2] = {cols * 2, cw * 2};
  cuuint32_t bd[3] = {cw, br, nc}, es[3] = {1, 1, 1};
  enc(m, CU_TENSOR_MAP_DATA_TYPE_BFLOAT16, 3, const_cast<void*>(p), gd, gs, bd, es, CU_TENSOR_MAP_INTERLEAVE_NONE,
      cw == 64 ? CU_TENSOR_MAP_SWIZZLE_128B : CU_TENSOR_MAP_SWIZZLE_64B, CU_TENSOR_MAP_L2_PROMOTION_L2_128B, CU_TENSOR_MAP_FLOAT_OOB_FILL_NONE);
}

}

extern "C" void kernel_launch(void* const* d_in, const int* in_sizes, int n_in, void* d_out, int out_size) {
  const bf16* x = (const bf16*)d_in[0];
  const bf16* wsre = (const bf16*)d_in[1];
  const bf16* wsim = (const bf16*)d_in[2];
  const bf16* wdre = (const bf16*)d_in[3];
  const bf16* wdim = (const bf16*)d_in[4];
  const bf16* win = (const bf16*)d_in[6];
  const bf16* wsp = (const bf16*)d_in[7];
  const bf16* bsp = (const bf16*)d_in[8];
  const bf16* wout = (const bf16*)d_in[9];

  void* fn = nullptr;
  cudaDriverEntryPointQueryResult qr;
  cudaGetDriverEntryPoint("cuTensorMapEncodeTiled", &fn, cudaEnableDefault, &qr);
  EncodeFn enc = (EncodeFn)fn;
  void *abT, *z2, *h, *xn;
  cudaGetSymbolAddress(&xn, g_xn);
  cudaGetSymbolAddress(&abT, g_abT);
  cudaGetSymbolAddress(&z2, g_z2);
  cudaGetSymbolAddress(&h, g_h);

  Maps maps;
  make2d(enc, &maps.m[M_X], x, DM, SEQ, 64, 64);
  make2d(enc, &maps.m[M_XN], xn, DM, SEQ, 64, 64);
  make2d(enc, &maps.m[M_WSRE], wsre, SEQ, SEQ, 64, 64);
  make2d(enc, &maps.m[M_WSIM], wsim, SEQ, SEQ, 64, 64);
  make2d(enc, &maps.m[M_WSP], wsp, SEQ, SEQ, 64, 64);
  make2d(enc, &maps.m[M_H], h, FH, SEQ, 64, 64);
  make3d(enc, &maps.m[M_WIN3], win, FF, DM, 64, 3);
  make3d(enc, &maps.m[M_Z23], z2, FH, SEQ, 64, 3);
  make2d(enc, &maps.m[M_WDRE], wdre, DM, DM, 64, 160);
  make2d(enc, &maps.m[M_WDIM], wdim, DM, DM, 64, 160);
  make2d(enc, &maps.m[M_AB], abT, SEQ, 2 * DM, 64, 160);
  make3d(enc, &maps.m[M_WOUT], wout, DM, FH, 32, 5);
  make2d(enc, &maps.m[M_HS], h, FH, SEQ, 64, 16);
  make2d(enc, &maps.m[M_ZS], z2, FH, SEQ, 64, 32);
  make2d(enc, &maps.m[M_ABS], abT, SEQ, 2 * DM, 64, 40);
  make2d(enc, &maps.m[M_OUT], d_out, DM, SEQ, 160, 16, false);

  cudaFuncSetAttribute(fused_kernel, cudaFuncAttributeMaxDynamicSharedMemorySize, SMEM_BYTES);
  fused_kernel<<<128, 384, SMEM_BYTES>>>(maps, x, win, wdre, bsp, (bf16*)d_out);
}
```

```cpp
#include <cuda_runtime.h>
#include <cuda_bf16.h>
#include <cuda.h>
#include <stdint.h>

namespace {

typedef __nv_bfloat16 bf16;

constexpr int SEQ = 2048, DM = 640, FF = 1536, FH = 768;
#define NXV 6
#define NOV 3
constexpr int NX = NXV;
constexpr int NO = NOV;
#define NSTB 5
#define PFB 1
constexpr int NST_A = 4, NST_B = NSTB, MAXST = 5;
constexpr int A_BYTES = 16384;
constexpr int BAR_OFF = 0;
constexpr int READY_OFF = 128;
constexpr int COLSUM_OFF = 256;
constexpr int ROWSTAT_OFF = 1024;
constexpr int ZSTAT_OFF = 2048;
constexpr int RED_OFF = 3072;
constexpr int RING_OFF = 4096;
constexpr int STAGE_A = 40960, STAGE_B = 36864;
constexpr int SMEM_BYTES = RING_OFF + 5 * STAGE_B + 40960;
constexpr int KB_A = 52 + NX + 12 - NO;
constexpr int KB_B = 84 - NX + NO;
constexpr float LN_EPS = 1e-5f;
constexpr unsigned POLL_LIMIT = 100000;
#define POLL_NS 100
#define PF_D 8
#define NORM2 1
#define Z1_NS 600
#define ZPRE 6
#define GF32 0
#define WATCH_NS 40

constexpr int BAR_ORD1 = 1, BAR_ORD2 = 2, BAR_WG1 = 3, BAR_WG2 = 4, BAR_LN = 5, BAR_BUF = 6, BAR_Z1 = 7, BAR_PUB1 = 8, BAR_PUB2 = 9,
              BAR_STATS = 10, BAR_U = 11;

enum { M_X, M_XN, M_WSRE, M_WSIM, M_WSP, M_H, M_WIN3, M_Z23, M_WDRE, M_WDIM, M_AB, M_WOUT, M_OUT, M_H3, M_ABS, M_COUNT };
struct Maps { CUtensorMap m[M_COUNT]; };

__device__ __align__(1024) bf16 g_abT[2 * DM * SEQ];
__device__ __align__(1024) bf16 g_z2[SEQ * FH];
__device__ __align__(1024) bf16 g_h[SEQ * FH];
__device__ __align__(1024) bf16 g_xn[SEQ * DM];
__device__ __align__(16) uint2 g_xstat[SEQ];
__device__ __align__(16) uint2 g_csum[5 * FH + DM];
__device__ __align__(16) uint2 g_zstat[64 * 128];
__device__ __align__(256) unsigned char g_flags[108 * 256];
constexpr int F_A = 0, F_B = 4, F_Z = 8, F_H = 12, F_XN = 28, F_Y = 44;
__device__ unsigned g_done;
#define TS(role, ev)
#define TC(i)

extern __shared__ __align__(1024) uint8_t smem[];

__device__ __forceinline__ uint32_t smem_u32(const void* p) { return (uint32_t)__cvta_generic_to_shared(p); }
__device__ __forceinline__ void mbar_init(uint32_t bar, uint32_t cnt) { asm volatile("mbarrier.init.shared::cta.b64 [%0], %1;" :: "r"(bar), "r"(cnt)); }
__device__ __forceinline__ void mbar_expect_tx(uint32_t bar, uint32_t bytes) { asm volatile("mbarrier.arrive.expect_tx.shared::cta.b64 _, [%0], %1;" :: "r"(bar), "r"(bytes) : "memory"); }
__device__ __forceinline__ void mbar_arrive(uint32_t bar) { asm volatile("mbarrier.arrive.shared::cta.b64 _, [%0];" :: "r"(bar) : "memory"); }
__device__ __forceinline__ void mbar_arrive_cluster(uint32_t bar, uint32_t cta) {
  asm volatile("{\n.reg .b32 ra;\nmapa.shared::cluster.u32 ra, %0, %1;\nmbarrier.arrive.shared::cluster.b64 _, [ra];\n}" :: "r"(bar), "r"(cta) : "memory");
}
__device__ __forceinline__ void mbar_wait(uint32_t bar, uint32_t parity) {
  asm volatile("{\n.reg .pred p;\n.reg .u32 n;\nmov.u32 n, 0;\n"
               "LW: mbarrier.try_wait.parity.shared::cta.b64 p, [%0], %1, 2000;\n@p bra LD;\n"
               "add.u32 n, n, 1;\nsetp.lt.u32 p, n, 20000;\n@p bra LW;\nLD:\n}" :: "r"(bar), "r"(parity) : "memory");
}
__device__ __forceinline__ void tma_load_2d(uint32_t dst, const CUtensorMap* map, uint32_t bar, int c0, int c1) {
  asm volatile("cp.async.bulk.tensor.2d.shared::cluster.global.mbarrier::complete_tx::bytes [%0], [%1, {%3, %4}], [%2];"
    :: "r"(dst), "l"((uint64_t)map), "r"(bar), "r"(c0), "r"(c1) : "memory");
}
__device__ __forceinline__ void tma_load_3d(uint32_t dst, const CUtensorMap* map, uint32_t bar, int c0, int c1, int c2) {
  asm volatile("cp.async.bulk.tensor.3d.shared::cluster.global.mbarrier::complete_tx::bytes [%0], [%1, {%3, %4, %5}], [%2];"
    :: "r"(dst), "l"((uint64_t)map), "r"(bar), "r"(c0), "r"(c1), "r"(c2) : "memory");
}
__device__ __forceinline__ void tma_load_2d_mc(uint32_t dst, const CUtensorMap* map, uint32_t bar, int c0, int c1, uint16_t mask) {
  asm volatile("cp.async.bulk.tensor.2d.shared::cluster.global.mbarrier::complete_tx::bytes.multicast::cluster [%0], [%1, {%3, %4}], [%2], %5;"
    :: "r"(dst), "l"((uint64_t)map), "r"(bar), "r"(c0), "r"(c1), "h"(mask) : "memory");
}
__device__ __forceinline__ void tma_store_2d(const CUtensorMap* map, uint32_t src, int c0, int c1) {
  asm volatile("cp.async.bulk.tensor.2d.global.shared::cta.bulk_group [%0, {%2, %3}], [%1];"
    :: "l"((uint64_t)map), "r"(src), "r"(c0), "r"(c1) : "memory");
}
__device__ __forceinline__ void tma_store_3d(const CUtensorMap* map, uint32_t src, int c0, int c1, int c2) {
  asm volatile("cp.async.bulk.tensor.3d.global.shared::cta.bulk_group [%0, {%2, %3, %4}], [%1];"
    :: "l"((uint64_t)map), "r"(src), "r"(c0), "r"(c1), "r"(c2) : "memory");
}
__device__ __forceinline__ void tma_reduce_2d(const CUtensorMap* map, uint32_t src, int c0, int c1) {
  asm volatile("cp.reduce.async.bulk.tensor.2d.global.shared::cta.add.tile.bulk_group [%0, {%2, %3}], [%1];"
    :: "l"((uint64_t)map), "r"(src), "r"(c0), "r"(c1) : "memory");
}
__device__ __forceinline__ void bulk_wait_all() { asm volatile("cp.async.bulk.wait_group 0;" ::: "memory"); }
__device__ __forceinline__ void bulk_commit() { asm volatile("cp.async.bulk.commit_group;" ::: "memory"); }
__device__ __forceinline__ void bulk_wait_read() { asm volatile("cp.async.bulk.wait_group.read 0;" ::: "memory"); }
__device__ __forceinline__ void fence_async_smem() { asm volatile("fence.proxy.async.shared::cta;" ::: "memory"); }
__device__ __forceinline__ void fence_async_global() { asm volatile("fence.proxy.async.global;" ::: "memory"); }
__device__ __forceinline__ void wgmma_fence() { asm volatile("wgmma.fence.sync.aligned;" ::: "memory"); }
__device__ __forceinline__ void wgmma_commit() { asm volatile("wgmma.commit_group.sync.aligned;" ::: "memory"); }
template<int N> __device__ __forceinline__ void wgmma_wait() { asm volatile("wgmma.wait_group.sync.aligned %0;" :: "n"(N) : "memory"); }
template<int ID> __device__ __forceinline__ void bar_sync(int n) { asm volatile("bar.sync %0, %1;" :: "n"(ID), "r"(n) : "memory"); }
template<int ID> __device__ __forceinline__ void bar_arrive(int n) { asm volatile("bar.arrive %0, %1;" :: "n"(ID), "r"(n) : "memory"); }
__device__ __forceinline__ void cluster_wait() { asm volatile("barrier.cluster.wait.aligned;" ::: "memory"); }
__device__ __forceinline__ uint64_t desc64(uint32_t lo, uint32_t hi) { return (uint64_t)lo | ((uint64_t)hi << 32); }
__device__ __forceinline__ uint4 ld_vol4(const uint4* p) {
  uint4 v; asm volatile("ld.relaxed.gpu.global.v4.u32 {%0,%1,%2,%3}, [%4];" : "=r"(v.x), "=r"(v.y), "=r"(v.z), "=r"(v.w) : "l"(p) : "memory"); return v;
}
__device__ __forceinline__ uint2 ld_vol2(const uint2* p) {
  uint2 v; asm volatile("ld.relaxed.gpu.global.v2.u32 {%0,%1}, [%2];" : "=r"(v.x), "=r"(v.y) : "l"(p) : "memory"); return v;
}
__device__ __forceinline__ void st_vol4(uint4* p, uint32_t a, uint32_t b, uint32_t c, uint32_t d) {
  asm volatile("st.relaxed.gpu.global.v4.u32 [%0], {%1,%2,%3,%4};" :: "l"(p), "r"(a), "r"(b), "r"(c), "r"(d) : "memory");
}
__device__ __forceinline__ void st_vol2(uint2* p, uint32_t a, uint32_t b) {
  asm volatile("st.relaxed.gpu.global.v2.u32 [%0], {%1,%2};" :: "l"(p), "r"(a), "r"(b) : "memory");
}
__device__ __forceinline__ void stg128(void* p, uint4 v) {
  asm volatile("st.global.v4.u32 [%0], {%1,%2,%3,%4};" :: "l"(p), "r"(v.x), "r"(v.y), "r"(v.z), "r"(v.w));
}
__device__ __forceinline__ unsigned ld_relaxed(const unsigned* p) {
  unsigned v; asm volatile("ld.relaxed.gpu.global.u32 %0, [%1];" : "=r"(v) : "l"(p) : "memory"); return v;
}
__device__ __forceinline__ uint32_t pack_bf16(float lo, float hi) {
  uint32_t r; asm("cvt.rn.bf16x2.f32 %0, %1, %2;" : "=r"(r) : "f"(hi), "f"(lo)); return r;
}
__device__ __forceinline__ float bf_lo(uint32_t v) { return __uint_as_float(v << 16); }
__device__ __forceinline__ float bf_hi(uint32_t v) { return __uint_as_float(v & 0xFFFF0000u); }
__device__ __forceinline__ void stsm4(uint32_t addr, uint32_t a, uint32_t b, uint32_t c, uint32_t d) {
  asm volatile("stmatrix.sync.aligned.m8n8.x4.shared.b16 [%0], {%1,%2,%3,%4};" :: "r"(addr), "r"(a), "r"(b), "r"(c), "r"(d));
}
__device__ __forceinline__ void stsm4_t(uint32_t addr, uint32_t a, uint32_t b, uint32_t c, uint32_t d) {
  asm volatile("stmatrix.sync.aligned.m8n8.x4.trans.shared.b16 [%0], {%1,%2,%3,%4};" :: "r"(addr), "r"(a), "r"(b), "r"(c), "r"(d));
}
__device__ __forceinline__ void ldsm4(uint32_t addr, uint32_t& a, uint32_t& b, uint32_t& c, uint32_t& d) {
  asm volatile("ldmatrix.sync.aligned.m8n8.x4.shared.b16 {%0,%1,%2,%3}, [%4];" : "=r"(a), "=r"(b), "=r"(c), "=r"(d) : "r"(addr));
}
__device__ __forceinline__ uint4 lds128(uint32_t a) {
  uint4 v; asm volatile("ld.shared.v4.u32 {%0,%1,%2,%3}, [%4];" : "=r"(v.x), "=r"(v.y), "=r"(v.z), "=r"(v.w) : "r"(a)); return v;
}
__device__ __forceinline__ void sts128(uint32_t a, uint32_t x, uint32_t y, uint32_t z, uint32_t w) {
  asm volatile("st.shared.v4.u32 [%0], {%1,%2,%3,%4};" :: "r"(a), "r"(x), "r"(y), "r"(z), "r"(w));
}
__device__ __forceinline__ uint32_t hmul2_bf16(uint32_t a, uint32_t b) {
  uint32_t r; asm("mul.rn.bf16x2 %0, %1, %2;" : "=r"(r) : "r"(a), "r"(b)); return r;
}
__device__ __forceinline__ uint32_t hadd2_bf16(uint32_t a, uint32_t b) {
  uint32_t r; asm("add.rn.bf16x2 %0, %1, %2;" : "=r"(r) : "r"(a), "r"(b)); return r;
}
__device__ __forceinline__ uint32_t hfma2_bf16(uint32_t a, uint32_t b, uint32_t c) {
  uint32_t r; asm("fma.rn.bf16x2 %0, %1, %2, %3;" : "=r"(r) : "r"(a), "r"(b), "r"(c)); return r;
}
__device__ __forceinline__ float gelu_tanh(float v) {
  float u = v * fmaf(0.0356774081f, v * v, 0.7978845608f);
  float t; asm("tanh.approx.f32 %0, %1;" : "=f"(t) : "f"(u));
  float hv = 0.5f * v;
  return fmaf(hv, t, hv);
}

template<int TB>
__device__ __forceinline__ void wgmma_n192(float (&d)[96], uint64_t da, uint64_t db, int scale_d) {
  asm volatile("{\n.reg .pred p;\nsetp.ne.b32 p, %98, 0;\n"
   "wgmma.mma_async.sync.aligned.m64n192k16.f32.bf16.bf16 {%0,%1,%2,%3,%4,%5,%6,%7,%8,%9,%10,%11,%12,%13,%14,%15,%16,%17,%18,%19,%20,%21,%22,%23,%24,%25,%26,%27,%28,%29,%30,%31,%32,%33,%34,%35,%36,%37,%38,%39,%40,%41,%42,%43,%44,%45,%46,%47,%48,%49,%50,%51,%52,%53,%54,%55,%56,%57,%58,%59,%60,%61,%62,%63,%64,%65,%66,%67,%68,%69,%70,%71,%72,%73,%74,%75,%76,%77,%78,%79,%80,%81,%82,%83,%84,%85,%86,%87,%88,%89,%90,%91,%92,%93,%94,%95}, %96, %97, p, 1, 1, 0, %99;\n}"
   : "+f"(d[0]),"+f"(d[1]),"+f"(d[2]),"+f"(d[3]),"+f"(d[4]),"+f"(d[5]),"+f"(d[6]),"+f"(d[7]),"+f"(d[8]),"+f"(d[9]),"+f"(d[10]),"+f"(d[11]),"+f"(d[12]),"+f"(d[13]),"+f"(d[14]),"+f"(d[15]),"+f"(d[16]),"+f"(d[17]),"+f"(d[18]),"+f"(d[19]),"+f"(d[20]),"+f"(d[21]),"+f"(d[22]),"+f"(d[23]),"+f"(d[24]),"+f"(d[25]),"+f"(d[26]),"+f"(d[27]),"+f"(d[28]),"+f"(d[29]),"+f"(d[30]),"+f"(d[31]),"+f"(d[32]),"+f"(d[33]),"+f"(d[34]),"+f"(d[35]),"+f"(d[36]),"+f"(d[37]),"+f"(d[38]),"+f"(d[39]),"+f"(d[40]),"+f"(d[41]),"+f"(d[42]),"+f"(d[43]),"+f"(d[44]),"+f"(d[45]),"+f"(d[46]),"+f"(d[47]),"+f"(d[48]),"+f"(d[49]),"+f"(d[50]),"+f"(d[51]),"+f"(d[52]),"+f"(d[53]),"+f"(d[54]),"+f"(d[55]),"+f"(d[56]),"+f"(d[57]),"+f"(d[58]),"+f"(d[59]),"+f"(d[60]),"+f"(d[61]),"+f"(d[62]),"+f"(d[63]),"+f"(d[64]),"+f"(d[65]),"+f"(d[66]),"+f"(d[67]),"+f"(d[68]),"+f"(d[69]),"+f"(d[70]),"+f"(d[71]),"+f"(d[72]),"+f"(d[73]),"+f"(d[74]),"+f"(d[75]),"+f"(d[76]),"+f"(d[77]),"+f"(d[78]),"+f"(d[79]),"+f"(d[80]),"+f"(d[81]),"+f"(d[82]),"+f"(d[83]),"+f"(d[84]),"+f"(d[85]),"+f"(d[86]),"+f"(d[87]),"+f"(d[88]),"+f"(d[89]),"+f"(d[90]),"+f"(d[91]),"+f"(d[92]),"+f"(d[93]),"+f"(d[94]),"+f"(d[95])
   : "l"(da), "l"(db), "r"(scale_d), "n"(TB));
}
template<int TB>
__device__ __forceinline__ void wgmma_n160(float (&d)[80], uint64_t da, uint64_t db, int scale_d) {
  asm volatile("{\n.reg .pred p;\nsetp.ne.b32 p, %82, 0;\n"
   "wgmma.mma_async.sync.aligned.m64n160k16.f32.bf16.bf16 {%0,%1,%2,%3,%4,%5,%6,%7,%8,%9,%10,%11,%12,%13,%14,%15,%16,%17,%18,%19,%20,%21,%22,%23,%24,%25,%26,%27,%28,%29,%30,%31,%32,%33,%34,%35,%36,%37,%38,%39,%40,%41,%42,%43,%44,%45,%46,%47,%48,%49,%50,%51,%52,%53,%54,%55,%56,%57,%58,%59,%60,%61,%62,%63,%64,%65,%66,%67,%68,%69,%70,%71,%72,%73,%74,%75,%76,%77,%78,%79}, %80, %81, p, 1, 1, 0, %83;\n}"
   : "+f"(d[0]),"+f"(d[1]),"+f"(d[2]),"+f"(d[3]),"+f"(d[4]),"+f"(d[5]),"+f"(d[6]),"+f"(d[7]),"+f"(d[8]),"+f"(d[9]),"+f"(d[10]),"+f"(d[11]),"+f"(d[12]),"+f"(d[13]),"+f"(d[14]),"+f"(d[15]),"+f"(d[16]),"+f"(d[17]),"+f"(d[18]),"+f"(d[19]),"+f"(d[20]),"+f"(d[21]),"+f"(d[22]),"+f"(d[23]),"+f"(d[24]),"+f"(d[25]),"+f"(d[26]),"+f"(d[27]),"+f"(d[28]),"+f"(d[29]),"+f"(d[30]),"+f"(d[31]),"+f"(d[32]),"+f"(d[33]),"+f"(d[34]),"+f"(d[35]),"+f"(d[36]),"+f"(d[37]),"+f"(d[38]),"+f"(d[39]),"+f"(d[40]),"+f"(d[41]),"+f"(d[42]),"+f"(d[43]),"+f"(d[44]),"+f"(d[45]),"+f"(d[46]),"+f"(d[47]),"+f"(d[48]),"+f"(d[49]),"+f"(d[50]),"+f"(d[51]),"+f"(d[52]),"+f"(d[53]),"+f"(d[54]),"+f"(d[55]),"+f"(d[56]),"+f"(d[57]),"+f"(d[58]),"+f"(d[59]),"+f"(d[60]),"+f"(d[61]),"+f"(d[62]),"+f"(d[63]),"+f"(d[64]),"+f"(d[65]),"+f"(d[66]),"+f"(d[67]),"+f"(d[68]),"+f"(d[69]),"+f"(d[70]),"+f"(d[71]),"+f"(d[72]),"+f"(d[73]),"+f"(d[74]),"+f"(d[75]),"+f"(d[76]),"+f"(d[77]),"+f"(d[78]),"+f"(d[79])
   : "l"(da), "l"(db), "r"(scale_d), "n"(TB));
}

template<int N, int TB>
__device__ __forceinline__ void wgmma_n(float (&d)[N / 2], uint64_t da, uint64_t db) {
  if constexpr (N == 192) wgmma_n192<TB>(d, da, db, 1); else wgmma_n160<TB>(d, da, db, 1);
}

template<int M, int R>
__device__ __forceinline__ void pin(float (&acc)[M][R]) {
  #pragma unroll
  for (int mi = 0; mi < M; mi++)
    #pragma unroll
    for (int i = 0; i < R; i++) asm volatile("" : "+f"(acc[mi][i]) :: "memory");
}
template<int M, int R>
__device__ __forceinline__ void zero(float (&acc)[M][R]) {
  #pragma unroll
  for (int mi = 0; mi < M; mi++)
    #pragma unroll
    for (int i = 0; i < R; i++) acc[mi][i] = 0.f;
  pin(acc);
}

template<int N, int M, int TB, bool CONT, int ORD_BAR, bool AOWN = false>
__device__ __forceinline__ void mainloop(float (&acc)[M][N / 2], uint32_t sbase, int grp, int g0, int nk, int m0 = 0) {
  const uint32_t full0 = sbase + BAR_OFF, empty0 = full0 + 8 * MAXST, ring = sbase + RING_OFF;
  const int nst = grp == 0 ? NST_A : NST_B, total = grp == 0 ? KB_A : KB_B;
  const uint32_t sstep = (grp == 0 ? STAGE_A : STAGE_B) >> 4;
  const int t = threadIdx.x & 127;
  const uint32_t da0 = (((ring + m0 * 8192) & 0x3FFFF) >> 4) | 0x10000u;
  const uint32_t db0 = (((ring + A_BYTES) & 0x3FFFF) >> 4) | ((TB == 2 ? 256u : TB ? 512u : 1u) << 16);
  constexpr uint32_t HI_A = 0x40000040u, HI_B = TB == 2 ? 0x80000020u : 0x40000040u;
  int s = g0 % nst, ph = (g0 / nst) & 1, ps = s == 0 ? nst - 1 : s - 1;
  #pragma unroll 1
  for (int g = g0; g < g0 + nk; g++) {
    const uint32_t so = s * sstep;
    mbar_wait(full0 + 8 * s, ph);
    wgmma_fence();
    #pragma unroll
    for (int k = 0; k < 4; k++) {
      const uint64_t db = desc64(db0 + so + (TB == 2 ? k * 64 : TB ? k * 128 : k * 2), HI_B);
      #pragma unroll
      for (int mi = 0; mi < M; mi++)
        wgmma_n<N, TB != 0>(acc[mi], desc64(AOWN ? da0 + ((NST_A * STAGE_A) >> 4) + (g - g0) * 512 + mi * 1536 + k * 2 : da0 + so + mi * 512 + k * 2, HI_A), db);
    }
    wgmma_commit();
    if (ORD_BAR != 0 && g == g0 + nk - 1) bar_arrive<ORD_BAR>(256);
    wgmma_wait<1>();
    if (t < 2 * M && (CONT || g > g0) && g - 1 + nst < total) mbar_arrive_cluster(empty0 + 8 * ps, t & 1);
    ps = s;
    if (++s == nst) { s = 0; ph ^= 1; }
  }
}
template<int M, int R>
__device__ __forceinline__ void drain(float (&acc)[M][R], uint32_t sbase, int grp, int glast) {
  wgmma_wait<0>();
  pin(acc);
  const int t = threadIdx.x & 127;
  const int nst = grp == 0 ? NST_A : NST_B, total = grp == 0 ? KB_A : KB_B;
  if (t < 2 * M && glast + nst < total) mbar_arrive_cluster(sbase + BAR_OFF + 8 * MAXST + 8 * (glast % nst), t & 1);
}

__device__ __forceinline__ void set_flag(int slot, int byte, unsigned epoch) {
  asm volatile("st.relaxed.gpu.global.u8 [%0], %1;" :: "l"(g_flags + slot * 256 + byte), "r"(epoch & 255u) : "memory");
}
__device__ __forceinline__ unsigned get_flag(int slot, int byte) {
  unsigned v; asm volatile("ld.relaxed.gpu.global.u8 %0, [%1];" : "=r"(v) : "l"(g_flags + slot * 256 + byte) : "memory"); return v;
}
__device__ __forceinline__ void store_tile(const CUtensorMap* m, uint32_t buf, int rb, int ct) {
  tma_store_3d(m, buf, 0, rb * 128, 3 * ct);
  tma_store_3d(m, buf + 24576, 0, rb * 128 + 64, 3 * ct);
  bulk_commit();
  bulk_wait_all();
}
__device__ __forceinline__ void publish(int slot, int byte, unsigned epoch) {
  asm volatile("fence.acq_rel.gpu;" ::: "memory");
  set_flag(slot, byte, epoch);
}
__device__ __forceinline__ float sum8(uint4 v) {
  return ((bf_lo(v.x) + bf_hi(v.x)) + (bf_lo(v.y) + bf_hi(v.y))) + ((bf_lo(v.z) + bf_hi(v.z)) + (bf_lo(v.w) + bf_hi(v.w)));
}
__device__ __forceinline__ uint4 ldg128(const void* p) {
  uint4 v; asm volatile("ld.global.nc.v4.u32 {%0,%1,%2,%3}, [%4];" : "=r"(v.x), "=r"(v.y), "=r"(v.z), "=r"(v.w) : "l"(p)); return v;
}

__device__ __forceinline__ void ln_rows(const uint4 (&rv)[5], uint32_t buf, int cta, unsigned epoch) {
  const int t = threadIdx.x - 128, row = cta * 16 + (t >> 4), c = t & 15;
  const float sh = __shfl_sync(0xffffffffu, bf_lo(rv[0].x), t & 16);
  float d[40], s = 0.f, q = 0.f;
  #pragma unroll
  for (int j = 0; j < 5; j++) {
    const uint32_t u[4] = {rv[j].x, rv[j].y, rv[j].z, rv[j].w};
    #pragma unroll
    for (int e = 0; e < 4; e++) {
      const float d0 = bf_lo(u[e]) - sh, d1 = bf_hi(u[e]) - sh;
      d[j * 8 + e * 2] = d0; d[j * 8 + e * 2 + 1] = d1;
      s += d0 + d1; q = fmaf(d0, d0, q); q = fmaf(d1, d1, q);
    }
  }
  #pragma unroll
  for (int o = 1; o < 16; o <<= 1) { s += __shfl_xor_sync(0xffffffffu, s, o); q += __shfl_xor_sync(0xffffffffu, q, o); }
  const float md = s * (1.f / DM);
  const float r = rsqrtf(fmaxf(fmaf(q, 1.f / DM, -md * md), 0.f) + LN_EPS), o = -md * r;
  if (c == 0) st_vol2(&g_xstat[row], __float_as_uint(r), (__float_as_uint(-(md + sh) * r) & ~255u) | (epoch & 255u));
  #pragma unroll
  for (int j = 0; j < 5; j++) {
    const float* a = &d[j * 8];
    sts128(buf + (t >> 4) * 1280 + (c + 16 * j) * 16,
           pack_bf16(fmaf(a[0], r, o), fmaf(a[1], r, o)), pack_bf16(fmaf(a[2], r, o), fmaf(a[3], r, o)),
           pack_bf16(fmaf(a[4], r, o), fmaf(a[5], r, o)), pack_bf16(fmaf(a[6], r, o), fmaf(a[7], r, o)));
  }
  fence_async_smem();
  bar_arrive<BAR_LN>(288);
}

__device__ __forceinline__ void weight_sums(const bf16* __restrict__ win, const bf16* __restrict__ wdre, int j, unsigned epoch) {
  const int t = threadIdx.x & 127, w = t >> 5, l = t & 31;
  const int cj = min(j, 59), cg = cj % 12, rg = cj / 12, wr = j * 10 + min(t >> 3, 9);
  uint4 cv[8], rv[10];
  #pragma unroll
  for (int i = 0; i < 8; i++) cv[i] = ldg128(reinterpret_cast<const uint4*>(win + (size_t)(rg * 128 + w * 32 + i * 4 + (l >> 3)) * FF + FH + cg * 64) + (l & 7));
  #pragma unroll
  for (int i = 0; i < 10; i++) rv[i] = ldg128(reinterpret_cast<const uint4*>(wdre + (size_t)wr * DM) + (l & 7) + 8 * i);
  float v[8];
  #pragma unroll
  for (int e = 0; e < 8; e++) v[e] = 0.f;
  #pragma unroll
  for (int i = 0; i < 8; i++) {
    v[0] += bf_lo(cv[i].x); v[1] += bf_hi(cv[i].x); v[2] += bf_lo(cv[i].y); v[3] += bf_hi(cv[i].y);
    v[4] += bf_lo(cv[i].z); v[5] += bf_hi(cv[i].z); v[6] += bf_lo(cv[i].w); v[7] += bf_hi(cv[i].w);
  }
  #pragma unroll
  for (int st = 0; st < 2; st++) {
    const int n = 4 >> st;
    const bool up = (l & (4 * n)) != 0;
    #pragma unroll
    for (int e = 0; e < 4; e++)
      if (e < n) { const float keep = up ? v[e + n] : v[e], send = up ? v[e] : v[e + n]; v[e] = keep + __shfl_xor_sync(0xffffffffu, send, 4 * n); }
  }
  float* red = reinterpret_cast<float*>(smem + RED_OFF);
  *reinterpret_cast<float2*>(red + w * 64 + (l & 7) * 8 + (l >> 3) * 2) = make_float2(v[0], v[1]);
  float s = 0.f;
  #pragma unroll
  for (int i = 0; i < 10; i++) s += sum8(rv[i]);
  #pragma unroll
  for (int o = 1; o < 8; o <<= 1) s += __shfl_xor_sync(0xffffffffu, s, o);
  if ((l & 7) == 0) st_vol2(&g_csum[5 * FH + wr], __float_as_uint(s), epoch);
  bar_sync<BAR_WG1>(128);
  if (t < 64) st_vol2(&g_csum[rg * FH + cg * 64 + t], __float_as_uint((red[t] + red[64 + t]) + (red[128 + t] + red[192 + t])), epoch);
}

__device__ __forceinline__ void gather96(const uint2* src, float* dst, unsigned epoch) {
  unsigned it = 0;
  while (true) {
    bool ok = true;
    uint2 u[15];
    #pragma unroll
    for (int j = 0; j < 15; j++) u[j] = ld_vol2(src + (j % 5) * FH + (j / 5) * 32);
    #pragma unroll
    for (int j = 0; j < 15; j++) ok = ok && u[j].y == epoch;
    #pragma unroll
    for (int j = 0; j < 3; j++)
      dst[j * 32] = ((__uint_as_float(u[j * 5].x) + __uint_as_float(u[j * 5 + 1].x)) + (__uint_as_float(u[j * 5 + 2].x) + __uint_as_float(u[j * 5 + 3].x))) + __uint_as_float(u[j * 5 + 4].x);
    if (ok || ++it > POLL_LIMIT) break;
    __nanosleep(2 * POLL_NS);
  }
}

__device__ __forceinline__ void a_entry(int g, int grp, int ct, int& mi, int& kb) {
  if (g < 10) { mi = M_X; kb = g; }
  else if (g < 20) { mi = M_XN; kb = g - 10; }
  else if (g < 52) { mi = grp == 0 ? M_WSP : M_WSRE; kb = g - 20; }
  else if (grp == 0) {
    if (g < 52 + NX) { mi = M_WSIM; kb = g - 52 + 32 - NX; }
    else {
      const int i = g - 52 - NX;
      mi = M_H; kb = i < 3 ? ct * 3 + i : i < 6 ? (ct ^ 1) * 3 + i - 3 : ((ct >> 1) ^ 1) * 6 + i - 6;
    }
  } else {
    if (g < 84 - NX) { mi = M_WSIM; kb = g - 52; }
    else { mi = M_H; kb = ((ct >> 1) ^ 1) * 6 + g - (84 - NX) + 6 - NO; }
  }
}

__global__ void __cluster_dims__(2, 1, 1) __launch_bounds__(384, 1)
fused_kernel(const __grid_constant__ Maps maps, const bf16* __restrict__ x, const bf16* __restrict__ win, const bf16* __restrict__ wdre,
             const bf16* __restrict__ bsp, bf16* __restrict__ out) {
  const uint32_t sbase = smem_u32(smem);
  const uint32_t full0 = sbase + BAR_OFF, empty0 = full0 + 8 * MAXST, dep0 = empty0 + 8 * MAXST, ring = sbase + RING_OFF;
  const int tid = threadIdx.x, wg = __shfl_sync(0xffffffffu, tid >> 7, 0);
  const int cta = blockIdx.x, rank = cta & 1, grp = (cta >> 1) & 1, rb = cta >> 3, ct = ((cta >> 2) & 1) * 2 + rank;
  const int total = grp == 0 ? KB_A : KB_B, gh = grp == 0 ? 52 + NX : 84 - NX;
  const uint32_t stage_bytes = grp == 0 ? STAGE_A : STAGE_B;
  const int nst = grp == 0 ? NST_A : NST_B;
  const uint32_t buf = ring + nst * stage_bytes;

  uint4 rv[5];
  if (wg != 0) {
    #pragma unroll
    for (int j = 0; j < 5; j++) rv[j] = ldg128(reinterpret_cast<const uint4*>(x + (size_t)(cta * 16 + ((tid - 128) >> 4)) * DM) + (tid & 15) + 16 * j);
  }
  const unsigned epoch = (ld_relaxed(&g_done) >> 7) + 1u;
  if (tid == 0) {
    TS(0, 0);
    for (int s = 0; s < MAXST; s++) { mbar_init(full0 + 8 * s, 2); mbar_init(empty0 + 8 * s, 4); mbar_init(dep0 + 8 * s, 1); }
    *reinterpret_cast<volatile int*>(smem + READY_OFF) = 0;
    asm volatile("fence.mbarrier_init.release.cluster;" ::: "memory");
  }
  __syncthreads();
  asm volatile("barrier.cluster.arrive.relaxed.aligned;" ::: "memory");

  if (wg == 0) {
    asm volatile("setmaxnreg.dec.sync.aligned.u32 40;");
    const int warp = tid >> 5, lane = tid & 31;
    if (warp == 0) {
      const int row = rb * 128;
      if (lane == 0) {
        for (int g = 0; g < nst; g++) {
          mbar_expect_tx(full0 + 8 * g, A_BYTES);
          tma_load_2d(ring + g * stage_bytes, &maps.m[M_X], full0 + 8 * g, g * 64, row);
          tma_load_2d(ring + g * stage_bytes + 8192, &maps.m[M_X], full0 + 8 * g, g * 64, row + 64);
        }
      }
      __syncwarp();
      cluster_wait();
      if (lane == 0) {
        int s = 0, ph = 0;
        #pragma unroll 1
        for (int g = nst; g < total; g++) {
          int mi, kb;
          a_entry(g, grp, ct, mi, kb);
          if (g == 10 || g == gh + 3 - 3 * grp) { TS(0, g > 10 ? 3 : 1); mbar_wait(dep0 + (g > 10 ? 24 : 0), 0); fence_async_global(); TS(0, g > 10 ? 4 : 2); }
          mbar_wait(empty0 + 8 * s, ph);
          if (grp == 0 && g >= gh && g < gh + 6) {
            if (g < gh + 3) {
              mbar_arrive(full0 + 8 * s);
            } else {
              mbar_expect_tx(full0 + 8 * s, A_BYTES);
              tma_load_2d(ring + s * stage_bytes, &maps.m[mi], full0 + 8 * s, kb * 64, row);
              tma_load_2d(ring + s * stage_bytes + 8192, &maps.m[mi], full0 + 8 * s, kb * 64, row + 64);
            }
          } else {
            mbar_expect_tx(full0 + 8 * s, A_BYTES);
            tma_load_2d_mc(ring + s * stage_bytes + rank * 8192, &maps.m[mi], full0 + 8 * s, kb * 64, row + rank * 64, 3);
          }
          if (++s == nst) { s = 0; ph ^= 1; }
          if (g + PF_D < gh && (PFB || grp == 0)) {
            a_entry(g + PF_D, grp, ct, mi, kb);
            if (mi >= M_WSRE && (kb & 1) == (ct >> 1))
              asm volatile("cp.async.bulk.prefetch.tensor.2d.L2.global.tile [%0, {%1, %2}];" :: "l"((uint64_t)&maps.m[mi]), "r"(kb * 64), "r"(row + rank * 64) : "memory");
          }
        }
        TS(0, 5);
      }
    } else if (warp == 1) {
      if (lane == 0) {
        int s = 0, ph = 1;
        int have = 0;
        #pragma unroll 1
        for (int g = 0; g < total; g++) {
          int mi, kb, c;
          a_entry(g, grp, ct, mi, kb);
          const bool nmaj = g >= gh || (grp == 0 && g < 52);
          uint32_t bytes = 20480;
          if (g >= gh) { mi = M_WOUT; c = ct * 5; }
          else if (g >= 52) { mi = M_AB; c = DM + ct * 160; }
          else if (grp == 0) { mi = g < 20 ? M_WIN3 : M_Z23; c = 3 * ct + (g < 10 ? 12 : 0); bytes = 24576; }
          else { mi = g < 10 ? M_WDRE : g < 20 ? M_WDIM : M_AB; c = ct * 160; }
          if (g >= 20 && g < 52 && ((g - 20) >> 1) >= have) {
            if (g == 20) TS(1, 0);
            unsigned it = 0;
            while ((have = *reinterpret_cast<volatile int*>(smem + READY_OFF)) <= ((g - 20) >> 1) && ++it < 50 * POLL_LIMIT) {}
            fence_async_global();
            if (g == 20) { TS(1, 1); TC(1); }
          }
          if (g == 52) { TS(1, 2); mbar_wait(dep0 + 16, 0); fence_async_global(); TS(1, 3); TC(2); }
          const uint32_t dst = ring + s * stage_bytes + A_BYTES, fb = full0 + 8 * s;
          mbar_wait(empty0 + 8 * s, ph);
          if (++s == nst) { s = 0; ph ^= 1; }
          mbar_expect_tx(fb, bytes);
          if (nmaj) tma_load_3d(dst, &maps.m[mi], fb, 0, kb * 64, c);
          else tma_load_2d(dst, &maps.m[mi], fb, kb * 64, c);
        }
      }
      __syncwarp();
      cluster_wait();
    } else if (warp == 2) {
      if (lane < M_COUNT) asm volatile("prefetch.tensormap [%0];" :: "l"((uint64_t)&maps.m[lane]) : "memory");
      cluster_wait();
      {
        unsigned it = 0;
        uint2 v[4];
        while (true) {
          bool ok = true;
          #pragma unroll
          for (int i = 0; i < 4; i++) { v[i] = ld_vol2(&g_xstat[rb * 128 + i * 32 + lane]); ok = ok && ((v[i].y ^ epoch) & 255u) == 0; }
          if (ok || ++it > POLL_LIMIT) break;
          __nanosleep(POLL_NS);
        }
        #pragma unroll
        for (int i = 0; i < 4; i++) reinterpret_cast<uint2*>(smem + ROWSTAT_OFF)[i * 32 + lane] = make_uint2(v[i].x, v[i].y & ~255u);
        __syncwarp();
        TS(0, 6);
        if (grp == 0) bar_arrive<BAR_STATS>(320); else bar_arrive<BAR_STATS>(192);
      }
      #pragma unroll 1
      for (int i = 0; i < 5; i++) {
        const int d = i == 3 ? 4 : i == 4 ? 3 : i;
        const int slot = d == 0 ? F_XN + rb : d == 4 ? F_Y + rb * 4 + ct : d == 3 ? F_H + rb : d == 2 ? F_B + ct : grp == 0 ? F_Z + ct : F_A + ct;
        const int byte = d == 0 ? lane & 7 : d == 4 ? 0 : d == 3 ? lane & 3 : lane & 15;
        unsigned it = 0, m;
        while ((m = __ballot_sync(0xffffffffu, get_flag(slot, byte) != (epoch & 255u))) != 0 && ++it < POLL_LIMIT) {
          if (d == 1 && lane == 0) *reinterpret_cast<volatile int*>(smem + READY_OFF) = __ffs(m) - 1;
          __nanosleep(WATCH_NS);
        }
        if (d == 1 && lane == 0) *reinterpret_cast<volatile int*>(smem + READY_OFF) = 16;
        if (d < 4) TS(0, 8 + d * 2); else TS(0, 7);
        fence_async_global();
        __syncwarp();
        if (lane == 0 && d != 1) mbar_arrive(dep0 + 8 * d);
      }
    } else {
      cluster_wait();
      bar_sync<BAR_LN>(288);
      if (lane == 0) {
        TS(1, 5);
        asm volatile("cp.async.bulk.global.shared::cta.bulk_group [%0], [%1], 20480;" :: "l"(g_xn + (size_t)cta * 16 * DM), "r"(buf) : "memory");
        bulk_commit();
        bulk_wait_all();
        set_flag(F_XN + rb, cta & 7, epoch);
        TS(1, 6);
      }
      __syncwarp();
      if (grp == 0) {
        #pragma unroll 1
        for (int i = 0; i < 2; i++) gather96(&g_csum[ct * 192 + i * 96 + lane], reinterpret_cast<float*>(smem + COLSUM_OFF) + i * 96 + lane, epoch);
      } else {
        unsigned it = 0;
        while (true) {
          bool ok = true;
          #pragma unroll
          for (int j = 0; j < 5; j++) {
            const uint2 u = ld_vol2(&g_csum[5 * FH + ct * 160 + j * 32 + lane]);
            ok = ok && u.y == epoch;
            reinterpret_cast<uint32_t*>(smem + COLSUM_OFF)[j * 32 + lane] = u.x;
          }
          if (ok || ++it > POLL_LIMIT) break;
          __nanosleep(2 * POLL_NS);
        }
      }
      __syncwarp();
      TS(1, 4);
      if (grp == 0) {
        bar_arrive<BAR_STATS>(320);
        bar_sync<BAR_PUB1>(160);
        if (lane == 0) { store_tile(&maps.m[M_Z23], buf, rb, ct); set_flag(F_Z + ct, rb, epoch); }
        TS(1, 8);
        __syncwarp();
        bar_arrive<BAR_BUF>(160);
      } else {
        bar_arrive<BAR_STATS>(192);
        bar_sync<BAR_PUB2>(160);
        if (lane == 0) set_flag(F_A + ct, rb, epoch);
        TS(1, 9);
        __syncwarp();
      }
      bar_sync<BAR_PUB1>(160);
      if (lane == 0) {
        if (grp == 0) store_tile(&maps.m[M_H3], buf, rb, ct);
        set_flag(grp == 0 ? F_H + rb : F_B + ct, grp == 0 ? ct : rb, epoch);
      }
      TS(1, 10);
      __syncwarp();
      bar_arrive<BAR_BUF>(160);
    }
  } else {
    asm volatile("setmaxnreg.inc.sync.aligned.u32 232;");
    const int t = tid & 127, w = t >> 5, l = t & 31;
    ln_rows(rv, buf, cta, epoch);
    TS(wg + 1, 0);
    cluster_wait();
    const uint32_t st_base = buf + (w * 16 + ((l >> 3) & 1) * 8 + (l & 7)) * 128;
    const uint32_t st_x = ((l >> 4) ^ (l & 7)) << 4;
    const float2* rs = reinterpret_cast<const float2*>(smem + ROWSTAT_OFF) + w * 16 + (l >> 2);
    const float2* cs = reinterpret_cast<const float2*>(smem + COLSUM_OFF) + (l & 3);
    if (grp == 0) {
      {
        const int mb = wg - 1;
        float acc[1][96];
        zero(acc);
        mainloop<192, 1, 1, false, 0>(acc, sbase, 0, 0, 10, mb);
        drain(acc, sbase, 0, 9);
        TS(wg + 1, 1);
        bar_sync<BAR_STATS>(320);
        const float2 s0 = rs[mb * 64], s1 = rs[mb * 64 + 8];
        const float nm[2] = {s0.y / s0.x, s1.y / s1.x}, hr[2] = {0.5f * s0.x, 0.5f * s1.x};
        const float k1[2] = {0.7978845608f * s0.x, 0.7978845608f * s1.x};
        const float k2[2] = {0.0356774081f * s0.x * s0.x * s0.x, 0.0356774081f * s1.x * s1.x * s1.x};
        float sm0 = 0.f, sm1 = 0.f, q0 = 0.f, q1 = 0.f;
        #pragma unroll
        for (int jj = 0; jj < 12; jj++) {
          float u[8];
          #pragma unroll
          for (int hf = 0; hf < 2; hf++) {
            const float2 c = cs[jj * 8 + hf * 4];
            #pragma unroll
            for (int e = 0; e < 4; e++) {
              const float wv = fmaf(nm[e >> 1], (e & 1) ? c.y : c.x, acc[0][8 * jj + 4 * hf + e]);
              float th; asm("tanh.approx.f32 %0, %1;" : "=f"(th) : "f"(wv * fmaf(k2[e >> 1], wv * wv, k1[e >> 1])));
              const float hv = hr[e >> 1] * wv;
              u[4 * hf + e] = fmaf(hv, th, hv);
            }
            sm0 += u[4 * hf] + u[4 * hf + 1]; q0 = fmaf(u[4 * hf], u[4 * hf], q0); q0 = fmaf(u[4 * hf + 1], u[4 * hf + 1], q0);
            sm1 += u[4 * hf + 2] + u[4 * hf + 3]; q1 = fmaf(u[4 * hf + 2], u[4 * hf + 2], q1); q1 = fmaf(u[4 * hf + 3], u[4 * hf + 3], q1);
          }
          stsm4(st_base + mb * 24576 + (jj >> 2) * 8192 + (st_x ^ ((jj & 3) << 5)),
                pack_bf16(u[0], u[1]), pack_bf16(u[2], u[3]), pack_bf16(u[4], u[5]), pack_bf16(u[6], u[7]));
        }
        #pragma unroll
        for (int o = 1; o < 4; o <<= 1) {
          sm0 += __shfl_xor_sync(0xffffffffu, sm0, o); q0 += __shfl_xor_sync(0xffffffffu, q0, o);
          sm1 += __shfl_xor_sync(0xffffffffu, sm1, o); q1 += __shfl_xor_sync(0xffffffffu, q1, o);
        }
        if ((l & 3) < 2) {
          const float sm = (l & 1) ? sm1 : sm0, sv = (l & 1) ? q1 : q0;
          const int row = mb * 64 + w * 16 + (l & 1) * 8 + (l >> 2);
          const float mu = sm * (1.f / 192), m2 = fmaxf(sv - sm * mu, 0.f);
          st_vol2(&g_zstat[(rb * 4 + ct) * 128 + row], __float_as_uint(mu), (__float_as_uint(m2) & ~255u) | (epoch & 255u));
          reinterpret_cast<float2*>(smem + ZSTAT_OFF)[row] = make_float2(mu, m2);
        }
        TS(wg + 1, 4);
      }
      float acc[2][96];
      if (wg == 1) {
        bar_sync<BAR_U>(256);
        const uint32_t rbase = buf + (t >> 6) * 24576 + (t & 63) * 128;
        uint4 zu[24];
        #pragma unroll
        for (int i = 0; i < 24; i++) zu[i] = lds128(rbase + (i >> 3) * 8192 + (((i ^ l) & 7) << 4));
        uint2 v[3];
        unsigned n = 0;
        while (true) {
          bool ok = true;
          #pragma unroll
          for (int j = 0; j < 3; j++) { v[j] = ld_vol2(&g_zstat[(rb * 4 + ((ct + 1 + j) & 3)) * 128 + t]); ok = ok && ((v[j].y ^ epoch) & 255u) == 0; }
          if (ok || ++n > POLL_LIMIT) break;
          __nanosleep(POLL_NS);
        }
        const float2 own = reinterpret_cast<const float2*>(smem + ZSTAT_OFF)[t];
        const float m0 = __uint_as_float(v[0].x), m1 = __uint_as_float(v[1].x), m3 = __uint_as_float(v[2].x);
        const float mean = 0.25f * ((own.x + m0) + (m1 + m3));
        const float d = (own.x - mean) * (own.x - mean) + (m0 - mean) * (m0 - mean) + (m1 - mean) * (m1 - mean) + (m3 - mean) * (m3 - mean);
        const float var = fmaf(192.f, d, (own.y + __uint_as_float(v[0].y & ~255u)) + (__uint_as_float(v[1].y & ~255u) + __uint_as_float(v[2].y & ~255u)));
        const float r = rsqrtf(var * (1.f / FH) + LN_EPS);
        TS(2, 5);
        const uint32_t m2 = pack_bf16(-mean, -mean), r2 = pack_bf16(r, r);
        const float res = (-mean - bf_lo(m2)) * r;
        const uint32_t e2 = pack_bf16(res, res);
        #pragma unroll
        for (int i = 0; i < 24; i++)
          sts128(rbase + (i >> 3) * 8192 + (((i ^ l) & 7) << 4), hfma2_bf16(hadd2_bf16(zu[i].x, m2), r2, e2), hfma2_bf16(hadd2_bf16(zu[i].y, m2), r2, e2),
                 hfma2_bf16(hadd2_bf16(zu[i].z, m2), r2, e2), hfma2_bf16(hadd2_bf16(zu[i].w, m2), r2, e2));
        fence_async_smem();
        TS(2, 6);
        bar_arrive<BAR_PUB1>(160);
        {
          const bf16* bp = bsp + rb * 128 + w * 16 + (l >> 2);
          const float bb[4] = {__bfloat162float(bp[0]), __bfloat162float(bp[8]), __bfloat162float(bp[64]), __bfloat162float(bp[72])};
          #pragma unroll
          for (int i = 0; i < 96; i++) { acc[0][i] = bb[(i >> 1) & 1]; acc[1][i] = bb[2 + ((i >> 1) & 1)]; }
          pin(acc);
        }
        bar_sync<BAR_ORD2>(256);
        mainloop<192, 2, 1, false, BAR_ORD1>(acc, sbase, 0, 20, 32);
        bar_sync<BAR_Z1>(256);
        uint32_t z[6][4][4];
        #pragma unroll
        for (int i = 0; i < ZPRE; i++) ldsm4(st_base + (i >> 2) * 8192 + (st_x ^ ((i & 3) << 5)), z[i >> 2][i & 3][0], z[i >> 2][i & 3][1], z[i >> 2][i & 3][2], z[i >> 2][i & 3][3]);
        drain(acc, sbase, 0, 51);
        TS(2, 7);
        #pragma unroll
        for (int bx = 0; bx < 6; bx++) {
          if (bx >= 1) {
            #pragma unroll
            for (int i = ZPRE + (bx - 1) * 10; i < ZPRE + bx * 10; i++)
              if (i < 24) ldsm4(st_base + (i >> 2) * 8192 + (st_x ^ ((i & 3) << 5)), z[i >> 2][i & 3][0], z[i >> 2][i & 3][1], z[i >> 2][i & 3][2], z[i >> 2][i & 3][3]);
          }
          #pragma unroll
          for (int i = 0; i < 4; i++) {
            const float* a = &acc[bx / 3][8 * ((bx % 3) * 4 + i)];
            const uint32_t* zz = z[bx][i];
            stsm4(st_base + bx * 8192 + (st_x ^ (i << 5)),
                  hmul2_bf16(zz[0], pack_bf16(a[0], a[1])), hmul2_bf16(zz[1], pack_bf16(a[2], a[3])),
                  hmul2_bf16(zz[2], pack_bf16(a[4], a[5])), hmul2_bf16(zz[3], pack_bf16(a[6], a[7])));
          }
        }
        fence_async_smem();
        bar_arrive<BAR_U>(256);
        TS(2, 8);
        bar_arrive<BAR_PUB1>(160);
        TS(2, 9);
        return;
      }
      bar_arrive<BAR_U>(256);
      zero(acc);
      mainloop<192, 2, 1, false, BAR_ORD2>(acc, sbase, 0, 10, 10);
      drain(acc, sbase, 0, 19);
      TS(3, 2);
      bar_sync<BAR_BUF>(160);
      #pragma unroll
      for (int mi = 0; mi < 2; mi++)
        #pragma unroll
        for (int jj = 0; jj < 12; jj++) {
          const float* a = &acc[mi][8 * jj];
          stsm4(st_base + mi * 24576 + (jj >> 2) * 8192 + (st_x ^ ((jj & 3) << 5)),
                pack_bf16(a[0], a[1]), pack_bf16(a[2], a[3]), pack_bf16(a[4], a[5]), pack_bf16(a[6], a[7]));
        }
      __syncwarp();
      TS(3, 3);
      const uint32_t rbase = buf + (l >> 4) * 24576 + (w * 16 + (l & 15)) * 128;
      #pragma unroll 1
      for (int c2 = 0; c2 < 12; c2++) {
        const uint32_t ab = rbase + (c2 >> 2) * 8192;
        uint4 v[2];
        #pragma unroll
        for (int i = 0; i < 2; i++) v[i] = lds128(ab + (((((c2 & 3) * 2 + i) ^ l) & 7) << 4));
        #pragma unroll
        for (int i = 0; i < 2; i++)
          sts128(ab + (((((c2 & 3) * 2 + i) ^ l) & 7) << 4),
                 pack_bf16(gelu_tanh(bf_lo(v[i].x)), gelu_tanh(bf_hi(v[i].x))), pack_bf16(gelu_tanh(bf_lo(v[i].y)), gelu_tanh(bf_hi(v[i].y))),
                 pack_bf16(gelu_tanh(bf_lo(v[i].z)), gelu_tanh(bf_hi(v[i].z))), pack_bf16(gelu_tanh(bf_lo(v[i].w)), gelu_tanh(bf_hi(v[i].w))));
        __nanosleep(Z1_NS);
      }
      TS(3, 5);
      bar_arrive<BAR_Z1>(256);
    }
    float acc[2][80];
    if (grp == 1) {
      zero(acc);
      if (wg == 2) {
        mainloop<160, 2, 0, false, BAR_ORD2>(acc, sbase, 1, 0, 10);
      } else {
        weight_sums(win, wdre, rb * 4 + ct, epoch);
        TS(2, 1);
        bar_sync<BAR_ORD2>(256);
        mainloop<160, 2, 0, false, BAR_ORD1>(acc, sbase, 1, 10, 10);
      }
      drain(acc, sbase, 1, wg == 2 ? 9 : 19);
      TS(wg + 1, wg == 1 ? 7 : 2);
      if (wg == 1) bar_sync<BAR_Z1>(256); else bar_sync<BAR_STATS>(192);
      const uint32_t tb = buf + ((l >> 4) * 8 + (l & 7)) * 128 + (((w * 2 + ((l >> 3) & 1)) ^ (l & 7)) << 4);
      float2 st[4];
      #pragma unroll
      for (int r = 0; r < 4; r++) st[r] = wg == 2 ? rs[(r >> 1) * 64 + (r & 1) * 8] : make_float2(-1.f, 0.f);
      #pragma unroll
      for (int jj = 0; jj < 10; jj++) {
        const float2 c0 = cs[jj * 8], c1 = cs[jj * 8 + 4];
        #pragma unroll
        for (int mi = 0; mi < 2; mi++) {
          const float* a = &acc[mi][8 * jj];
          const float2 s0 = st[mi * 2], s1 = st[mi * 2 + 1];
          stsm4_t(tb + mi * 20480 + jj * 2048,
                  pack_bf16(fmaf(a[0], s0.x, s0.y * c0.x), fmaf(a[1], s0.x, s0.y * c0.y)), pack_bf16(fmaf(a[2], s1.x, s1.y * c0.x), fmaf(a[3], s1.x, s1.y * c0.y)),
                  pack_bf16(fmaf(a[4], s0.x, s0.y * c1.x), fmaf(a[5], s0.x, s0.y * c1.y)), pack_bf16(fmaf(a[6], s1.x, s1.y * c1.x), fmaf(a[7], s1.x, s1.y * c1.y)));
        }
      }
      fence_async_smem();
      if (wg == 1) bar_sync<BAR_WG1>(128); else bar_sync<BAR_WG2>(128);
      TS(wg + 1, wg == 1 ? 8 : 6);
      if (l < 2) {
        tma_store_2d(&maps.m[M_ABS], buf + l * 20480 + w * 5120, rb * 128 + l * 64, (2 - wg) * DM + ct * 160 + w * 40);
        bulk_commit();
        bulk_wait_all();
      }
      __syncwarp();
      TS(wg + 1, wg == 1 ? 9 : 10);
      if (wg == 1) {
        bar_arrive<BAR_PUB1>(160);
        #pragma unroll 1
        for (int i = 0; i < 4; i++) {
          uint4 v[5];
          #pragma unroll
          for (int j = 0; j < 5; j++) {
            const int e = (i * 5 + j) * 128 + t;
            v[j] = ldg128(x + (size_t)(rb * 128 + e / 20) * DM + ct * 160 + (e % 20) * 8);
          }
          #pragma unroll
          for (int j = 0; j < 5; j++) {
            const int e = (i * 5 + j) * 128 + t;
            stg128(out + (size_t)(rb * 128 + e / 20) * DM + ct * 160 + (e % 20) * 8, v[j]);
          }
        }
        bar_sync<BAR_WG1>(128);
        if (t == 0) publish(F_Y + rb * 4 + ct, 0, epoch);
        return;
      }
      bar_arrive<BAR_PUB2>(160);
      bar_arrive<BAR_Z1>(256);
    }
    zero(acc);
    bar_sync<BAR_ORD1>(256);
    mainloop<160, 2, 0, false, 0>(acc, sbase, grp, grp == 0 ? 52 : 20, grp == 0 ? NX : 64 - NX);
    if (grp == 0) {
      bar_sync<BAR_U>(256);
      mainloop<160, 2, 2, true, 0, true>(acc, sbase, 0, 52 + NX, 3);
    }
    mainloop<160, 2, 2, true, 0>(acc, sbase, grp, gh + 3 - 3 * grp, total - gh - 3 + 3 * grp);
    const uint32_t slab = buf + w * (16 * 320);
    const uint32_t addr = slab + (((l >> 3) & 1) * 8 + (l & 7)) * 320 + (l >> 4) * 16;
    bar_sync<BAR_BUF>(160);
    mbar_wait(dep0 + 32, 0);
    drain(acc, sbase, grp, total - 1);
    TS(3, 12);
    #pragma unroll
    for (int mi = 0; mi < 2; mi++) {
      #pragma unroll
      for (int jj = 0; jj < 10; jj++) {
        const float* a = &acc[mi][8 * jj];
        stsm4(addr + mi * 20480 + jj * 32, pack_bf16(a[0], a[1]), pack_bf16(a[2], a[3]), pack_bf16(a[4], a[5]), pack_bf16(a[6], a[7]));
      }
      fence_async_smem();
      __syncwarp();
      if (l == 0) {
        tma_reduce_2d(&maps.m[M_OUT], slab + mi * 20480, ct * 160, rb * 128 + mi * 64 + w * 16);
        bulk_commit();
      }
    }
    TS(3, 13);
    if (l == 0) {
      bulk_wait_read();
      if (w == 0) atomicAdd(&g_done, 1u);
    }
    TS(3, 15);
  }
}

typedef CUresult (*EncodeFn)(CUtensorMap*, CUtensorMapDataType, cuuint32_t, void*, const cuuint64_t*, const cuuint64_t*,
                             const cuuint32_t*, const cuuint32_t*, CUtensorMapInterleave, CUtensorMapSwizzle,
                             CUtensorMapL2promotion, CUtensorMapFloatOOBfill);

void make2d(EncodeFn enc, CUtensorMap* m, const void* p, uint64_t cols, uint64_t rows, uint32_t bc, uint32_t br, bool swz = true) {
  cuuint64_t gd[2] = {cols, rows}, gs[1] = {cols * 2};
  cuuint32_t bd[2] = {bc, br}, es[2] = {1, 1};
  enc(m, CU_TENSOR_MAP_DATA_TYPE_BFLOAT16, 2, const_cast<void*>(p), gd, gs, bd, es, CU_TENSOR_MAP_INTERLEAVE_NONE,
      swz ? CU_TENSOR_MAP_SWIZZLE_128B : CU_TENSOR_MAP_SWIZZLE_NONE, CU_TENSOR_MAP_L2_PROMOTION_L2_128B, CU_TENSOR_MAP_FLOAT_OOB_FILL_NONE);
}
void make3d(EncodeFn enc, CUtensorMap* m, const void* p, uint64_t cols, uint64_t rows, uint32_t cw, uint32_t nc, uint32_t br = 64) {
  cuuint64_t gd[3] = {cw, rows, cols / cw}, gs[2] = {cols * 2, cw * 2};
  cuuint32_t bd[3] = {cw, br, nc}, es[3] = {1, 1, 1};
  enc(m, CU_TENSOR_MAP_DATA_TYPE_BFLOAT16, 3, const_cast<void*>(p), gd, gs, bd, es, CU_TENSOR_MAP_INTERLEAVE_NONE,
      cw == 64 ? CU_TENSOR_MAP_SWIZZLE_128B : CU_TENSOR_MAP_SWIZZLE_64B, CU_TENSOR_MAP_L2_PROMOTION_L2_128B, CU_TENSOR_MAP_FLOAT_OOB_FILL_NONE);
}

}

extern "C" void kernel_launch(void* const* d_in, const int* in_sizes, int n_in, void* d_out, int out_size) {
  const bf16* x = (const bf16*)d_in[0];
  const bf16* wsre = (const bf16*)d_in[1];
  const bf16* wsim = (const bf16*)d_in[2];
  const bf16* wdre = (const bf16*)d_in[3];
  const bf16* wdim = (const bf16*)d_in[4];
  const bf16* win = (const bf16*)d_in[6];
  const bf16* wsp = (const bf16*)d_in[7];
  const bf16* bsp = (const bf16*)d_in[8];
  const bf16* wout = (const bf16*)d_in[9];

  void* fn = nullptr;
  cudaDriverEntryPointQueryResult qr;
  cudaGetDriverEntryPoint("cuTensorMapEncodeTiled", &fn, cudaEnableDefault, &qr);
  EncodeFn enc = (EncodeFn)fn;
  void *abT, *z2, *h, *xn;
  cudaGetSymbolAddress(&xn, g_xn);
  cudaGetSymbolAddress(&abT, g_abT);
  cudaGetSymbolAddress(&z2, g_z2);
  cudaGetSymbolAddress(&h, g_h);

  Maps maps;
  make2d(enc, &maps.m[M_X], x, DM, SEQ, 64, 64);
  make2d(enc, &maps.m[M_XN], xn, DM, SEQ, 64, 64);
  make2d(enc, &maps.m[M_WSRE], wsre, SEQ, SEQ, 64, 64);
  make2d(enc, &maps.m[M_WSIM], wsim, SEQ, SEQ, 64, 64);
  make2d(enc, &maps.m[M_WSP], wsp, SEQ, SEQ, 64, 64);
  make2d(enc, &maps.m[M_H], h, FH, SEQ, 64, 64);
  make3d(enc, &maps.m[M_WIN3], win, FF, DM, 64, 3);
  make3d(enc, &maps.m[M_Z23], z2, FH, SEQ, 64, 3);
  make2d(enc, &maps.m[M_WDRE], wdre, DM, DM, 64, 160);
  make2d(enc, &maps.m[M_WDIM], wdim, DM, DM, 64, 160);
  make2d(enc, &maps.m[M_AB], abT, SEQ, 2 * DM, 64, 160);
  make3d(enc, &maps.m[M_WOUT], wout, DM, FH, 32, 5);
  make3d(enc, &maps.m[M_H3], h, FH, SEQ, 64, 3);
  make2d(enc, &maps.m[M_ABS], abT, SEQ, 2 * DM, 64, 40);
  make2d(enc, &maps.m[M_OUT], d_out, DM, SEQ, 160, 16, false);

  cudaFuncSetAttribute(fused_kernel, cudaFuncAttributeMaxDynamicSharedMemorySize, SMEM_BYTES);
  fused_kernel<<<128, 384, SMEM_BYTES>>>(maps, x, win, wdre, bsp, (bf16*)d_out);
}
```

```cpp
#include <cuda_runtime.h>
#include <cuda_bf16.h>
#include <cuda.h>
#include <stdint.h>

namespace {

typedef __nv_bfloat16 bf16;

constexpr int SEQ = 2048, DM = 640, FF = 1536, FH = 768;
constexpr int NX = 6;
constexpr int NO = 3;
constexpr int NST_A = 4, NST_B = 5, MAXST = 5;
constexpr int A_BYTES = 16384;
constexpr int BAR_OFF = 0;
constexpr int READY_OFF = 128;
constexpr int COLSUM_OFF = 256;
constexpr int ROWSTAT_OFF = 1024;
constexpr int ZSTAT_OFF = 2048;
constexpr int RED_OFF = 3072;
constexpr int RING_OFF = 4096;
constexpr int STAGE_A = 40960, STAGE_B = 36864;
constexpr int SMEM_BYTES = RING_OFF + 5 * STAGE_B + 40960;
constexpr int KB_A = 52 + NX + 12 - NO;
constexpr int KB_B = 84 - NX + NO;
constexpr float LN_EPS = 1e-5f;
constexpr unsigned POLL_LIMIT = 100000;
constexpr unsigned POLL_NS = 100, WATCH_NS = 40;
constexpr unsigned Z1_NS = 500;
constexpr int PF_D = 8;
constexpr int ZPRE = 6;

constexpr int BAR_ORD1 = 1, BAR_ORD2 = 2, BAR_WG1 = 3, BAR_WG2 = 4, BAR_LN = 5, BAR_BUF = 6, BAR_Z1 = 7, BAR_PUB1 = 8, BAR_PUB2 = 9,
              BAR_STATS = 10, BAR_U = 11;

enum { M_X, M_XN, M_WSRE, M_WSIM, M_WSP, M_H, M_WIN3, M_Z23, M_WDRE, M_WDIM, M_AB, M_WOUT, M_OUT, M_HS, M_ZS, M_ABS, M_COUNT };
struct Maps { CUtensorMap m[M_COUNT]; };

__device__ __align__(1024) bf16 g_abT[2 * DM * SEQ];
__device__ __align__(1024) bf16 g_z2[SEQ * FH];
__device__ __align__(1024) bf16 g_h[SEQ * FH];
__device__ __align__(1024) bf16 g_xn[SEQ * DM];
__device__ __align__(16) uint2 g_xstat[SEQ];
__device__ __align__(16) uint2 g_csum[5 * FH + DM];
__device__ __align__(16) uint2 g_zstat[64 * 128];
__device__ __align__(256) unsigned char g_flags[108 * 256];
constexpr int F_A = 0, F_B = 4, F_Z = 8, F_H = 12, F_XN = 28, F_Y = 44;
__device__ unsigned g_done;
#define TS(role, ev)
#define TC(i)

extern __shared__ __align__(1024) uint8_t smem[];

__device__ __forceinline__ uint32_t smem_u32(const void* p) { return (uint32_t)__cvta_generic_to_shared(p); }
__device__ __forceinline__ void mbar_init(uint32_t bar, uint32_t cnt) { asm volatile("mbarrier.init.shared::cta.b64 [%0], %1;" :: "r"(bar), "r"(cnt)); }
__device__ __forceinline__ void mbar_expect_tx(uint32_t bar, uint32_t bytes) { asm volatile("mbarrier.arrive.expect_tx.shared::cta.b64 _, [%0], %1;" :: "r"(bar), "r"(bytes) : "memory"); }
__device__ __forceinline__ void mbar_arrive(uint32_t bar) { asm volatile("mbarrier.arrive.shared::cta.b64 _, [%0];" :: "r"(bar) : "memory"); }
__device__ __forceinline__ void mbar_arrive_cluster(uint32_t bar, uint32_t cta) {
  asm volatile("{\n.reg .b32 ra;\nmapa.shared::cluster.u32 ra, %0, %1;\nmbarrier.arrive.shared::cluster.b64 _, [ra];\n}" :: "r"(bar), "r"(cta) : "memory");
}
__device__ __forceinline__ void mbar_wait(uint32_t bar, uint32_t parity) {
  asm volatile("{\n.reg .pred p;\n.reg .u32 n;\nmov.u32 n, 0;\n"
               "LW: mbarrier.try_wait.parity.shared::cta.b64 p, [%0], %1, 2000;\n@p bra LD;\n"
               "add.u32 n, n, 1;\nsetp.lt.u32 p, n, 20000;\n@p bra LW;\nLD:\n}" :: "r"(bar), "r"(parity) : "memory");
}
__device__ __forceinline__ void tma_load_2d(uint32_t dst, const CUtensorMap* map, uint32_t bar, int c0, int c1) {
  asm volatile("cp.async.bulk.tensor.2d.shared::cluster.global.mbarrier::complete_tx::bytes [%0], [%1, {%3, %4}], [%2];"
    :: "r"(dst), "l"((uint64_t)map), "r"(bar), "r"(c0), "r"(c1) : "memory");
}
__device__ __forceinline__ void tma_load_3d(uint32_t dst, const CUtensorMap* map, uint32_t bar, int c0, int c1, int c2) {
  asm volatile("cp.async.bulk.tensor.3d.shared::cluster.global.mbarrier::complete_tx::bytes [%0], [%1, {%3, %4, %5}], [%2];"
    :: "r"(dst), "l"((uint64_t)map), "r"(bar), "r"(c0), "r"(c1), "r"(c2) : "memory");
}
__device__ __forceinline__ void tma_load_2d_mc(uint32_t dst, const CUtensorMap* map, uint32_t bar, int c0, int c1, uint16_t mask) {
  asm volatile("cp.async.bulk.tensor.2d.shared::cluster.global.mbarrier::complete_tx::bytes.multicast::cluster [%0], [%1, {%3, %4}], [%2], %5;"
    :: "r"(dst), "l"((uint64_t)map), "r"(bar), "r"(c0), "r"(c1), "h"(mask) : "memory");
}
__device__ __forceinline__ void tma_store_2d(const CUtensorMap* map, uint32_t src, int c0, int c1) {
  asm volatile("cp.async.bulk.tensor.2d.global.shared::cta.bulk_group [%0, {%2, %3}], [%1];"
    :: "l"((uint64_t)map), "r"(src), "r"(c0), "r"(c1) : "memory");
}
__device__ __forceinline__ void tma_reduce_2d(const CUtensorMap* map, uint32_t src, int c0, int c1) {
  asm volatile("cp.reduce.async.bulk.tensor.2d.global.shared::cta.add.tile.bulk_group [%0, {%2, %3}], [%1];"
    :: "l"((uint64_t)map), "r"(src), "r"(c0), "r"(c1) : "memory");
}
__device__ __forceinline__ void bulk_wait_all() { asm volatile("cp.async.bulk.wait_group 0;" ::: "memory"); }
__device__ __forceinline__ void bulk_commit() { asm volatile("cp.async.bulk.commit_group;" ::: "memory"); }
__device__ __forceinline__ void bulk_wait_read() { asm volatile("cp.async.bulk.wait_group.read 0;" ::: "memory"); }
__device__ __forceinline__ void fence_async_smem() { asm volatile("fence.proxy.async.shared::cta;" ::: "memory"); }
__device__ __forceinline__ void fence_async_global() { asm volatile("fence.proxy.async.global;" ::: "memory"); }
__device__ __forceinline__ void wgmma_fence() { asm volatile("wgmma.fence.sync.aligned;" ::: "memory"); }
__device__ __forceinline__ void wgmma_commit() { asm volatile("wgmma.commit_group.sync.aligned;" ::: "memory"); }
template<int N> __device__ __forceinline__ void wgmma_wait() { asm volatile("wgmma.wait_group.sync.aligned %0;" :: "n"(N) : "memory"); }
template<int ID> __device__ __forceinline__ void bar_sync(int n) { asm volatile("bar.sync %0, %1;" :: "n"(ID), "r"(n) : "memory"); }
template<int ID> __device__ __forceinline__ void bar_arrive(int n) { asm volatile("bar.arrive %0, %1;" :: "n"(ID), "r"(n) : "memory"); }
__device__ __forceinline__ void cluster_wait() { asm volatile("barrier.cluster.wait.aligned;" ::: "memory"); }
__device__ __forceinline__ uint64_t desc64(uint32_t lo, uint32_t hi) { return (uint64_t)lo | ((uint64_t)hi << 32); }
__device__ __forceinline__ uint2 ld_tag2(const uint2* p) {
  uint2 v; asm volatile("ld.relaxed.gpu.global.v2.u32 {%0,%1}, [%2];" : "=r"(v.x), "=r"(v.y) : "l"(p) : "memory"); return v;
}
__device__ __forceinline__ void st_tag2(uint2* p, uint32_t a, uint32_t b) {
  asm volatile("st.relaxed.gpu.global.v2.u32 [%0], {%1,%2};" :: "l"(p), "r"(a), "r"(b) : "memory");
}
__device__ __forceinline__ void stg128(void* p, uint4 v) {
  asm volatile("st.global.v4.u32 [%0], {%1,%2,%3,%4};" :: "l"(p), "r"(v.x), "r"(v.y), "r"(v.z), "r"(v.w));
}
__device__ __forceinline__ unsigned ld_relaxed(const unsigned* p) {
  unsigned v; asm volatile("ld.relaxed.gpu.global.u32 %0, [%1];" : "=r"(v) : "l"(p) : "memory"); return v;
}
__device__ __forceinline__ uint32_t pack_bf16(float lo, float hi) {
  uint32_t r; asm("cvt.rn.bf16x2.f32 %0, %1, %2;" : "=r"(r) : "f"(hi), "f"(lo)); return r;
}
__device__ __forceinline__ float bf_lo(uint32_t v) { return __uint_as_float(v << 16); }
__device__ __forceinline__ float bf_hi(uint32_t v) { return __uint_as_float(v & 0xFFFF0000u); }
__device__ __forceinline__ void stsm4(uint32_t addr, uint32_t a, uint32_t b, uint32_t c, uint32_t d) {
  asm volatile("stmatrix.sync.aligned.m8n8.x4.shared.b16 [%0], {%1,%2,%3,%4};" :: "r"(addr), "r"(a), "r"(b), "r"(c), "r"(d));
}
__device__ __forceinline__ void stsm4_t(uint32_t addr, uint32_t a, uint32_t b, uint32_t c, uint32_t d) {
  asm volatile("stmatrix.sync.aligned.m8n8.x4.trans.shared.b16 [%0], {%1,%2,%3,%4};" :: "r"(addr), "r"(a), "r"(b), "r"(c), "r"(d));
}
__device__ __forceinline__ void ldsm4(uint32_t addr, uint32_t& a, uint32_t& b, uint32_t& c, uint32_t& d) {
  asm volatile("ldmatrix.sync.aligned.m8n8.x4.shared.b16 {%0,%1,%2,%3}, [%4];" : "=r"(a), "=r"(b), "=r"(c), "=r"(d) : "r"(addr));
}
__device__ __forceinline__ uint4 lds128(uint32_t a) {
  uint4 v; asm volatile("ld.shared.v4.u32 {%0,%1,%2,%3}, [%4];" : "=r"(v.x), "=r"(v.y), "=r"(v.z), "=r"(v.w) : "r"(a)); return v;
}
__device__ __forceinline__ void sts128(uint32_t a, uint32_t x, uint32_t y, uint32_t z, uint32_t w) {
  asm volatile("st.shared.v4.u32 [%0], {%1,%2,%3,%4};" :: "r"(a), "r"(x), "r"(y), "r"(z), "r"(w));
}
__device__ __forceinline__ uint32_t hmul2_bf16(uint32_t a, uint32_t b) {
  uint32_t r; asm("mul.rn.bf16x2 %0, %1, %2;" : "=r"(r) : "r"(a), "r"(b)); return r;
}
__device__ __forceinline__ uint32_t hadd2_bf16(uint32_t a, uint32_t b) {
  uint32_t r; asm("add.rn.bf16x2 %0, %1, %2;" : "=r"(r) : "r"(a), "r"(b)); return r;
}
__device__ __forceinline__ uint32_t hfma2_bf16(uint32_t a, uint32_t b, uint32_t c) {
  uint32_t r; asm("fma.rn.bf16x2 %0, %1, %2, %3;" : "=r"(r) : "r"(a), "r"(b), "r"(c)); return r;
}
__device__ __forceinline__ float gelu_tanh(float v) {
  float u = v * fmaf(0.0356774081f, v * v, 0.7978845608f);
  float t; asm("tanh.approx.f32 %0, %1;" : "=f"(t) : "f"(u));
  float hv = 0.5f * v;
  return fmaf(hv, t, hv);
}

template<int TB>
__device__ __forceinline__ void wgmma_n192(float (&d)[96], uint64_t da, uint64_t db, int scale_d) {
  asm volatile("{\n.reg .pred p;\nsetp.ne.b32 p, %98, 0;\n"
   "wgmma.mma_async.sync.aligned.m64n192k16.f32.bf16.bf16 {%0,%1,%2,%3,%4,%5,%6,%7,%8,%9,%10,%11,%12,%13,%14,%15,%16,%17,%18,%19,%20,%21,%22,%23,%24,%25,%26,%27,%28,%29,%30,%31,%32,%33,%34,%35,%36,%37,%38,%39,%40,%41,%42,%43,%44,%45,%46,%47,%48,%49,%50,%51,%52,%53,%54,%55,%56,%57,%58,%59,%60,%61,%62,%63,%64,%65,%66,%67,%68,%69,%70,%71,%72,%73,%74,%75,%76,%77,%78,%79,%80,%81,%82,%83,%84,%85,%86,%87,%88,%89,%90,%91,%92,%93,%94,%95}, %96, %97, p, 1, 1, 0, %99;\n}"
   : "+f"(d[0]),"+f"(d[1]),"+f"(d[2]),"+f"(d[3]),"+f"(d[4]),"+f"(d[5]),"+f"(d[6]),"+f"(d[7]),"+f"(d[8]),"+f"(d[9]),"+f"(d[10]),"+f"(d[11]),"+f"(d[12]),"+f"(d[13]),"+f"(d[14]),"+f"(d[15]),"+f"(d[16]),"+f"(d[17]),"+f"(d[18]),"+f"(d[19]),"+f"(d[20]),"+f"(d[21]),"+f"(d[22]),"+f"(d[23]),"+f"(d[24]),"+f"(d[25]),"+f"(d[26]),"+f"(d[27]),"+f"(d[28]),"+f"(d[29]),"+f"(d[30]),"+f"(d[31]),"+f"(d[32]),"+f"(d[33]),"+f"(d[34]),"+f"(d[35]),"+f"(d[36]),"+f"(d[37]),"+f"(d[38]),"+f"(d[39]),"+f"(d[40]),"+f"(d[41]),"+f"(d[42]),"+f"(d[43]),"+f"(d[44]),"+f"(d[45]),"+f"(d[46]),"+f"(d[47]),"+f"(d[48]),"+f"(d[49]),"+f"(d[50]),"+f"(d[51]),"+f"(d[52]),"+f"(d[53]),"+f"(d[54]),"+f"(d[55]),"+f"(d[56]),"+f"(d[57]),"+f"(d[58]),"+f"(d[59]),"+f"(d[60]),"+f"(d[61]),"+f"(d[62]),"+f"(d[63]),"+f"(d[64]),"+f"(d[65]),"+f"(d[66]),"+f"(d[67]),"+f"(d[68]),"+f"(d[69]),"+f"(d[70]),"+f"(d[71]),"+f"(d[72]),"+f"(d[73]),"+f"(d[74]),"+f"(d[75]),"+f"(d[76]),"+f"(d[77]),"+f"(d[78]),"+f"(d[79]),"+f"(d[80]),"+f"(d[81]),"+f"(d[82]),"+f"(d[83]),"+f"(d[84]),"+f"(d[85]),"+f"(d[86]),"+f"(d[87]),"+f"(d[88]),"+f"(d[89]),"+f"(d[90]),"+f"(d[91]),"+f"(d[92]),"+f"(d[93]),"+f"(d[94]),"+f"(d[95])
   : "l"(da), "l"(db), "r"(scale_d), "n"(TB));
}
template<int TB>
__device__ __forceinline__ void wgmma_n160(float (&d)[80], uint64_t da, uint64_t db, int scale_d) {
  asm volatile("{\n.reg .pred p;\nsetp.ne.b32 p, %82, 0;\n"
   "wgmma.mma_async.sync.aligned.m64n160k16.f32.bf16.bf16 {%0,%1,%2,%3,%4,%5,%6,%7,%8,%9,%10,%11,%12,%13,%14,%15,%16,%17,%18,%19,%20,%21,%22,%23,%24,%25,%26,%27,%28,%29,%30,%31,%32,%33,%34,%35,%36,%37,%38,%39,%40,%41,%42,%43,%44,%45,%46,%47,%48,%49,%50,%51,%52,%53,%54,%55,%56,%57,%58,%59,%60,%61,%62,%63,%64,%65,%66,%67,%68,%69,%70,%71,%72,%73,%74,%75,%76,%77,%78,%79}, %80, %81, p, 1, 1, 0, %83;\n}"
   : "+f"(d[0]),"+f"(d[1]),"+f"(d[2]),"+f"(d[3]),"+f"(d[4]),"+f"(d[5]),"+f"(d[6]),"+f"(d[7]),"+f"(d[8]),"+f"(d[9]),"+f"(d[10]),"+f"(d[11]),"+f"(d[12]),"+f"(d[13]),"+f"(d[14]),"+f"(d[15]),"+f"(d[16]),"+f"(d[17]),"+f"(d[18]),"+f"(d[19]),"+f"(d[20]),"+f"(d[21]),"+f"(d[22]),"+f"(d[23]),"+f"(d[24]),"+f"(d[25]),"+f"(d[26]),"+f"(d[27]),"+f"(d[28]),"+f"(d[29]),"+f"(d[30]),"+f"(d[31]),"+f"(d[32]),"+f"(d[33]),"+f"(d[34]),"+f"(d[35]),"+f"(d[36]),"+f"(d[37]),"+f"(d[38]),"+f"(d[39]),"+f"(d[40]),"+f"(d[41]),"+f"(d[42]),"+f"(d[43]),"+f"(d[44]),"+f"(d[45]),"+f"(d[46]),"+f"(d[47]),"+f"(d[48]),"+f"(d[49]),"+f"(d[50]),"+f"(d[51]),"+f"(d[52]),"+f"(d[53]),"+f"(d[54]),"+f"(d[55]),"+f"(d[56]),"+f"(d[57]),"+f"(d[58]),"+f"(d[59]),"+f"(d[60]),"+f"(d[61]),"+f"(d[62]),"+f"(d[63]),"+f"(d[64]),"+f"(d[65]),"+f"(d[66]),"+f"(d[67]),"+f"(d[68]),"+f"(d[69]),"+f"(d[70]),"+f"(d[71]),"+f"(d[72]),"+f"(d[73]),"+f"(d[74]),"+f"(d[75]),"+f"(d[76]),"+f"(d[77]),"+f"(d[78]),"+f"(d[79])
   : "l"(da), "l"(db), "r"(scale_d), "n"(TB));
}

template<int N, int TB>
__device__ __forceinline__ void wgmma_n(float (&d)[N / 2], uint64_t da, uint64_t db) {
  if constexpr (N == 192) wgmma_n192<TB>(d, da, db, 1); else wgmma_n160<TB>(d, da, db, 1);
}

template<int M, int R>
__device__ __forceinline__ void pin(float (&acc)[M][R]) {
  #pragma unroll
  for (int mi = 0; mi < M; mi++)
    #pragma unroll
    for (int i = 0; i < R; i++) asm volatile("" : "+f"(acc[mi][i]) :: "memory");
}
template<int M, int R>
__device__ __forceinline__ void zero(float (&acc)[M][R]) {
  #pragma unroll
  for (int mi = 0; mi < M; mi++)
    #pragma unroll
    for (int i = 0; i < R; i++) acc[mi][i] = 0.f;
  pin(acc);
}

template<int N, int M, int TB, bool CONT, int ORD_BAR, bool AOWN = false>
__device__ __forceinline__ void mainloop(float (&acc)[M][N / 2], uint32_t sbase, int grp, int g0, int nk, int m0 = 0) {
  const uint32_t full0 = sbase + BAR_OFF, empty0 = full0 + 8 * MAXST, ring = sbase + RING_OFF;
  const int nst = grp == 0 ? NST_A : NST_B, total = grp == 0 ? KB_A : KB_B;
  const uint32_t sstep = (grp == 0 ? STAGE_A : STAGE_B) >> 4;
  const int t = threadIdx.x & 127;
  const uint32_t da0 = (((ring + m0 * 8192) & 0x3FFFF) >> 4) | 0x10000u;
  const uint32_t db0 = (((ring + A_BYTES) & 0x3FFFF) >> 4) | ((TB == 2 ? 256u : TB ? 512u : 1u) << 16);
  constexpr uint32_t HI_A = 0x40000040u, HI_B = TB == 2 ? 0x80000020u : 0x40000040u;
  int s = g0 % nst, ph = (g0 / nst) & 1, ps = s == 0 ? nst - 1 : s - 1;
  #pragma unroll 1
  for (int g = g0; g < g0 + nk; g++) {
    const uint32_t so = s * sstep;
    mbar_wait(full0 + 8 * s, ph);
    wgmma_fence();
    #pragma unroll
    for (int k = 0; k < 4; k++) {
      const uint64_t db = desc64(db0 + so + (TB == 2 ? k * 64 : TB ? k * 128 : k * 2), HI_B);
      #pragma unroll
      for (int mi = 0; mi < M; mi++)
        wgmma_n<N, TB != 0>(acc[mi], desc64(AOWN ? da0 + ((NST_A * STAGE_A) >> 4) + (g - g0) * 512 + mi * 1536 + k * 2 : da0 + so + mi * 512 + k * 2, HI_A), db);
    }
    wgmma_commit();
    if (ORD_BAR != 0 && g == g0 + nk - 1) bar_arrive<ORD_BAR>(256);
    wgmma_wait<1>();
    if (t < 2 * M && (CONT || g > g0) && g - 1 + nst < total) mbar_arrive_cluster(empty0 + 8 * ps, t & 1);
    ps = s;
    if (++s == nst) { s = 0; ph ^= 1; }
  }
}
template<int M, int R>
__device__ __forceinline__ void drain(float (&acc)[M][R], uint32_t sbase, int grp, int glast) {
  wgmma_wait<0>();
  pin(acc);
  const int t = threadIdx.x & 127;
  const int nst = grp == 0 ? NST_A : NST_B, total = grp == 0 ? KB_A : KB_B;
  if (t < 2 * M && glast + nst < total) mbar_arrive_cluster(sbase + BAR_OFF + 8 * MAXST + 8 * (glast % nst), t & 1);
}

__device__ __forceinline__ void set_flag(int slot, int byte, unsigned epoch) {
  asm volatile("st.relaxed.gpu.global.u8 [%0], %1;" :: "l"(g_flags + slot * 256 + byte), "r"(epoch & 255u) : "memory");
}
__device__ __forceinline__ unsigned get_flag(int slot, int byte) {
  unsigned v; asm volatile("ld.relaxed.gpu.global.u8 %0, [%1];" : "=r"(v) : "l"(g_flags + slot * 256 + byte) : "memory"); return v;
}
__device__ __forceinline__ void publish(int slot, int byte, unsigned epoch) {
  asm volatile("fence.acq_rel.gpu;" ::: "memory");
  set_flag(slot, byte, epoch);
}
__device__ __forceinline__ float sum8(uint4 v) {
  return ((bf_lo(v.x) + bf_hi(v.x)) + (bf_lo(v.y) + bf_hi(v.y))) + ((bf_lo(v.z) + bf_hi(v.z)) + (bf_lo(v.w) + bf_hi(v.w)));
}
__device__ __forceinline__ uint4 ldg128(const void* p) {
  uint4 v; asm volatile("ld.global.nc.v4.u32 {%0,%1,%2,%3}, [%4];" : "=r"(v.x), "=r"(v.y), "=r"(v.z), "=r"(v.w) : "l"(p)); return v;
}

__device__ __forceinline__ void ln_rows(const uint4 (&rv)[5], uint32_t buf, int cta, unsigned epoch) {
  const int t = threadIdx.x - 128, row = cta * 16 + (t >> 4), c = t & 15;
  const float sh = __shfl_sync(0xffffffffu, bf_lo(rv[0].x), t & 16);
  float d[40], s = 0.f, q = 0.f;
  #pragma unroll
  for (int j = 0; j < 5; j++) {
    const uint32_t u[4] = {rv[j].x, rv[j].y, rv[j].z, rv[j].w};
    #pragma unroll
    for (int e = 0; e < 4; e++) {
      const float d0 = bf_lo(u[e]) - sh, d1 = bf_hi(u[e]) - sh;
      d[j * 8 + e * 2] = d0; d[j * 8 + e * 2 + 1] = d1;
      s += d0 + d1; q = fmaf(d0, d0, q); q = fmaf(d1, d1, q);
    }
  }
  #pragma unroll
  for (int o = 1; o < 16; o <<= 1) { s += __shfl_xor_sync(0xffffffffu, s, o); q += __shfl_xor_sync(0xffffffffu, q, o); }
  const float md = s * (1.f / DM);
  const float r = rsqrtf(fmaxf(fmaf(q, 1.f / DM, -md * md), 0.f) + LN_EPS), o = -md * r;
  if (c == 0) st_tag2(&g_xstat[row], __float_as_uint(r), (__float_as_uint(-(md + sh) * r) & ~255u) | (epoch & 255u));
  #pragma unroll
  for (int j = 0; j < 5; j++) {
    const float* a = &d[j * 8];
    sts128(buf + (t >> 4) * 1280 + (c + 16 * j) * 16,
           pack_bf16(fmaf(a[0], r, o), fmaf(a[1], r, o)), pack_bf16(fmaf(a[2], r, o), fmaf(a[3], r, o)),
           pack_bf16(fmaf(a[4], r, o), fmaf(a[5], r, o)), pack_bf16(fmaf(a[6], r, o), fmaf(a[7], r, o)));
  }
  fence_async_smem();
  bar_arrive<BAR_LN>(288);
}

__device__ __forceinline__ void weight_sums(const bf16* __restrict__ win, const bf16* __restrict__ wdre, int j, unsigned epoch) {
  const int t = threadIdx.x & 127, w = t >> 5, l = t & 31;
  const int cj = min(j, 59), cg = cj % 12, rg = cj / 12, wr = j * 10 + min(t >> 3, 9);
  uint4 cv[8], rv[10];
  #pragma unroll
  for (int i = 0; i < 8; i++) cv[i] = ldg128(reinterpret_cast<const uint4*>(win + (size_t)(rg * 128 + w * 32 + i * 4 + (l >> 3)) * FF + FH + cg * 64) + (l & 7));
  #pragma unroll
  for (int i = 0; i < 10; i++) rv[i] = ldg128(reinterpret_cast<const uint4*>(wdre + (size_t)wr * DM) + (l & 7) + 8 * i);
  float v[8];
  #pragma unroll
  for (int e = 0; e < 8; e++) v[e] = 0.f;
  #pragma unroll
  for (int i = 0; i < 8; i++) {
    v[0] += bf_lo(cv[i].x); v[1] += bf_hi(cv[i].x); v[2] += bf_lo(cv[i].y); v[3] += bf_hi(cv[i].y);
    v[4] += bf_lo(cv[i].z); v[5] += bf_hi(cv[i].z); v[6] += bf_lo(cv[i].w); v[7] += bf_hi(cv[i].w);
  }
  #pragma unroll
  for (int st = 0; st < 2; st++) {
    const int n = 4 >> st;
    const bool up = (l & (4 * n)) != 0;
    #pragma unroll
    for (int e = 0; e < 4; e++)
      if (e < n) { const float keep = up ? v[e + n] : v[e], send = up ? v[e] : v[e + n]; v[e] = keep + __shfl_xor_sync(0xffffffffu, send, 4 * n); }
  }
  float* red = reinterpret_cast<float*>(smem + RED_OFF);
  *reinterpret_cast<float2*>(red + w * 64 + (l & 7) * 8 + (l >> 3) * 2) = make_float2(v[0], v[1]);
  float s = 0.f;
  #pragma unroll
  for (int i = 0; i < 10; i++) s += sum8(rv[i]);
  #pragma unroll
  for (int o = 1; o < 8; o <<= 1) s += __shfl_xor_sync(0xffffffffu, s, o);
  if ((l & 7) == 0) st_tag2(&g_csum[5 * FH + wr], __float_as_uint(s), epoch);
  bar_sync<BAR_WG1>(128);
  if (t < 64) st_tag2(&g_csum[rg * FH + cg * 64 + t], __float_as_uint((red[t] + red[64 + t]) + (red[128 + t] + red[192 + t])), epoch);
}

__device__ __forceinline__ void gather96(const uint2* src, float* dst, unsigned epoch) {
  unsigned it = 0;
  while (true) {
    bool ok = true;
    uint2 u[15];
    #pragma unroll
    for (int j = 0; j < 15; j++) u[j] = ld_tag2(src + (j % 5) * FH + (j / 5) * 32);
    #pragma unroll
    for (int j = 0; j < 15; j++) ok = ok && u[j].y == epoch;
    #pragma unroll
    for (int j = 0; j < 3; j++)
      dst[j * 32] = ((__uint_as_float(u[j * 5].x) + __uint_as_float(u[j * 5 + 1].x)) + (__uint_as_float(u[j * 5 + 2].x) + __uint_as_float(u[j * 5 + 3].x))) + __uint_as_float(u[j * 5 + 4].x);
    if (ok || ++it > POLL_LIMIT) break;
    __nanosleep(2 * POLL_NS);
  }
}

__device__ __forceinline__ void a_entry(int g, int grp, int ct, int& mi, int& kb) {
  if (g < 10) { mi = M_X; kb = g; }
  else if (g < 20) { mi = M_XN; kb = g - 10; }
  else if (g < 52) { mi = grp == 0 ? M_WSP : M_WSRE; kb = g - 20; }
  else if (grp == 0) {
    if (g < 52 + NX) { mi = M_WSIM; kb = g - 52 + 32 - NX; }
    else {
      const int i = g - 52 - NX;
      mi = M_H; kb = i < 3 ? ct * 3 + i : i < 6 ? (ct ^ 1) * 3 + i - 3 : ((ct >> 1) ^ 1) * 6 + i - 6;
    }
  } else {
    if (g < 84 - NX) { mi = M_WSIM; kb = g - 52; }
    else { mi = M_H; kb = ((ct >> 1) ^ 1) * 6 + g - (84 - NX) + 6 - NO; }
  }
}

__global__ void __cluster_dims__(2, 1, 1) __launch_bounds__(384, 1)
fused_kernel(const __grid_constant__ Maps maps, const bf16* __restrict__ x, const bf16* __restrict__ win, const bf16* __restrict__ wdre,
             const bf16* __restrict__ bsp, bf16* __restrict__ out) {
  const uint32_t sbase = smem_u32(smem);
  const uint32_t full0 = sbase + BAR_OFF, empty0 = full0 + 8 * MAXST, dep0 = empty0 + 8 * MAXST, ring = sbase + RING_OFF;
  const int tid = threadIdx.x, wg = __shfl_sync(0xffffffffu, tid >> 7, 0);
  const int cta = blockIdx.x, rank = cta & 1, grp = (cta >> 1) & 1, rb = cta >> 3, ct = ((cta >> 2) & 1) * 2 + rank;
  const int total = grp == 0 ? KB_A : KB_B, gh = grp == 0 ? 52 + NX : 84 - NX;
  const uint32_t stage_bytes = grp == 0 ? STAGE_A : STAGE_B;
  const int nst = grp == 0 ? NST_A : NST_B;
  const uint32_t buf = ring + nst * stage_bytes;

  uint4 rv[5];
  if (wg != 0) {
    #pragma unroll
    for (int j = 0; j < 5; j++) rv[j] = ldg128(reinterpret_cast<const uint4*>(x + (size_t)(cta * 16 + ((tid - 128) >> 4)) * DM) + (tid & 15) + 16 * j);
  }
  const unsigned epoch = (ld_relaxed(&g_done) >> 7) + 1u;
  if (tid == 0) {
    TS(0, 0);
    for (int s = 0; s < MAXST; s++) { mbar_init(full0 + 8 * s, 2); mbar_init(empty0 + 8 * s, 4); mbar_init(dep0 + 8 * s, 1); }
    *reinterpret_cast<volatile int*>(smem + READY_OFF) = 0;
    asm volatile("fence.mbarrier_init.release.cluster;" ::: "memory");
  }
  __syncthreads();
  asm volatile("barrier.cluster.arrive.relaxed.aligned;" ::: "memory");

  if (wg == 0) {
    asm volatile("setmaxnreg.dec.sync.aligned.u32 40;");
    const int warp = tid >> 5, lane = tid & 31;
    if (warp == 0) {
      const int row = rb * 128;
      if (lane == 0) {
        for (int g = 0; g < nst; g++) {
          mbar_expect_tx(full0 + 8 * g, A_BYTES);
          tma_load_2d(ring + g * stage_bytes, &maps.m[M_X], full0 + 8 * g, g * 64, row);
          tma_load_2d(ring + g * stage_bytes + 8192, &maps.m[M_X], full0 + 8 * g, g * 64, row + 64);
        }
      }
      __syncwarp();
      cluster_wait();
      if (lane == 0) {
        int s = 0, ph = 0;
        #pragma unroll 1
        for (int g = nst; g < total; g++) {
          int mi, kb;
          a_entry(g, grp, ct, mi, kb);
          if (g == 10 || g == gh + 3 - 3 * grp) { TS(0, g > 10 ? 3 : 1); mbar_wait(dep0 + (g > 10 ? 24 : 0), 0); fence_async_global(); TS(0, g > 10 ? 4 : 2); }
          mbar_wait(empty0 + 8 * s, ph);
          if (grp == 0 && g >= gh && g < gh + 6) {
            if (g < gh + 3) {
              mbar_arrive(full0 + 8 * s);
            } else {
              mbar_expect_tx(full0 + 8 * s, A_BYTES);
              tma_load_2d(ring + s * stage_bytes, &maps.m[mi], full0 + 8 * s, kb * 64, row);
              tma_load_2d(ring + s * stage_bytes + 8192, &maps.m[mi], full0 + 8 * s, kb * 64, row + 64);
            }
          } else {
            mbar_expect_tx(full0 + 8 * s, A_BYTES);
            tma_load_2d_mc(ring + s * stage_bytes + rank * 8192, &maps.m[mi], full0 + 8 * s, kb * 64, row + rank * 64, 3);
          }
          if (++s == nst) { s = 0; ph ^= 1; }
          if (g + PF_D < gh) {
            a_entry(g + PF_D, grp, ct, mi, kb);
            if (mi >= M_WSRE && (kb & 1) == (ct >> 1))
              asm volatile("cp.async.bulk.prefetch.tensor.2d.L2.global.tile [%0, {%1, %2}];" :: "l"((uint64_t)&maps.m[mi]), "r"(kb * 64), "r"(row + rank * 64) : "memory");
          }
        }
        TS(0, 5);
      }
    } else if (warp == 1) {
      if (lane == 0) {
        int s = 0, ph = 1;
        int have = 0;
        #pragma unroll 1
        for (int g = 0; g < total; g++) {
          int mi, kb, c;
          a_entry(g, grp, ct, mi, kb);
          const bool nmaj = g >= gh || (grp == 0 && g < 52);
          uint32_t bytes = 20480;
          if (g >= gh) { mi = M_WOUT; c = ct * 5; }
          else if (g >= 52) { mi = M_AB; c = DM + ct * 160; }
          else if (grp == 0) { mi = g < 20 ? M_WIN3 : M_Z23; c = 3 * ct + (g < 10 ? 12 : 0); bytes = 24576; }
          else { mi = g < 10 ? M_WDRE : g < 20 ? M_WDIM : M_AB; c = ct * 160; }
          if (g >= 20 && g < 52 && ((g - 20) >> 1) >= have) {
            if (g == 20) TS(1, 0);
            unsigned it = 0;
            while ((have = *reinterpret_cast<volatile int*>(smem + READY_OFF)) <= ((g - 20) >> 1) && ++it < 50 * POLL_LIMIT) {}
            fence_async_global();
            if (g == 20) { TS(1, 1); TC(1); }
          }
          if (g == 52) { TS(1, 2); mbar_wait(dep0 + 16, 0); fence_async_global(); TS(1, 3); TC(2); }
          const uint32_t dst = ring + s * stage_bytes + A_BYTES, fb = full0 + 8 * s;
          mbar_wait(empty0 + 8 * s, ph);
          if (++s == nst) { s = 0; ph ^= 1; }
          mbar_expect_tx(fb, bytes);
          if (nmaj) tma_load_3d(dst, &maps.m[mi], fb, 0, kb * 64, c);
          else tma_load_2d(dst, &maps.m[mi], fb, kb * 64, c);
        }
      }
      __syncwarp();
      cluster_wait();
    } else if (warp == 2) {
      if (lane < M_COUNT) asm volatile("prefetch.tensormap [%0];" :: "l"((uint64_t)&maps.m[lane]) : "memory");
      cluster_wait();
      {
        unsigned it = 0;
        uint2 v[4];
        while (true) {
          bool ok = true;
          #pragma unroll
          for (int i = 0; i < 4; i++) { v[i] = ld_tag2(&g_xstat[rb * 128 + i * 32 + lane]); ok = ok && ((v[i].y ^ epoch) & 255u) == 0; }
          if (ok || ++it > POLL_LIMIT) break;
          __nanosleep(POLL_NS);
        }
        #pragma unroll
        for (int i = 0; i < 4; i++) reinterpret_cast<uint2*>(smem + ROWSTAT_OFF)[i * 32 + lane] = make_uint2(v[i].x, v[i].y & ~255u);
        __syncwarp();
        TS(0, 6);
        if (grp == 0) bar_arrive<BAR_STATS>(320); else bar_arrive<BAR_STATS>(192);
      }
      #pragma unroll 1
      for (int i = 0; i < 5; i++) {
        const int d = i == 3 ? 4 : i == 4 ? 3 : i;
        const int slot = d == 0 ? F_XN + rb : d == 4 ? F_Y + rb * 4 + ct : d == 3 ? F_H + rb : d == 2 ? F_B + ct : grp == 0 ? F_Z + ct : F_A + ct;
        const int byte = d == 0 ? lane & 7 : d == 4 ? 0 : d == 3 ? lane & 3 : lane & 15;
        unsigned it = 0, m;
        while ((m = __ballot_sync(0xffffffffu, get_flag(slot, byte) != (epoch & 255u))) != 0 && ++it < POLL_LIMIT) {
          if (d == 1 && lane == 0) *reinterpret_cast<volatile int*>(smem + READY_OFF) = __ffs(m) - 1;
          __nanosleep(WATCH_NS);
        }
        if (d == 1 && lane == 0) *reinterpret_cast<volatile int*>(smem + READY_OFF) = 16;
        if (d < 4) TS(0, 8 + d * 2); else TS(0, 7);
        fence_async_global();
        __syncwarp();
        if (lane == 0 && d != 1) mbar_arrive(dep0 + 8 * d);
      }
    } else {
      cluster_wait();
      bar_sync<BAR_LN>(288);
      if (lane == 0) {
        TS(1, 5);
        asm volatile("cp.async.bulk.global.shared::cta.bulk_group [%0], [%1], 20480;" :: "l"(g_xn + (size_t)cta * 16 * DM), "r"(buf) : "memory");
        bulk_commit();
        bulk_wait_all();
        set_flag(F_XN + rb, cta & 7, epoch);
        TS(1, 6);
      }
      __syncwarp();
      if (grp == 0) {
        #pragma unroll 1
        for (int i = 0; i < 2; i++) gather96(&g_csum[ct * 192 + i * 96 + lane], reinterpret_cast<float*>(smem + COLSUM_OFF) + i * 96 + lane, epoch);
      } else {
        unsigned it = 0;
        while (true) {
          bool ok = true;
          #pragma unroll
          for (int j = 0; j < 5; j++) {
            const uint2 u = ld_tag2(&g_csum[5 * FH + ct * 160 + j * 32 + lane]);
            ok = ok && u.y == epoch;
            reinterpret_cast<uint32_t*>(smem + COLSUM_OFF)[j * 32 + lane] = u.x;
          }
          if (ok || ++it > POLL_LIMIT) break;
          __nanosleep(2 * POLL_NS);
        }
      }
      __syncwarp();
      TS(1, 4);
      if (grp == 0) {
        bar_arrive<BAR_STATS>(320);
        bar_sync<BAR_PUB1>(160);
        if (lane == 0) set_flag(F_Z + ct, rb, epoch);
        TS(1, 8);
        __syncwarp();
        bar_arrive<BAR_BUF>(160);
      } else {
        bar_arrive<BAR_STATS>(192);
        bar_sync<BAR_PUB2>(160);
        if (lane == 0) set_flag(F_A + ct, rb, epoch);
        TS(1, 9);
        __syncwarp();
      }
      bar_sync<BAR_PUB1>(160);
      if (lane == 0) set_flag(grp == 0 ? F_H + rb : F_B + ct, grp == 0 ? ct : rb, epoch);
      TS(1, 10);
      __syncwarp();
      bar_arrive<BAR_BUF>(160);
    }
  } else {
    asm volatile("setmaxnreg.inc.sync.aligned.u32 232;");
    const int t = tid & 127, w = t >> 5, l = t & 31;
    ln_rows(rv, buf, cta, epoch);
    TS(wg + 1, 0);
    cluster_wait();
    const uint32_t st_base = buf + (w * 16 + ((l >> 3) & 1) * 8 + (l & 7)) * 128;
    const uint32_t st_x = ((l >> 4) ^ (l & 7)) << 4;
    const float2* rs = reinterpret_cast<const float2*>(smem + ROWSTAT_OFF) + w * 16 + (l >> 2);
    const float2* cs = reinterpret_cast<const float2*>(smem + COLSUM_OFF) + (l & 3);
    if (grp == 0) {
      {
        const int mb = wg - 1;
        float acc[1][96];
        zero(acc);
        mainloop<192, 1, 1, false, 0>(acc, sbase, 0, 0, 10, mb);
        drain(acc, sbase, 0, 9);
        TS(wg + 1, 1);
        bar_sync<BAR_STATS>(320);
        const float2 s0 = rs[mb * 64], s1 = rs[mb * 64 + 8];
        const float nm[2] = {s0.y / s0.x, s1.y / s1.x}, hr[2] = {0.5f * s0.x, 0.5f * s1.x};
        const float k1[2] = {0.7978845608f * s0.x, 0.7978845608f * s1.x};
        const float k2[2] = {0.0356774081f * s0.x * s0.x * s0.x, 0.0356774081f * s1.x * s1.x * s1.x};
        float sm0 = 0.f, sm1 = 0.f, q0 = 0.f, q1 = 0.f;
        #pragma unroll
        for (int jj = 0; jj < 12; jj++) {
          float u[8];
          #pragma unroll
          for (int hf = 0; hf < 2; hf++) {
            const float2 c = cs[jj * 8 + hf * 4];
            #pragma unroll
            for (int e = 0; e < 4; e++) {
              const float wv = fmaf(nm[e >> 1], (e & 1) ? c.y : c.x, acc[0][8 * jj + 4 * hf + e]);
              float th; asm("tanh.approx.f32 %0, %1;" : "=f"(th) : "f"(wv * fmaf(k2[e >> 1], wv * wv, k1[e >> 1])));
              const float hv = hr[e >> 1] * wv;
              u[4 * hf + e] = fmaf(hv, th, hv);
            }
            sm0 += u[4 * hf] + u[4 * hf + 1]; q0 = fmaf(u[4 * hf], u[4 * hf], q0); q0 = fmaf(u[4 * hf + 1], u[4 * hf + 1], q0);
            sm1 += u[4 * hf + 2] + u[4 * hf + 3]; q1 = fmaf(u[4 * hf + 2], u[4 * hf + 2], q1); q1 = fmaf(u[4 * hf + 3], u[4 * hf + 3], q1);
          }
          stsm4(st_base + mb * 24576 + (jj >> 2) * 8192 + (st_x ^ ((jj & 3) << 5)),
                pack_bf16(u[0], u[1]), pack_bf16(u[2], u[3]), pack_bf16(u[4], u[5]), pack_bf16(u[6], u[7]));
        }
        #pragma unroll
        for (int o = 1; o < 4; o <<= 1) {
          sm0 += __shfl_xor_sync(0xffffffffu, sm0, o); q0 += __shfl_xor_sync(0xffffffffu, q0, o);
          sm1 += __shfl_xor_sync(0xffffffffu, sm1, o); q1 += __shfl_xor_sync(0xffffffffu, q1, o);
        }
        if ((l & 3) < 2) {
          const float sm = (l & 1) ? sm1 : sm0, sv = (l & 1) ? q1 : q0;
          const int row = mb * 64 + w * 16 + (l & 1) * 8 + (l >> 2);
          const float mu = sm * (1.f / 192), m2 = fmaxf(sv - sm * mu, 0.f);
          st_tag2(&g_zstat[(rb * 4 + ct) * 128 + row], __float_as_uint(mu), (__float_as_uint(m2) & ~255u) | (epoch & 255u));
          reinterpret_cast<float2*>(smem + ZSTAT_OFF)[row] = make_float2(mu, m2);
        }
        TS(wg + 1, 4);
      }
      float acc[2][96];
      if (wg == 1) {
        bar_sync<BAR_U>(256);
        uint2 v[3];
        unsigned n = 0;
        while (true) {
          bool ok = true;
          #pragma unroll
          for (int j = 0; j < 3; j++) { v[j] = ld_tag2(&g_zstat[(rb * 4 + ((ct + 1 + j) & 3)) * 128 + t]); ok = ok && ((v[j].y ^ epoch) & 255u) == 0; }
          if (ok || ++n > POLL_LIMIT) break;
          __nanosleep(POLL_NS);
        }
        const float2 own = reinterpret_cast<const float2*>(smem + ZSTAT_OFF)[t];
        const float m0 = __uint_as_float(v[0].x), m1 = __uint_as_float(v[1].x), m3 = __uint_as_float(v[2].x);
        const float mean = 0.25f * ((own.x + m0) + (m1 + m3));
        const float d = (own.x - mean) * (own.x - mean) + (m0 - mean) * (m0 - mean) + (m1 - mean) * (m1 - mean) + (m3 - mean) * (m3 - mean);
        const float var = fmaf(192.f, d, (own.y + __uint_as_float(v[0].y & ~255u)) + (__uint_as_float(v[1].y & ~255u) + __uint_as_float(v[2].y & ~255u)));
        const float r = rsqrtf(var * (1.f / FH) + LN_EPS);
        TS(2, 5);
        const uint32_t rbase = buf + (t >> 6) * 24576 + (t & 63) * 128;
        const uint32_t m2 = pack_bf16(-mean, -mean), r2 = pack_bf16(r, r);
        const float res = (-mean - bf_lo(m2)) * r;
        const uint32_t e2 = pack_bf16(res, res);
        #pragma unroll 1
        for (int c = 0; c < 3; c++) {
          uint4 z[8];
          #pragma unroll
          for (int i = 0; i < 8; i++) z[i] = lds128(rbase + c * 8192 + (((i ^ l) & 7) << 4));
          #pragma unroll
          for (int i = 0; i < 8; i++)
            sts128(rbase + c * 8192 + (((i ^ l) & 7) << 4), hfma2_bf16(hadd2_bf16(z[i].x, m2), r2, e2), hfma2_bf16(hadd2_bf16(z[i].y, m2), r2, e2),
                   hfma2_bf16(hadd2_bf16(z[i].z, m2), r2, e2), hfma2_bf16(hadd2_bf16(z[i].w, m2), r2, e2));
          fence_async_smem();
          __syncwarp();
          if (l == 0) {
            tma_store_2d(&maps.m[M_ZS], buf + (w >> 1) * 24576 + c * 8192 + (w & 1) * 4096, ct * 192 + c * 64, rb * 128 + w * 32);
            bulk_commit();
          }
        }
        TS(2, 6);
        if (l == 0) bulk_wait_all();
        __syncwarp();
        bar_arrive<BAR_PUB1>(160);
        {
          const bf16* bp = bsp + rb * 128 + w * 16 + (l >> 2);
          const float bb[4] = {__bfloat162float(bp[0]), __bfloat162float(bp[8]), __bfloat162float(bp[64]), __bfloat162float(bp[72])};
          #pragma unroll
          for (int i = 0; i < 96; i++) { acc[0][i] = bb[(i >> 1) & 1]; acc[1][i] = bb[2 + ((i >> 1) & 1)]; }
          pin(acc);
        }
        bar_sync<BAR_ORD2>(256);
        mainloop<192, 2, 1, false, BAR_ORD1>(acc, sbase, 0, 20, 32);
        bar_sync<BAR_Z1>(256);
        uint32_t z[6][4][4];
        #pragma unroll
        for (int i = 0; i < ZPRE; i++) ldsm4(st_base + (i >> 2) * 8192 + (st_x ^ ((i & 3) << 5)), z[i >> 2][i & 3][0], z[i >> 2][i & 3][1], z[i >> 2][i & 3][2], z[i >> 2][i & 3][3]);
        drain(acc, sbase, 0, 51);
        TS(2, 7);
        #pragma unroll
        for (int bx = 0; bx < 6; bx++) {
          if (bx >= 1) {
            #pragma unroll
            for (int i = ZPRE + (bx - 1) * 10; i < ZPRE + bx * 10; i++)
              if (i < 24) ldsm4(st_base + (i >> 2) * 8192 + (st_x ^ ((i & 3) << 5)), z[i >> 2][i & 3][0], z[i >> 2][i & 3][1], z[i >> 2][i & 3][2], z[i >> 2][i & 3][3]);
          }
          #pragma unroll
          for (int i = 0; i < 4; i++) {
            const float* a = &acc[bx / 3][8 * ((bx % 3) * 4 + i)];
            const uint32_t* zz = z[bx][i];
            stsm4(st_base + bx * 8192 + (st_x ^ (i << 5)),
                  hmul2_bf16(zz[0], pack_bf16(a[0], a[1])), hmul2_bf16(zz[1], pack_bf16(a[2], a[3])),
                  hmul2_bf16(zz[2], pack_bf16(a[4], a[5])), hmul2_bf16(zz[3], pack_bf16(a[6], a[7])));

          }
          if (bx % 3 == 2) {
            fence_async_smem();
            __syncwarp();
            if (l < 3) {
              tma_store_2d(&maps.m[M_HS], buf + (bx - 2 + l) * 8192 + w * 2048, ct * 192 + l * 64, rb * 128 + (bx / 3) * 64 + w * 16);
              bulk_commit();
            }
          }
        }
        bar_arrive<BAR_U>(256);
        TS(2, 8);
        if (l < 3) bulk_wait_all();
        __syncwarp();
        bar_arrive<BAR_PUB1>(160);
        TS(2, 9);
        return;
      }
      bar_arrive<BAR_U>(256);
      zero(acc);
      mainloop<192, 2, 1, false, BAR_ORD2>(acc, sbase, 0, 10, 10);
      drain(acc, sbase, 0, 19);
      TS(3, 2);
      bar_sync<BAR_BUF>(160);
      #pragma unroll
      for (int mi = 0; mi < 2; mi++)
        #pragma unroll
        for (int jj = 0; jj < 12; jj++) {
          const float* a = &acc[mi][8 * jj];
          stsm4(st_base + mi * 24576 + (jj >> 2) * 8192 + (st_x ^ ((jj & 3) << 5)),
                pack_bf16(a[0], a[1]), pack_bf16(a[2], a[3]), pack_bf16(a[4], a[5]), pack_bf16(a[6], a[7]));
        }
      __syncwarp();
      TS(3, 3);
      const uint32_t rbase = buf + (l >> 4) * 24576 + (w * 16 + (l & 15)) * 128;
      #pragma unroll 1
      for (int c2 = 0; c2 < 12; c2++) {
        const uint32_t ab = rbase + (c2 >> 2) * 8192;
        uint4 v[2];
        #pragma unroll
        for (int i = 0; i < 2; i++) v[i] = lds128(ab + (((((c2 & 3) * 2 + i) ^ l) & 7) << 4));
        #pragma unroll
        for (int i = 0; i < 2; i++)
          sts128(ab + (((((c2 & 3) * 2 + i) ^ l) & 7) << 4),
                 pack_bf16(gelu_tanh(bf_lo(v[i].x)), gelu_tanh(bf_hi(v[i].x))), pack_bf16(gelu_tanh(bf_lo(v[i].y)), gelu_tanh(bf_hi(v[i].y))),
                 pack_bf16(gelu_tanh(bf_lo(v[i].z)), gelu_tanh(bf_hi(v[i].z))), pack_bf16(gelu_tanh(bf_lo(v[i].w)), gelu_tanh(bf_hi(v[i].w))));
        __nanosleep(Z1_NS);
      }
      TS(3, 5);
      bar_arrive<BAR_Z1>(256);
    }
    float acc[2][80];
    if (grp == 1) {
      zero(acc);
      if (wg == 2) {
        mainloop<160, 2, 0, false, BAR_ORD2>(acc, sbase, 1, 0, 10);
      } else {
        weight_sums(win, wdre, rb * 4 + ct, epoch);
        TS(2, 1);
        bar_sync<BAR_ORD2>(256);
        mainloop<160, 2, 0, false, BAR_ORD1>(acc, sbase, 1, 10, 10);
      }
      drain(acc, sbase, 1, wg == 2 ? 9 : 19);
      TS(wg + 1, wg == 1 ? 7 : 2);
      if (wg == 1) bar_sync<BAR_Z1>(256); else bar_sync<BAR_STATS>(192);
      const uint32_t tb = buf + ((l >> 4) * 8 + (l & 7)) * 128 + (((w * 2 + ((l >> 3) & 1)) ^ (l & 7)) << 4);
      float2 st[4];
      #pragma unroll
      for (int r = 0; r < 4; r++) st[r] = wg == 2 ? rs[(r >> 1) * 64 + (r & 1) * 8] : make_float2(-1.f, 0.f);
      #pragma unroll
      for (int jj = 0; jj < 10; jj++) {
        const float2 c0 = cs[jj * 8], c1 = cs[jj * 8 + 4];
        #pragma unroll
        for (int mi = 0; mi < 2; mi++) {
          const float* a = &acc[mi][8 * jj];
          const float2 s0 = st[mi * 2], s1 = st[mi * 2 + 1];
          stsm4_t(tb + mi * 20480 + jj * 2048,
                  pack_bf16(fmaf(a[0], s0.x, s0.y * c0.x), fmaf(a[1], s0.x, s0.y * c0.y)), pack_bf16(fmaf(a[2], s1.x, s1.y * c0.x), fmaf(a[3], s1.x, s1.y * c0.y)),
                  pack_bf16(fmaf(a[4], s0.x, s0.y * c1.x), fmaf(a[5], s0.x, s0.y * c1.y)), pack_bf16(fmaf(a[6], s1.x, s1.y * c1.x), fmaf(a[7], s1.x, s1.y * c1.y)));
        }
      }
      fence_async_smem();
      if (wg == 1) bar_sync<BAR_WG1>(128); else bar_sync<BAR_WG2>(128);
      TS(wg + 1, wg == 1 ? 8 : 6);
      if (l < 2) {
        tma_store_2d(&maps.m[M_ABS], buf + l * 20480 + w * 5120, rb * 128 + l * 64, (2 - wg) * DM + ct * 160 + w * 40);
        bulk_commit();
        bulk_wait_all();
      }
      __syncwarp();
      TS(wg + 1, wg == 1 ? 9 : 10);
      if (wg == 1) {
        bar_arrive<BAR_PUB1>(160);
        #pragma unroll 1
        for (int i = 0; i < 4; i++) {
          uint4 v[5];
          #pragma unroll
          for (int j = 0; j < 5; j++) {
            const int e = (i * 5 + j) * 128 + t;
            v[j] = ldg128(x + (size_t)(rb * 128 + e / 20) * DM + ct * 160 + (e % 20) * 8);
          }
          #pragma unroll
          for (int j = 0; j < 5; j++) {
            const int e = (i * 5 + j) * 128 + t;
            stg128(out + (size_t)(rb * 128 + e / 20) * DM + ct * 160 + (e % 20) * 8, v[j]);
          }
        }
        bar_sync<BAR_WG1>(128);
        if (t == 0) publish(F_Y + rb * 4 + ct, 0, epoch);
        return;
      }
      bar_arrive<BAR_PUB2>(160);
      bar_arrive<BAR_Z1>(256);
    }
    zero(acc);
    bar_sync<BAR_ORD1>(256);
    mainloop<160, 2, 0, false, 0>(acc, sbase, grp, grp == 0 ? 52 : 20, grp == 0 ? NX : 64 - NX);
    if (grp == 0) {
      bar_sync<BAR_U>(256);
      mainloop<160, 2, 2, true, 0, true>(acc, sbase, 0, 52 + NX, 3);
    }
    mainloop<160, 2, 2, true, 0>(acc, sbase, grp, gh + 3 - 3 * grp, total - gh - 3 + 3 * grp);
    const uint32_t slab = buf + w * (16 * 320);
    const uint32_t addr = slab + (((l >> 3) & 1) * 8 + (l & 7)) * 320 + (l >> 4) * 16;
    bar_sync<BAR_BUF>(160);
    mbar_wait(dep0 + 32, 0);
    drain(acc, sbase, grp, total - 1);
    TS(3, 12);
    #pragma unroll
    for (int mi = 0; mi < 2; mi++) {
      #pragma unroll
      for (int jj = 0; jj < 10; jj++) {
        const float* a = &acc[mi][8 * jj];
        stsm4(addr + mi * 20480 + jj * 32, pack_bf16(a[0], a[1]), pack_bf16(a[2], a[3]), pack_bf16(a[4], a[5]), pack_bf16(a[6], a[7]));
      }
      fence_async_smem();
      __syncwarp();
      if (l == 0) {
        tma_reduce_2d(&maps.m[M_OUT], slab + mi * 20480, ct * 160, rb * 128 + mi * 64 + w * 16);
        bulk_commit();
      }
    }
    TS(3, 13);
    if (l == 0) {
      bulk_wait_read();
      if (w == 0) atomicAdd(&g_done, 1u);
    }
    TS(3, 15);
  }
}

typedef CUresult (*EncodeFn)(CUtensorMap*, CUtensorMapDataType, cuuint32_t, void*, const cuuint64_t*, const cuuint64_t*,
                             const cuuint32_t*, const cuuint32_t*, CUtensorMapInterleave, CUtensorMapSwizzle,
                             CUtensorMapL2promotion, CUtensorMapFloatOOBfill);

void make2d(EncodeFn enc, CUtensorMap* m, const void* p, uint64_t cols, uint64_t rows, uint32_t bc, uint32_t br, bool swz = true) {
  cuuint64_t gd[2] = {cols, rows}, gs[1] = {cols * 2};
  cuuint32_t bd[2] = {bc, br}, es[2] = {1, 1};
  enc(m, CU_TENSOR_MAP_DATA_TYPE_BFLOAT16, 2, const_cast<void*>(p), gd, gs, bd, es, CU_TENSOR_MAP_INTERLEAVE_NONE,
      swz ? CU_TENSOR_MAP_SWIZZLE_128B : CU_TENSOR_MAP_SWIZZLE_NONE, CU_TENSOR_MAP_L2_PROMOTION_L2_128B, CU_TENSOR_MAP_FLOAT_OOB_FILL_NONE);
}
void make3d(EncodeFn enc, CUtensorMap* m, const void* p, uint64_t cols, uint64_t rows, uint32_t cw, uint32_t nc, uint32_t br = 64) {
  cuuint64_t gd[3] = {cw, rows, cols / cw}, gs[2] = {cols * 2, cw * 2};
  cuuint32_t bd[3] = {cw, br, nc}, es[3] = {1, 1, 1};
  enc(m, CU_TENSOR_MAP_DATA_TYPE_BFLOAT16, 3, const_cast<void*>(p), gd, gs, bd, es, CU_TENSOR_MAP_INTERLEAVE_NONE,
      cw == 64 ? CU_TENSOR_MAP_SWIZZLE_128B : CU_TENSOR_MAP_SWIZZLE_64B, CU_TENSOR_MAP_L2_PROMOTION_L2_128B, CU_TENSOR_MAP_FLOAT_OOB_FILL_NONE);
}

}

extern "C" void kernel_launch(void* const* d_in, const int* in_sizes, int n_in, void* d_out, int out_size) {
  const bf16* x = (const bf16*)d_in[0];
  const bf16* wsre = (const bf16*)d_in[1];
  const bf16* wsim = (const bf16*)d_in[2];
  const bf16* wdre = (const bf16*)d_in[3];
  const bf16* wdim = (const bf16*)d_in[4];
  const bf16* win = (const bf16*)d_in[6];
  const bf16* wsp = (const bf16*)d_in[7];
  const bf16* bsp = (const bf16*)d_in[8];
  const bf16* wout = (const bf16*)d_in[9];

  void* fn = nullptr;
  cudaDriverEntryPointQueryResult qr;
  cudaGetDriverEntryPoint("cuTensorMapEncodeTiled", &fn, cudaEnableDefault, &qr);
  EncodeFn enc = (EncodeFn)fn;
  void *abT, *z2, *h, *xn;
  cudaGetSymbolAddress(&xn, g_xn);
  cudaGetSymbolAddress(&abT, g_abT);
  cudaGetSymbolAddress(&z2, g_z2);
  cudaGetSymbolAddress(&h, g_h);

  Maps maps;
  make2d(enc, &maps.m[M_X], x, DM, SEQ, 64, 64);
  make2d(enc, &maps.m[M_XN], xn, DM, SEQ, 64, 64);
  make2d(enc, &maps.m[M_WSRE], wsre, SEQ, SEQ, 64, 64);
  make2d(enc, &maps.m[M_WSIM], wsim, SEQ, SEQ, 64, 64);
  make2d(enc, &maps.m[M_WSP], wsp, SEQ, SEQ, 64, 64);
  make2d(enc, &maps.m[M_H], h, FH, SEQ, 64, 64);
  make3d(enc, &maps.m[M_WIN3], win, FF, DM, 64, 3);
  make3d(enc, &maps.m[M_Z23], z2, FH, SEQ, 64, 3);
  make2d(enc, &maps.m[M_WDRE], wdre, DM, DM, 64, 160);
  make2d(enc, &maps.m[M_WDIM], wdim, DM, DM, 64, 160);
  make2d(enc, &maps.m[M_AB], abT, SEQ, 2 * DM, 64, 160);
  make3d(enc, &maps.m[M_WOUT], wout, DM, FH, 32, 5);
  make2d(enc, &maps.m[M_HS], h, FH, SEQ, 64, 16);
  make2d(enc, &maps.m[M_ZS], z2, FH, SEQ, 64, 32);
  make2d(enc, &maps.m[M_ABS], abT, SEQ, 2 * DM, 64, 40);
  make2d(enc, &maps.m[M_OUT], d_out, DM, SEQ, 160, 16, false);

  cudaFuncSetAttribute(fused_kernel, cudaFuncAttributeMaxDynamicSharedMemorySize, SMEM_BYTES);
  fused_kernel<<<128, 384, SMEM_BYTES>>>(maps, x, win, wdre, bsp, (bf16*)d_out);
}
```

```cpp
#include <cuda_runtime.h>
#include <cuda_bf16.h>
#include <cuda.h>
#include <stdint.h>

namespace {

typedef __nv_bfloat16 bf16;

constexpr int SEQ = 2048, DM = 640, FF = 1536, FH = 768;
constexpr int NX = 6;
constexpr int NO = 3;
constexpr int NST_A = 4, NST_B = 5, MAXST = 5;
constexpr int A_BYTES = 16384;
constexpr int BAR_OFF = 0;
constexpr int READY_OFF = 128;
constexpr int COLSUM_OFF = 256;
constexpr int ROWSTAT_OFF = 1024;
constexpr int ZSTAT_OFF = 2048;
constexpr int RED_OFF = 3072;
constexpr int RING_OFF = 4096;
constexpr int STAGE_A = 40960, STAGE_B = 36864;
constexpr int SMEM_BYTES = RING_OFF + 5 * STAGE_B + 40960;
constexpr int KB_A = 52 + NX + 12 - NO;
constexpr int KB_B = 84 - NX + NO;
constexpr float LN_EPS = 1e-5f;
constexpr unsigned POLL_LIMIT = 100000;
constexpr unsigned POLL_NS = 100, WATCH_NS = 40;
constexpr unsigned Z1_NS = 500;
constexpr int PF_D = 8;
constexpr int ZPRE = 6;

constexpr int BAR_ORD1 = 1, BAR_ORD2 = 2, BAR_WG1 = 3, BAR_WG2 = 4, BAR_LN = 5, BAR_BUF = 6, BAR_Z1 = 7, BAR_PUB1 = 8, BAR_PUB2 = 9,
              BAR_STATS = 10, BAR_U = 11;

enum { M_X, M_XN, M_WSRE, M_WSIM, M_WSP, M_H, M_WIN3, M_Z23, M_WDRE, M_WDIM, M_AB, M_WOUT, M_OUT, M_HS, M_ZS, M_ABS, M_COUNT };
struct Maps { CUtensorMap m[M_COUNT]; };

__device__ __align__(1024) bf16 g_abT[2 * DM * SEQ];
__device__ __align__(1024) bf16 g_z2[SEQ * FH];
__device__ __align__(1024) bf16 g_h[SEQ * FH];
__device__ __align__(1024) bf16 g_xn[SEQ * DM];
__device__ __align__(16) uint2 g_xstat[SEQ];
__device__ __align__(16) uint2 g_csum[5 * FH + DM];
__device__ __align__(16) uint2 g_zstat[64 * 128];
__device__ __align__(256) unsigned char g_flags[108 * 256];
constexpr int F_A = 0, F_B = 4, F_Z = 8, F_H = 12, F_XN = 28, F_Y = 44;
__device__ unsigned g_done;
#define TS(role, ev)
#define TC(i)

extern __shared__ __align__(1024) uint8_t smem[];

__device__ __forceinline__ uint32_t smem_u32(const void* p) { return (uint32_t)__cvta_generic_to_shared(p); }
__device__ __forceinline__ void mbar_init(uint32_t bar, uint32_t cnt) { asm volatile("mbarrier.init.shared::cta.b64 [%0], %1;" :: "r"(bar), "r"(cnt)); }
__device__ __forceinline__ void mbar_expect_tx(uint32_t bar, uint32_t bytes) { asm volatile("mbarrier.arrive.expect_tx.shared::cta.b64 _, [%0], %1;" :: "r"(bar), "r"(bytes) : "memory"); }
__device__ __forceinline__ void mbar_arrive(uint32_t bar) { asm volatile("mbarrier.arrive.shared::cta.b64 _, [%0];" :: "r"(bar) : "memory"); }
__device__ __forceinline__ void mbar_arrive_cluster(uint32_t bar, uint32_t cta) {
  asm volatile("{\n.reg .b32 ra;\nmapa.shared::cluster.u32 ra, %0, %1;\nmbarrier.arrive.shared::cluster.b64 _, [ra];\n}" :: "r"(bar), "r"(cta) : "memory");
}
__device__ __forceinline__ void mbar_wait(uint32_t bar, uint32_t parity) {
  asm volatile("{\n.reg .pred p;\n.reg .u32 n;\nmov.u32 n, 0;\n"
               "LW: mbarrier.try_wait.parity.shared::cta.b64 p, [%0], %1, 2000;\n@p bra LD;\n"
               "add.u32 n, n, 1;\nsetp.lt.u32 p, n, 20000;\n@p bra LW;\nLD:\n}" :: "r"(bar), "r"(parity) : "memory");
}
__device__ __forceinline__ void tma_load_2d(uint32_t dst, const CUtensorMap* map, uint32_t bar, int c0, int c1) {
  asm volatile("cp.async.bulk.tensor.2d.shared::cluster.global.mbarrier::complete_tx::bytes [%0], [%1, {%3, %4}], [%2];"
    :: "r"(dst), "l"((uint64_t)map), "r"(bar), "r"(c0), "r"(c1) : "memory");
}
__device__ __forceinline__ void tma_load_3d(uint32_t dst, const CUtensorMap* map, uint32_t bar, int c0, int c1, int c2) {
  asm volatile("cp.async.bulk.tensor.3d.shared::cluster.global.mbarrier::complete_tx::bytes [%0], [%1, {%3, %4, %5}], [%2];"
    :: "r"(dst), "l"((uint64_t)map), "r"(bar), "r"(c0), "r"(c1), "r"(c2) : "memory");
}
__device__ __forceinline__ void tma_load_2d_mc(uint32_t dst, const CUtensorMap* map, uint32_t bar, int c0, int c1, uint16_t mask) {
  asm volatile("cp.async.bulk.tensor.2d.shared::cluster.global.mbarrier::complete_tx::bytes.multicast::cluster [%0], [%1, {%3, %4}], [%2], %5;"
    :: "r"(dst), "l"((uint64_t)map), "r"(bar), "r"(c0), "r"(c1), "h"(mask) : "memory");
}
__device__ __forceinline__ void tma_store_2d(const CUtensorMap* map, uint32_t src, int c0, int c1) {
  asm volatile("cp.async.bulk.tensor.2d.global.shared::cta.bulk_group [%0, {%2, %3}], [%1];"
    :: "l"((uint64_t)map), "r"(src), "r"(c0), "r"(c1) : "memory");
}
__device__ __forceinline__ void tma_reduce_2d(const CUtensorMap* map, uint32_t src, int c0, int c1) {
  asm volatile("cp.reduce.async.bulk.tensor.2d.global.shared::cta.add.tile.bulk_group [%0, {%2, %3}], [%1];"
    :: "l"((uint64_t)map), "r"(src), "r"(c0), "r"(c1) : "memory");
}
__device__ __forceinline__ void bulk_wait_all() { asm volatile("cp.async.bulk.wait_group 0;" ::: "memory"); }
__device__ __forceinline__ void bulk_commit() { asm volatile("cp.async.bulk.commit_group;" ::: "memory"); }
__device__ __forceinline__ void bulk_wait_read() { asm volatile("cp.async.bulk.wait_group.read 0;" ::: "memory"); }
__device__ __forceinline__ void fence_async_smem() { asm volatile("fence.proxy.async.shared::cta;" ::: "memory"); }
__device__ __forceinline__ void fence_async_global() { asm volatile("fence.proxy.async.global;" ::: "memory"); }
__device__ __forceinline__ void wgmma_fence() { asm volatile("wgmma.fence.sync.aligned;" ::: "memory"); }
__device__ __forceinline__ void wgmma_commit() { asm volatile("wgmma.commit_group.sync.aligned;" ::: "memory"); }
template<int N> __device__ __forceinline__ void wgmma_wait() { asm volatile("wgmma.wait_group.sync.aligned %0;" :: "n"(N) : "memory"); }
template<int ID> __device__ __forceinline__ void bar_sync(int n) { asm volatile("bar.sync %0, %1;" :: "n"(ID), "r"(n) : "memory"); }
template<int ID> __device__ __forceinline__ void bar_arrive(int n) { asm volatile("bar.arrive %0, %1;" :: "n"(ID), "r"(n) : "memory"); }
__device__ __forceinline__ void cluster_wait() { asm volatile("barrier.cluster.wait.aligned;" ::: "memory"); }
__device__ __forceinline__ uint64_t desc64(uint32_t lo, uint32_t hi) { return (uint64_t)lo | ((uint64_t)hi << 32); }
__device__ __forceinline__ uint2 ld_tag2(const uint2* p) {
  uint2 v; asm volatile("ld.relaxed.gpu.global.v2.u32 {%0,%1}, [%2];" : "=r"(v.x), "=r"(v.y) : "l"(p) : "memory"); return v;
}
__device__ __forceinline__ void st_tag2(uint2* p, uint32_t a, uint32_t b) {
  asm volatile("st.relaxed.gpu.global.v2.u32 [%0], {%1,%2};" :: "l"(p), "r"(a), "r"(b) : "memory");
}
__device__ __forceinline__ void stg128(void* p, uint4 v) {
  asm volatile("st.global.v4.u32 [%0], {%1,%2,%3,%4};" :: "l"(p), "r"(v.x), "r"(v.y), "r"(v.z), "r"(v.w));
}
__device__ __forceinline__ unsigned ld_relaxed(const unsigned* p) {
  unsigned v; asm volatile("ld.relaxed.gpu.global.u32 %0, [%1];" : "=r"(v) : "l"(p) : "memory"); return v;
}
__device__ __forceinline__ uint32_t pack_bf16(float lo, float hi) {
  uint32_t r; asm("cvt.rn.bf16x2.f32 %0, %1, %2;" : "=r"(r) : "f"(hi), "f"(lo)); return r;
}
__device__ __forceinline__ float bf_lo(uint32_t v) { return __uint_as_float(v << 16); }
__device__ __forceinline__ float bf_hi(uint32_t v) { return __uint_as_float(v & 0xFFFF0000u); }
__device__ __forceinline__ void stsm4(uint32_t addr, uint32_t a, uint32_t b, uint32_t c, uint32_t d) {
  asm volatile("stmatrix.sync.aligned.m8n8.x4.shared.b16 [%0], {%1,%2,%3,%4};" :: "r"(addr), "r"(a), "r"(b), "r"(c), "r"(d));
}
__device__ __forceinline__ void stsm4_t(uint32_t addr, uint32_t a, uint32_t b, uint32_t c, uint32_t d) {
  asm volatile("stmatrix.sync.aligned.m8n8.x4.trans.shared.b16 [%0], {%1,%2,%3,%4};" :: "r"(addr), "r"(a), "r"(b), "r"(c), "r"(d));
}
__device__ __forceinline__ void ldsm4(uint32_t addr, uint32_t& a, uint32_t& b, uint32_t& c, uint32_t& d) {
  asm volatile("ldmatrix.sync.aligned.m8n8.x4.shared.b16 {%0,%1,%2,%3}, [%4];" : "=r"(a), "=r"(b), "=r"(c), "=r"(d) : "r"(addr));
}
__device__ __forceinline__ uint4 lds128(uint32_t a) {
  uint4 v; asm volatile("ld.shared.v4.u32 {%0,%1,%2,%3}, [%4];" : "=r"(v.x), "=r"(v.y), "=r"(v.z), "=r"(v.w) : "r"(a)); return v;
}
__device__ __forceinline__ void sts128(uint32_t a, uint32_t x, uint32_t y, uint32_t z, uint32_t w) {
  asm volatile("st.shared.v4.u32 [%0], {%1,%2,%3,%4};" :: "r"(a), "r"(x), "r"(y), "r"(z), "r"(w));
}
__device__ __forceinline__ uint32_t hmul2_bf16(uint32_t a, uint32_t b) {
  uint32_t r; asm("mul.rn.bf16x2 %0, %1, %2;" : "=r"(r) : "r"(a), "r"(b)); return r;
}
__device__ __forceinline__ uint32_t hadd2_bf16(uint32_t a, uint32_t b) {
  uint32_t r; asm("add.rn.bf16x2 %0, %1, %2;" : "=r"(r) : "r"(a), "r"(b)); return r;
}
__device__ __forceinline__ uint32_t hfma2_bf16(uint32_t a, uint32_t b, uint32_t c) {
  uint32_t r; asm("fma.rn.bf16x2 %0, %1, %2, %3;" : "=r"(r) : "r"(a), "r"(b), "r"(c)); return r;
}
__device__ __forceinline__ float gelu_tanh(float v) {
  float u = v * fmaf(0.0356774081f, v * v, 0.7978845608f);
  float t; asm("tanh.approx.f32 %0, %1;" : "=f"(t) : "f"(u));
  float hv = 0.5f * v;
  return fmaf(hv, t, hv);
}

template<int TB>
__device__ __forceinline__ void wgmma_n192(float (&d)[96], uint64_t da, uint64_t db, int scale_d) {
  asm volatile("{\n.reg .pred p;\nsetp.ne.b32 p, %98, 0;\n"
   "wgmma.mma_async.sync.aligned.m64n192k16.f32.bf16.bf16 {%0,%1,%2,%3,%4,%5,%6,%7,%8,%9,%10,%11,%12,%13,%14,%15,%16,%17,%18,%19,%20,%21,%22,%23,%24,%25,%26,%27,%28,%29,%30,%31,%32,%33,%34,%35,%36,%37,%38,%39,%40,%41,%42,%43,%44,%45,%46,%47,%48,%49,%50,%51,%52,%53,%54,%55,%56,%57,%58,%59,%60,%61,%62,%63,%64,%65,%66,%67,%68,%69,%70,%71,%72,%73,%74,%75,%76,%77,%78,%79,%80,%81,%82,%83,%84,%85,%86,%87,%88,%89,%90,%91,%92,%93,%94,%95}, %96, %97, p, 1, 1, 0, %99;\n}"
   : "+f"(d[0]),"+f"(d[1]),"+f"(d[2]),"+f"(d[3]),"+f"(d[4]),"+f"(d[5]),"+f"(d[6]),"+f"(d[7]),"+f"(d[8]),"+f"(d[9]),"+f"(d[10]),"+f"(d[11]),"+f"(d[12]),"+f"(d[13]),"+f"(d[14]),"+f"(d[15]),"+f"(d[16]),"+f"(d[17]),"+f"(d[18]),"+f"(d[19]),"+f"(d[20]),"+f"(d[21]),"+f"(d[22]),"+f"(d[23]),"+f"(d[24]),"+f"(d[25]),"+f"(d[26]),"+f"(d[27]),"+f"(d[28]),"+f"(d[29]),"+f"(d[30]),"+f"(d[31]),"+f"(d[32]),"+f"(d[33]),"+f"(d[34]),"+f"(d[35]),"+f"(d[36]),"+f"(d[37]),"+f"(d[38]),"+f"(d[39]),"+f"(d[40]),"+f"(d[41]),"+f"(d[42]),"+f"(d[43]),"+f"(d[44]),"+f"(d[45]),"+f"(d[46]),"+f"(d[47]),"+f"(d[48]),"+f"(d[49]),"+f"(d[50]),"+f"(d[51]),"+f"(d[52]),"+f"(d[53]),"+f"(d[54]),"+f"(d[55]),"+f"(d[56]),"+f"(d[57]),"+f"(d[58]),"+f"(d[59]),"+f"(d[60]),"+f"(d[61]),"+f"(d[62]),"+f"(d[63]),"+f"(d[64]),"+f"(d[65]),"+f"(d[66]),"+f"(d[67]),"+f"(d[68]),"+f"(d[69]),"+f"(d[70]),"+f"(d[71]),"+f"(d[72]),"+f"(d[73]),"+f"(d[74]),"+f"(d[75]),"+f"(d[76]),"+f"(d[77]),"+f"(d[78]),"+f"(d[79]),"+f"(d[80]),"+f"(d[81]),"+f"(d[82]),"+f"(d[83]),"+f"(d[84]),"+f"(d[85]),"+f"(d[86]),"+f"(d[87]),"+f"(d[88]),"+f"(d[89]),"+f"(d[90]),"+f"(d[91]),"+f"(d[92]),"+f"(d[93]),"+f"(d[94]),"+f"(d[95])
   : "l"(da), "l"(db), "r"(scale_d), "n"(TB));
}
template<int TB>
__device__ __forceinline__ void wgmma_n160(float (&d)[80], uint64_t da, uint64_t db, int scale_d) {
  asm volatile("{\n.reg .pred p;\nsetp.ne.b32 p, %82, 0;\n"
   "wgmma.mma_async.sync.aligned.m64n160k16.f32.bf16.bf16 {%0,%1,%2,%3,%4,%5,%6,%7,%8,%9,%10,%11,%12,%13,%14,%15,%16,%17,%18,%19,%20,%21,%22,%23,%24,%25,%26,%27,%28,%29,%30,%31,%32,%33,%34,%35,%36,%37,%38,%39,%40,%41,%42,%43,%44,%45,%46,%47,%48,%49,%50,%51,%52,%53,%54,%55,%56,%57,%58,%59,%60,%61,%62,%63,%64,%65,%66,%67,%68,%69,%70,%71,%72,%73,%74,%75,%76,%77,%78,%79}, %80, %81, p, 1, 1, 0, %83;\n}"
   : "+f"(d[0]),"+f"(d[1]),"+f"(d[2]),"+f"(d[3]),"+f"(d[4]),"+f"(d[5]),"+f"(d[6]),"+f"(d[7]),"+f"(d[8]),"+f"(d[9]),"+f"(d[10]),"+f"(d[11]),"+f"(d[12]),"+f"(d[13]),"+f"(d[14]),"+f"(d[15]),"+f"(d[16]),"+f"(d[17]),"+f"(d[18]),"+f"(d[19]),"+f"(d[20]),"+f"(d[21]),"+f"(d[22]),"+f"(d[23]),"+f"(d[24]),"+f"(d[25]),"+f"(d[26]),"+f"(d[27]),"+f"(d[28]),"+f"(d[29]),"+f"(d[30]),"+f"(d[31]),"+f"(d[32]),"+f"(d[33]),"+f"(d[34]),"+f"(d[35]),"+f"(d[36]),"+f"(d[37]),"+f"(d[38]),"+f"(d[39]),"+f"(d[40]),"+f"(d[41]),"+f"(d[42]),"+f"(d[43]),"+f"(d[44]),"+f"(d[45]),"+f"(d[46]),"+f"(d[47]),"+f"(d[48]),"+f"(d[49]),"+f"(d[50]),"+f"(d[51]),"+f"(d[52]),"+f"(d[53]),"+f"(d[54]),"+f"(d[55]),"+f"(d[56]),"+f"(d[57]),"+f"(d[58]),"+f"(d[59]),"+f"(d[60]),"+f"(d[61]),"+f"(d[62]),"+f"(d[63]),"+f"(d[64]),"+f"(d[65]),"+f"(d[66]),"+f"(d[67]),"+f"(d[68]),"+f"(d[69]),"+f"(d[70]),"+f"(d[71]),"+f"(d[72]),"+f"(d[73]),"+f"(d[74]),"+f"(d[75]),"+f"(d[76]),"+f"(d[77]),"+f"(d[78]),"+f"(d[79])
   : "l"(da), "l"(db), "r"(scale_d), "n"(TB));
}

template<int N, int TB>
__device__ __forceinline__ void wgmma_n(float (&d)[N / 2], uint64_t da, uint64_t db) {
  if constexpr (N == 192) wgmma_n192<TB>(d, da, db, 1); else wgmma_n160<TB>(d, da, db, 1);
}

template<int M, int R>
__device__ __forceinline__ void pin(float (&acc)[M][R]) {
  #pragma unroll
  for (int mi = 0; mi < M; mi++)
    #pragma unroll
    for (int i = 0; i < R; i++) asm volatile("" : "+f"(acc[mi][i]) :: "memory");
}
template<int M, int R>
__device__ __forceinline__ void zero(float (&acc)[M][R]) {
  #pragma unroll
  for (int mi = 0; mi < M; mi++)
    #pragma unroll
    for (int i = 0; i < R; i++) acc[mi][i] = 0.f;
  pin(acc);
}

template<int N, int M, int TB, bool CONT, int ORD_BAR, bool AOWN = false>
__device__ __forceinline__ void mainloop(float (&acc)[M][N / 2], uint32_t sbase, int grp, int g0, int nk, int m0 = 0) {
  const uint32_t full0 = sbase + BAR_OFF, empty0 = full0 + 8 * MAXST, ring = sbase + RING_OFF;
  const int nst = grp == 0 ? NST_A : NST_B, total = grp == 0 ? KB_A : KB_B;
  const uint32_t sstep = (grp == 0 ? STAGE_A : STAGE_B) >> 4;
  const int t = threadIdx.x & 127;
  const uint32_t da0 = (((ring + m0 * 8192) & 0x3FFFF) >> 4) | 0x10000u;
  const uint32_t db0 = (((ring + A_BYTES) & 0x3FFFF) >> 4) | ((TB == 2 ? 256u : TB ? 512u : 1u) << 16);
  constexpr uint32_t HI_A = 0x40000040u, HI_B = TB == 2 ? 0x80000020u : 0x40000040u;
  int s = g0 % nst, ph = (g0 / nst) & 1, ps = s == 0 ? nst - 1 : s - 1;
  #pragma unroll 1
  for (int g = g0; g < g0 + nk; g++) {
    const uint32_t so = s * sstep;
    mbar_wait(full0 + 8 * s, ph);
    wgmma_fence();
    #pragma unroll
    for (int k = 0; k < 4; k++) {
      const uint64_t db = desc64(db0 + so + (TB == 2 ? k * 64 : TB ? k * 128 : k * 2), HI_B);
      #pragma unroll
      for (int mi = 0; mi < M; mi++)
        wgmma_n<N, TB != 0>(acc[mi], desc64(AOWN ? da0 + ((NST_A * STAGE_A) >> 4) + (g - g0) * 512 + mi * 1536 + k * 2 : da0 + so + mi * 512 + k * 2, HI_A), db);
    }
    wgmma_commit();
    if (ORD_BAR != 0 && g == g0 + nk - 1) bar_arrive<ORD_BAR>(256);
    wgmma_wait<1>();
    if (t < 2 * M && (CONT || g > g0) && g - 1 + nst < total) mbar_arrive_cluster(empty0 + 8 * ps, t & 1);
    ps = s;
    if (++s == nst) { s = 0; ph ^= 1; }
  }
}
__device__ __forceinline__ void tail3(float (&acc)[2][80], uint32_t sbase, int grp) {
  const uint32_t full0 = sbase + BAR_OFF, ring = sbase + RING_OFF;
  const int nst = grp == 0 ? NST_A : NST_B, g0 = (grp == 0 ? KB_A : KB_B) - 3;
  const uint32_t sstep = (grp == 0 ? STAGE_A : STAGE_B) >> 4;
  const uint32_t da0 = ((ring & 0x3FFFF) >> 4) | 0x10000u, db0 = (((ring + A_BYTES) & 0x3FFFF) >> 4) | (256u << 16);
  #pragma unroll 1
  for (int i = 0; i < 6; i++) {
    const int g = g0 + (i < 3 ? i : i - 3), s = g % nst;
    const uint32_t so = s * sstep;
    if (i < 3) {
      mbar_wait(full0 + 8 * s, (g / nst) & 1);
      wgmma_fence();
      #pragma unroll
      for (int k = 0; k < 4; k++) wgmma_n<160, 1>(acc[1], desc64(da0 + so + 512 + k * 2, 0x40000040u), desc64(db0 + so + k * 64, 0x80000020u));
      if (i == 2) wgmma_commit();
    } else {
      wgmma_fence();
      #pragma unroll
      for (int k = 0; k < 4; k++) wgmma_n<160, 1>(acc[0], desc64(da0 + so + k * 2, 0x40000040u), desc64(db0 + so + k * 64, 0x80000020u));
    }
  }
  wgmma_commit();
}
template<int M, int R>
__device__ __forceinline__ void drain(float (&acc)[M][R], uint32_t sbase, int grp, int glast) {
  wgmma_wait<0>();
  pin(acc);
  const int t = threadIdx.x & 127;
  const int nst = grp == 0 ? NST_A : NST_B, total = grp == 0 ? KB_A : KB_B;
  if (t < 2 * M && glast + nst < total) mbar_arrive_cluster(sbase + BAR_OFF + 8 * MAXST + 8 * (glast % nst), t & 1);
}

__device__ __forceinline__ void set_flag(int slot, int byte, unsigned epoch) {
  asm volatile("st.relaxed.gpu.global.u8 [%0], %1;" :: "l"(g_flags + slot * 256 + byte), "r"(epoch & 255u) : "memory");
}
__device__ __forceinline__ unsigned get_flag(int slot, int byte) {
  unsigned v; asm volatile("ld.relaxed.gpu.global.u8 %0, [%1];" : "=r"(v) : "l"(g_flags + slot * 256 + byte) : "memory"); return v;
}
__device__ __forceinline__ void publish(int slot, int byte, unsigned epoch) {
  asm volatile("fence.acq_rel.gpu;" ::: "memory");
  set_flag(slot, byte, epoch);
}
__device__ __forceinline__ float sum8(uint4 v) {
  return ((bf_lo(v.x) + bf_hi(v.x)) + (bf_lo(v.y) + bf_hi(v.y))) + ((bf_lo(v.z) + bf_hi(v.z)) + (bf_lo(v.w) + bf_hi(v.w)));
}
__device__ __forceinline__ uint4 ldg128(const void* p) {
  uint4 v; asm volatile("ld.global.nc.v4.u32 {%0,%1,%2,%3}, [%4];" : "=r"(v.x), "=r"(v.y), "=r"(v.z), "=r"(v.w) : "l"(p)); return v;
}

__device__ __forceinline__ void ln_rows(const uint4 (&rv)[5], uint32_t buf, int cta, unsigned epoch) {
  const int t = threadIdx.x - 128, row = cta * 16 + (t >> 4), c = t & 15;
  const float sh = __shfl_sync(0xffffffffu, bf_lo(rv[0].x), t & 16);
  float d[40], s = 0.f, q = 0.f;
  #pragma unroll
  for (int j = 0; j < 5; j++) {
    const uint32_t u[4] = {rv[j].x, rv[j].y, rv[j].z, rv[j].w};
    #pragma unroll
    for (int e = 0; e < 4; e++) {
      const float d0 = bf_lo(u[e]) - sh, d1 = bf_hi(u[e]) - sh;
      d[j * 8 + e * 2] = d0; d[j * 8 + e * 2 + 1] = d1;
      s += d0 + d1; q = fmaf(d0, d0, q); q = fmaf(d1, d1, q);
    }
  }
  #pragma unroll
  for (int o = 1; o < 16; o <<= 1) { s += __shfl_xor_sync(0xffffffffu, s, o); q += __shfl_xor_sync(0xffffffffu, q, o); }
  const float md = s * (1.f / DM);
  const float r = rsqrtf(fmaxf(fmaf(q, 1.f / DM, -md * md), 0.f) + LN_EPS), o = -md * r;
  if (c == 0) st_tag2(&g_xstat[row], __float_as_uint(r), (__float_as_uint(-(md + sh) * r) & ~255u) | (epoch & 255u));
  #pragma unroll
  for (int j = 0; j < 5; j++) {
    const float* a = &d[j * 8];
    sts128(buf + (t >> 4) * 1280 + (c + 16 * j) * 16,
           pack_bf16(fmaf(a[0], r, o), fmaf(a[1], r, o)), pack_bf16(fmaf(a[2], r, o), fmaf(a[3], r, o)),
           pack_bf16(fmaf(a[4], r, o), fmaf(a[5], r, o)), pack_bf16(fmaf(a[6], r, o), fmaf(a[7], r, o)));
  }
  fence_async_smem();
  bar_arrive<BAR_LN>(288);
}

__device__ __forceinline__ void weight_sums(const bf16* __restrict__ win, const bf16* __restrict__ wdre, int j, unsigned epoch) {
  const int t = threadIdx.x & 127, w = t >> 5, l = t & 31;
  const int cj = min(j, 59), cg = cj % 12, rg = cj / 12, wr = j * 10 + min(t >> 3, 9);
  uint4 cv[8], rv[10];
  #pragma unroll
  for (int i = 0; i < 8; i++) cv[i] = ldg128(reinterpret_cast<const uint4*>(win + (size_t)(rg * 128 + w * 32 + i * 4 + (l >> 3)) * FF + FH + cg * 64) + (l & 7));
  #pragma unroll
  for (int i = 0; i < 10; i++) rv[i] = ldg128(reinterpret_cast<const uint4*>(wdre + (size_t)wr * DM) + (l & 7) + 8 * i);
  float v[8];
  #pragma unroll
  for (int e = 0; e < 8; e++) v[e] = 0.f;
  #pragma unroll
  for (int i = 0; i < 8; i++) {
    v[0] += bf_lo(cv[i].x); v[1] += bf_hi(cv[i].x); v[2] += bf_lo(cv[i].y); v[3] += bf_hi(cv[i].y);
    v[4] += bf_lo(cv[i].z); v[5] += bf_hi(cv[i].z); v[6] += bf_lo(cv[i].w); v[7] += bf_hi(cv[i].w);
  }
  #pragma unroll
  for (int st = 0; st < 2; st++) {
    const int n = 4 >> st;
    const bool up = (l & (4 * n)) != 0;
    #pragma unroll
    for (int e = 0; e < 4; e++)
      if (e < n) { const float keep = up ? v[e + n] : v[e], send = up ? v[e] : v[e + n]; v[e] = keep + __shfl_xor_sync(0xffffffffu, send, 4 * n); }
  }
  float* red = reinterpret_cast<float*>(smem + RED_OFF);
  *reinterpret_cast<float2*>(red + w * 64 + (l & 7) * 8 + (l >> 3) * 2) = make_float2(v[0], v[1]);
  float s = 0.f;
  #pragma unroll
  for (int i = 0; i < 10; i++) s += sum8(rv[i]);
  #pragma unroll
  for (int o = 1; o < 8; o <<= 1) s += __shfl_xor_sync(0xffffffffu, s, o);
  if ((l & 7) == 0) st_tag2(&g_csum[5 * FH + wr], __float_as_uint(s), epoch);
  bar_sync<BAR_WG1>(128);
  if (t < 64) st_tag2(&g_csum[rg * FH + cg * 64 + t], __float_as_uint((red[t] + red[64 + t]) + (red[128 + t] + red[192 + t])), epoch);
}

__device__ __forceinline__ void gather96(const uint2* src, float* dst, unsigned epoch) {
  unsigned it = 0;
  while (true) {
    bool ok = true;
    uint2 u[15];
    #pragma unroll
    for (int j = 0; j < 15; j++) u[j] = ld_tag2(src + (j % 5) * FH + (j / 5) * 32);
    #pragma unroll
    for (int j = 0; j < 15; j++) ok = ok && u[j].y == epoch;
    #pragma unroll
    for (int j = 0; j < 3; j++)
      dst[j * 32] = ((__uint_as_float(u[j * 5].x) + __uint_as_float(u[j * 5 + 1].x)) + (__uint_as_float(u[j * 5 + 2].x) + __uint_as_float(u[j * 5 + 3].x))) + __uint_as_float(u[j * 5 + 4].x);
    if (ok || ++it > POLL_LIMIT) break;
    __nanosleep(2 * POLL_NS);
  }
}

__device__ __forceinline__ void a_entry(int g, int grp, int ct, int& mi, int& kb) {
  if (g < 10) { mi = M_X; kb = g; }
  else if (g < 20) { mi = M_XN; kb = g - 10; }
  else if (g < 52) { mi = grp == 0 ? M_WSP : M_WSRE; kb = g - 20; }
  else if (grp == 0) {
    if (g < 52 + NX) { mi = M_WSIM; kb = g - 52 + 32 - NX; }
    else {
      const int i = g - 52 - NX;
      mi = M_H; kb = i < 3 ? ct * 3 + i : i < 6 ? (ct ^ 1) * 3 + i - 3 : ((ct >> 1) ^ 1) * 6 + i - 6;
    }
  } else {
    if (g < 84 - NX) { mi = M_WSIM; kb = g - 52; }
    else { mi = M_H; kb = ((ct >> 1) ^ 1) * 6 + g - (84 - NX) + 6 - NO; }
  }
}

__global__ void __cluster_dims__(2, 1, 1) __launch_bounds__(384, 1)
fused_kernel(const __grid_constant__ Maps maps, const bf16* __restrict__ x, const bf16* __restrict__ win, const bf16* __restrict__ wdre,
             const bf16* __restrict__ bsp, bf16* __restrict__ out) {
  const uint32_t sbase = smem_u32(smem);
  const uint32_t full0 = sbase + BAR_OFF, empty0 = full0 + 8 * MAXST, dep0 = empty0 + 8 * MAXST, ring = sbase + RING_OFF;
  const int tid = threadIdx.x, wg = __shfl_sync(0xffffffffu, tid >> 7, 0);
  const int cta = blockIdx.x, rank = cta & 1, grp = (cta >> 1) & 1, rb = cta >> 3, ct = ((cta >> 2) & 1) * 2 + rank;
  const int total = grp == 0 ? KB_A : KB_B, gh = grp == 0 ? 52 + NX : 84 - NX;
  const uint32_t stage_bytes = grp == 0 ? STAGE_A : STAGE_B;
  const int nst = grp == 0 ? NST_A : NST_B;
  const uint32_t buf = ring + nst * stage_bytes;

  uint4 rv[5];
  if (wg != 0) {
    #pragma unroll
    for (int j = 0; j < 5; j++) rv[j] = ldg128(reinterpret_cast<const uint4*>(x + (size_t)(cta * 16 + ((tid - 128) >> 4)) * DM) + (tid & 15) + 16 * j);
  }
  const unsigned epoch = (ld_relaxed(&g_done) >> 7) + 1u;
  if (tid == 0) {
    TS(0, 0);
    for (int s = 0; s < MAXST; s++) { mbar_init(full0 + 8 * s, 2); mbar_init(empty0 + 8 * s, 4); mbar_init(dep0 + 8 * s, 1); }
    *reinterpret_cast<volatile int*>(smem + READY_OFF) = 0;
    asm volatile("fence.mbarrier_init.release.cluster;" ::: "memory");
  }
  __syncthreads();
  asm volatile("barrier.cluster.arrive.relaxed.aligned;" ::: "memory");

  if (wg == 0) {
    asm volatile("setmaxnreg.dec.sync.aligned.u32 40;");
    const int warp = tid >> 5, lane = tid & 31;
    if (warp == 0) {
      const int row = rb * 128;
      if (lane == 0) {
        for (int g = 0; g < nst; g++) {
          mbar_expect_tx(full0 + 8 * g, A_BYTES);
          tma_load_2d(ring + g * stage_bytes, &maps.m[M_X], full0 + 8 * g, g * 64, row);
          tma_load_2d(ring + g * stage_bytes + 8192, &maps.m[M_X], full0 + 8 * g, g * 64, row + 64);
        }
      }
      __syncwarp();
      cluster_wait();
      if (lane == 0) {
        int s = 0, ph = 0;
        #pragma unroll 1
        for (int g = nst; g < total; g++) {
          int mi, kb;
          a_entry(g, grp, ct, mi, kb);
          if (g == 10 || g == gh + 3 - 3 * grp) { TS(0, g > 10 ? 3 : 1); mbar_wait(dep0 + (g > 10 ? 24 : 0), 0); fence_async_global(); TS(0, g > 10 ? 4 : 2); }
          mbar_wait(empty0 + 8 * s, ph);
          if (grp == 0 && g >= gh && g < gh + 6) {
            if (g < gh + 3) {
              mbar_arrive(full0 + 8 * s);
            } else {
              mbar_expect_tx(full0 + 8 * s, A_BYTES);
              tma_load_2d(ring + s * stage_bytes, &maps.m[mi], full0 + 8 * s, kb * 64, row);
              tma_load_2d(ring + s * stage_bytes + 8192, &maps.m[mi], full0 + 8 * s, kb * 64, row + 64);
            }
          } else {
            mbar_expect_tx(full0 + 8 * s, A_BYTES);
            tma_load_2d_mc(ring + s * stage_bytes + rank * 8192, &maps.m[mi], full0 + 8 * s, kb * 64, row + rank * 64, 3);
          }
          if (++s == nst) { s = 0; ph ^= 1; }
          if (g + PF_D < gh) {
            a_entry(g + PF_D, grp, ct, mi, kb);
            if (mi >= M_WSRE && (kb & 1) == (ct >> 1))
              asm volatile("cp.async.bulk.prefetch.tensor.2d.L2.global.tile [%0, {%1, %2}];" :: "l"((uint64_t)&maps.m[mi]), "r"(kb * 64), "r"(row + rank * 64) : "memory");
          }
        }
        TS(0, 5);
      }
    } else if (warp == 1) {
      if (lane == 0) {
        int s = 0, ph = 1;
        int have = 0;
        #pragma unroll 1
        for (int g = 0; g < total; g++) {
          int mi, kb, c;
          a_entry(g, grp, ct, mi, kb);
          const bool nmaj = g >= gh || (grp == 0 && g < 52);
          uint32_t bytes = 20480;
          if (g >= gh) { mi = M_WOUT; c = ct * 5; }
          else if (g >= 52) { mi = M_AB; c = DM + ct * 160; }
          else if (grp == 0) { mi = g < 20 ? M_WIN3 : M_Z23; c = 3 * ct + (g < 10 ? 12 : 0); bytes = 24576; }
          else { mi = g < 10 ? M_WDRE : g < 20 ? M_WDIM : M_AB; c = ct * 160; }
          if (g >= 20 && g < 52 && ((g - 20) >> 1) >= have) {
            if (g == 20) TS(1, 0);
            unsigned it = 0;
            while ((have = *reinterpret_cast<volatile int*>(smem + READY_OFF)) <= ((g - 20) >> 1) && ++it < 50 * POLL_LIMIT) {}
            fence_async_global();
            if (g == 20) { TS(1, 1); TC(1); }
          }
          if (g == 52) { TS(1, 2); mbar_wait(dep0 + 16, 0); fence_async_global(); TS(1, 3); TC(2); }
          const uint32_t dst = ring + s * stage_bytes + A_BYTES, fb = full0 + 8 * s;
          mbar_wait(empty0 + 8 * s, ph);
          if (++s == nst) { s = 0; ph ^= 1; }
          mbar_expect_tx(fb, bytes);
          if (nmaj) tma_load_3d(dst, &maps.m[mi], fb, 0, kb * 64, c);
          else tma_load_2d(dst, &maps.m[mi], fb, kb * 64, c);
        }
      }
      __syncwarp();
      cluster_wait();
    } else if (warp == 2) {
      if (lane < M_COUNT) asm volatile("prefetch.tensormap [%0];" :: "l"((uint64_t)&maps.m[lane]) : "memory");
      cluster_wait();
      {
        unsigned it = 0;
        uint2 v[4];
        while (true) {
          bool ok = true;
          #pragma unroll
          for (int i = 0; i < 4; i++) { v[i] = ld_tag2(&g_xstat[rb * 128 + i * 32 + lane]); ok = ok && ((v[i].y ^ epoch) & 255u) == 0; }
          if (ok || ++it > POLL_LIMIT) break;
          __nanosleep(POLL_NS);
        }
        #pragma unroll
        for (int i = 0; i < 4; i++) reinterpret_cast<uint2*>(smem + ROWSTAT_OFF)[i * 32 + lane] = make_uint2(v[i].x, v[i].y & ~255u);
        __syncwarp();
        TS(0, 6);
        if (grp == 0) bar_arrive<BAR_STATS>(320); else bar_arrive<BAR_STATS>(192);
      }
      #pragma unroll 1
      for (int i = 0; i < 5; i++) {
        const int d = i == 3 ? 4 : i == 4 ? 3 : i;
        const int slot = d == 0 ? F_XN + rb : d == 4 ? F_Y + rb * 4 + ct : d == 3 ? F_H + rb : d == 2 ? F_B + ct : grp == 0 ? F_Z + ct : F_A + ct;
        const int byte = d == 0 ? lane & 7 : d == 4 ? 0 : d == 3 ? lane & 3 : lane & 15;
        unsigned it = 0, m;
        while ((m = __ballot_sync(0xffffffffu, get_flag(slot, byte) != (epoch & 255u))) != 0 && ++it < POLL_LIMIT) {
          if (d == 1 && lane == 0) *reinterpret_cast<volatile int*>(smem + READY_OFF) = __ffs(m) - 1;
          __nanosleep(WATCH_NS);
        }
        if (d == 1 && lane == 0) *reinterpret_cast<volatile int*>(smem + READY_OFF) = 16;
        if (d < 4) TS(0, 8 + d * 2); else TS(0, 7);
        fence_async_global();
        __syncwarp();
        if (lane == 0 && d != 1) mbar_arrive(dep0 + 8 * d);
      }
    } else {
      cluster_wait();
      bar_sync<BAR_LN>(288);
      if (lane == 0) {
        TS(1, 5);
        asm volatile("cp.async.bulk.global.shared::cta.bulk_group [%0], [%1], 20480;" :: "l"(g_xn + (size_t)cta * 16 * DM), "r"(buf) : "memory");
        bulk_commit();
        bulk_wait_all();
        set_flag(F_XN + rb, cta & 7, epoch);
        TS(1, 6);
      }
      __syncwarp();
      if (grp == 0) {
        #pragma unroll 1
        for (int i = 0; i < 2; i++) gather96(&g_csum[ct * 192 + i * 96 + lane], reinterpret_cast<float*>(smem + COLSUM_OFF) + i * 96 + lane, epoch);
      } else {
        unsigned it = 0;
        while (true) {
          bool ok = true;
          #pragma unroll
          for (int j = 0; j < 5; j++) {
            const uint2 u = ld_tag2(&g_csum[5 * FH + ct * 160 + j * 32 + lane]);
            ok = ok && u.y == epoch;
            reinterpret_cast<uint32_t*>(smem + COLSUM_OFF)[j * 32 + lane] = u.x;
          }
          if (ok || ++it > POLL_LIMIT) break;
          __nanosleep(2 * POLL_NS);
        }
      }
      __syncwarp();
      TS(1, 4);
      if (grp == 0) {
        bar_arrive<BAR_STATS>(320);
        bar_sync<BAR_PUB1>(160);
        if (lane == 0) set_flag(F_Z + ct, rb, epoch);
        TS(1, 8);
        __syncwarp();
        bar_arrive<BAR_BUF>(160);
      } else {
        bar_arrive<BAR_STATS>(192);
        bar_sync<BAR_PUB2>(160);
        if (lane == 0) set_flag(F_A + ct, rb, epoch);
        TS(1, 9);
        __syncwarp();
      }
      bar_sync<BAR_PUB1>(160);
      if (lane == 0) set_flag(grp == 0 ? F_H + rb : F_B + ct, grp == 0 ? ct : rb, epoch);
      TS(1, 10);
      __syncwarp();
      bar_arrive<BAR_BUF>(160);
    }
  } else {
    asm volatile("setmaxnreg.inc.sync.aligned.u32 232;");
    const int t = tid & 127, w = t >> 5, l = t & 31;
    ln_rows(rv, buf, cta, epoch);
    TS(wg + 1, 0);
    cluster_wait();
    const uint32_t st_base = buf + (w * 16 + ((l >> 3) & 1) * 8 + (l & 7)) * 128;
    const uint32_t st_x = ((l >> 4) ^ (l & 7)) << 4;
    const float2* rs = reinterpret_cast<const float2*>(smem + ROWSTAT_OFF) + w * 16 + (l >> 2);
    const float2* cs = reinterpret_cast<const float2*>(smem + COLSUM_OFF) + (l & 3);
    if (grp == 0) {
      {
        const int mb = wg - 1;
        float acc[1][96];
        zero(acc);
        mainloop<192, 1, 1, false, 0>(acc, sbase, 0, 0, 10, mb);
        drain(acc, sbase, 0, 9);
        TS(wg + 1, 1);
        bar_sync<BAR_STATS>(320);
        const float2 s0 = rs[mb * 64], s1 = rs[mb * 64 + 8];
        const float nm[2] = {s0.y / s0.x, s1.y / s1.x}, hr[2] = {0.5f * s0.x, 0.5f * s1.x};
        const float k1[2] = {0.7978845608f * s0.x, 0.7978845608f * s1.x};
        const float k2[2] = {0.0356774081f * s0.x * s0.x * s0.x, 0.0356774081f * s1.x * s1.x * s1.x};
        float sm0 = 0.f, sm1 = 0.f, q0 = 0.f, q1 = 0.f;
        #pragma unroll
        for (int jj = 0; jj < 12; jj++) {
          float u[8];
          #pragma unroll
          for (int hf = 0; hf < 2; hf++) {
            const float2 c = cs[jj * 8 + hf * 4];
            #pragma unroll
            for (int e = 0; e < 4; e++) {
              const float wv = fmaf(nm[e >> 1], (e & 1) ? c.y : c.x, acc[0][8 * jj + 4 * hf + e]);
              float th; asm("tanh.approx.f32 %0, %1;" : "=f"(th) : "f"(wv * fmaf(k2[e >> 1], wv * wv, k1[e >> 1])));
              const float hv = hr[e >> 1] * wv;
              u[4 * hf + e] = fmaf(hv, th, hv);
            }
            sm0 += u[4 * hf] + u[4 * hf + 1]; q0 = fmaf(u[4 * hf], u[4 * hf], q0); q0 = fmaf(u[4 * hf + 1], u[4 * hf + 1], q0);
            sm1 += u[4 * hf + 2] + u[4 * hf + 3]; q1 = fmaf(u[4 * hf + 2], u[4 * hf + 2], q1); q1 = fmaf(u[4 * hf + 3], u[4 * hf + 3], q1);
          }
          stsm4(st_base + mb * 24576 + (jj >> 2) * 8192 + (st_x ^ ((jj & 3) << 5)),
                pack_bf16(u[0], u[1]), pack_bf16(u[2], u[3]), pack_bf16(u[4], u[5]), pack_bf16(u[6], u[7]));
        }
        #pragma unroll
        for (int o = 1; o < 4; o <<= 1) {
          sm0 += __shfl_xor_sync(0xffffffffu, sm0, o); q0 += __shfl_xor_sync(0xffffffffu, q0, o);
          sm1 += __shfl_xor_sync(0xffffffffu, sm1, o); q1 += __shfl_xor_sync(0xffffffffu, q1, o);
        }
        if ((l & 3) < 2) {
          const float sm = (l & 1) ? sm1 : sm0, sv = (l & 1) ? q1 : q0;
          const int row = mb * 64 + w * 16 + (l & 1) * 8 + (l >> 2);
          const float mu = sm * (1.f / 192), m2 = fmaxf(sv - sm * mu, 0.f);
          st_tag2(&g_zstat[(rb * 4 + ct) * 128 + row], __float_as_uint(mu), (__float_as_uint(m2) & ~255u) | (epoch & 255u));
          reinterpret_cast<float2*>(smem + ZSTAT_OFF)[row] = make_float2(mu, m2);
        }
        TS(wg + 1, 4);
      }
      float acc[2][96];
      if (wg == 1) {
        bar_sync<BAR_U>(256);
        uint2 v[3];
        unsigned n = 0;
        while (true) {
          bool ok = true;
          #pragma unroll
          for (int j = 0; j < 3; j++) { v[j] = ld_tag2(&g_zstat[(rb * 4 + ((ct + 1 + j) & 3)) * 128 + t]); ok = ok && ((v[j].y ^ epoch) & 255u) == 0; }
          if (ok || ++n > POLL_LIMIT) break;
          __nanosleep(POLL_NS);
        }
        const float2 own = reinterpret_cast<const float2*>(smem + ZSTAT_OFF)[t];
        const float m0 = __uint_as_float(v[0].x), m1 = __uint_as_float(v[1].x), m3 = __uint_as_float(v[2].x);
        const float mean = 0.25f * ((own.x + m0) + (m1 + m3));
        const float d = (own.x - mean) * (own.x - mean) + (m0 - mean) * (m0 - mean) + (m1 - mean) * (m1 - mean) + (m3 - mean) * (m3 - mean);
        const float var = fmaf(192.f, d, (own.y + __uint_as_float(v[0].y & ~255u)) + (__uint_as_float(v[1].y & ~255u) + __uint_as_float(v[2].y & ~255u)));
        const float r = rsqrtf(var * (1.f / FH) + LN_EPS);
        TS(2, 5);
        const uint32_t rbase = buf + (t >> 6) * 24576 + (t & 63) * 128;
        const uint32_t m2 = pack_bf16(-mean, -mean), r2 = pack_bf16(r, r);
        const float res = (-mean - bf_lo(m2)) * r;
        const uint32_t e2 = pack_bf16(res, res);
        #pragma unroll 1
        for (int c = 0; c < 3; c++) {
          uint4 z[8];
          #pragma unroll
          for (int i = 0; i < 8; i++) z[i] = lds128(rbase + c * 8192 + (((i ^ l) & 7) << 4));
          #pragma unroll
          for (int i = 0; i < 8; i++)
            sts128(rbase + c * 8192 + (((i ^ l) & 7) << 4), hfma2_bf16(hadd2_bf16(z[i].x, m2), r2, e2), hfma2_bf16(hadd2_bf16(z[i].y, m2), r2, e2),
                   hfma2_bf16(hadd2_bf16(z[i].z, m2), r2, e2), hfma2_bf16(hadd2_bf16(z[i].w, m2), r2, e2));
          fence_async_smem();
          __syncwarp();
          if (l == 0) {
            tma_store_2d(&maps.m[M_ZS], buf + (w >> 1) * 24576 + c * 8192 + (w & 1) * 4096, ct * 192 + c * 64, rb * 128 + w * 32);
            bulk_commit();
          }
        }
        TS(2, 6);
        if (l == 0) bulk_wait_all();
        __syncwarp();
        bar_arrive<BAR_PUB1>(160);
        {
          const bf16* bp = bsp + rb * 128 + w * 16 + (l >> 2);
          const float bb[4] = {__bfloat162float(bp[0]), __bfloat162float(bp[8]), __bfloat162float(bp[64]), __bfloat162float(bp[72])};
          #pragma unroll
          for (int i = 0; i < 96; i++) { acc[0][i] = bb[(i >> 1) & 1]; acc[1][i] = bb[2 + ((i >> 1) & 1)]; }
          pin(acc);
        }
        bar_sync<BAR_ORD2>(256);
        mainloop<192, 2, 1, false, BAR_ORD1>(acc, sbase, 0, 20, 32);
        bar_sync<BAR_Z1>(256);
        uint32_t z[6][4][4];
        #pragma unroll
        for (int i = 0; i < ZPRE; i++) ldsm4(st_base + (i >> 2) * 8192 + (st_x ^ ((i & 3) << 5)), z[i >> 2][i & 3][0], z[i >> 2][i & 3][1], z[i >> 2][i & 3][2], z[i >> 2][i & 3][3]);
        drain(acc, sbase, 0, 51);
        TS(2, 7);
        #pragma unroll
        for (int bx = 0; bx < 6; bx++) {
          if (bx >= 1) {
            #pragma unroll
            for (int i = ZPRE + (bx - 1) * 10; i < ZPRE + bx * 10; i++)
              if (i < 24) ldsm4(st_base + (i >> 2) * 8192 + (st_x ^ ((i & 3) << 5)), z[i >> 2][i & 3][0], z[i >> 2][i & 3][1], z[i >> 2][i & 3][2], z[i >> 2][i & 3][3]);
          }
          #pragma unroll
          for (int i = 0; i < 4; i++) {
            const float* a = &acc[bx / 3][8 * ((bx % 3) * 4 + i)];
            const uint32_t* zz = z[bx][i];
            stsm4(st_base + bx * 8192 + (st_x ^ (i << 5)),
                  hmul2_bf16(zz[0], pack_bf16(a[0], a[1])), hmul2_bf16(zz[1], pack_bf16(a[2], a[3])),
                  hmul2_bf16(zz[2], pack_bf16(a[4], a[5])), hmul2_bf16(zz[3], pack_bf16(a[6], a[7])));

          }
          if (bx % 3 == 2) {
            fence_async_smem();
            __syncwarp();
            if (l < 3) {
              tma_store_2d(&maps.m[M_HS], buf + (bx - 2 + l) * 8192 + w * 2048, ct * 192 + l * 64, rb * 128 + (bx / 3) * 64 + w * 16);
              bulk_commit();
            }
          }
        }
        bar_arrive<BAR_U>(256);
        TS(2, 8);
        if (l < 3) bulk_wait_all();
        __syncwarp();
        bar_arrive<BAR_PUB1>(160);
        TS(2, 9);
        return;
      }
      bar_arrive<BAR_U>(256);
      zero(acc);
      mainloop<192, 2, 1, false, BAR_ORD2>(acc, sbase, 0, 10, 10);
      drain(acc, sbase, 0, 19);
      TS(3, 2);
      bar_sync<BAR_BUF>(160);
      #pragma unroll
      for (int mi = 0; mi < 2; mi++)
        #pragma unroll
        for (int jj = 0; jj < 12; jj++) {
          const float* a = &acc[mi][8 * jj];
          stsm4(st_base + mi * 24576 + (jj >> 2) * 8192 + (st_x ^ ((jj & 3) << 5)),
                pack_bf16(a[0], a[1]), pack_bf16(a[2], a[3]), pack_bf16(a[4], a[5]), pack_bf16(a[6], a[7]));
        }
      __syncwarp();
      TS(3, 3);
      const uint32_t rbase = buf + (l >> 4) * 24576 + (w * 16 + (l & 15)) * 128;
      #pragma unroll 1
      for (int c2 = 0; c2 < 12; c2++) {
        const uint32_t ab = rbase + (c2 >> 2) * 8192;
        uint4 v[2];
        #pragma unroll
        for (int i = 0; i < 2; i++) v[i] = lds128(ab + (((((c2 & 3) * 2 + i) ^ l) & 7) << 4));
        #pragma unroll
        for (int i = 0; i < 2; i++)
          sts128(ab + (((((c2 & 3) * 2 + i) ^ l) & 7) << 4),
                 pack_bf16(gelu_tanh(bf_lo(v[i].x)), gelu_tanh(bf_hi(v[i].x))), pack_bf16(gelu_tanh(bf_lo(v[i].y)), gelu_tanh(bf_hi(v[i].y))),
                 pack_bf16(gelu_tanh(bf_lo(v[i].z)), gelu_tanh(bf_hi(v[i].z))), pack_bf16(gelu_tanh(bf_lo(v[i].w)), gelu_tanh(bf_hi(v[i].w))));
        __nanosleep(Z1_NS);
      }
      TS(3, 5);
      bar_arrive<BAR_Z1>(256);
    }
    float acc[2][80];
    if (grp == 1) {
      zero(acc);
      if (wg == 2) {
        mainloop<160, 2, 0, false, BAR_ORD2>(acc, sbase, 1, 0, 10);
      } else {
        weight_sums(win, wdre, rb * 4 + ct, epoch);
        TS(2, 1);
        bar_sync<BAR_ORD2>(256);
        mainloop<160, 2, 0, false, BAR_ORD1>(acc, sbase, 1, 10, 10);
      }
      drain(acc, sbase, 1, wg == 2 ? 9 : 19);
      TS(wg + 1, wg == 1 ? 7 : 2);
      if (wg == 1) bar_sync<BAR_Z1>(256); else bar_sync<BAR_STATS>(192);
      const uint32_t tb = buf + ((l >> 4) * 8 + (l & 7)) * 128 + (((w * 2 + ((l >> 3) & 1)) ^ (l & 7)) << 4);
      float2 st[4];
      #pragma unroll
      for (int r = 0; r < 4; r++) st[r] = wg == 2 ? rs[(r >> 1) * 64 + (r & 1) * 8] : make_float2(-1.f, 0.f);
      #pragma unroll
      for (int jj = 0; jj < 10; jj++) {
        const float2 c0 = cs[jj * 8], c1 = cs[jj * 8 + 4];
        #pragma unroll
        for (int mi = 0; mi < 2; mi++) {
          const float* a = &acc[mi][8 * jj];
          const float2 s0 = st[mi * 2], s1 = st[mi * 2 + 1];
          stsm4_t(tb + mi * 20480 + jj * 2048,
                  pack_bf16(fmaf(a[0], s0.x, s0.y * c0.x), fmaf(a[1], s0.x, s0.y * c0.y)), pack_bf16(fmaf(a[2], s1.x, s1.y * c0.x), fmaf(a[3], s1.x, s1.y * c0.y)),
                  pack_bf16(fmaf(a[4], s0.x, s0.y * c1.x), fmaf(a[5], s0.x, s0.y * c1.y)), pack_bf16(fmaf(a[6], s1.x, s1.y * c1.x), fmaf(a[7], s1.x, s1.y * c1.y)));
        }
      }
      fence_async_smem();
      if (wg == 1) bar_sync<BAR_WG1>(128); else bar_sync<BAR_WG2>(128);
      TS(wg + 1, wg == 1 ? 8 : 6);
      if (l < 2) {
        tma_store_2d(&maps.m[M_ABS], buf + l * 20480 + w * 5120, rb * 128 + l * 64, (2 - wg) * DM + ct * 160 + w * 40);
        bulk_commit();
        bulk_wait_all();
      }
      __syncwarp();
      TS(wg + 1, wg == 1 ? 9 : 10);
      if (wg == 1) {
        bar_arrive<BAR_PUB1>(160);
        #pragma unroll 1
        for (int i = 0; i < 4; i++) {
          uint4 v[5];
          #pragma unroll
          for (int j = 0; j < 5; j++) {
            const int e = (i * 5 + j) * 128 + t;
            v[j] = ldg128(x + (size_t)(rb * 128 + e / 20) * DM + ct * 160 + (e % 20) * 8);
          }
          #pragma unroll
          for (int j = 0; j < 5; j++) {
            const int e = (i * 5 + j) * 128 + t;
            stg128(out + (size_t)(rb * 128 + e / 20) * DM + ct * 160 + (e % 20) * 8, v[j]);
          }
        }
        bar_sync<BAR_WG1>(128);
        if (t == 0) publish(F_Y + rb * 4 + ct, 0, epoch);
        return;
      }
      bar_arrive<BAR_PUB2>(160);
      bar_arrive<BAR_Z1>(256);
    }
    zero(acc);
    bar_sync<BAR_ORD1>(256);
    mainloop<160, 2, 0, false, 0>(acc, sbase, grp, grp == 0 ? 52 : 20, grp == 0 ? NX : 64 - NX);
    if (grp == 0) {
      bar_sync<BAR_U>(256);
      mainloop<160, 2, 2, true, 0, true>(acc, sbase, 0, 52 + NX, 3);
      mainloop<160, 2, 2, true, 0>(acc, sbase, 0, 55 + NX, 6 - NO);
    }
    static_assert(NO == 3, "tail3 covers group B's whole share");
    tail3(acc, sbase, grp);
    const uint32_t slab = buf + w * (16 * 320);
    const uint32_t addr = slab + (((l >> 3) & 1) * 8 + (l & 7)) * 320 + (l >> 4) * 16;
    bar_sync<BAR_BUF>(160);
    mbar_wait(dep0 + 32, 0);
    #pragma unroll
    for (int mi = 1; mi >= 0; mi--) {
      if (mi == 1) wgmma_wait<1>(); else wgmma_wait<0>();
      #pragma unroll
      for (int i = 0; i < 80; i++) asm volatile("" : "+f"(acc[mi][i]) :: "memory");
      if (mi == 1) TS(3, 12);
      #pragma unroll
      for (int jj = 0; jj < 10; jj++) {
        const float* a = &acc[mi][8 * jj];
        stsm4(addr + mi * 20480 + jj * 32, pack_bf16(a[0], a[1]), pack_bf16(a[2], a[3]), pack_bf16(a[4], a[5]), pack_bf16(a[6], a[7]));
      }
      fence_async_smem();
      __syncwarp();
      if (l == 0) {
        tma_reduce_2d(&maps.m[M_OUT], slab + mi * 20480, ct * 160, rb * 128 + mi * 64 + w * 16);
        bulk_commit();
      }
    }
    TS(3, 13);
    if (l == 0) {
      bulk_wait_read();
      if (w == 0) atomicAdd(&g_done, 1u);
    }
    TS(3, 15);
  }
}

typedef CUresult (*EncodeFn)(CUtensorMap*, CUtensorMapDataType, cuuint32_t, void*, const cuuint64_t*, const cuuint64_t*,
                             const cuuint32_t*, const cuuint32_t*, CUtensorMapInterleave, CUtensorMapSwizzle,
                             CUtensorMapL2promotion, CUtensorMapFloatOOBfill);

void make2d(EncodeFn enc, CUtensorMap* m, const void* p, uint64_t cols, uint64_t rows, uint32_t bc, uint32_t br, bool swz = true) {
  cuuint64_t gd[2] = {cols, rows}, gs[1] = {cols * 2};
  cuuint32_t bd[2] = {bc, br}, es[2] = {1, 1};
  enc(m, CU_TENSOR_MAP_DATA_TYPE_BFLOAT16, 2, const_cast<void*>(p), gd, gs, bd, es, CU_TENSOR_MAP_INTERLEAVE_NONE,
      swz ? CU_TENSOR_MAP_SWIZZLE_128B : CU_TENSOR_MAP_SWIZZLE_NONE, CU_TENSOR_MAP_L2_PROMOTION_L2_128B, CU_TENSOR_MAP_FLOAT_OOB_FILL_NONE);
}
void make3d(EncodeFn enc, CUtensorMap* m, const void* p, uint64_t cols, uint64_t rows, uint32_t cw, uint32_t nc, uint32_t br = 64) {
  cuuint64_t gd[3] = {cw, rows, cols / cw}, gs[2] = {cols * 2, cw * 2};
  cuuint32_t bd[3] = {cw, br, nc}, es[3] = {1, 1, 1};
  enc(m, CU_TENSOR_MAP_DATA_TYPE_BFLOAT16, 3, const_cast<void*>(p), gd, gs, bd, es, CU_TENSOR_MAP_INTERLEAVE_NONE,
      cw == 64 ? CU_TENSOR_MAP_SWIZZLE_128B : CU_TENSOR_MAP_SWIZZLE_64B, CU_TENSOR_MAP_L2_PROMOTION_L2_128B, CU_TENSOR_MAP_FLOAT_OOB_FILL_NONE);
}

}

extern "C" void kernel_launch(void* const* d_in, const int* in_sizes, int n_in, void* d_out, int out_size) {
  const bf16* x = (const bf16*)d_in[0];
  const bf16* wsre = (const bf16*)d_in[1];
  const bf16* wsim = (const bf16*)d_in[2];
  const bf16* wdre = (const bf16*)d_in[3];
  const bf16* wdim = (const bf16*)d_in[4];
  const bf16* win = (const bf16*)d_in[6];
  const bf16* wsp = (const bf16*)d_in[7];
  const bf16* bsp = (const bf16*)d_in[8];
  const bf16* wout = (const bf16*)d_in[9];

  void* fn = nullptr;
  cudaDriverEntryPointQueryResult qr;
  cudaGetDriverEntryPoint("cuTensorMapEncodeTiled", &fn, cudaEnableDefault, &qr);
  EncodeFn enc = (EncodeFn)fn;
  void *abT, *z2, *h, *xn;
  cudaGetSymbolAddress(&xn, g_xn);
  cudaGetSymbolAddress(&abT, g_abT);
  cudaGetSymbolAddress(&z2, g_z2);
  cudaGetSymbolAddress(&h, g_h);

  Maps maps;
  make2d(enc, &maps.m[M_X], x, DM, SEQ, 64, 64);
  make2d(enc, &maps.m[M_XN], xn, DM, SEQ, 64, 64);
  make2d(enc, &maps.m[M_WSRE], wsre, SEQ, SEQ, 64, 64);
  make2d(enc, &maps.m[M_WSIM], wsim, SEQ, SEQ, 64, 64);
  make2d(enc, &maps.m[M_WSP], wsp, SEQ, SEQ, 64, 64);
  make2d(enc, &maps.m[M_H], h, FH, SEQ, 64, 64);
  make3d(enc, &maps.m[M_WIN3], win, FF, DM, 64, 3);
  make3d(enc, &maps.m[M_Z23], z2, FH, SEQ, 64, 3);
  make2d(enc, &maps.m[M_WDRE], wdre, DM, DM, 64, 160);
  make2d(enc, &maps.m[M_WDIM], wdim, DM, DM, 64, 160);
  make2d(enc, &maps.m[M_AB], abT, SEQ, 2 * DM, 64, 160);
  make3d(enc, &maps.m[M_WOUT], wout, DM, FH, 32, 5);
  make2d(enc, &maps.m[M_HS], h, FH, SEQ, 64, 16);
  make2d(enc, &maps.m[M_ZS], z2, FH, SEQ, 64, 32);
  make2d(enc, &maps.m[M_ABS], abT, SEQ, 2 * DM, 64, 40);
  make2d(enc, &maps.m[M_OUT], d_out, DM, SEQ, 160, 16, false);

  cudaFuncSetAttribute(fused_kernel, cudaFuncAttributeMaxDynamicSharedMemorySize, SMEM_BYTES);
  fused_kernel<<<128, 384, SMEM_BYTES>>>(maps, x, win, wdre, bsp, (bf16*)d_out);
}
```

```cpp
#include <cuda_runtime.h>
#include <cuda_bf16.h>
#include <cuda.h>
#include <stdint.h>

namespace {

typedef __nv_bfloat16 bf16;

constexpr int SEQ = 2048, DM = 640, FF = 1536, FH = 768;
#define NOV 3
#define NXV 6
constexpr int NX = NXV;
constexpr int NO = NOV;
constexpr int NST_A = 4, NST_B = 5, MAXST = 5;
constexpr int A_BYTES = 16384;
constexpr int BAR_OFF = 0;
constexpr int READY_OFF = 128;
constexpr int COLSUM_OFF = 256;
constexpr int ROWSTAT_OFF = 1024;
constexpr int ZSTAT_OFF = 2048;
constexpr int RED_OFF = 3072;
constexpr int RING_OFF = 4096;
constexpr int STAGE_A = 40960, STAGE_B = 36864;
constexpr int SMEM_BYTES = RING_OFF + 5 * STAGE_B + 40960;
constexpr int KB_A = 52 + NX + 12 - NO;
constexpr int KB_B = 84 - NX + NO;
constexpr float LN_EPS = 1e-5f;
constexpr unsigned POLL_LIMIT = 100000;
constexpr unsigned POLL_NS = 100, WATCH_NS = 40;
constexpr unsigned Z1_NS = 600;
constexpr int PF_D = 8;
constexpr int ZPRE = 6;

constexpr int BAR_ORD1 = 1, BAR_ORD2 = 2, BAR_WG1 = 3, BAR_WG2 = 4, BAR_LN = 5, BAR_BUF = 6, BAR_Z1 = 7, BAR_PUB1 = 8, BAR_PUB2 = 9,
              BAR_STATS = 10, BAR_U = 11;

enum { M_X, M_XN, M_WSRE, M_WSIM, M_WSP, M_H, M_WIN3, M_Z23, M_WDRE, M_WDIM, M_AB, M_WOUT, M_OUT, M_HS, M_ZS, M_ABS, M_COUNT };
struct Maps { CUtensorMap m[M_COUNT]; };

__device__ __align__(1024) bf16 g_abT[2 * DM * SEQ];
__device__ __align__(1024) bf16 g_z2[SEQ * FH];
__device__ __align__(1024) bf16 g_h[SEQ * FH];
__device__ __align__(1024) bf16 g_xn[SEQ * DM];
__device__ __align__(16) uint2 g_xstat[SEQ];
__device__ __align__(16) uint2 g_csum[5 * FH + DM];
__device__ __align__(16) uint2 g_zstat[64 * 128];
__device__ __align__(256) unsigned char g_flags[108 * 256];
constexpr int F_A = 0, F_B = 4, F_Z = 8, F_H = 12, F_XN = 28, F_Y = 44;
__device__ unsigned g_done;
#define TS(role, ev)
#define TC(i)

extern __shared__ __align__(1024) uint8_t smem[];

__device__ __forceinline__ uint32_t smem_u32(const void* p) { return (uint32_t)__cvta_generic_to_shared(p); }
__device__ __forceinline__ void mbar_init(uint32_t bar, uint32_t cnt) { asm volatile("mbarrier.init.shared::cta.b64 [%0], %1;" :: "r"(bar), "r"(cnt)); }
__device__ __forceinline__ void mbar_expect_tx(uint32_t bar, uint32_t bytes) { asm volatile("mbarrier.arrive.expect_tx.shared::cta.b64 _, [%0], %1;" :: "r"(bar), "r"(bytes) : "memory"); }
__device__ __forceinline__ void mbar_arrive(uint32_t bar) { asm volatile("mbarrier.arrive.shared::cta.b64 _, [%0];" :: "r"(bar) : "memory"); }
__device__ __forceinline__ void mbar_arrive_cluster(uint32_t bar, uint32_t cta) {
  asm volatile("{\n.reg .b32 ra;\nmapa.shared::cluster.u32 ra, %0, %1;\nmbarrier.arrive.shared::cluster.b64 _, [ra];\n}" :: "r"(bar), "r"(cta) : "memory");
}
__device__ __forceinline__ void mbar_wait(uint32_t bar, uint32_t parity) {
  asm volatile("{\n.reg .pred p;\n.reg .u32 n;\nmov.u32 n, 0;\n"
               "LW: mbarrier.try_wait.parity.shared::cta.b64 p, [%0], %1, 2000;\n@p bra LD;\n"
               "add.u32 n, n, 1;\nsetp.lt.u32 p, n, 20000;\n@p bra LW;\nLD:\n}" :: "r"(bar), "r"(parity) : "memory");
}
__device__ __forceinline__ void tma_load_2d(uint32_t dst, const CUtensorMap* map, uint32_t bar, int c0, int c1) {
  asm volatile("cp.async.bulk.tensor.2d.shared::cluster.global.mbarrier::complete_tx::bytes [%0], [%1, {%3, %4}], [%2];"
    :: "r"(dst), "l"((uint64_t)map), "r"(bar), "r"(c0), "r"(c1) : "memory");
}
__device__ __forceinline__ void tma_load_3d(uint32_t dst, const CUtensorMap* map, uint32_t bar, int c0, int c1, int c2) {
  asm volatile("cp.async.bulk.tensor.3d.shared::cluster.global.mbarrier::complete_tx::bytes [%0], [%1, {%3, %4, %5}], [%2];"
    :: "r"(dst), "l"((uint64_t)map), "r"(bar), "r"(c0), "r"(c1), "r"(c2) : "memory");
}
__device__ __forceinline__ void tma_load_2d_mc(uint32_t dst, const CUtensorMap* map, uint32_t bar, int c0, int c1, uint16_t mask) {
  asm volatile("cp.async.bulk.tensor.2d.shared::cluster.global.mbarrier::complete_tx::bytes.multicast::cluster [%0], [%1, {%3, %4}], [%2], %5;"
    :: "r"(dst), "l"((uint64_t)map), "r"(bar), "r"(c0), "r"(c1), "h"(mask) : "memory");
}
__device__ __forceinline__ void tma_store_2d(const CUtensorMap* map, uint32_t src, int c0, int c1) {
  asm volatile("cp.async.bulk.tensor.2d.global.shared::cta.bulk_group [%0, {%2, %3}], [%1];"
    :: "l"((uint64_t)map), "r"(src), "r"(c0), "r"(c1) : "memory");
}
__device__ __forceinline__ void tma_reduce_2d(const CUtensorMap* map, uint32_t src, int c0, int c1) {
  asm volatile("cp.reduce.async.bulk.tensor.2d.global.shared::cta.add.tile.bulk_group [%0, {%2, %3}], [%1];"
    :: "l"((uint64_t)map), "r"(src), "r"(c0), "r"(c1) : "memory");
}
__device__ __forceinline__ void bulk_wait_all() { asm volatile("cp.async.bulk.wait_group 0;" ::: "memory"); }
__device__ __forceinline__ void bulk_commit() { asm volatile("cp.async.bulk.commit_group;" ::: "memory"); }
__device__ __forceinline__ void bulk_wait_read() { asm volatile("cp.async.bulk.wait_group.read 0;" ::: "memory"); }
__device__ __forceinline__ void fence_async_smem() { asm volatile("fence.proxy.async.shared::cta;" ::: "memory"); }
__device__ __forceinline__ void fence_async_global() { asm volatile("fence.proxy.async.global;" ::: "memory"); }
__device__ __forceinline__ void wgmma_fence() { asm volatile("wgmma.fence.sync.aligned;" ::: "memory"); }
__device__ __forceinline__ void wgmma_commit() { asm volatile("wgmma.commit_group.sync.aligned;" ::: "memory"); }
template<int N> __device__ __forceinline__ void wgmma_wait() { asm volatile("wgmma.wait_group.sync.aligned %0;" :: "n"(N) : "memory"); }
template<int ID> __device__ __forceinline__ void bar_sync(int n) { asm volatile("bar.sync %0, %1;" :: "n"(ID), "r"(n) : "memory"); }
template<int ID> __device__ __forceinline__ void bar_arrive(int n) { asm volatile("bar.arrive %0, %1;" :: "n"(ID), "r"(n) : "memory"); }
__device__ __forceinline__ void cluster_wait() { asm volatile("barrier.cluster.wait.aligned;" ::: "memory"); }
__device__ __forceinline__ uint64_t desc64(uint32_t lo, uint32_t hi) { return (uint64_t)lo | ((uint64_t)hi << 32); }
__device__ __forceinline__ uint2 ld_tag2(const uint2* p) {
  uint2 v; asm volatile("ld.relaxed.gpu.global.v2.u32 {%0,%1}, [%2];" : "=r"(v.x), "=r"(v.y) : "l"(p) : "memory"); return v;
}
__device__ __forceinline__ void st_tag2(uint2* p, uint32_t a, uint32_t b) {
  asm volatile("st.relaxed.gpu.global.v2.u32 [%0], {%1,%2};" :: "l"(p), "r"(a), "r"(b) : "memory");
}
__device__ __forceinline__ void stg128(void* p, uint4 v) {
  asm volatile("st.global.v4.u32 [%0], {%1,%2,%3,%4};" :: "l"(p), "r"(v.x), "r"(v.y), "r"(v.z), "r"(v.w));
}
__device__ __forceinline__ unsigned ld_relaxed(const unsigned* p) {
  unsigned v; asm volatile("ld.relaxed.gpu.global.u32 %0, [%1];" : "=r"(v) : "l"(p) : "memory"); return v;
}
__device__ __forceinline__ uint32_t pack_bf16(float lo, float hi) {
  uint32_t r; asm("cvt.rn.bf16x2.f32 %0, %1, %2;" : "=r"(r) : "f"(hi), "f"(lo)); return r;
}
__device__ __forceinline__ float bf_lo(uint32_t v) { return __uint_as_float(v << 16); }
__device__ __forceinline__ float bf_hi(uint32_t v) { return __uint_as_float(v & 0xFFFF0000u); }
__device__ __forceinline__ void stsm4(uint32_t addr, uint32_t a, uint32_t b, uint32_t c, uint32_t d) {
  asm volatile("stmatrix.sync.aligned.m8n8.x4.shared.b16 [%0], {%1,%2,%3,%4};" :: "r"(addr), "r"(a), "r"(b), "r"(c), "r"(d));
}
__device__ __forceinline__ void stsm4_t(uint32_t addr, uint32_t a, uint32_t b, uint32_t c, uint32_t d) {
  asm volatile("stmatrix.sync.aligned.m8n8.x4.trans.shared.b16 [%0], {%1,%2,%3,%4};" :: "r"(addr), "r"(a), "r"(b), "r"(c), "r"(d));
}
__device__ __forceinline__ void ldsm4(uint32_t addr, uint32_t& a, uint32_t& b, uint32_t& c, uint32_t& d) {
  asm volatile("ldmatrix.sync.aligned.m8n8.x4.shared.b16 {%0,%1,%2,%3}, [%4];" : "=r"(a), "=r"(b), "=r"(c), "=r"(d) : "r"(addr));
}
__device__ __forceinline__ uint4 lds128(uint32_t a) {
  uint4 v; asm volatile("ld.shared.v4.u32 {%0,%1,%2,%3}, [%4];" : "=r"(v.x), "=r"(v.y), "=r"(v.z), "=r"(v.w) : "r"(a)); return v;
}
__device__ __forceinline__ void sts128(uint32_t a, uint32_t x, uint32_t y, uint32_t z, uint32_t w) {
  asm volatile("st.shared.v4.u32 [%0], {%1,%2,%3,%4};" :: "r"(a), "r"(x), "r"(y), "r"(z), "r"(w));
}
__device__ __forceinline__ uint32_t hmul2_bf16(uint32_t a, uint32_t b) {
  uint32_t r; asm("mul.rn.bf16x2 %0, %1, %2;" : "=r"(r) : "r"(a), "r"(b)); return r;
}
__device__ __forceinline__ uint32_t hadd2_bf16(uint32_t a, uint32_t b) {
  uint32_t r; asm("add.rn.bf16x2 %0, %1, %2;" : "=r"(r) : "r"(a), "r"(b)); return r;
}
__device__ __forceinline__ uint32_t hfma2_bf16(uint32_t a, uint32_t b, uint32_t c) {
  uint32_t r; asm("fma.rn.bf16x2 %0, %1, %2, %3;" : "=r"(r) : "r"(a), "r"(b), "r"(c)); return r;
}
__device__ __forceinline__ float gelu_tanh(float v) {
  float u = v * fmaf(0.0356774081f, v * v, 0.7978845608f);
  float t; asm("tanh.approx.f32 %0, %1;" : "=f"(t) : "f"(u));
  float hv = 0.5f * v;
  return fmaf(hv, t, hv);
}

template<int TB>
__device__ __forceinline__ void wgmma_n192(float (&d)[96], uint64_t da, uint64_t db, int scale_d) {
  asm volatile("{\n.reg .pred p;\nsetp.ne.b32 p, %98, 0;\n"
   "wgmma.mma_async.sync.aligned.m64n192k16.f32.bf16.bf16 {%0,%1,%2,%3,%4,%5,%6,%7,%8,%9,%10,%11,%12,%13,%14,%15,%16,%17,%18,%19,%20,%21,%22,%23,%24,%25,%26,%27,%28,%29,%30,%31,%32,%33,%34,%35,%36,%37,%38,%39,%40,%41,%42,%43,%44,%45,%46,%47,%48,%49,%50,%51,%52,%53,%54,%55,%56,%57,%58,%59,%60,%61,%62,%63,%64,%65,%66,%67,%68,%69,%70,%71,%72,%73,%74,%75,%76,%77,%78,%79,%80,%81,%82,%83,%84,%85,%86,%87,%88,%89,%90,%91,%92,%93,%94,%95}, %96, %97, p, 1, 1, 0, %99;\n}"
   : "+f"(d[0]),"+f"(d[1]),"+f"(d[2]),"+f"(d[3]),"+f"(d[4]),"+f"(d[5]),"+f"(d[6]),"+f"(d[7]),"+f"(d[8]),"+f"(d[9]),"+f"(d[10]),"+f"(d[11]),"+f"(d[12]),"+f"(d[13]),"+f"(d[14]),"+f"(d[15]),"+f"(d[16]),"+f"(d[17]),"+f"(d[18]),"+f"(d[19]),"+f"(d[20]),"+f"(d[21]),"+f"(d[22]),"+f"(d[23]),"+f"(d[24]),"+f"(d[25]),"+f"(d[26]),"+f"(d[27]),"+f"(d[28]),"+f"(d[29]),"+f"(d[30]),"+f"(d[31]),"+f"(d[32]),"+f"(d[33]),"+f"(d[34]),"+f"(d[35]),"+f"(d[36]),"+f"(d[37]),"+f"(d[38]),"+f"(d[39]),"+f"(d[40]),"+f"(d[41]),"+f"(d[42]),"+f"(d[43]),"+f"(d[44]),"+f"(d[45]),"+f"(d[46]),"+f"(d[47]),"+f"(d[48]),"+f"(d[49]),"+f"(d[50]),"+f"(d[51]),"+f"(d[52]),"+f"(d[53]),"+f"(d[54]),"+f"(d[55]),"+f"(d[56]),"+f"(d[57]),"+f"(d[58]),"+f"(d[59]),"+f"(d[60]),"+f"(d[61]),"+f"(d[62]),"+f"(d[63]),"+f"(d[64]),"+f"(d[65]),"+f"(d[66]),"+f"(d[67]),"+f"(d[68]),"+f"(d[69]),"+f"(d[70]),"+f"(d[71]),"+f"(d[72]),"+f"(d[73]),"+f"(d[74]),"+f"(d[75]),"+f"(d[76]),"+f"(d[77]),"+f"(d[78]),"+f"(d[79]),"+f"(d[80]),"+f"(d[81]),"+f"(d[82]),"+f"(d[83]),"+f"(d[84]),"+f"(d[85]),"+f"(d[86]),"+f"(d[87]),"+f"(d[88]),"+f"(d[89]),"+f"(d[90]),"+f"(d[91]),"+f"(d[92]),"+f"(d[93]),"+f"(d[94]),"+f"(d[95])
   : "l"(da), "l"(db), "r"(scale_d), "n"(TB));
}
template<int TB>
__device__ __forceinline__ void wgmma_n160(float (&d)[80], uint64_t da, uint64_t db, int scale_d) {
  asm volatile("{\n.reg .pred p;\nsetp.ne.b32 p, %82, 0;\n"
   "wgmma.mma_async.sync.aligned.m64n160k16.f32.bf16.bf16 {%0,%1,%2,%3,%4,%5,%6,%7,%8,%9,%10,%11,%12,%13,%14,%15,%16,%17,%18,%19,%20,%21,%22,%23,%24,%25,%26,%27,%28,%29,%30,%31,%32,%33,%34,%35,%36,%37,%38,%39,%40,%41,%42,%43,%44,%45,%46,%47,%48,%49,%50,%51,%52,%53,%54,%55,%56,%57,%58,%59,%60,%61,%62,%63,%64,%65,%66,%67,%68,%69,%70,%71,%72,%73,%74,%75,%76,%77,%78,%79}, %80, %81, p, 1, 1, 0, %83;\n}"
   : "+f"(d[0]),"+f"(d[1]),"+f"(d[2]),"+f"(d[3]),"+f"(d[4]),"+f"(d[5]),"+f"(d[6]),"+f"(d[7]),"+f"(d[8]),"+f"(d[9]),"+f"(d[10]),"+f"(d[11]),"+f"(d[12]),"+f"(d[13]),"+f"(d[14]),"+f"(d[15]),"+f"(d[16]),"+f"(d[17]),"+f"(d[18]),"+f"(d[19]),"+f"(d[20]),"+f"(d[21]),"+f"(d[22]),"+f"(d[23]),"+f"(d[24]),"+f"(d[25]),"+f"(d[26]),"+f"(d[27]),"+f"(d[28]),"+f"(d[29]),"+f"(d[30]),"+f"(d[31]),"+f"(d[32]),"+f"(d[33]),"+f"(d[34]),"+f"(d[35]),"+f"(d[36]),"+f"(d[37]),"+f"(d[38]),"+f"(d[39]),"+f"(d[40]),"+f"(d[41]),"+f"(d[42]),"+f"(d[43]),"+f"(d[44]),"+f"(d[45]),"+f"(d[46]),"+f"(d[47]),"+f"(d[48]),"+f"(d[49]),"+f"(d[50]),"+f"(d[51]),"+f"(d[52]),"+f"(d[53]),"+f"(d[54]),"+f"(d[55]),"+f"(d[56]),"+f"(d[57]),"+f"(d[58]),"+f"(d[59]),"+f"(d[60]),"+f"(d[61]),"+f"(d[62]),"+f"(d[63]),"+f"(d[64]),"+f"(d[65]),"+f"(d[66]),"+f"(d[67]),"+f"(d[68]),"+f"(d[69]),"+f"(d[70]),"+f"(d[71]),"+f"(d[72]),"+f"(d[73]),"+f"(d[74]),"+f"(d[75]),"+f"(d[76]),"+f"(d[77]),"+f"(d[78]),"+f"(d[79])
   : "l"(da), "l"(db), "r"(scale_d), "n"(TB));
}

template<int N, int TB>
__device__ __forceinline__ void wgmma_n(float (&d)[N / 2], uint64_t da, uint64_t db) {
  if constexpr (N == 192) wgmma_n192<TB>(d, da, db, 1); else wgmma_n160<TB>(d, da, db, 1);
}

template<int M, int R>
__device__ __forceinline__ void pin(float (&acc)[M][R]) {
  #pragma unroll
  for (int mi = 0; mi < M; mi++)
    #pragma unroll
    for (int i = 0; i < R; i++) asm volatile("" : "+f"(acc[mi][i]) :: "memory");
}
template<int M, int R>
__device__ __forceinline__ void zero(float (&acc)[M][R]) {
  #pragma unroll
  for (int mi = 0; mi < M; mi++)
    #pragma unroll
    for (int i = 0; i < R; i++) acc[mi][i] = 0.f;
  pin(acc);
}

template<int N, int M, int TB, bool CONT, int ORD_BAR, bool AOWN = false>
__device__ __forceinline__ void mainloop(float (&acc)[M][N / 2], uint32_t sbase, int grp, int g0, int nk, int m0 = 0) {
  const uint32_t full0 = sbase + BAR_OFF, empty0 = full0 + 8 * MAXST, ring = sbase + RING_OFF;
  const int nst = grp == 0 ? NST_A : NST_B, total = grp == 0 ? KB_A : KB_B;
  const uint32_t sstep = (grp == 0 ? STAGE_A : STAGE_B) >> 4;
  const int t = threadIdx.x & 127;
  const uint32_t da0 = (((ring + m0 * 8192) & 0x3FFFF) >> 4) | 0x10000u;
  const uint32_t db0 = (((ring + A_BYTES) & 0x3FFFF) >> 4) | ((TB == 2 ? 256u : TB ? 512u : 1u) << 16);
  constexpr uint32_t HI_A = 0x40000040u, HI_B = TB == 2 ? 0x80000020u : 0x40000040u;
  int s = g0 % nst, ph = (g0 / nst) & 1, ps = s == 0 ? nst - 1 : s - 1;
  #pragma unroll 1
  for (int g = g0; g < g0 + nk; g++) {
    const uint32_t so = s * sstep;
    mbar_wait(full0 + 8 * s, ph);
    wgmma_fence();
    #pragma unroll
    for (int k = 0; k < 4; k++) {
      const uint64_t db = desc64(db0 + so + (TB == 2 ? k * 64 : TB ? k * 128 : k * 2), HI_B);
      #pragma unroll
      for (int mi = 0; mi < M; mi++)
        wgmma_n<N, TB != 0>(acc[mi], desc64(AOWN ? da0 + ((NST_A * STAGE_A) >> 4) + (g - g0) * 512 + mi * 1536 + k * 2 : da0 + so + mi * 512 + k * 2, HI_A), db);
    }
    wgmma_commit();
    if (ORD_BAR != 0 && g == g0 + nk - 1) bar_arrive<ORD_BAR>(256);
    wgmma_wait<1>();
    if (t < 2 * M && (CONT || g > g0) && g - 1 + nst < total) mbar_arrive_cluster(empty0 + 8 * ps, t & 1);
    ps = s;
    if (++s == nst) { s = 0; ph ^= 1; }
  }
}
template<int M, int R>
__device__ __forceinline__ void drain(float (&acc)[M][R], uint32_t sbase, int grp, int glast) {
  wgmma_wait<0>();
  pin(acc);
  const int t = threadIdx.x & 127;
  const int nst = grp == 0 ? NST_A : NST_B, total = grp == 0 ? KB_A : KB_B;
  if (t < 2 * M && glast + nst < total) mbar_arrive_cluster(sbase + BAR_OFF + 8 * MAXST + 8 * (glast % nst), t & 1);
}

__device__ __forceinline__ void set_flag(int slot, int byte, unsigned epoch) {
  asm volatile("st.relaxed.gpu.global.u8 [%0], %1;" :: "l"(g_flags + slot * 256 + byte), "r"(epoch & 255u) : "memory");
}
__device__ __forceinline__ unsigned get_flag(int slot, int byte) {
  unsigned v; asm volatile("ld.relaxed.gpu.global.u8 %0, [%1];" : "=r"(v) : "l"(g_flags + slot * 256 + byte) : "memory"); return v;
}
__device__ __forceinline__ void publish(int slot, int byte, unsigned epoch) {
  asm volatile("fence.acq_rel.gpu;" ::: "memory");
  set_flag(slot, byte, epoch);
}
__device__ __forceinline__ float sum8(uint4 v) {
  return ((bf_lo(v.x) + bf_hi(v.x)) + (bf_lo(v.y) + bf_hi(v.y))) + ((bf_lo(v.z) + bf_hi(v.z)) + (bf_lo(v.w) + bf_hi(v.w)));
}
__device__ __forceinline__ uint4 ldg128(const void* p) {
  uint4 v; asm volatile("ld.global.nc.v4.u32 {%0,%1,%2,%3}, [%4];" : "=r"(v.x), "=r"(v.y), "=r"(v.z), "=r"(v.w) : "l"(p)); return v;
}

__device__ __forceinline__ void ln_rows(const uint4 (&rv)[5], uint32_t buf, int cta, unsigned epoch) {
  const int t = threadIdx.x - 128, row = cta * 16 + (t >> 4), c = t & 15;
  const float sh = __shfl_sync(0xffffffffu, bf_lo(rv[0].x), t & 16);
  float d[40], s = 0.f, q = 0.f;
  #pragma unroll
  for (int j = 0; j < 5; j++) {
    const uint32_t u[4] = {rv[j].x, rv[j].y, rv[j].z, rv[j].w};
    #pragma unroll
    for (int e = 0; e < 4; e++) {
      const float d0 = bf_lo(u[e]) - sh, d1 = bf_hi(u[e]) - sh;
      d[j * 8 + e * 2] = d0; d[j * 8 + e * 2 + 1] = d1;
      s += d0 + d1; q = fmaf(d0, d0, q); q = fmaf(d1, d1, q);
    }
  }
  #pragma unroll
  for (int o = 1; o < 16; o <<= 1) { s += __shfl_xor_sync(0xffffffffu, s, o); q += __shfl_xor_sync(0xffffffffu, q, o); }
  const float md = s * (1.f / DM);
  const float r = rsqrtf(fmaxf(fmaf(q, 1.f / DM, -md * md), 0.f) + LN_EPS), o = -md * r;
  if (c == 0) st_tag2(&g_xstat[row], __float_as_uint(r), (__float_as_uint(-(md + sh) * r) & ~255u) | (epoch & 255u));
  #pragma unroll
  for (int j = 0; j < 5; j++) {
    const float* a = &d[j * 8];
    sts128(buf + (t >> 4) * 1280 + (c + 16 * j) * 16,
           pack_bf16(fmaf(a[0], r, o), fmaf(a[1], r, o)), pack_bf16(fmaf(a[2], r, o), fmaf(a[3], r, o)),
           pack_bf16(fmaf(a[4], r, o), fmaf(a[5], r, o)), pack_bf16(fmaf(a[6], r, o), fmaf(a[7], r, o)));
  }
  fence_async_smem();
  bar_arrive<BAR_LN>(288);
}

__device__ __forceinline__ void weight_sums(const bf16* __restrict__ win, const bf16* __restrict__ wdre, int j, unsigned epoch) {
  const int t = threadIdx.x & 127, w = t >> 5, l = t & 31;
  const int cj = min(j, 59), cg = cj % 12, rg = cj / 12, wr = j * 10 + min(t >> 3, 9);
  uint4 cv[8], rv[10];
  #pragma unroll
  for (int i = 0; i < 8; i++) cv[i] = ldg128(reinterpret_cast<const uint4*>(win + (size_t)(rg * 128 + w * 32 + i * 4 + (l >> 3)) * FF + FH + cg * 64) + (l & 7));
  #pragma unroll
  for (int i = 0; i < 10; i++) rv[i] = ldg128(reinterpret_cast<const uint4*>(wdre + (size_t)wr * DM) + (l & 7) + 8 * i);
  float v[8];
  #pragma unroll
  for (int e = 0; e < 8; e++) v[e] = 0.f;
  #pragma unroll
  for (int i = 0; i < 8; i++) {
    v[0] += bf_lo(cv[i].x); v[1] += bf_hi(cv[i].x); v[2] += bf_lo(cv[i].y); v[3] += bf_hi(cv[i].y);
    v[4] += bf_lo(cv[i].z); v[5] += bf_hi(cv[i].z); v[6] += bf_lo(cv[i].w); v[7] += bf_hi(cv[i].w);
  }
  #pragma unroll
  for (int st = 0; st < 2; st++) {
    const int n = 4 >> st;
    const bool up = (l & (4 * n)) != 0;
    #pragma unroll
    for (int e = 0; e < 4; e++)
      if (e < n) { const float keep = up ? v[e + n] : v[e], send = up ? v[e] : v[e + n]; v[e] = keep + __shfl_xor_sync(0xffffffffu, send, 4 * n); }
  }
  float* red = reinterpret_cast<float*>(smem + RED_OFF);
  *reinterpret_cast<float2*>(red + w * 64 + (l & 7) * 8 + (l >> 3) * 2) = make_float2(v[0], v[1]);
  float s = 0.f;
  #pragma unroll
  for (int i = 0; i < 10; i++) s += sum8(rv[i]);
  #pragma unroll
  for (int o = 1; o < 8; o <<= 1) s += __shfl_xor_sync(0xffffffffu, s, o);
  if ((l & 7) == 0) st_tag2(&g_csum[5 * FH + wr], __float_as_uint(s), epoch);
  bar_sync<BAR_WG1>(128);
  if (t < 64) st_tag2(&g_csum[rg * FH + cg * 64 + t], __float_as_uint((red[t] + red[64 + t]) + (red[128 + t] + red[192 + t])), epoch);
}

__device__ __forceinline__ void gather96(const uint2* src, float* dst, unsigned epoch) {
  unsigned it = 0;
  while (true) {
    bool ok = true;
    uint2 u[15];
    #pragma unroll
    for (int j = 0; j < 15; j++) u[j] = ld_tag2(src + (j % 5) * FH + (j / 5) * 32);
    #pragma unroll
    for (int j = 0; j < 15; j++) ok = ok && u[j].y == epoch;
    #pragma unroll
    for (int j = 0; j < 3; j++)
      dst[j * 32] = ((__uint_as_float(u[j * 5].x) + __uint_as_float(u[j * 5 + 1].x)) + (__uint_as_float(u[j * 5 + 2].x) + __uint_as_float(u[j * 5 + 3].x))) + __uint_as_float(u[j * 5 + 4].x);
    if (ok || ++it > POLL_LIMIT) break;
    __nanosleep(2 * POLL_NS);
  }
}

__device__ __forceinline__ void a_entry(int g, int grp, int ct, int& mi, int& kb) {
  if (g < 10) { mi = M_X; kb = g; }
  else if (g < 20) { mi = M_XN; kb = g - 10; }
  else if (g < 52) { mi = grp == 0 ? M_WSP : M_WSRE; kb = g - 20; }
  else if (grp == 0) {
    if (g < 52 + NX) { mi = M_WSIM; kb = g - 52 + 32 - NX; }
    else {
      const int i = g - 52 - NX;
      mi = M_H; kb = i < 3 ? ct * 3 + i : i < 6 ? (ct ^ 1) * 3 + i - 3 : ((ct >> 1) ^ 1) * 6 + i - 6;
    }
  } else {
    if (g < 84 - NX) { mi = M_WSIM; kb = g - 52; }
    else { mi = M_H; kb = ((ct >> 1) ^ 1) * 6 + g - (84 - NX) + 6 - NO; }
  }
}

__global__ void __cluster_dims__(2, 1, 1) __launch_bounds__(384, 1)
fused_kernel(const __grid_constant__ Maps maps, const bf16* __restrict__ x, const bf16* __restrict__ win, const bf16* __restrict__ wdre,
             const bf16* __restrict__ bsp, bf16* __restrict__ out) {
  const uint32_t sbase = smem_u32(smem);
  const uint32_t full0 = sbase + BAR_OFF, empty0 = full0 + 8 * MAXST, dep0 = empty0 + 8 * MAXST, ring = sbase + RING_OFF;
  const int tid = threadIdx.x, wg = __shfl_sync(0xffffffffu, tid >> 7, 0);
  const int cta = blockIdx.x, rank = cta & 1, grp = (cta >> 1) & 1, rb = cta >> 3, ct = ((cta >> 2) & 1) * 2 + rank;
  const int total = grp == 0 ? KB_A : KB_B, gh = grp == 0 ? 52 + NX : 84 - NX;
  const uint32_t stage_bytes = grp == 0 ? STAGE_A : STAGE_B;
  const int nst = grp == 0 ? NST_A : NST_B;
  const uint32_t buf = ring + nst * stage_bytes;

  uint4 rv[5];
  if (wg != 0) {
    #pragma unroll
    for (int j = 0; j < 5; j++) rv[j] = ldg128(reinterpret_cast<const uint4*>(x + (size_t)(cta * 16 + ((tid - 128) >> 4)) * DM) + (tid & 15) + 16 * j);
  }
  const unsigned epoch = (ld_relaxed(&g_done) >> 7) + 1u;
  if (tid == 0) {
    TS(0, 0);
    for (int s = 0; s < MAXST; s++) { mbar_init(full0 + 8 * s, 2); mbar_init(empty0 + 8 * s, 4); mbar_init(dep0 + 8 * s, 1); }
    *reinterpret_cast<volatile int*>(smem + READY_OFF) = 0;
    asm volatile("fence.mbarrier_init.release.cluster;" ::: "memory");
  }
  __syncthreads();
  asm volatile("barrier.cluster.arrive.relaxed.aligned;" ::: "memory");

  if (wg == 0) {
    asm volatile("setmaxnreg.dec.sync.aligned.u32 40;");
    const int warp = tid >> 5, lane = tid & 31;
    if (warp == 0) {
      const int row = rb * 128;
      if (lane == 0) {
        for (int g = 0; g < nst; g++) {
          mbar_expect_tx(full0 + 8 * g, A_BYTES);
          tma_load_2d(ring + g * stage_bytes, &maps.m[M_X], full0 + 8 * g, g * 64, row);
          tma_load_2d(ring + g * stage_bytes + 8192, &maps.m[M_X], full0 + 8 * g, g * 64, row + 64);
        }
      }
      __syncwarp();
      cluster_wait();
      if (lane == 0) {
        int s = 0, ph = 0;
        #pragma unroll 1
        for (int g = nst; g < total; g++) {
          int mi, kb;
          a_entry(g, grp, ct, mi, kb);
          if (g == 10 || g == gh + 6 - 6 * grp || (grp == 0 && g == gh + 3)) {
            TS(0, g > 10 ? 3 : 1);
            mbar_wait(dep0 + (g == 10 ? 0 : g == gh + 6 - 6 * grp ? 24 : 8), 0);
            fence_async_global();
            TS(0, g > 10 ? 4 : 2);
          }
          mbar_wait(empty0 + 8 * s, ph);
          if (grp == 0 && g >= gh && g < gh + 6) {
            if (g < gh + 3) {
              mbar_arrive(full0 + 8 * s);
            } else {
              mbar_expect_tx(full0 + 8 * s, A_BYTES);
              tma_load_2d(ring + s * stage_bytes, &maps.m[mi], full0 + 8 * s, kb * 64, row);
              tma_load_2d(ring + s * stage_bytes + 8192, &maps.m[mi], full0 + 8 * s, kb * 64, row + 64);
            }
          } else {
            mbar_expect_tx(full0 + 8 * s, A_BYTES);
            tma_load_2d_mc(ring + s * stage_bytes + rank * 8192, &maps.m[mi], full0 + 8 * s, kb * 64, row + rank * 64, 3);
          }
          if (++s == nst) { s = 0; ph ^= 1; }
          if (g + PF_D < gh) {
            a_entry(g + PF_D, grp, ct, mi, kb);
            if (mi >= M_WSRE && (kb & 1) == (ct >> 1))
              asm volatile("cp.async.bulk.prefetch.tensor.2d.L2.global.tile [%0, {%1, %2}];" :: "l"((uint64_t)&maps.m[mi]), "r"(kb * 64), "r"(row + rank * 64) : "memory");
          }
        }
        TS(0, 5);
      }
    } else if (warp == 1) {
      if (lane == 0) {
        int s = 0, ph = 1;
        int have = 0;
        #pragma unroll 1
        for (int g = 0; g < total; g++) {
          int mi, kb, c;
          a_entry(g, grp, ct, mi, kb);
          const bool nmaj = g >= gh || (grp == 0 && g < 52);
          uint32_t bytes = 20480;
          if (g >= gh) { mi = M_WOUT; c = ct * 5; }
          else if (g >= 52) { mi = M_AB; c = DM + ct * 160; }
          else if (grp == 0) { mi = g < 20 ? M_WIN3 : M_Z23; c = 3 * ct + (g < 10 ? 12 : 0); bytes = 24576; }
          else { mi = g < 10 ? M_WDRE : g < 20 ? M_WDIM : M_AB; c = ct * 160; }
          if (g >= 20 && g < 52 && ((g - 20) >> 1) >= have) {
            if (g == 20) TS(1, 0);
            unsigned it = 0;
            while ((have = *reinterpret_cast<volatile int*>(smem + READY_OFF)) <= ((g - 20) >> 1) && ++it < 50 * POLL_LIMIT) {}
            fence_async_global();
            if (g == 20) { TS(1, 1); TC(1); }
          }
          if (g == 52) { TS(1, 2); mbar_wait(dep0 + 16, 0); fence_async_global(); TS(1, 3); TC(2); }
          const uint32_t dst = ring + s * stage_bytes + A_BYTES, fb = full0 + 8 * s;
          mbar_wait(empty0 + 8 * s, ph);
          if (++s == nst) { s = 0; ph ^= 1; }
          mbar_expect_tx(fb, bytes);
          if (nmaj) tma_load_3d(dst, &maps.m[mi], fb, 0, kb * 64, c);
          else tma_load_2d(dst, &maps.m[mi], fb, kb * 64, c);
        }
      }
      __syncwarp();
      cluster_wait();
    } else if (warp == 2) {
      if (lane < M_COUNT) asm volatile("prefetch.tensormap [%0];" :: "l"((uint64_t)&maps.m[lane]) : "memory");
      cluster_wait();
      {
        unsigned it = 0;
        uint2 v[4];
        while (true) {
          bool ok = true;
          #pragma unroll
          for (int i = 0; i < 4; i++) { v[i] = ld_tag2(&g_xstat[rb * 128 + i * 32 + lane]); ok = ok && ((v[i].y ^ epoch) & 255u) == 0; }
          if (ok || ++it > POLL_LIMIT) break;
          __nanosleep(POLL_NS);
        }
        #pragma unroll
        for (int i = 0; i < 4; i++) reinterpret_cast<uint2*>(smem + ROWSTAT_OFF)[i * 32 + lane] = make_uint2(v[i].x, v[i].y & ~255u);
        __syncwarp();
        TS(0, 6);
        if (grp == 0) bar_arrive<BAR_STATS>(320); else bar_arrive<BAR_STATS>(192);
      }
      #pragma unroll 1
      for (int i = 0; i < 5; i++) {
        const int d = i == 3 ? 4 : i == 4 ? 3 : i;
        const int slot = d == 0 ? F_XN + rb : d == 4 ? F_Y + rb * 4 + ct : d == 3 ? F_H + rb : d == 2 ? F_B + ct : grp == 0 ? F_Z + ct : F_A + ct;
        const int byte = d == 0 ? lane & 7 : d == 4 ? 0 : d == 3 ? lane & 3 : lane & 15;
        unsigned it = 0, m;
        while ((m = __ballot_sync(0xffffffffu, get_flag(slot, byte) != (epoch & 255u))) != 0 && ++it < POLL_LIMIT) {
          if (d == 1 && lane == 0) *reinterpret_cast<volatile int*>(smem + READY_OFF) = __ffs(m) - 1;
          __nanosleep(WATCH_NS);
        }
        if (d == 1 && lane == 0) *reinterpret_cast<volatile int*>(smem + READY_OFF) = 16;
        if (d < 4) TS(0, 8 + d * 2); else TS(0, 7);
        fence_async_global();
        __syncwarp();
        if (lane == 0 && d != 1) mbar_arrive(dep0 + 8 * d);
      }
    } else {
      cluster_wait();
      bar_sync<BAR_LN>(288);
      if (lane == 0) {
        TS(1, 5);
        asm volatile("cp.async.bulk.global.shared::cta.bulk_group [%0], [%1], 20480;" :: "l"(g_xn + (size_t)cta * 16 * DM), "r"(buf) : "memory");
        bulk_commit();
        bulk_wait_all();
        set_flag(F_XN + rb, cta & 7, epoch);
        TS(1, 6);
      }
      __syncwarp();
      if (grp == 0) {
        #pragma unroll 1
        for (int i = 0; i < 2; i++) gather96(&g_csum[ct * 192 + i * 96 + lane], reinterpret_cast<float*>(smem + COLSUM_OFF) + i * 96 + lane, epoch);
      } else {
        unsigned it = 0;
        while (true) {
          bool ok = true;
          #pragma unroll
          for (int j = 0; j < 5; j++) {
            const uint2 u = ld_tag2(&g_csum[5 * FH + ct * 160 + j * 32 + lane]);
            ok = ok && u.y == epoch;
            reinterpret_cast<uint32_t*>(smem + COLSUM_OFF)[j * 32 + lane] = u.x;
          }
          if (ok || ++it > POLL_LIMIT) break;
          __nanosleep(2 * POLL_NS);
        }
      }
      __syncwarp();
      TS(1, 4);
      if (grp == 0) {
        bar_arrive<BAR_STATS>(320);
        bar_sync<BAR_PUB1>(160);
        if (lane == 0) set_flag(F_Z + ct, rb, epoch);
        TS(1, 8);
        __syncwarp();
        bar_arrive<BAR_BUF>(160);
      } else {
        bar_arrive<BAR_STATS>(192);
        bar_sync<BAR_PUB2>(160);
        if (lane == 0) set_flag(F_A + ct, rb, epoch);
        TS(1, 9);
        __syncwarp();
      }
      bar_sync<BAR_PUB1>(160);
      if (lane == 0) {
        set_flag(grp == 0 ? F_H + rb : F_B + ct, grp == 0 ? ct : rb, epoch);
        if (grp == 0) mbar_arrive_cluster(dep0 + 8, rank ^ 1);
      }
      TS(1, 10);
      __syncwarp();
      bar_arrive<BAR_BUF>(160);
    }
  } else {
    asm volatile("setmaxnreg.inc.sync.aligned.u32 232;");
    const int t = tid & 127, w = t >> 5, l = t & 31;
    ln_rows(rv, buf, cta, epoch);
    TS(wg + 1, 0);
    cluster_wait();
    const uint32_t st_base = buf + (w * 16 + ((l >> 3) & 1) * 8 + (l & 7)) * 128;
    const uint32_t st_x = ((l >> 4) ^ (l & 7)) << 4;
    const float2* rs = reinterpret_cast<const float2*>(smem + ROWSTAT_OFF) + w * 16 + (l >> 2);
    const float2* cs = reinterpret_cast<const float2*>(smem + COLSUM_OFF) + (l & 3);
    if (grp == 0) {
      {
        const int mb = wg - 1;
        float acc[1][96];
        zero(acc);
        mainloop<192, 1, 1, false, 0>(acc, sbase, 0, 0, 10, mb);
        drain(acc, sbase, 0, 9);
        TS(wg + 1, 1);
        bar_sync<BAR_STATS>(320);
        const float2 s0 = rs[mb * 64], s1 = rs[mb * 64 + 8];
        const float nm[2] = {s0.y / s0.x, s1.y / s1.x}, hr[2] = {0.5f * s0.x, 0.5f * s1.x};
        const float k1[2] = {0.7978845608f * s0.x, 0.7978845608f * s1.x};
        const float k2[2] = {0.0356774081f * s0.x * s0.x * s0.x, 0.0356774081f * s1.x * s1.x * s1.x};
        float sm0 = 0.f, sm1 = 0.f, q0 = 0.f, q1 = 0.f;
        #pragma unroll
        for (int jj = 0; jj < 12; jj++) {
          float u[8];
          #pragma unroll
          for (int hf = 0; hf < 2; hf++) {
            const float2 c = cs[jj * 8 + hf * 4];
            #pragma unroll
            for (int e = 0; e < 4; e++) {
              const float wv = fmaf(nm[e >> 1], (e & 1) ? c.y : c.x, acc[0][8 * jj + 4 * hf + e]);
              float th; asm("tanh.approx.f32 %0, %1;" : "=f"(th) : "f"(wv * fmaf(k2[e >> 1], wv * wv, k1[e >> 1])));
              const float hv = hr[e >> 1] * wv;
              u[4 * hf + e] = fmaf(hv, th, hv);
            }
            sm0 += u[4 * hf] + u[4 * hf + 1]; q0 = fmaf(u[4 * hf], u[4 * hf], q0); q0 = fmaf(u[4 * hf + 1], u[4 * hf + 1], q0);
            sm1 += u[4 * hf + 2] + u[4 * hf + 3]; q1 = fmaf(u[4 * hf + 2], u[4 * hf + 2], q1); q1 = fmaf(u[4 * hf + 3], u[4 * hf + 3], q1);
          }
          stsm4(st_base + mb * 24576 + (jj >> 2) * 8192 + (st_x ^ ((jj & 3) << 5)),
                pack_bf16(u[0], u[1]), pack_bf16(u[2], u[3]), pack_bf16(u[4], u[5]), pack_bf16(u[6], u[7]));
        }
        #pragma unroll
        for (int o = 1; o < 4; o <<= 1) {
          sm0 += __shfl_xor_sync(0xffffffffu, sm0, o); q0 += __shfl_xor_sync(0xffffffffu, q0, o);
          sm1 += __shfl_xor_sync(0xffffffffu, sm1, o); q1 += __shfl_xor_sync(0xffffffffu, q1, o);
        }
        if ((l & 3) < 2) {
          const float sm = (l & 1) ? sm1 : sm0, sv = (l & 1) ? q1 : q0;
          const int row = mb * 64 + w * 16 + (l & 1) * 8 + (l >> 2);
          const float mu = sm * (1.f / 192), m2 = fmaxf(sv - sm * mu, 0.f);
          st_tag2(&g_zstat[(rb * 4 + ct) * 128 + row], __float_as_uint(mu), (__float_as_uint(m2) & ~255u) | (epoch & 255u));
          reinterpret_cast<float2*>(smem + ZSTAT_OFF)[row] = make_float2(mu, m2);
        }
        TS(wg + 1, 4);
      }
      float acc[2][96];
      if (wg == 1) {
        bar_sync<BAR_U>(256);
        uint2 v[3];
        unsigned n = 0;
        while (true) {
          bool ok = true;
          #pragma unroll
          for (int j = 0; j < 3; j++) { v[j] = ld_tag2(&g_zstat[(rb * 4 + ((ct + 1 + j) & 3)) * 128 + t]); ok = ok && ((v[j].y ^ epoch) & 255u) == 0; }
          if (ok || ++n > POLL_LIMIT) break;
          __nanosleep(POLL_NS);
        }
        const float2 own = reinterpret_cast<const float2*>(smem + ZSTAT_OFF)[t];
        const float m0 = __uint_as_float(v[0].x), m1 = __uint_as_float(v[1].x), m3 = __uint_as_float(v[2].x);
        const float mean = 0.25f * ((own.x + m0) + (m1 + m3));
        const float d = (own.x - mean) * (own.x - mean) + (m0 - mean) * (m0 - mean) + (m1 - mean) * (m1 - mean) + (m3 - mean) * (m3 - mean);
        const float var = fmaf(192.f, d, (own.y + __uint_as_float(v[0].y & ~255u)) + (__uint_as_float(v[1].y & ~255u) + __uint_as_float(v[2].y & ~255u)));
        const float r = rsqrtf(var * (1.f / FH) + LN_EPS);
        TS(2, 5);
        const uint32_t rbase = buf + (t >> 6) * 24576 + (t & 63) * 128;
        const uint32_t m2 = pack_bf16(-mean, -mean), r2 = pack_bf16(r, r);
        const float res = (-mean - bf_lo(m2)) * r;
        const uint32_t e2 = pack_bf16(res, res);
        #pragma unroll 1
        for (int c = 0; c < 3; c++) {
          uint4 z[8];
          #pragma unroll
          for (int i = 0; i < 8; i++) z[i] = lds128(rbase + c * 8192 + (((i ^ l) & 7) << 4));
          #pragma unroll
          for (int i = 0; i < 8; i++)
            sts128(rbase + c * 8192 + (((i ^ l) & 7) << 4), hfma2_bf16(hadd2_bf16(z[i].x, m2), r2, e2), hfma2_bf16(hadd2_bf16(z[i].y, m2), r2, e2),
                   hfma2_bf16(hadd2_bf16(z[i].z, m2), r2, e2), hfma2_bf16(hadd2_bf16(z[i].w, m2), r2, e2));
          fence_async_smem();
          __syncwarp();
          if (l == 0) {
            tma_store_2d(&maps.m[M_ZS], buf + (w >> 1) * 24576 + c * 8192 + (w & 1) * 4096, ct * 192 + c * 64, rb * 128 + w * 32);
            bulk_commit();
          }
        }
        TS(2, 6);
        if (l == 0) bulk_wait_all();
        __syncwarp();
        bar_arrive<BAR_PUB1>(160);
        {
          const bf16* bp = bsp + rb * 128 + w * 16 + (l >> 2);
          const float bb[4] = {__bfloat162float(bp[0]), __bfloat162float(bp[8]), __bfloat162float(bp[64]), __bfloat162float(bp[72])};
          #pragma unroll
          for (int i = 0; i < 96; i++) { acc[0][i] = bb[(i >> 1) & 1]; acc[1][i] = bb[2 + ((i >> 1) & 1)]; }
          pin(acc);
        }
        bar_sync<BAR_ORD2>(256);
        mainloop<192, 2, 1, false, BAR_ORD1>(acc, sbase, 0, 20, 32);
        bar_sync<BAR_Z1>(256);
        uint32_t z[6][4][4];
        #pragma unroll
        for (int i = 0; i < ZPRE; i++) ldsm4(st_base + (i >> 2) * 8192 + (st_x ^ ((i & 3) << 5)), z[i >> 2][i & 3][0], z[i >> 2][i & 3][1], z[i >> 2][i & 3][2], z[i >> 2][i & 3][3]);
        drain(acc, sbase, 0, 51);
        TS(2, 7);
        #pragma unroll
        for (int bx = 0; bx < 6; bx++) {
          if (bx >= 1) {
            #pragma unroll
            for (int i = ZPRE + (bx - 1) * 10; i < ZPRE + bx * 10; i++)
              if (i < 24) ldsm4(st_base + (i >> 2) * 8192 + (st_x ^ ((i & 3) << 5)), z[i >> 2][i & 3][0], z[i >> 2][i & 3][1], z[i >> 2][i & 3][2], z[i >> 2][i & 3][3]);
          }
          #pragma unroll
          for (int i = 0; i < 4; i++) {
            const float* a = &acc[bx / 3][8 * ((bx % 3) * 4 + i)];
            const uint32_t* zz = z[bx][i];
            stsm4(st_base + bx * 8192 + (st_x ^ (i << 5)),
                  hmul2_bf16(zz[0], pack_bf16(a[0], a[1])), hmul2_bf16(zz[1], pack_bf16(a[2], a[3])),
                  hmul2_bf16(zz[2], pack_bf16(a[4], a[5])), hmul2_bf16(zz[3], pack_bf16(a[6], a[7])));

          }
          if (bx % 3 == 2) {
            fence_async_smem();
            __syncwarp();
            if (l < 3) {
              tma_store_2d(&maps.m[M_HS], buf + (bx - 2 + l) * 8192 + w * 2048, ct * 192 + l * 64, rb * 128 + (bx / 3) * 64 + w * 16);
              bulk_commit();
            }
          }
        }
        bar_arrive<BAR_U>(256);
        TS(2, 8);
        if (l < 3) bulk_wait_all();
        __syncwarp();
        bar_arrive<BAR_PUB1>(160);
        TS(2, 9);
        return;
      }
      bar_arrive<BAR_U>(256);
      zero(acc);
      mainloop<192, 2, 1, false, BAR_ORD2>(acc, sbase, 0, 10, 10);
      drain(acc, sbase, 0, 19);
      TS(3, 2);
      bar_sync<BAR_BUF>(160);
      #pragma unroll
      for (int mi = 0; mi < 2; mi++)
        #pragma unroll
        for (int jj = 0; jj < 12; jj++) {
          const float* a = &acc[mi][8 * jj];
          stsm4(st_base + mi * 24576 + (jj >> 2) * 8192 + (st_x ^ ((jj & 3) << 5)),
                pack_bf16(a[0], a[1]), pack_bf16(a[2], a[3]), pack_bf16(a[4], a[5]), pack_bf16(a[6], a[7]));
        }
      __syncwarp();
      TS(3, 3);
      const uint32_t rbase = buf + (l >> 4) * 24576 + (w * 16 + (l & 15)) * 128;
      #pragma unroll 1
      for (int c2 = 0; c2 < 12; c2++) {
        const uint32_t ab = rbase + (c2 >> 2) * 8192;
        uint4 v[2];
        #pragma unroll
        for (int i = 0; i < 2; i++) v[i] = lds128(ab + (((((c2 & 3) * 2 + i) ^ l) & 7) << 4));
        #pragma unroll
        for (int i = 0; i < 2; i++)
          sts128(ab + (((((c2 & 3) * 2 + i) ^ l) & 7) << 4),
                 pack_bf16(gelu_tanh(bf_lo(v[i].x)), gelu_tanh(bf_hi(v[i].x))), pack_bf16(gelu_tanh(bf_lo(v[i].y)), gelu_tanh(bf_hi(v[i].y))),
                 pack_bf16(gelu_tanh(bf_lo(v[i].z)), gelu_tanh(bf_hi(v[i].z))), pack_bf16(gelu_tanh(bf_lo(v[i].w)), gelu_tanh(bf_hi(v[i].w))));
        __nanosleep(Z1_NS);
      }
      TS(3, 5);
      bar_arrive<BAR_Z1>(256);
    }
    float acc[2][80];
    if (grp == 1) {
      zero(acc);
      if (wg == 2) {
        mainloop<160, 2, 0, false, BAR_ORD2>(acc, sbase, 1, 0, 10);
      } else {
        weight_sums(win, wdre, rb * 4 + ct, epoch);
        TS(2, 1);
        bar_sync<BAR_ORD2>(256);
        mainloop<160, 2, 0, false, BAR_ORD1>(acc, sbase, 1, 10, 10);
      }
      drain(acc, sbase, 1, wg == 2 ? 9 : 19);
      TS(wg + 1, wg == 1 ? 7 : 2);
      if (wg == 1) bar_sync<BAR_Z1>(256); else bar_sync<BAR_STATS>(192);
      const uint32_t tb = buf + ((l >> 4) * 8 + (l & 7)) * 128 + (((w * 2 + ((l >> 3) & 1)) ^ (l & 7)) << 4);
      float2 st[4];
      #pragma unroll
      for (int r = 0; r < 4; r++) st[r] = wg == 2 ? rs[(r >> 1) * 64 + (r & 1) * 8] : make_float2(-1.f, 0.f);
      #pragma unroll
      for (int jj = 0; jj < 10; jj++) {
        const float2 c0 = cs[jj * 8], c1 = cs[jj * 8 + 4];
        #pragma unroll
        for (int mi = 0; mi < 2; mi++) {
          const float* a = &acc[mi][8 * jj];
          const float2 s0 = st[mi * 2], s1 = st[mi * 2 + 1];
          stsm4_t(tb + mi * 20480 + jj * 2048,
                  pack_bf16(fmaf(a[0], s0.x, s0.y * c0.x), fmaf(a[1], s0.x, s0.y * c0.y)), pack_bf16(fmaf(a[2], s1.x, s1.y * c0.x), fmaf(a[3], s1.x, s1.y * c0.y)),
                  pack_bf16(fmaf(a[4], s0.x, s0.y * c1.x), fmaf(a[5], s0.x, s0.y * c1.y)), pack_bf16(fmaf(a[6], s1.x, s1.y * c1.x), fmaf(a[7], s1.x, s1.y * c1.y)));
        }
      }
      fence_async_smem();
      if (wg == 1) bar_sync<BAR_WG1>(128); else bar_sync<BAR_WG2>(128);
      TS(wg + 1, wg == 1 ? 8 : 6);
      if (l < 2) {
        tma_store_2d(&maps.m[M_ABS], buf + l * 20480 + w * 5120, rb * 128 + l * 64, (2 - wg) * DM + ct * 160 + w * 40);
        bulk_commit();
        bulk_wait_all();
      }
      __syncwarp();
      TS(wg + 1, wg == 1 ? 9 : 10);
      if (wg == 1) {
        bar_arrive<BAR_PUB1>(160);
        #pragma unroll 1
        for (int i = 0; i < 4; i++) {
          uint4 v[5];
          #pragma unroll
          for (int j = 0; j < 5; j++) {
            const int e = (i * 5 + j) * 128 + t;
            v[j] = ldg128(x + (size_t)(rb * 128 + e / 20) * DM + ct * 160 + (e % 20) * 8);
          }
          #pragma unroll
          for (int j = 0; j < 5; j++) {
            const int e = (i * 5 + j) * 128 + t;
            stg128(out + (size_t)(rb * 128 + e / 20) * DM + ct * 160 + (e % 20) * 8, v[j]);
          }
        }
        bar_sync<BAR_WG1>(128);
        if (t == 0) publish(F_Y + rb * 4 + ct, 0, epoch);
        return;
      }
      bar_arrive<BAR_PUB2>(160);
      bar_arrive<BAR_Z1>(256);
    }
    zero(acc);
    bar_sync<BAR_ORD1>(256);
    mainloop<160, 2, 0, false, 0>(acc, sbase, grp, grp == 0 ? 52 : 20, grp == 0 ? NX : 64 - NX);
    if (grp == 0) {
      bar_sync<BAR_U>(256);
      mainloop<160, 2, 2, true, 0, true>(acc, sbase, 0, 52 + NX, 3);
    }
    mainloop<160, 2, 2, true, 0>(acc, sbase, grp, gh + 3 - 3 * grp, total - gh - 3 + 3 * grp);
    const uint32_t slab = buf + w * (16 * 320);
    const uint32_t addr = slab + (((l >> 3) & 1) * 8 + (l & 7)) * 320 + (l >> 4) * 16;
    bar_sync<BAR_BUF>(160);
    mbar_wait(dep0 + 32, 0);
    drain(acc, sbase, grp, total - 1);
    TS(3, 12);
    #pragma unroll
    for (int mi = 0; mi < 2; mi++) {
      #pragma unroll
      for (int jj = 0; jj < 10; jj++) {
        const float* a = &acc[mi][8 * jj];
        stsm4(addr + mi * 20480 + jj * 32, pack_bf16(a[0], a[1]), pack_bf16(a[2], a[3]), pack_bf16(a[4], a[5]), pack_bf16(a[6], a[7]));
      }
      fence_async_smem();
      __syncwarp();
      if (l == 0) {
        tma_reduce_2d(&maps.m[M_OUT], slab + mi * 20480, ct * 160, rb * 128 + mi * 64 + w * 16);
        bulk_commit();
      }
    }
    TS(3, 13);
    if (l == 0) {
      bulk_wait_read();
      if (w == 0) atomicAdd(&g_done, 1u);
    }
    TS(3, 15);
  }
}

typedef CUresult (*EncodeFn)(CUtensorMap*, CUtensorMapDataType, cuuint32_t, void*, const cuuint64_t*, const cuuint64_t*,
                             const cuuint32_t*, const cuuint32_t*, CUtensorMapInterleave, CUtensorMapSwizzle,
                             CUtensorMapL2promotion, CUtensorMapFloatOOBfill);

void make2d(EncodeFn enc, CUtensorMap* m, const void* p, uint64_t cols, uint64_t rows, uint32_t bc, uint32_t br, bool swz = true) {
  cuuint64_t gd[2] = {cols, rows}, gs[1] = {cols * 2};
  cuuint32_t bd[2] = {bc, br}, es[2] = {1, 1};
  enc(m, CU_TENSOR_MAP_DATA_TYPE_BFLOAT16, 2, const_cast<void*>(p), gd, gs, bd, es, CU_TENSOR_MAP_INTERLEAVE_NONE,
      swz ? CU_TENSOR_MAP_SWIZZLE_128B : CU_TENSOR_MAP_SWIZZLE_NONE, CU_TENSOR_MAP_L2_PROMOTION_L2_128B, CU_TENSOR_MAP_FLOAT_OOB_FILL_NONE);
}
void make3d(EncodeFn enc, CUtensorMap* m, const void* p, uint64_t cols, uint64_t rows, uint32_t cw, uint32_t nc, uint32_t br = 64) {
  cuuint64_t gd[3] = {cw, rows, cols / cw}, gs[2] = {cols * 2, cw * 2};
  cuuint32_t bd[3] = {cw, br, nc}, es[3] = {1, 1, 1};
  enc(m, CU_TENSOR_MAP_DATA_TYPE_BFLOAT16, 3, const_cast<void*>(p), gd, gs, bd, es, CU_TENSOR_MAP_INTERLEAVE_NONE,
      cw == 64 ? CU_TENSOR_MAP_SWIZZLE_128B : CU_TENSOR_MAP_SWIZZLE_64B, CU_TENSOR_MAP_L2_PROMOTION_L2_128B, CU_TENSOR_MAP_FLOAT_OOB_FILL_NONE);
}

}

extern "C" void kernel_launch(void* const* d_in, const int* in_sizes, int n_in, void* d_out, int out_size) {
  const bf16* x = (const bf16*)d_in[0];
  const bf16* wsre = (const bf16*)d_in[1];
  const bf16* wsim = (const bf16*)d_in[2];
  const bf16* wdre = (const bf16*)d_in[3];
  const bf16* wdim = (const bf16*)d_in[4];
  const bf16* win = (const bf16*)d_in[6];
  const bf16* wsp = (const bf16*)d_in[7];
  const bf16* bsp = (const bf16*)d_in[8];
  const bf16* wout = (const bf16*)d_in[9];

  void* fn = nullptr;
  cudaDriverEntryPointQueryResult qr;
  cudaGetDriverEntryPoint("cuTensorMapEncodeTiled", &fn, cudaEnableDefault, &qr);
  EncodeFn enc = (EncodeFn)fn;
  void *abT, *z2, *h, *xn;
  cudaGetSymbolAddress(&xn, g_xn);
  cudaGetSymbolAddress(&abT, g_abT);
  cudaGetSymbolAddress(&z2, g_z2);
  cudaGetSymbolAddress(&h, g_h);

  Maps maps;
  make2d(enc, &maps.m[M_X], x, DM, SEQ, 64, 64);
  make2d(enc, &maps.m[M_XN], xn, DM, SEQ, 64, 64);
  make2d(enc, &maps.m[M_WSRE], wsre, SEQ, SEQ, 64, 64);
  make2d(enc, &maps.m[M_WSIM], wsim, SEQ, SEQ, 64, 64);
  make2d(enc, &maps.m[M_WSP], wsp, SEQ, SEQ, 64, 64);
  make2d(enc, &maps.m[M_H], h, FH, SEQ, 64, 64);
  make3d(enc, &maps.m[M_WIN3], win, FF, DM, 64, 3);
  make3d(enc, &maps.m[M_Z23], z2, FH, SEQ, 64, 3);
  make2d(enc, &maps.m[M_WDRE], wdre, DM, DM, 64, 160);
  make2d(enc, &maps.m[M_WDIM], wdim, DM, DM, 64, 160);
  make2d(enc, &maps.m[M_AB], abT, SEQ, 2 * DM, 64, 160);
  make3d(enc, &maps.m[M_WOUT], wout, DM, FH, 32, 5);
  make2d(enc, &maps.m[M_HS], h, FH, SEQ, 64, 16);
  make2d(enc, &maps.m[M_ZS], z2, FH, SEQ, 64, 32);
  make2d(enc, &maps.m[M_ABS], abT, SEQ, 2 * DM, 64, 40);
  make2d(enc, &maps.m[M_OUT], d_out, DM, SEQ, 160, 16, false);

  cudaFuncSetAttribute(fused_kernel, cudaFuncAttributeMaxDynamicSharedMemorySize, SMEM_BYTES);
  fused_kernel<<<128, 384, SMEM_BYTES>>>(maps, x, win, wdre, bsp, (bf16*)d_out);
}
```

```cpp
#include <cuda_runtime.h>
#include <cuda_bf16.h>
#include <cuda.h>
#include <stdint.h>

namespace {

typedef __nv_bfloat16 bf16;

constexpr int SEQ = 2048, DM = 640, FF = 1536, FH = 768;
constexpr int NX = 6;
constexpr int NO = 3;
constexpr int NST_A = 4, NST_B = 5, MAXST = 5;
constexpr int A_BYTES = 16384;
constexpr int BAR_OFF = 0;
constexpr int READY_OFF = 128;
constexpr int COLSUM_OFF = 256;
constexpr int ROWSTAT_OFF = 1024;
constexpr int ZSTAT_OFF = 2048;
constexpr int RED_OFF = 3072;
constexpr int RING_OFF = 4096;
constexpr int STAGE_A = 40960, STAGE_B = 36864;
constexpr int SMEM_BYTES = RING_OFF + 5 * STAGE_B + 40960;
constexpr int KB_A = 52 + NX + 12 - NO;
constexpr int KB_B = 84 - NX + NO;
constexpr float LN_EPS = 1e-5f;
constexpr unsigned POLL_LIMIT = 100000;
constexpr unsigned POLL_NS = 100, WATCH_NS = 40;
constexpr unsigned Z1_NS = 600;
constexpr int PF_D = 8;
constexpr int ZPRE = 6;

constexpr int BAR_ORD1 = 1, BAR_ORD2 = 2, BAR_WG1 = 3, BAR_WG2 = 4, BAR_LN = 5, BAR_BUF = 6, BAR_Z1 = 7, BAR_PUB1 = 8, BAR_PUB2 = 9,
              BAR_STATS = 10, BAR_U = 11;

enum { M_X, M_XN, M_WSRE, M_WSIM, M_WSP, M_H, M_WIN3, M_Z23, M_WDRE, M_WDIM, M_AB, M_WOUT, M_OUT, M_HS, M_ZS, M_ABS, M_COUNT };
struct Maps { CUtensorMap m[M_COUNT]; };

__device__ __align__(1024) bf16 g_abT[2 * DM * SEQ];
__device__ __align__(1024) bf16 g_z2[SEQ * FH];
__device__ __align__(1024) bf16 g_h[SEQ * FH];
__device__ __align__(1024) bf16 g_xn[SEQ * DM];
__device__ __align__(16) uint2 g_xstat[SEQ];
__device__ __align__(16) uint2 g_csum[5 * FH + DM];
__device__ __align__(16) uint2 g_zstat[64 * 128];
__device__ __align__(256) unsigned char g_flags[108 * 256];
constexpr int F_A = 0, F_B = 4, F_Z = 8, F_H = 12, F_XN = 28, F_Y = 44;
__device__ unsigned g_done;
#define TS(role, ev)
#define TC(i)

extern __shared__ __align__(1024) uint8_t smem[];

__device__ __forceinline__ uint32_t smem_u32(const void* p) { return (uint32_t)__cvta_generic_to_shared(p); }
__device__ __forceinline__ void mbar_init(uint32_t bar, uint32_t cnt) { asm volatile("mbarrier.init.shared::cta.b64 [%0], %1;" :: "r"(bar), "r"(cnt)); }
__device__ __forceinline__ void mbar_expect_tx(uint32_t bar, uint32_t bytes) { asm volatile("mbarrier.arrive.expect_tx.shared::cta.b64 _, [%0], %1;" :: "r"(bar), "r"(bytes) : "memory"); }
__device__ __forceinline__ void mbar_arrive(uint32_t bar) { asm volatile("mbarrier.arrive.shared::cta.b64 _, [%0];" :: "r"(bar) : "memory"); }
__device__ __forceinline__ void mbar_arrive_cluster(uint32_t bar, uint32_t cta) {
  asm volatile("{\n.reg .b32 ra;\nmapa.shared::cluster.u32 ra, %0, %1;\nmbarrier.arrive.shared::cluster.b64 _, [ra];\n}" :: "r"(bar), "r"(cta) : "memory");
}
__device__ __forceinline__ void mbar_wait(uint32_t bar, uint32_t parity) {
  asm volatile("{\n.reg .pred p;\n.reg .u32 n;\nmov.u32 n, 0;\n"
               "LW: mbarrier.try_wait.parity.shared::cta.b64 p, [%0], %1, 2000;\n@p bra LD;\n"
               "add.u32 n, n, 1;\nsetp.lt.u32 p, n, 20000;\n@p bra LW;\nLD:\n}" :: "r"(bar), "r"(parity) : "memory");
}
__device__ __forceinline__ void tma_load_2d(uint32_t dst, const CUtensorMap* map, uint32_t bar, int c0, int c1) {
  asm volatile("cp.async.bulk.tensor.2d.shared::cluster.global.mbarrier::complete_tx::bytes [%0], [%1, {%3, %4}], [%2];"
    :: "r"(dst), "l"((uint64_t)map), "r"(bar), "r"(c0), "r"(c1) : "memory");
}
__device__ __forceinline__ void tma_load_3d(uint32_t dst, const CUtensorMap* map, uint32_t bar, int c0, int c1, int c2) {
  asm volatile("cp.async.bulk.tensor.3d.shared::cluster.global.mbarrier::complete_tx::bytes [%0], [%1, {%3, %4, %5}], [%2];"
    :: "r"(dst), "l"((uint64_t)map), "r"(bar), "r"(c0), "r"(c1), "r"(c2) : "memory");
}
__device__ __forceinline__ void tma_load_2d_mc(uint32_t dst, const CUtensorMap* map, uint32_t bar, int c0, int c1, uint16_t mask) {
  asm volatile("cp.async.bulk.tensor.2d.shared::cluster.global.mbarrier::complete_tx::bytes.multicast::cluster [%0], [%1, {%3, %4}], [%2], %5;"
    :: "r"(dst), "l"((uint64_t)map), "r"(bar), "r"(c0), "r"(c1), "h"(mask) : "memory");
}
__device__ __forceinline__ void tma_store_2d(const CUtensorMap* map, uint32_t src, int c0, int c1) {
  asm volatile("cp.async.bulk.tensor.2d.global.shared::cta.bulk_group [%0, {%2, %3}], [%1];"
    :: "l"((uint64_t)map), "r"(src), "r"(c0), "r"(c1) : "memory");
}
__device__ __forceinline__ void tma_reduce_2d(const CUtensorMap* map, uint32_t src, int c0, int c1) {
  asm volatile("cp.reduce.async.bulk.tensor.2d.global.shared::cta.add.tile.bulk_group [%0, {%2, %3}], [%1];"
    :: "l"((uint64_t)map), "r"(src), "r"(c0), "r"(c1) : "memory");
}
__device__ __forceinline__ void bulk_wait_all() { asm volatile("cp.async.bulk.wait_group 0;" ::: "memory"); }
__device__ __forceinline__ void bulk_commit() { asm volatile("cp.async.bulk.commit_group;" ::: "memory"); }
__device__ __forceinline__ void bulk_wait_read() { asm volatile("cp.async.bulk.wait_group.read 0;" ::: "memory"); }
__device__ __forceinline__ void fence_async_smem() { asm volatile("fence.proxy.async.shared::cta;" ::: "memory"); }
__device__ __forceinline__ void fence_async_global() { asm volatile("fence.proxy.async.global;" ::: "memory"); }
__device__ __forceinline__ void wgmma_fence() { asm volatile("wgmma.fence.sync.aligned;" ::: "memory"); }
__device__ __forceinline__ void wgmma_commit() { asm volatile("wgmma.commit_group.sync.aligned;" ::: "memory"); }
template<int N> __device__ __forceinline__ void wgmma_wait() { asm volatile("wgmma.wait_group.sync.aligned %0;" :: "n"(N) : "memory"); }
template<int ID> __device__ __forceinline__ void bar_sync(int n) { asm volatile("bar.sync %0, %1;" :: "n"(ID), "r"(n) : "memory"); }
template<int ID> __device__ __forceinline__ void bar_arrive(int n) { asm volatile("bar.arrive %0, %1;" :: "n"(ID), "r"(n) : "memory"); }
__device__ __forceinline__ void cluster_wait() { asm volatile("barrier.cluster.wait.aligned;" ::: "memory"); }
__device__ __forceinline__ uint64_t desc64(uint32_t lo, uint32_t hi) { return (uint64_t)lo | ((uint64_t)hi << 32); }
__device__ __forceinline__ uint2 ld_tag2(const uint2* p) {
  uint2 v; asm volatile("ld.relaxed.gpu.global.v2.u32 {%0,%1}, [%2];" : "=r"(v.x), "=r"(v.y) : "l"(p) : "memory"); return v;
}
__device__ __forceinline__ void st_tag2(uint2* p, uint32_t a, uint32_t b) {
  asm volatile("st.relaxed.gpu.global.v2.u32 [%0], {%1,%2};" :: "l"(p), "r"(a), "r"(b) : "memory");
}
__device__ __forceinline__ void stg128(void* p, uint4 v) {
  asm volatile("st.global.v4.u32 [%0], {%1,%2,%3,%4};" :: "l"(p), "r"(v.x), "r"(v.y), "r"(v.z), "r"(v.w));
}
__device__ __forceinline__ unsigned ld_relaxed(const unsigned* p) {
  unsigned v; asm volatile("ld.relaxed.gpu.global.u32 %0, [%1];" : "=r"(v) : "l"(p) : "memory"); return v;
}
__device__ __forceinline__ uint32_t pack_bf16(float lo, float hi) {
  uint32_t r; asm("cvt.rn.bf16x2.f32 %0, %1, %2;" : "=r"(r) : "f"(hi), "f"(lo)); return r;
}
__device__ __forceinline__ float bf_lo(uint32_t v) { return __uint_as_float(v << 16); }
__device__ __forceinline__ float bf_hi(uint32_t v) { return __uint_as_float(v & 0xFFFF0000u); }
__device__ __forceinline__ void stsm4(uint32_t addr, uint32_t a, uint32_t b, uint32_t c, uint32_t d) {
  asm volatile("stmatrix.sync.aligned.m8n8.x4.shared.b16 [%0], {%1,%2,%3,%4};" :: "r"(addr), "r"(a), "r"(b), "r"(c), "r"(d));
}
__device__ __forceinline__ void stsm4_t(uint32_t addr, uint32_t a, uint32_t b, uint32_t c, uint32_t d) {
  asm volatile("stmatrix.sync.aligned.m8n8.x4.trans.shared.b16 [%0], {%1,%2,%3,%4};" :: "r"(addr), "r"(a), "r"(b), "r"(c), "r"(d));
}
__device__ __forceinline__ void ldsm4(uint32_t addr, uint32_t& a, uint32_t& b, uint32_t& c, uint32_t& d) {
  asm volatile("ldmatrix.sync.aligned.m8n8.x4.shared.b16 {%0,%1,%2,%3}, [%4];" : "=r"(a), "=r"(b), "=r"(c), "=r"(d) : "r"(addr));
}
__device__ __forceinline__ uint4 lds128(uint32_t a) {
  uint4 v; asm volatile("ld.shared.v4.u32 {%0,%1,%2,%3}, [%4];" : "=r"(v.x), "=r"(v.y), "=r"(v.z), "=r"(v.w) : "r"(a)); return v;
}
__device__ __forceinline__ void sts128(uint32_t a, uint32_t x, uint32_t y, uint32_t z, uint32_t w) {
  asm volatile("st.shared.v4.u32 [%0], {%1,%2,%3,%4};" :: "r"(a), "r"(x), "r"(y), "r"(z), "r"(w));
}
__device__ __forceinline__ uint32_t hmul2_bf16(uint32_t a, uint32_t b) {
  uint32_t r; asm("mul.rn.bf16x2 %0, %1, %2;" : "=r"(r) : "r"(a), "r"(b)); return r;
}
__device__ __forceinline__ uint32_t hadd2_bf16(uint32_t a, uint32_t b) {
  uint32_t r; asm("add.rn.bf16x2 %0, %1, %2;" : "=r"(r) : "r"(a), "r"(b)); return r;
}
__device__ __forceinline__ uint32_t hfma2_bf16(uint32_t a, uint32_t b, uint32_t c) {
  uint32_t r; asm("fma.rn.bf16x2 %0, %1, %2, %3;" : "=r"(r) : "r"(a), "r"(b), "r"(c)); return r;
}
__device__ __forceinline__ float gelu_tanh(float v) {
  float u = v * fmaf(0.0356774081f, v * v, 0.7978845608f);
  float t; asm("tanh.approx.f32 %0, %1;" : "=f"(t) : "f"(u));
  float hv = 0.5f * v;
  return fmaf(hv, t, hv);
}

template<int TB>
__device__ __forceinline__ void wgmma_n192(float (&d)[96], uint64_t da, uint64_t db, int scale_d) {
  asm volatile("{\n.reg .pred p;\nsetp.ne.b32 p, %98, 0;\n"
   "wgmma.mma_async.sync.aligned.m64n192k16.f32.bf16.bf16 {%0,%1,%2,%3,%4,%5,%6,%7,%8,%9,%10,%11,%12,%13,%14,%15,%16,%17,%18,%19,%20,%21,%22,%23,%24,%25,%26,%27,%28,%29,%30,%31,%32,%33,%34,%35,%36,%37,%38,%39,%40,%41,%42,%43,%44,%45,%46,%47,%48,%49,%50,%51,%52,%53,%54,%55,%56,%57,%58,%59,%60,%61,%62,%63,%64,%65,%66,%67,%68,%69,%70,%71,%72,%73,%74,%75,%76,%77,%78,%79,%80,%81,%82,%83,%84,%85,%86,%87,%88,%89,%90,%91,%92,%93,%94,%95}, %96, %97, p, 1, 1, 0, %99;\n}"
   : "+f"(d[0]),"+f"(d[1]),"+f"(d[2]),"+f"(d[3]),"+f"(d[4]),"+f"(d[5]),"+f"(d[6]),"+f"(d[7]),"+f"(d[8]),"+f"(d[9]),"+f"(d[10]),"+f"(d[11]),"+f"(d[12]),"+f"(d[13]),"+f"(d[14]),"+f"(d[15]),"+f"(d[16]),"+f"(d[17]),"+f"(d[18]),"+f"(d[19]),"+f"(d[20]),"+f"(d[21]),"+f"(d[22]),"+f"(d[23]),"+f"(d[24]),"+f"(d[25]),"+f"(d[26]),"+f"(d[27]),"+f"(d[28]),"+f"(d[29]),"+f"(d[30]),"+f"(d[31]),"+f"(d[32]),"+f"(d[33]),"+f"(d[34]),"+f"(d[35]),"+f"(d[36]),"+f"(d[37]),"+f"(d[38]),"+f"(d[39]),"+f"(d[40]),"+f"(d[41]),"+f"(d[42]),"+f"(d[43]),"+f"(d[44]),"+f"(d[45]),"+f"(d[46]),"+f"(d[47]),"+f"(d[48]),"+f"(d[49]),"+f"(d[50]),"+f"(d[51]),"+f"(d[52]),"+f"(d[53]),"+f"(d[54]),"+f"(d[55]),"+f"(d[56]),"+f"(d[57]),"+f"(d[58]),"+f"(d[59]),"+f"(d[60]),"+f"(d[61]),"+f"(d[62]),"+f"(d[63]),"+f"(d[64]),"+f"(d[65]),"+f"(d[66]),"+f"(d[67]),"+f"(d[68]),"+f"(d[69]),"+f"(d[70]),"+f"(d[71]),"+f"(d[72]),"+f"(d[73]),"+f"(d[74]),"+f"(d[75]),"+f"(d[76]),"+f"(d[77]),"+f"(d[78]),"+f"(d[79]),"+f"(d[80]),"+f"(d[81]),"+f"(d[82]),"+f"(d[83]),"+f"(d[84]),"+f"(d[85]),"+f"(d[86]),"+f"(d[87]),"+f"(d[88]),"+f"(d[89]),"+f"(d[90]),"+f"(d[91]),"+f"(d[92]),"+f"(d[93]),"+f"(d[94]),"+f"(d[95])
   : "l"(da), "l"(db), "r"(scale_d), "n"(TB));
}
template<int TB>
__device__ __forceinline__ void wgmma_n160(float (&d)[80], uint64_t da, uint64_t db, int scale_d) {
  asm volatile("{\n.reg .pred p;\nsetp.ne.b32 p, %82, 0;\n"
   "wgmma.mma_async.sync.aligned.m64n160k16.f32.bf16.bf16 {%0,%1,%2,%3,%4,%5,%6,%7,%8,%9,%10,%11,%12,%13,%14,%15,%16,%17,%18,%19,%20,%21,%22,%23,%24,%25,%26,%27,%28,%29,%30,%31,%32,%33,%34,%35,%36,%37,%38,%39,%40,%41,%42,%43,%44,%45,%46,%47,%48,%49,%50,%51,%52,%53,%54,%55,%56,%57,%58,%59,%60,%61,%62,%63,%64,%65,%66,%67,%68,%69,%70,%71,%72,%73,%74,%75,%76,%77,%78,%79}, %80, %81, p, 1, 1, 0, %83;\n}"
   : "+f"(d[0]),"+f"(d[1]),"+f"(d[2]),"+f"(d[3]),"+f"(d[4]),"+f"(d[5]),"+f"(d[6]),"+f"(d[7]),"+f"(d[8]),"+f"(d[9]),"+f"(d[10]),"+f"(d[11]),"+f"(d[12]),"+f"(d[13]),"+f"(d[14]),"+f"(d[15]),"+f"(d[16]),"+f"(d[17]),"+f"(d[18]),"+f"(d[19]),"+f"(d[20]),"+f"(d[21]),"+f"(d[22]),"+f"(d[23]),"+f"(d[24]),"+f"(d[25]),"+f"(d[26]),"+f"(d[27]),"+f"(d[28]),"+f"(d[29]),"+f"(d[30]),"+f"(d[31]),"+f"(d[32]),"+f"(d[33]),"+f"(d[34]),"+f"(d[35]),"+f"(d[36]),"+f"(d[37]),"+f"(d[38]),"+f"(d[39]),"+f"(d[40]),"+f"(d[41]),"+f"(d[42]),"+f"(d[43]),"+f"(d[44]),"+f"(d[45]),"+f"(d[46]),"+f"(d[47]),"+f"(d[48]),"+f"(d[49]),"+f"(d[50]),"+f"(d[51]),"+f"(d[52]),"+f"(d[53]),"+f"(d[54]),"+f"(d[55]),"+f"(d[56]),"+f"(d[57]),"+f"(d[58]),"+f"(d[59]),"+f"(d[60]),"+f"(d[61]),"+f"(d[62]),"+f"(d[63]),"+f"(d[64]),"+f"(d[65]),"+f"(d[66]),"+f"(d[67]),"+f"(d[68]),"+f"(d[69]),"+f"(d[70]),"+f"(d[71]),"+f"(d[72]),"+f"(d[73]),"+f"(d[74]),"+f"(d[75]),"+f"(d[76]),"+f"(d[77]),"+f"(d[78]),"+f"(d[79])
   : "l"(da), "l"(db), "r"(scale_d), "n"(TB));
}

template<int N, int TB>
__device__ __forceinline__ void wgmma_n(float (&d)[N / 2], uint64_t da, uint64_t db) {
  if constexpr (N == 192) wgmma_n192<TB>(d, da, db, 1); else wgmma_n160<TB>(d, da, db, 1);
}

template<int M, int R>
__device__ __forceinline__ void pin(float (&acc)[M][R]) {
  #pragma unroll
  for (int mi = 0; mi < M; mi++)
    #pragma unroll
    for (int i = 0; i < R; i++) asm volatile("" : "+f"(acc[mi][i]) :: "memory");
}
template<int M, int R>
__device__ __forceinline__ void zero(float (&acc)[M][R]) {
  #pragma unroll
  for (int mi = 0; mi < M; mi++)
    #pragma unroll
    for (int i = 0; i < R; i++) acc[mi][i] = 0.f;
  pin(acc);
}

template<int N, int M, int TB, bool CONT, int ORD_BAR, bool AOWN = false>
__device__ __forceinline__ void mainloop(float (&acc)[M][N / 2], uint32_t sbase, int grp, int g0, int nk, int m0 = 0) {
  const uint32_t full0 = sbase + BAR_OFF, empty0 = full0 + 8 * MAXST, ring = sbase + RING_OFF;
  const int nst = grp == 0 ? NST_A : NST_B, total = grp == 0 ? KB_A : KB_B;
  const uint32_t sstep = (grp == 0 ? STAGE_A : STAGE_B) >> 4;
  const int t = threadIdx.x & 127;
  const uint32_t da0 = (((ring + m0 * 8192) & 0x3FFFF) >> 4) | 0x10000u;
  const uint32_t db0 = (((ring + A_BYTES) & 0x3FFFF) >> 4) | ((TB == 2 ? 256u : TB ? 512u : 1u) << 16);
  constexpr uint32_t HI_A = 0x40000040u, HI_B = TB == 2 ? 0x80000020u : 0x40000040u;
  int s = g0 % nst, ph = (g0 / nst) & 1, ps = s == 0 ? nst - 1 : s - 1;
  #pragma unroll 1
  for (int g = g0; g < g0 + nk; g++) {
    const uint32_t so = s * sstep;
    mbar_wait(full0 + 8 * s, ph);
    wgmma_fence();
    #pragma unroll
    for (int k = 0; k < 4; k++) {
      const uint64_t db = desc64(db0 + so + (TB == 2 ? k * 64 : TB ? k * 128 : k * 2), HI_B);
      #pragma unroll
      for (int mi = 0; mi < M; mi++)
        wgmma_n<N, TB != 0>(acc[mi], desc64(AOWN ? da0 + ((NST_A * STAGE_A) >> 4) + (g - g0) * 512 + mi * 1536 + k * 2 : da0 + so + mi * 512 + k * 2, HI_A), db);
    }
    wgmma_commit();
    if (ORD_BAR != 0 && g == g0 + nk - 1) bar_arrive<ORD_BAR>(256);
    wgmma_wait<1>();
    if (t < 2 * M && (CONT || g > g0) && g - 1 + nst < total) mbar_arrive_cluster(empty0 + 8 * ps, t & 1);
    ps = s;
    if (++s == nst) { s = 0; ph ^= 1; }
  }
}
template<int M, int R>
__device__ __forceinline__ void drain(float (&acc)[M][R], uint32_t sbase, int grp, int glast) {
  wgmma_wait<0>();
  pin(acc);
  const int t = threadIdx.x & 127;
  const int nst = grp == 0 ? NST_A : NST_B, total = grp == 0 ? KB_A : KB_B;
  if (t < 2 * M && glast + nst < total) mbar_arrive_cluster(sbase + BAR_OFF + 8 * MAXST + 8 * (glast % nst), t & 1);
}

__device__ __forceinline__ void set_flag(int slot, int byte, unsigned epoch) {
  asm volatile("st.relaxed.gpu.global.u8 [%0], %1;" :: "l"(g_flags + slot * 256 + byte), "r"(epoch & 255u) : "memory");
}
__device__ __forceinline__ unsigned get_flag(int slot, int byte) {
  unsigned v; asm volatile("ld.relaxed.gpu.global.u8 %0, [%1];" : "=r"(v) : "l"(g_flags + slot * 256 + byte) : "memory"); return v;
}
__device__ __forceinline__ void publish(int slot, int byte, unsigned epoch) {
  asm volatile("fence.acq_rel.gpu;" ::: "memory");
  set_flag(slot, byte, epoch);
}
__device__ __forceinline__ float sum8(uint4 v) {
  return ((bf_lo(v.x) + bf_hi(v.x)) + (bf_lo(v.y) + bf_hi(v.y))) + ((bf_lo(v.z) + bf_hi(v.z)) + (bf_lo(v.w) + bf_hi(v.w)));
}
__device__ __forceinline__ uint4 ldg128(const void* p) {
  uint4 v; asm volatile("ld.global.nc.v4.u32 {%0,%1,%2,%3}, [%4];" : "=r"(v.x), "=r"(v.y), "=r"(v.z), "=r"(v.w) : "l"(p)); return v;
}

__device__ __forceinline__ void ln_rows(const uint4 (&rv)[5], uint32_t buf, int cta, unsigned epoch) {
  const int t = threadIdx.x - 128, row = cta * 16 + (t >> 4), c = t & 15;
  const float sh = __shfl_sync(0xffffffffu, bf_lo(rv[0].x), t & 16);
  float d[40], s = 0.f, q = 0.f;
  #pragma unroll
  for (int j = 0; j < 5; j++) {
    const uint32_t u[4] = {rv[j].x, rv[j].y, rv[j].z, rv[j].w};
    #pragma unroll
    for (int e = 0; e < 4; e++) {
      const float d0 = bf_lo(u[e]) - sh, d1 = bf_hi(u[e]) - sh;
      d[j * 8 + e * 2] = d0; d[j * 8 + e * 2 + 1] = d1;
      s += d0 + d1; q = fmaf(d0, d0, q); q = fmaf(d1, d1, q);
    }
  }
  #pragma unroll
  for (int o = 1; o < 16; o <<= 1) { s += __shfl_xor_sync(0xffffffffu, s, o); q += __shfl_xor_sync(0xffffffffu, q, o); }
  const float md = s * (1.f / DM);
  const float r = rsqrtf(fmaxf(fmaf(q, 1.f / DM, -md * md), 0.f) + LN_EPS), o = -md * r;
  if (c == 0) st_tag2(&g_xstat[row], __float_as_uint(r), (__float_as_uint(-(md + sh) * r) & ~255u) | (epoch & 255u));
  #pragma unroll
  for (int j = 0; j < 5; j++) {
    const float* a = &d[j * 8];
    sts128(buf + (t >> 4) * 1280 + (c + 16 * j) * 16,
           pack_bf16(fmaf(a[0], r, o), fmaf(a[1], r, o)), pack_bf16(fmaf(a[2], r, o), fmaf(a[3], r, o)),
           pack_bf16(fmaf(a[4], r, o), fmaf(a[5], r, o)), pack_bf16(fmaf(a[6], r, o), fmaf(a[7], r, o)));
  }
  fence_async_smem();
  bar_arrive<BAR_LN>(288);
}

__device__ __forceinline__ void weight_sums(const bf16* __restrict__ win, const bf16* __restrict__ wdre, int j, unsigned epoch) {
  const int t = threadIdx.x & 127, w = t >> 5, l = t & 31;
  const int cj = min(j, 59), cg = cj % 12, rg = cj / 12, wr = j * 10 + min(t >> 3, 9);
  uint4 cv[8], rv[10];
  #pragma unroll
  for (int i = 0; i < 8; i++) cv[i] = ldg128(reinterpret_cast<const uint4*>(win + (size_t)(rg * 128 + w * 32 + i * 4 + (l >> 3)) * FF + FH + cg * 64) + (l & 7));
  #pragma unroll
  for (int i = 0; i < 10; i++) rv[i] = ldg128(reinterpret_cast<const uint4*>(wdre + (size_t)wr * DM) + (l & 7) + 8 * i);
  float v[8];
  #pragma unroll
  for (int e = 0; e < 8; e++) v[e] = 0.f;
  #pragma unroll
  for (int i = 0; i < 8; i++) {
    v[0] += bf_lo(cv[i].x); v[1] += bf_hi(cv[i].x); v[2] += bf_lo(cv[i].y); v[3] += bf_hi(cv[i].y);
    v[4] += bf_lo(cv[i].z); v[5] += bf_hi(cv[i].z); v[6] += bf_lo(cv[i].w); v[7] += bf_hi(cv[i].w);
  }
  #pragma unroll
  for (int st = 0; st < 2; st++) {
    const int n = 4 >> st;
    const bool up = (l & (4 * n)) != 0;
    #pragma unroll
    for (int e = 0; e < 4; e++)
      if (e < n) { const float keep = up ? v[e + n] : v[e], send = up ? v[e] : v[e + n]; v[e] = keep + __shfl_xor_sync(0xffffffffu, send, 4 * n); }
  }
  float* red = reinterpret_cast<float*>(smem + RED_OFF);
  *reinterpret_cast<float2*>(red + w * 64 + (l & 7) * 8 + (l >> 3) * 2) = make_float2(v[0], v[1]);
  float s = 0.f;
  #pragma unroll
  for (int i = 0; i < 10; i++) s += sum8(rv[i]);
  #pragma unroll
  for (int o = 1; o < 8; o <<= 1) s += __shfl_xor_sync(0xffffffffu, s, o);
  if ((l & 7) == 0) st_tag2(&g_csum[5 * FH + wr], __float_as_uint(s), epoch);
  bar_sync<BAR_WG1>(128);
  if (t < 64) st_tag2(&g_csum[rg * FH + cg * 64 + t], __float_as_uint((red[t] + red[64 + t]) + (red[128 + t] + red[192 + t])), epoch);
}

__device__ __forceinline__ void gather96(const uint2* src, float* dst, unsigned epoch) {
  unsigned it = 0;
  while (true) {
    bool ok = true;
    uint2 u[15];
    #pragma unroll
    for (int j = 0; j < 15; j++) u[j] = ld_tag2(src + (j % 5) * FH + (j / 5) * 32);
    #pragma unroll
    for (int j = 0; j < 15; j++) ok = ok && u[j].y == epoch;
    #pragma unroll
    for (int j = 0; j < 3; j++)
      dst[j * 32] = ((__uint_as_float(u[j * 5].x) + __uint_as_float(u[j * 5 + 1].x)) + (__uint_as_float(u[j * 5 + 2].x) + __uint_as_float(u[j * 5 + 3].x))) + __uint_as_float(u[j * 5 + 4].x);
    if (ok || ++it > POLL_LIMIT) break;
    __nanosleep(2 * POLL_NS);
  }
}

__device__ __forceinline__ void a_entry(int g, int grp, int ct, int& mi, int& kb) {
  if (g < 10) { mi = M_X; kb = g; }
  else if (g < 20) { mi = M_XN; kb = g - 10; }
  else if (g < 52) { mi = grp == 0 ? M_WSP : M_WSRE; kb = g - 20; }
  else if (grp == 0) {
    if (g < 52 + NX) { mi = M_WSIM; kb = g - 52 + 32 - NX; }
    else {
      const int i = g - 52 - NX;
      mi = M_H; kb = i < 3 ? ct * 3 + i : i < 6 ? (ct ^ 1) * 3 + i - 3 : ((ct >> 1) ^ 1) * 6 + i - 6;
    }
  } else {
    if (g < 84 - NX) { mi = M_WSIM; kb = g - 52; }
    else { mi = M_H; kb = ((ct >> 1) ^ 1) * 6 + g - (84 - NX) + 6 - NO; }
  }
}

__global__ void __cluster_dims__(2, 1, 1) __launch_bounds__(384, 1)
fused_kernel(const __grid_constant__ Maps maps, const bf16* __restrict__ x, const bf16* __restrict__ win, const bf16* __restrict__ wdre,
             const bf16* __restrict__ bsp, const bf16* __restrict__ wout, bf16* __restrict__ out) {
  const uint32_t sbase = smem_u32(smem);
  const uint32_t full0 = sbase + BAR_OFF, empty0 = full0 + 8 * MAXST, dep0 = empty0 + 8 * MAXST, ring = sbase + RING_OFF;
  const int tid = threadIdx.x, wg = __shfl_sync(0xffffffffu, tid >> 7, 0);
  const int cta = blockIdx.x, rank = cta & 1, grp = (cta >> 1) & 1, rb = cta >> 3, ct = ((cta >> 2) & 1) * 2 + rank;
  const int total = grp == 0 ? KB_A : KB_B, gh = grp == 0 ? 52 + NX : 84 - NX;
  const uint32_t stage_bytes = grp == 0 ? STAGE_A : STAGE_B;
  const int nst = grp == 0 ? NST_A : NST_B;
  const uint32_t buf = ring + nst * stage_bytes;

  uint4 rv[5];
  if (wg != 0) {
    #pragma unroll
    for (int j = 0; j < 5; j++) rv[j] = ldg128(reinterpret_cast<const uint4*>(x + (size_t)(cta * 16 + ((tid - 128) >> 4)) * DM) + (tid & 15) + 16 * j);
  }
  const unsigned epoch = (ld_relaxed(&g_done) >> 7) + 1u;
  if (tid == 0) {
    TS(0, 0);
    for (int s = 0; s < MAXST; s++) { mbar_init(full0 + 8 * s, 2); mbar_init(empty0 + 8 * s, 4); mbar_init(dep0 + 8 * s, 1); }
    *reinterpret_cast<volatile int*>(smem + READY_OFF) = 0;
    asm volatile("fence.mbarrier_init.release.cluster;" ::: "memory");
  }
  __syncthreads();
  asm volatile("barrier.cluster.arrive.relaxed.aligned;" ::: "memory");

  if (wg == 0) {
    asm volatile("setmaxnreg.dec.sync.aligned.u32 40;");
    const int warp = tid >> 5, lane = tid & 31;
    if (warp == 0) {
      const int row = rb * 128;
      if (lane == 0) {
        for (int g = 0; g < nst; g++) {
          mbar_expect_tx(full0 + 8 * g, A_BYTES);
          tma_load_2d(ring + g * stage_bytes, &maps.m[M_X], full0 + 8 * g, g * 64, row);
          tma_load_2d(ring + g * stage_bytes + 8192, &maps.m[M_X], full0 + 8 * g, g * 64, row + 64);
        }
      }
      __syncwarp();
      cluster_wait();
      if (lane == 0) {
        int s = 0, ph = 0;
        #pragma unroll 1
        for (int g = nst; g < total; g++) {
          int mi, kb;
          a_entry(g, grp, ct, mi, kb);
          if (g == 10 || g == gh + 6 - 6 * grp || (grp == 0 && g == gh + 3)) {
            TS(0, g > 10 ? 3 : 1);
            mbar_wait(dep0 + (g == 10 ? 0 : g == gh + 6 - 6 * grp ? 24 : 8), 0);
            fence_async_global();
            TS(0, g > 10 ? 4 : 2);
          }
          mbar_wait(empty0 + 8 * s, ph);
          if (grp == 0 && g >= gh && g < gh + 6) {
            if (g < gh + 3) {
              mbar_arrive(full0 + 8 * s);
            } else {
              mbar_expect_tx(full0 + 8 * s, A_BYTES);
              tma_load_2d(ring + s * stage_bytes, &maps.m[mi], full0 + 8 * s, kb * 64, row);
              tma_load_2d(ring + s * stage_bytes + 8192, &maps.m[mi], full0 + 8 * s, kb * 64, row + 64);
            }
          } else {
            mbar_expect_tx(full0 + 8 * s, A_BYTES);
            tma_load_2d_mc(ring + s * stage_bytes + rank * 8192, &maps.m[mi], full0 + 8 * s, kb * 64, row + rank * 64, 3);
          }
          if (++s == nst) { s = 0; ph ^= 1; }
          if (g + PF_D < gh) {
            a_entry(g + PF_D, grp, ct, mi, kb);
            if (mi >= M_WSRE && (kb & 1) == (ct >> 1))
              asm volatile("cp.async.bulk.prefetch.tensor.2d.L2.global.tile [%0, {%1, %2}];" :: "l"((uint64_t)&maps.m[mi]), "r"(kb * 64), "r"(row + rank * 64) : "memory");
          }
        }
        TS(0, 5);
      }
    } else if (warp == 1) {
      if (lane == 0) {
        int s = 0, ph = 1;
        int have = 0;
        #pragma unroll 1
        for (int g = 0; g < total; g++) {
          int mi, kb, c;
          a_entry(g, grp, ct, mi, kb);
          const bool nmaj = g >= gh || (grp == 0 && g < 52);
          uint32_t bytes = 20480;
          if (g >= gh) { mi = M_WOUT; c = ct * 5; }
          else if (g >= 52) { mi = M_AB; c = DM + ct * 160; }
          else if (grp == 0) { mi = g < 20 ? M_WIN3 : M_Z23; c = 3 * ct + (g < 10 ? 12 : 0); bytes = 24576; }
          else { mi = g < 10 ? M_WDRE : g < 20 ? M_WDIM : M_AB; c = ct * 160; }
          if (g >= 20 && g < 52 && ((g - 20) >> 1) >= have) {
            if (g == 20) TS(1, 0);
            unsigned it = 0;
            while ((have = *reinterpret_cast<volatile int*>(smem + READY_OFF)) <= ((g - 20) >> 1) && ++it < 50 * POLL_LIMIT) {}
            fence_async_global();
            if (g == 20) { TS(1, 1); TC(1); }
          }
          if (g == 52) { TS(1, 2); mbar_wait(dep0 + 16, 0); fence_async_global(); TS(1, 3); TC(2); }
          const uint32_t dst = ring + s * stage_bytes + A_BYTES, fb = full0 + 8 * s;
          mbar_wait(empty0 + 8 * s, ph);
          if (++s == nst) { s = 0; ph ^= 1; }
          mbar_expect_tx(fb, bytes);
          if (nmaj) tma_load_3d(dst, &maps.m[mi], fb, 0, kb * 64, c);
          else tma_load_2d(dst, &maps.m[mi], fb, kb * 64, c);
        }
      }
      __syncwarp();
      cluster_wait();
    } else if (warp == 2) {
      if (lane < M_COUNT) asm volatile("prefetch.tensormap [%0];" :: "l"((uint64_t)&maps.m[lane]) : "memory");
      cluster_wait();
      {
        unsigned it = 0;
        uint2 v[4];
        while (true) {
          bool ok = true;
          #pragma unroll
          for (int i = 0; i < 4; i++) { v[i] = ld_tag2(&g_xstat[rb * 128 + i * 32 + lane]); ok = ok && ((v[i].y ^ epoch) & 255u) == 0; }
          if (ok || ++it > POLL_LIMIT) break;
          __nanosleep(POLL_NS);
        }
        #pragma unroll
        for (int i = 0; i < 4; i++) reinterpret_cast<uint2*>(smem + ROWSTAT_OFF)[i * 32 + lane] = make_uint2(v[i].x, v[i].y & ~255u);
        __syncwarp();
        TS(0, 6);
        if (grp == 0) bar_arrive<BAR_STATS>(320); else bar_arrive<BAR_STATS>(192);
      }
      #pragma unroll 1
      for (int i = 0; i < 5; i++) {
        const int d = i == 3 ? 4 : i == 4 ? 3 : i;
        const int slot = d == 0 ? F_XN + rb : d == 4 ? F_Y + rb * 4 + ct : d == 3 ? F_H + rb : d == 2 ? F_B + ct : grp == 0 ? F_Z + ct : F_A + ct;
        const int byte = d == 0 ? lane & 7 : d == 4 ? 0 : d == 3 ? lane & 3 : lane & 15;
        unsigned it = 0, m;
        while ((m = __ballot_sync(0xffffffffu, get_flag(slot, byte) != (epoch & 255u))) != 0 && ++it < POLL_LIMIT) {
          if (d == 1 && lane == 0) *reinterpret_cast<volatile int*>(smem + READY_OFF) = __ffs(m) - 1;
          __nanosleep(WATCH_NS);
        }
        if (d == 1 && lane == 0) *reinterpret_cast<volatile int*>(smem + READY_OFF) = 16;
        if (d < 4) TS(0, 8 + d * 2); else TS(0, 7);
        fence_async_global();
        __syncwarp();
        if (lane == 0 && d != 1) mbar_arrive(dep0 + 8 * d);
        if (d == 2 && lane < 30) {
          asm volatile("prefetch.global.L2 [%0];" :: "l"(wout + (size_t)cta * 6 * DM + lane * 128));
          asm volatile("prefetch.global.L2 [%0];" :: "l"(wout + (size_t)cta * 6 * DM + lane * 128 + 64));
        }
      }
    } else {
      cluster_wait();
      bar_sync<BAR_LN>(288);
      if (lane == 0) {
        TS(1, 5);
        asm volatile("cp.async.bulk.global.shared::cta.bulk_group [%0], [%1], 20480;" :: "l"(g_xn + (size_t)cta * 16 * DM), "r"(buf) : "memory");
        bulk_commit();
        bulk_wait_all();
        set_flag(F_XN + rb, cta & 7, epoch);
        TS(1, 6);
      }
      __syncwarp();
      if (grp == 0) {
        #pragma unroll 1
        for (int i = 0; i < 2; i++) gather96(&g_csum[ct * 192 + i * 96 + lane], reinterpret_cast<float*>(smem + COLSUM_OFF) + i * 96 + lane, epoch);
      } else {
        unsigned it = 0;
        while (true) {
          bool ok = true;
          #pragma unroll
          for (int j = 0; j < 5; j++) {
            const uint2 u = ld_tag2(&g_csum[5 * FH + ct * 160 + j * 32 + lane]);
            ok = ok && u.y == epoch;
            reinterpret_cast<uint32_t*>(smem + COLSUM_OFF)[j * 32 + lane] = u.x;
          }
          if (ok || ++it > POLL_LIMIT) break;
          __nanosleep(2 * POLL_NS);
        }
      }
      __syncwarp();
      TS(1, 4);
      if (grp == 0) {
        bar_arrive<BAR_STATS>(320);
        bar_sync<BAR_PUB1>(160);
        if (lane == 0) set_flag(F_Z + ct, rb, epoch);
        TS(1, 8);
        __syncwarp();
        bar_arrive<BAR_BUF>(160);
      } else {
        bar_arrive<BAR_STATS>(192);
        bar_sync<BAR_PUB2>(160);
        if (lane == 0) set_flag(F_A + ct, rb, epoch);
        TS(1, 9);
        __syncwarp();
      }
      bar_sync<BAR_PUB1>(160);
      if (lane == 0) {
        set_flag(grp == 0 ? F_H + rb : F_B + ct, grp == 0 ? ct : rb, epoch);
        if (grp == 0) mbar_arrive_cluster(dep0 + 8, rank ^ 1);
      }
      TS(1, 10);
      __syncwarp();
      bar_arrive<BAR_BUF>(160);
    }
  } else {
    asm volatile("setmaxnreg.inc.sync.aligned.u32 232;");
    const int t = tid & 127, w = t >> 5, l = t & 31;
    ln_rows(rv, buf, cta, epoch);
    TS(wg + 1, 0);
    cluster_wait();
    const uint32_t st_base = buf + (w * 16 + ((l >> 3) & 1) * 8 + (l & 7)) * 128;
    const uint32_t st_x = ((l >> 4) ^ (l & 7)) << 4;
    const float2* rs = reinterpret_cast<const float2*>(smem + ROWSTAT_OFF) + w * 16 + (l >> 2);
    const float2* cs = reinterpret_cast<const float2*>(smem + COLSUM_OFF) + (l & 3);
    if (grp == 0) {
      {
        const int mb = wg - 1;
        float acc[1][96];
        zero(acc);
        mainloop<192, 1, 1, false, 0>(acc, sbase, 0, 0, 10, mb);
        drain(acc, sbase, 0, 9);
        TS(wg + 1, 1);
        bar_sync<BAR_STATS>(320);
        const float2 s0 = rs[mb * 64], s1 = rs[mb * 64 + 8];
        const float nm[2] = {s0.y / s0.x, s1.y / s1.x}, hr[2] = {0.5f * s0.x, 0.5f * s1.x};
        const float k1[2] = {0.7978845608f * s0.x, 0.7978845608f * s1.x};
        const float k2[2] = {0.0356774081f * s0.x * s0.x * s0.x, 0.0356774081f * s1.x * s1.x * s1.x};
        float sm0 = 0.f, sm1 = 0.f, q0 = 0.f, q1 = 0.f;
        #pragma unroll
        for (int jj = 0; jj < 12; jj++) {
          float u[8];
          #pragma unroll
          for (int hf = 0; hf < 2; hf++) {
            const float2 c = cs[jj * 8 + hf * 4];
            #pragma unroll
            for (int e = 0; e < 4; e++) {
              const float wv = fmaf(nm[e >> 1], (e & 1) ? c.y : c.x, acc[0][8 * jj + 4 * hf + e]);
              float th; asm("tanh.approx.f32 %0, %1;" : "=f"(th) : "f"(wv * fmaf(k2[e >> 1], wv * wv, k1[e >> 1])));
              const float hv = hr[e >> 1] * wv;
              u[4 * hf + e] = fmaf(hv, th, hv);
            }
            sm0 += u[4 * hf] + u[4 * hf + 1]; q0 = fmaf(u[4 * hf], u[4 * hf], q0); q0 = fmaf(u[4 * hf + 1], u[4 * hf + 1], q0);
            sm1 += u[4 * hf + 2] + u[4 * hf + 3]; q1 = fmaf(u[4 * hf + 2], u[4 * hf + 2], q1); q1 = fmaf(u[4 * hf + 3], u[4 * hf + 3], q1);
          }
          stsm4(st_base + mb * 24576 + (jj >> 2) * 8192 + (st_x ^ ((jj & 3) << 5)),
                pack_bf16(u[0], u[1]), pack_bf16(u[2], u[3]), pack_bf16(u[4], u[5]), pack_bf16(u[6], u[7]));
        }
        #pragma unroll
        for (int o = 1; o < 4; o <<= 1) {
          sm0 += __shfl_xor_sync(0xffffffffu, sm0, o); q0 += __shfl_xor_sync(0xffffffffu, q0, o);
          sm1 += __shfl_xor_sync(0xffffffffu, sm1, o); q1 += __shfl_xor_sync(0xffffffffu, q1, o);
        }
        if ((l & 3) < 2) {
          const float sm = (l & 1) ? sm1 : sm0, sv = (l & 1) ? q1 : q0;
          const int row = mb * 64 + w * 16 + (l & 1) * 8 + (l >> 2);
          const float mu = sm * (1.f / 192), m2 = fmaxf(sv - sm * mu, 0.f);
          st_tag2(&g_zstat[(rb * 4 + ct) * 128 + row], __float_as_uint(mu), (__float_as_uint(m2) & ~255u) | (epoch & 255u));
          reinterpret_cast<float2*>(smem + ZSTAT_OFF)[row] = make_float2(mu, m2);
        }
        TS(wg + 1, 4);
      }
      float acc[2][96];
      if (wg == 1) {
        bar_sync<BAR_U>(256);
        uint2 v[3];
        unsigned n = 0;
        while (true) {
          bool ok = true;
          #pragma unroll
          for (int j = 0; j < 3; j++) { v[j] = ld_tag2(&g_zstat[(rb * 4 + ((ct + 1 + j) & 3)) * 128 + t]); ok = ok && ((v[j].y ^ epoch) & 255u) == 0; }
          if (ok || ++n > POLL_LIMIT) break;
          __nanosleep(POLL_NS);
        }
        const float2 own = reinterpret_cast<const float2*>(smem + ZSTAT_OFF)[t];
        const float m0 = __uint_as_float(v[0].x), m1 = __uint_as_float(v[1].x), m3 = __uint_as_float(v[2].x);
        const float mean = 0.25f * ((own.x + m0) + (m1 + m3));
        const float d = (own.x - mean) * (own.x - mean) + (m0 - mean) * (m0 - mean) + (m1 - mean) * (m1 - mean) + (m3 - mean) * (m3 - mean);
        const float var = fmaf(192.f, d, (own.y + __uint_as_float(v[0].y & ~255u)) + (__uint_as_float(v[1].y & ~255u) + __uint_as_float(v[2].y & ~255u)));
        const float r = rsqrtf(var * (1.f / FH) + LN_EPS);
        TS(2, 5);
        const uint32_t rbase = buf + (t >> 6) * 24576 + (t & 63) * 128;
        const uint32_t m2 = pack_bf16(-mean, -mean), r2 = pack_bf16(r, r);
        const float res = (-mean - bf_lo(m2)) * r;
        const uint32_t e2 = pack_bf16(res, res);
        #pragma unroll 1
        for (int c = 0; c < 3; c++) {
          uint4 z[8];
          #pragma unroll
          for (int i = 0; i < 8; i++) z[i] = lds128(rbase + c * 8192 + (((i ^ l) & 7) << 4));
          #pragma unroll
          for (int i = 0; i < 8; i++)
            sts128(rbase + c * 8192 + (((i ^ l) & 7) << 4), hfma2_bf16(hadd2_bf16(z[i].x, m2), r2, e2), hfma2_bf16(hadd2_bf16(z[i].y, m2), r2, e2),
                   hfma2_bf16(hadd2_bf16(z[i].z, m2), r2, e2), hfma2_bf16(hadd2_bf16(z[i].w, m2), r2, e2));
          fence_async_smem();
          __syncwarp();
          if (l == 0) {
            tma_store_2d(&maps.m[M_ZS], buf + (w >> 1) * 24576 + c * 8192 + (w & 1) * 4096, ct * 192 + c * 64, rb * 128 + w * 32);
            bulk_commit();
          }
        }
        TS(2, 6);
        if (l == 0) bulk_wait_all();
        __syncwarp();
        bar_arrive<BAR_PUB1>(160);
        {
          const bf16* bp = bsp + rb * 128 + w * 16 + (l >> 2);
          const float bb[4] = {__bfloat162float(bp[0]), __bfloat162float(bp[8]), __bfloat162float(bp[64]), __bfloat162float(bp[72])};
          #pragma unroll
          for (int i = 0; i < 96; i++) { acc[0][i] = bb[(i >> 1) & 1]; acc[1][i] = bb[2 + ((i >> 1) & 1)]; }
          pin(acc);
        }
        bar_sync<BAR_ORD2>(256);
        mainloop<192, 2, 1, false, BAR_ORD1>(acc, sbase, 0, 20, 32);
        bar_sync<BAR_Z1>(256);
        uint32_t z[6][4][4];
        #pragma unroll
        for (int i = 0; i < ZPRE; i++) ldsm4(st_base + (i >> 2) * 8192 + (st_x ^ ((i & 3) << 5)), z[i >> 2][i & 3][0], z[i >> 2][i & 3][1], z[i >> 2][i & 3][2], z[i >> 2][i & 3][3]);
        drain(acc, sbase, 0, 51);
        TS(2, 7);
        #pragma unroll
        for (int bx = 0; bx < 6; bx++) {
          if (bx >= 1) {
            #pragma unroll
            for (int i = ZPRE + (bx - 1) * 10; i < ZPRE + bx * 10; i++)
              if (i < 24) ldsm4(st_base + (i >> 2) * 8192 + (st_x ^ ((i & 3) << 5)), z[i >> 2][i & 3][0], z[i >> 2][i & 3][1], z[i >> 2][i & 3][2], z[i >> 2][i & 3][3]);
          }
          #pragma unroll
          for (int i = 0; i < 4; i++) {
            const float* a = &acc[bx / 3][8 * ((bx % 3) * 4 + i)];
            const uint32_t* zz = z[bx][i];
            stsm4(st_base + bx * 8192 + (st_x ^ (i << 5)),
                  hmul2_bf16(zz[0], pack_bf16(a[0], a[1])), hmul2_bf16(zz[1], pack_bf16(a[2], a[3])),
                  hmul2_bf16(zz[2], pack_bf16(a[4], a[5])), hmul2_bf16(zz[3], pack_bf16(a[6], a[7])));

          }
          if (bx % 3 == 2) {
            fence_async_smem();
            __syncwarp();
            if (l < 3) {
              tma_store_2d(&maps.m[M_HS], buf + (bx - 2 + l) * 8192 + w * 2048, ct * 192 + l * 64, rb * 128 + (bx / 3) * 64 + w * 16);
              bulk_commit();
            }
          }
        }
        bar_arrive<BAR_U>(256);
        TS(2, 8);
        if (l < 3) bulk_wait_all();
        __syncwarp();
        bar_arrive<BAR_PUB1>(160);
        TS(2, 9);
        return;
      }
      bar_arrive<BAR_U>(256);
      zero(acc);
      mainloop<192, 2, 1, false, BAR_ORD2>(acc, sbase, 0, 10, 10);
      drain(acc, sbase, 0, 19);
      TS(3, 2);
      bar_sync<BAR_BUF>(160);
      #pragma unroll
      for (int mi = 0; mi < 2; mi++)
        #pragma unroll
        for (int jj = 0; jj < 12; jj++) {
          const float* a = &acc[mi][8 * jj];
          stsm4(st_base + mi * 24576 + (jj >> 2) * 8192 + (st_x ^ ((jj & 3) << 5)),
                pack_bf16(a[0], a[1]), pack_bf16(a[2], a[3]), pack_bf16(a[4], a[5]), pack_bf16(a[6], a[7]));
        }
      __syncwarp();
      TS(3, 3);
      const uint32_t rbase = buf + (l >> 4) * 24576 + (w * 16 + (l & 15)) * 128;
      #pragma unroll 1
      for (int c2 = 0; c2 < 12; c2++) {
        const uint32_t ab = rbase + (c2 >> 2) * 8192;
        uint4 v[2];
        #pragma unroll
        for (int i = 0; i < 2; i++) v[i] = lds128(ab + (((((c2 & 3) * 2 + i) ^ l) & 7) << 4));
        #pragma unroll
        for (int i = 0; i < 2; i++)
          sts128(ab + (((((c2 & 3) * 2 + i) ^ l) & 7) << 4),
                 pack_bf16(gelu_tanh(bf_lo(v[i].x)), gelu_tanh(bf_hi(v[i].x))), pack_bf16(gelu_tanh(bf_lo(v[i].y)), gelu_tanh(bf_hi(v[i].y))),
                 pack_bf16(gelu_tanh(bf_lo(v[i].z)), gelu_tanh(bf_hi(v[i].z))), pack_bf16(gelu_tanh(bf_lo(v[i].w)), gelu_tanh(bf_hi(v[i].w))));
        __nanosleep(Z1_NS);
      }
      TS(3, 5);
      bar_arrive<BAR_Z1>(256);
    }
    float acc[2][80];
    if (grp == 1) {
      zero(acc);
      if (wg == 2) {
        mainloop<160, 2, 0, false, BAR_ORD2>(acc, sbase, 1, 0, 10);
      } else {
        weight_sums(win, wdre, rb * 4 + ct, epoch);
        TS(2, 1);
        bar_sync<BAR_ORD2>(256);
        mainloop<160, 2, 0, false, BAR_ORD1>(acc, sbase, 1, 10, 10);
      }
      drain(acc, sbase, 1, wg == 2 ? 9 : 19);
      TS(wg + 1, wg == 1 ? 7 : 2);
      if (wg == 1) bar_sync<BAR_Z1>(256); else bar_sync<BAR_STATS>(192);
      const uint32_t tb = buf + ((l >> 4) * 8 + (l & 7)) * 128 + (((w * 2 + ((l >> 3) & 1)) ^ (l & 7)) << 4);
      float2 st[4];
      #pragma unroll
      for (int r = 0; r < 4; r++) st[r] = wg == 2 ? rs[(r >> 1) * 64 + (r & 1) * 8] : make_float2(-1.f, 0.f);
      #pragma unroll
      for (int jj = 0; jj < 10; jj++) {
        const float2 c0 = cs[jj * 8], c1 = cs[jj * 8 + 4];
        #pragma unroll
        for (int mi = 0; mi < 2; mi++) {
          const float* a = &acc[mi][8 * jj];
          const float2 s0 = st[mi * 2], s1 = st[mi * 2 + 1];
          stsm4_t(tb + mi * 20480 + jj * 2048,
                  pack_bf16(fmaf(a[0], s0.x, s0.y * c0.x), fmaf(a[1], s0.x, s0.y * c0.y)), pack_bf16(fmaf(a[2], s1.x, s1.y * c0.x), fmaf(a[3], s1.x, s1.y * c0.y)),
                  pack_bf16(fmaf(a[4], s0.x, s0.y * c1.x), fmaf(a[5], s0.x, s0.y * c1.y)), pack_bf16(fmaf(a[6], s1.x, s1.y * c1.x), fmaf(a[7], s1.x, s1.y * c1.y)));
        }
      }
      fence_async_smem();
      if (wg == 1) bar_sync<BAR_WG1>(128); else bar_sync<BAR_WG2>(128);
      TS(wg + 1, wg == 1 ? 8 : 6);
      if (l < 2) {
        tma_store_2d(&maps.m[M_ABS], buf + l * 20480 + w * 5120, rb * 128 + l * 64, (2 - wg) * DM + ct * 160 + w * 40);
        bulk_commit();
        bulk_wait_all();
      }
      __syncwarp();
      TS(wg + 1, wg == 1 ? 9 : 10);
      if (wg == 1) {
        bar_arrive<BAR_PUB1>(160);
        #pragma unroll 1
        for (int i = 0; i < 4; i++) {
          uint4 v[5];
          #pragma unroll
          for (int j = 0; j < 5; j++) {
            const int e = (i * 5 + j) * 128 + t;
            v[j] = ldg128(x + (size_t)(rb * 128 + e / 20) * DM + ct * 160 + (e % 20) * 8);
          }
          #pragma unroll
          for (int j = 0; j < 5; j++) {
            const int e = (i * 5 + j) * 128 + t;
            stg128(out + (size_t)(rb * 128 + e / 20) * DM + ct * 160 + (e % 20) * 8, v[j]);
          }
        }
        bar_sync<BAR_WG1>(128);
        if (t == 0) publish(F_Y + rb * 4 + ct, 0, epoch);
        return;
      }
      bar_arrive<BAR_PUB2>(160);
      bar_arrive<BAR_Z1>(256);
    }
    zero(acc);
    bar_sync<BAR_ORD1>(256);
    mainloop<160, 2, 0, false, 0>(acc, sbase, grp, grp == 0 ? 52 : 20, grp == 0 ? NX : 64 - NX);
    if (grp == 0) {
      bar_sync<BAR_U>(256);
      mainloop<160, 2, 2, true, 0, true>(acc, sbase, 0, 52 + NX, 3);
    }
    mainloop<160, 2, 2, true, 0>(acc, sbase, grp, gh + 3 - 3 * grp, total - gh - 3 + 3 * grp);
    const uint32_t slab = buf + w * (16 * 320);
    const uint32_t addr = slab + (((l >> 3) & 1) * 8 + (l & 7)) * 320 + (l >> 4) * 16;
    bar_sync<BAR_BUF>(160);
    mbar_wait(dep0 + 32, 0);
    drain(acc, sbase, grp, total - 1);
    TS(3, 12);
    #pragma unroll
    for (int mi = 0; mi < 2; mi++) {
      #pragma unroll
      for (int jj = 0; jj < 10; jj++) {
        const float* a = &acc[mi][8 * jj];
        stsm4(addr + mi * 20480 + jj * 32, pack_bf16(a[0], a[1]), pack_bf16(a[2], a[3]), pack_bf16(a[4], a[5]), pack_bf16(a[6], a[7]));
      }
      fence_async_smem();
      __syncwarp();
      if (l == 0) {
        tma_reduce_2d(&maps.m[M_OUT], slab + mi * 20480, ct * 160, rb * 128 + mi * 64 + w * 16);
        bulk_commit();
      }
    }
    TS(3, 13);
    if (l == 0) {
      bulk_wait_read();
      if (w == 0) atomicAdd(&g_done, 1u);
    }
    TS(3, 15);
  }
}

typedef CUresult (*EncodeFn)(CUtensorMap*, CUtensorMapDataType, cuuint32_t, void*, const cuuint64_t*, const cuuint64_t*,
                             const cuuint32_t*, const cuuint32_t*, CUtensorMapInterleave, CUtensorMapSwizzle,
                             CUtensorMapL2promotion, CUtensorMapFloatOOBfill);

void make2d(EncodeFn enc, CUtensorMap* m, const void* p, uint64_t cols, uint64_t rows, uint32_t bc, uint32_t br, bool swz = true) {
  cuuint64_t gd[2] = {cols, rows}, gs[1] = {cols * 2};
  cuuint32_t bd[2] = {bc, br}, es[2] = {1, 1};
  enc(m, CU_TENSOR_MAP_DATA_TYPE_BFLOAT16, 2, const_cast<void*>(p), gd, gs, bd, es, CU_TENSOR_MAP_INTERLEAVE_NONE,
      swz ? CU_TENSOR_MAP_SWIZZLE_128B : CU_TENSOR_MAP_SWIZZLE_NONE, CU_TENSOR_MAP_L2_PROMOTION_L2_128B, CU_TENSOR_MAP_FLOAT_OOB_FILL_NONE);
}
void make3d(EncodeFn enc, CUtensorMap* m, const void* p, uint64_t cols, uint64_t rows, uint32_t cw, uint32_t nc, uint32_t br = 64) {
  cuuint64_t gd[3] = {cw, rows, cols / cw}, gs[2] = {cols * 2, cw * 2};
  cuuint32_t bd[3] = {cw, br, nc}, es[3] = {1, 1, 1};
  enc(m, CU_TENSOR_MAP_DATA_TYPE_BFLOAT16, 3, const_cast<void*>(p), gd, gs, bd, es, CU_TENSOR_MAP_INTERLEAVE_NONE,
      cw == 64 ? CU_TENSOR_MAP_SWIZZLE_128B : CU_TENSOR_MAP_SWIZZLE_64B, CU_TENSOR_MAP_L2_PROMOTION_L2_128B, CU_TENSOR_MAP_FLOAT_OOB_FILL_NONE);
}

}

extern "C" void kernel_launch(void* const* d_in, const int* in_sizes, int n_in, void* d_out, int out_size) {
  const bf16* x = (const bf16*)d_in[0];
  const bf16* wsre = (const bf16*)d_in[1];
  const bf16* wsim = (const bf16*)d_in[2];
  const bf16* wdre = (const bf16*)d_in[3];
  const bf16* wdim = (const bf16*)d_in[4];
  const bf16* win = (const bf16*)d_in[6];
  const bf16* wsp = (const bf16*)d_in[7];
  const bf16* bsp = (const bf16*)d_in[8];
  const bf16* wout = (const bf16*)d_in[9];

  void* fn = nullptr;
  cudaDriverEntryPointQueryResult qr;
  cudaGetDriverEntryPoint("cuTensorMapEncodeTiled", &fn, cudaEnableDefault, &qr);
  EncodeFn enc = (EncodeFn)fn;
  void *abT, *z2, *h, *xn;
  cudaGetSymbolAddress(&xn, g_xn);
  cudaGetSymbolAddress(&abT, g_abT);
  cudaGetSymbolAddress(&z2, g_z2);
  cudaGetSymbolAddress(&h, g_h);

  Maps maps;
  make2d(enc, &maps.m[M_X], x, DM, SEQ, 64, 64);
  make2d(enc, &maps.m[M_XN], xn, DM, SEQ, 64, 64);
  make2d(enc, &maps.m[M_WSRE], wsre, SEQ, SEQ, 64, 64);
  make2d(enc, &maps.m[M_WSIM], wsim, SEQ, SEQ, 64, 64);
  make2d(enc, &maps.m[M_WSP], wsp, SEQ, SEQ, 64, 64);
  make2d(enc, &maps.m[M_H], h, FH, SEQ, 64, 64);
  make3d(enc, &maps.m[M_WIN3], win, FF, DM, 64, 3);
  make3d(enc, &maps.m[M_Z23], z2, FH, SEQ, 64, 3);
  make2d(enc, &maps.m[M_WDRE], wdre, DM, DM, 64, 160);
  make2d(enc, &maps.m[M_WDIM], wdim, DM, DM, 64, 160);
  make2d(enc, &maps.m[M_AB], abT, SEQ, 2 * DM, 64, 160);
  make3d(enc, &maps.m[M_WOUT], wout, DM, FH, 32, 5);
  make2d(enc, &maps.m[M_HS], h, FH, SEQ, 64, 16);
  make2d(enc, &maps.m[M_ZS], z2, FH, SEQ, 64, 32);
  make2d(enc, &maps.m[M_ABS], abT, SEQ, 2 * DM, 64, 40);
  make2d(enc, &maps.m[M_OUT], d_out, DM, SEQ, 160, 16, false);

  cudaFuncSetAttribute(fused_kernel, cudaFuncAttributeMaxDynamicSharedMemorySize, SMEM_BYTES);
  fused_kernel<<<128, 384, SMEM_BYTES>>>(maps, x, win, wdre, bsp, wout, (bf16*)d_out);
}
```

```cpp
#include <cuda_runtime.h>
#include <cuda_bf16.h>
#include <cuda.h>
#include <stdint.h>

namespace {

typedef __nv_bfloat16 bf16;

constexpr int SEQ = 2048, DM = 640, FF = 1536, FH = 768;
#define NOV 3
#define NXV 6
constexpr int NX = NXV;
constexpr int NO = NOV;
constexpr int NST_A = 4, NST_B = 5, MAXST = 5;
constexpr int A_BYTES = 16384;
constexpr int BAR_OFF = 0;
constexpr int READY_OFF = 128;
constexpr int COLSUM_OFF = 256;
constexpr int ROWSTAT_OFF = 1024;
constexpr int ZSTAT_OFF = 2048;
constexpr int RED_OFF = 3072;
constexpr int RING_OFF = 4096;
constexpr int STAGE_A = 40960, STAGE_B = 36864;
constexpr int SMEM_BYTES = RING_OFF + 5 * STAGE_B + 40960;
constexpr int KB_A = 52 + NX + 12 - NO;
constexpr int KB_B = 84 - NX + NO;
constexpr float LN_EPS = 1e-5f;
constexpr unsigned POLL_LIMIT = 100000;
constexpr unsigned POLL_NS = 100, WATCH_NS = 40;
constexpr unsigned Z1_NS = 600;
constexpr int PF_D = 8;
constexpr int ZPRE = 6;

#define HELP_NS 4000
constexpr int BAR_ORD1 = 1, BAR_ORD2 = 2, BAR_WG1 = 3, BAR_WG2 = 4, BAR_LN = 5, BAR_BUF = 6, BAR_Z1 = 7, BAR_PUB1 = 8, BAR_PUB2 = 9,
              BAR_STATS = 10, BAR_U = 11;

enum { M_X, M_XN, M_WSRE, M_WSIM, M_WSP, M_H, M_WIN3, M_Z23, M_WDRE, M_WDIM, M_AB, M_WOUT, M_OUT, M_HS, M_ZS, M_ABS, M_COUNT };
struct Maps { CUtensorMap m[M_COUNT]; };

__device__ __align__(1024) bf16 g_abT[2 * DM * SEQ];
__device__ __align__(1024) bf16 g_z2[SEQ * FH];
__device__ __align__(1024) bf16 g_h[SEQ * FH];
__device__ __align__(1024) bf16 g_xn[SEQ * DM];
__device__ __align__(16) uint2 g_xstat[SEQ];
__device__ __align__(16) uint2 g_csum[5 * FH + DM];
__device__ __align__(16) uint2 g_zstat[64 * 128];
__device__ __align__(256) unsigned char g_flags[108 * 256];
constexpr int F_A = 0, F_B = 4, F_Z = 8, F_H = 12, F_XN = 28, F_Y = 44;
__device__ unsigned g_done;
#define TS(role, ev)
#define TC(i)

extern __shared__ __align__(1024) uint8_t smem[];

__device__ __forceinline__ uint32_t smem_u32(const void* p) { return (uint32_t)__cvta_generic_to_shared(p); }
__device__ __forceinline__ void mbar_init(uint32_t bar, uint32_t cnt) { asm volatile("mbarrier.init.shared::cta.b64 [%0], %1;" :: "r"(bar), "r"(cnt)); }
__device__ __forceinline__ void mbar_expect_tx(uint32_t bar, uint32_t bytes) { asm volatile("mbarrier.arrive.expect_tx.shared::cta.b64 _, [%0], %1;" :: "r"(bar), "r"(bytes) : "memory"); }
__device__ __forceinline__ void mbar_arrive(uint32_t bar) { asm volatile("mbarrier.arrive.shared::cta.b64 _, [%0];" :: "r"(bar) : "memory"); }
__device__ __forceinline__ void mbar_arrive_cluster(uint32_t bar, uint32_t cta) {
  asm volatile("{\n.reg .b32 ra;\nmapa.shared::cluster.u32 ra, %0, %1;\nmbarrier.arrive.shared::cluster.b64 _, [ra];\n}" :: "r"(bar), "r"(cta) : "memory");
}
__device__ __forceinline__ void mbar_wait(uint32_t bar, uint32_t parity) {
  asm volatile("{\n.reg .pred p;\n.reg .u32 n;\nmov.u32 n, 0;\n"
               "LW: mbarrier.try_wait.parity.shared::cta.b64 p, [%0], %1, 2000;\n@p bra LD;\n"
               "add.u32 n, n, 1;\nsetp.lt.u32 p, n, 20000;\n@p bra LW;\nLD:\n}" :: "r"(bar), "r"(parity) : "memory");
}
__device__ __forceinline__ void tma_load_2d(uint32_t dst, const CUtensorMap* map, uint32_t bar, int c0, int c1) {
  asm volatile("cp.async.bulk.tensor.2d.shared::cluster.global.mbarrier::complete_tx::bytes [%0], [%1, {%3, %4}], [%2];"
    :: "r"(dst), "l"((uint64_t)map), "r"(bar), "r"(c0), "r"(c1) : "memory");
}
__device__ __forceinline__ void tma_load_3d(uint32_t dst, const CUtensorMap* map, uint32_t bar, int c0, int c1, int c2) {
  asm volatile("cp.async.bulk.tensor.3d.shared::cluster.global.mbarrier::complete_tx::bytes [%0], [%1, {%3, %4, %5}], [%2];"
    :: "r"(dst), "l"((uint64_t)map), "r"(bar), "r"(c0), "r"(c1), "r"(c2) : "memory");
}
__device__ __forceinline__ void tma_load_2d_mc(uint32_t dst, const CUtensorMap* map, uint32_t bar, int c0, int c1, uint16_t mask) {
  asm volatile("cp.async.bulk.tensor.2d.shared::cluster.global.mbarrier::complete_tx::bytes.multicast::cluster [%0], [%1, {%3, %4}], [%2], %5;"
    :: "r"(dst), "l"((uint64_t)map), "r"(bar), "r"(c0), "r"(c1), "h"(mask) : "memory");
}
__device__ __forceinline__ void tma_store_2d(const CUtensorMap* map, uint32_t src, int c0, int c1) {
  asm volatile("cp.async.bulk.tensor.2d.global.shared::cta.bulk_group [%0, {%2, %3}], [%1];"
    :: "l"((uint64_t)map), "r"(src), "r"(c0), "r"(c1) : "memory");
}
__device__ __forceinline__ void tma_reduce_2d(const CUtensorMap* map, uint32_t src, int c0, int c1) {
  asm volatile("cp.reduce.async.bulk.tensor.2d.global.shared::cta.add.tile.bulk_group [%0, {%2, %3}], [%1];"
    :: "l"((uint64_t)map), "r"(src), "r"(c0), "r"(c1) : "memory");
}
__device__ __forceinline__ void bulk_wait_all() { asm volatile("cp.async.bulk.wait_group 0;" ::: "memory"); }
__device__ __forceinline__ void bulk_commit() { asm volatile("cp.async.bulk.commit_group;" ::: "memory"); }
__device__ __forceinline__ void bulk_wait_read() { asm volatile("cp.async.bulk.wait_group.read 0;" ::: "memory"); }
__device__ __forceinline__ void fence_async_smem() { asm volatile("fence.proxy.async.shared::cta;" ::: "memory"); }
__device__ __forceinline__ void fence_async_global() { asm volatile("fence.proxy.async.global;" ::: "memory"); }
__device__ __forceinline__ void wgmma_fence() { asm volatile("wgmma.fence.sync.aligned;" ::: "memory"); }
__device__ __forceinline__ void wgmma_commit() { asm volatile("wgmma.commit_group.sync.aligned;" ::: "memory"); }
template<int N> __device__ __forceinline__ void wgmma_wait() { asm volatile("wgmma.wait_group.sync.aligned %0;" :: "n"(N) : "memory"); }
template<int ID> __device__ __forceinline__ void bar_sync(int n) { asm volatile("bar.sync %0, %1;" :: "n"(ID), "r"(n) : "memory"); }
template<int ID> __device__ __forceinline__ void bar_arrive(int n) { asm volatile("bar.arrive %0, %1;" :: "n"(ID), "r"(n) : "memory"); }
__device__ __forceinline__ void cluster_wait() { asm volatile("barrier.cluster.wait.aligned;" ::: "memory"); }
__device__ __forceinline__ uint64_t desc64(uint32_t lo, uint32_t hi) { return (uint64_t)lo | ((uint64_t)hi << 32); }
__device__ __forceinline__ uint2 ld_tag2(const uint2* p) {
  uint2 v; asm volatile("ld.relaxed.gpu.global.v2.u32 {%0,%1}, [%2];" : "=r"(v.x), "=r"(v.y) : "l"(p) : "memory"); return v;
}
__device__ __forceinline__ void st_tag2(uint2* p, uint32_t a, uint32_t b) {
  asm volatile("st.relaxed.gpu.global.v2.u32 [%0], {%1,%2};" :: "l"(p), "r"(a), "r"(b) : "memory");
}
__device__ __forceinline__ void stg128(void* p, uint4 v) {
  asm volatile("st.global.v4.u32 [%0], {%1,%2,%3,%4};" :: "l"(p), "r"(v.x), "r"(v.y), "r"(v.z), "r"(v.w));
}
__device__ __forceinline__ unsigned ld_relaxed(const unsigned* p) {
  unsigned v; asm volatile("ld.relaxed.gpu.global.u32 %0, [%1];" : "=r"(v) : "l"(p) : "memory"); return v;
}
__device__ __forceinline__ uint32_t pack_bf16(float lo, float hi) {
  uint32_t r; asm("cvt.rn.bf16x2.f32 %0, %1, %2;" : "=r"(r) : "f"(hi), "f"(lo)); return r;
}
__device__ __forceinline__ float bf_lo(uint32_t v) { return __uint_as_float(v << 16); }
__device__ __forceinline__ float bf_hi(uint32_t v) { return __uint_as_float(v & 0xFFFF0000u); }
__device__ __forceinline__ void stsm4(uint32_t addr, uint32_t a, uint32_t b, uint32_t c, uint32_t d) {
  asm volatile("stmatrix.sync.aligned.m8n8.x4.shared.b16 [%0], {%1,%2,%3,%4};" :: "r"(addr), "r"(a), "r"(b), "r"(c), "r"(d));
}
__device__ __forceinline__ void stsm4_t(uint32_t addr, uint32_t a, uint32_t b, uint32_t c, uint32_t d) {
  asm volatile("stmatrix.sync.aligned.m8n8.x4.trans.shared.b16 [%0], {%1,%2,%3,%4};" :: "r"(addr), "r"(a), "r"(b), "r"(c), "r"(d));
}
__device__ __forceinline__ void ldsm4(uint32_t addr, uint32_t& a, uint32_t& b, uint32_t& c, uint32_t& d) {
  asm volatile("ldmatrix.sync.aligned.m8n8.x4.shared.b16 {%0,%1,%2,%3}, [%4];" : "=r"(a), "=r"(b), "=r"(c), "=r"(d) : "r"(addr));
}
__device__ __forceinline__ uint4 lds128(uint32_t a) {
  uint4 v; asm volatile("ld.shared.v4.u32 {%0,%1,%2,%3}, [%4];" : "=r"(v.x), "=r"(v.y), "=r"(v.z), "=r"(v.w) : "r"(a)); return v;
}
__device__ __forceinline__ void sts128(uint32_t a, uint32_t x, uint32_t y, uint32_t z, uint32_t w) {
  asm volatile("st.shared.v4.u32 [%0], {%1,%2,%3,%4};" :: "r"(a), "r"(x), "r"(y), "r"(z), "r"(w));
}
__device__ __forceinline__ uint32_t hmul2_bf16(uint32_t a, uint32_t b) {
  uint32_t r; asm("mul.rn.bf16x2 %0, %1, %2;" : "=r"(r) : "r"(a), "r"(b)); return r;
}
__device__ __forceinline__ uint32_t hadd2_bf16(uint32_t a, uint32_t b) {
  uint32_t r; asm("add.rn.bf16x2 %0, %1, %2;" : "=r"(r) : "r"(a), "r"(b)); return r;
}
__device__ __forceinline__ uint32_t hfma2_bf16(uint32_t a, uint32_t b, uint32_t c) {
  uint32_t r; asm("fma.rn.bf16x2 %0, %1, %2, %3;" : "=r"(r) : "r"(a), "r"(b), "r"(c)); return r;
}
__device__ __forceinline__ float gelu_tanh(float v) {
  float u = v * fmaf(0.0356774081f, v * v, 0.7978845608f);
  float t; asm("tanh.approx.f32 %0, %1;" : "=f"(t) : "f"(u));
  float hv = 0.5f * v;
  return fmaf(hv, t, hv);
}

template<int TB>
__device__ __forceinline__ void wgmma_n192(float (&d)[96], uint64_t da, uint64_t db, int scale_d) {
  asm volatile("{\n.reg .pred p;\nsetp.ne.b32 p, %98, 0;\n"
   "wgmma.mma_async.sync.aligned.m64n192k16.f32.bf16.bf16 {%0,%1,%2,%3,%4,%5,%6,%7,%8,%9,%10,%11,%12,%13,%14,%15,%16,%17,%18,%19,%20,%21,%22,%23,%24,%25,%26,%27,%28,%29,%30,%31,%32,%33,%34,%35,%36,%37,%38,%39,%40,%41,%42,%43,%44,%45,%46,%47,%48,%49,%50,%51,%52,%53,%54,%55,%56,%57,%58,%59,%60,%61,%62,%63,%64,%65,%66,%67,%68,%69,%70,%71,%72,%73,%74,%75,%76,%77,%78,%79,%80,%81,%82,%83,%84,%85,%86,%87,%88,%89,%90,%91,%92,%93,%94,%95}, %96, %97, p, 1, 1, 0, %99;\n}"
   : "+f"(d[0]),"+f"(d[1]),"+f"(d[2]),"+f"(d[3]),"+f"(d[4]),"+f"(d[5]),"+f"(d[6]),"+f"(d[7]),"+f"(d[8]),"+f"(d[9]),"+f"(d[10]),"+f"(d[11]),"+f"(d[12]),"+f"(d[13]),"+f"(d[14]),"+f"(d[15]),"+f"(d[16]),"+f"(d[17]),"+f"(d[18]),"+f"(d[19]),"+f"(d[20]),"+f"(d[21]),"+f"(d[22]),"+f"(d[23]),"+f"(d[24]),"+f"(d[25]),"+f"(d[26]),"+f"(d[27]),"+f"(d[28]),"+f"(d[29]),"+f"(d[30]),"+f"(d[31]),"+f"(d[32]),"+f"(d[33]),"+f"(d[34]),"+f"(d[35]),"+f"(d[36]),"+f"(d[37]),"+f"(d[38]),"+f"(d[39]),"+f"(d[40]),"+f"(d[41]),"+f"(d[42]),"+f"(d[43]),"+f"(d[44]),"+f"(d[45]),"+f"(d[46]),"+f"(d[47]),"+f"(d[48]),"+f"(d[49]),"+f"(d[50]),"+f"(d[51]),"+f"(d[52]),"+f"(d[53]),"+f"(d[54]),"+f"(d[55]),"+f"(d[56]),"+f"(d[57]),"+f"(d[58]),"+f"(d[59]),"+f"(d[60]),"+f"(d[61]),"+f"(d[62]),"+f"(d[63]),"+f"(d[64]),"+f"(d[65]),"+f"(d[66]),"+f"(d[67]),"+f"(d[68]),"+f"(d[69]),"+f"(d[70]),"+f"(d[71]),"+f"(d[72]),"+f"(d[73]),"+f"(d[74]),"+f"(d[75]),"+f"(d[76]),"+f"(d[77]),"+f"(d[78]),"+f"(d[79]),"+f"(d[80]),"+f"(d[81]),"+f"(d[82]),"+f"(d[83]),"+f"(d[84]),"+f"(d[85]),"+f"(d[86]),"+f"(d[87]),"+f"(d[88]),"+f"(d[89]),"+f"(d[90]),"+f"(d[91]),"+f"(d[92]),"+f"(d[93]),"+f"(d[94]),"+f"(d[95])
   : "l"(da), "l"(db), "r"(scale_d), "n"(TB));
}
template<int TB>
__device__ __forceinline__ void wgmma_n160(float (&d)[80], uint64_t da, uint64_t db, int scale_d) {
  asm volatile("{\n.reg .pred p;\nsetp.ne.b32 p, %82, 0;\n"
   "wgmma.mma_async.sync.aligned.m64n160k16.f32.bf16.bf16 {%0,%1,%2,%3,%4,%5,%6,%7,%8,%9,%10,%11,%12,%13,%14,%15,%16,%17,%18,%19,%20,%21,%22,%23,%24,%25,%26,%27,%28,%29,%30,%31,%32,%33,%34,%35,%36,%37,%38,%39,%40,%41,%42,%43,%44,%45,%46,%47,%48,%49,%50,%51,%52,%53,%54,%55,%56,%57,%58,%59,%60,%61,%62,%63,%64,%65,%66,%67,%68,%69,%70,%71,%72,%73,%74,%75,%76,%77,%78,%79}, %80, %81, p, 1, 1, 0, %83;\n}"
   : "+f"(d[0]),"+f"(d[1]),"+f"(d[2]),"+f"(d[3]),"+f"(d[4]),"+f"(d[5]),"+f"(d[6]),"+f"(d[7]),"+f"(d[8]),"+f"(d[9]),"+f"(d[10]),"+f"(d[11]),"+f"(d[12]),"+f"(d[13]),"+f"(d[14]),"+f"(d[15]),"+f"(d[16]),"+f"(d[17]),"+f"(d[18]),"+f"(d[19]),"+f"(d[20]),"+f"(d[21]),"+f"(d[22]),"+f"(d[23]),"+f"(d[24]),"+f"(d[25]),"+f"(d[26]),"+f"(d[27]),"+f"(d[28]),"+f"(d[29]),"+f"(d[30]),"+f"(d[31]),"+f"(d[32]),"+f"(d[33]),"+f"(d[34]),"+f"(d[35]),"+f"(d[36]),"+f"(d[37]),"+f"(d[38]),"+f"(d[39]),"+f"(d[40]),"+f"(d[41]),"+f"(d[42]),"+f"(d[43]),"+f"(d[44]),"+f"(d[45]),"+f"(d[46]),"+f"(d[47]),"+f"(d[48]),"+f"(d[49]),"+f"(d[50]),"+f"(d[51]),"+f"(d[52]),"+f"(d[53]),"+f"(d[54]),"+f"(d[55]),"+f"(d[56]),"+f"(d[57]),"+f"(d[58]),"+f"(d[59]),"+f"(d[60]),"+f"(d[61]),"+f"(d[62]),"+f"(d[63]),"+f"(d[64]),"+f"(d[65]),"+f"(d[66]),"+f"(d[67]),"+f"(d[68]),"+f"(d[69]),"+f"(d[70]),"+f"(d[71]),"+f"(d[72]),"+f"(d[73]),"+f"(d[74]),"+f"(d[75]),"+f"(d[76]),"+f"(d[77]),"+f"(d[78]),"+f"(d[79])
   : "l"(da), "l"(db), "r"(scale_d), "n"(TB));
}

template<int N, int TB>
__device__ __forceinline__ void wgmma_n(float (&d)[N / 2], uint64_t da, uint64_t db) {
  if constexpr (N == 192) wgmma_n192<TB>(d, da, db, 1); else wgmma_n160<TB>(d, da, db, 1);
}

template<int M, int R>
__device__ __forceinline__ void pin(float (&acc)[M][R]) {
  #pragma unroll
  for (int mi = 0; mi < M; mi++)
    #pragma unroll
    for (int i = 0; i < R; i++) asm volatile("" : "+f"(acc[mi][i]) :: "memory");
}
template<int M, int R>
__device__ __forceinline__ void zero(float (&acc)[M][R]) {
  #pragma unroll
  for (int mi = 0; mi < M; mi++)
    #pragma unroll
    for (int i = 0; i < R; i++) acc[mi][i] = 0.f;
  pin(acc);
}

template<int N, int M, int TB, bool CONT, int ORD_BAR, bool AOWN = false>
__device__ __forceinline__ void mainloop(float (&acc)[M][N / 2], uint32_t sbase, int grp, int g0, int nk, int m0 = 0) {
  const uint32_t full0 = sbase + BAR_OFF, empty0 = full0 + 8 * MAXST, ring = sbase + RING_OFF;
  const int nst = grp == 0 ? NST_A : NST_B, total = grp == 0 ? KB_A : KB_B;
  const uint32_t sstep = (grp == 0 ? STAGE_A : STAGE_B) >> 4;
  const int t = threadIdx.x & 127;
  const uint32_t da0 = (((ring + m0 * 8192) & 0x3FFFF) >> 4) | 0x10000u;
  const uint32_t db0 = (((ring + A_BYTES) & 0x3FFFF) >> 4) | ((TB == 2 ? 256u : TB ? 512u : 1u) << 16);
  constexpr uint32_t HI_A = 0x40000040u, HI_B = TB == 2 ? 0x80000020u : 0x40000040u;
  int s = g0 % nst, ph = (g0 / nst) & 1, ps = s == 0 ? nst - 1 : s - 1;
  #pragma unroll 1
  for (int g = g0; g < g0 + nk; g++) {
    const uint32_t so = s * sstep;
    mbar_wait(full0 + 8 * s, ph);
    wgmma_fence();
    #pragma unroll
    for (int k = 0; k < 4; k++) {
      const uint64_t db = desc64(db0 + so + (TB == 2 ? k * 64 : TB ? k * 128 : k * 2), HI_B);
      #pragma unroll
      for (int mi = 0; mi < M; mi++)
        wgmma_n<N, TB != 0>(acc[mi], desc64(AOWN ? da0 + ((NST_A * STAGE_A) >> 4) + (g - g0) * 512 + mi * 1536 + k * 2 : da0 + so + mi * 512 + k * 2, HI_A), db);
    }
    wgmma_commit();
    if (ORD_BAR != 0 && g == g0 + nk - 1) bar_arrive<ORD_BAR>(256);
    wgmma_wait<1>();
    if (t < 2 * M && (CONT || g > g0) && g - 1 + nst < total) mbar_arrive_cluster(empty0 + 8 * ps, t & 1);
    ps = s;
    if (++s == nst) { s = 0; ph ^= 1; }
  }
}
template<int M, int R>
__device__ __forceinline__ void drain(float (&acc)[M][R], uint32_t sbase, int grp, int glast) {
  wgmma_wait<0>();
  pin(acc);
  const int t = threadIdx.x & 127;
  const int nst = grp == 0 ? NST_A : NST_B, total = grp == 0 ? KB_A : KB_B;
  if (t < 2 * M && glast + nst < total) mbar_arrive_cluster(sbase + BAR_OFF + 8 * MAXST + 8 * (glast % nst), t & 1);
}

__device__ __forceinline__ void set_flag(int slot, int byte, unsigned epoch) {
  asm volatile("st.relaxed.gpu.global.u8 [%0], %1;" :: "l"(g_flags + slot * 256 + byte), "r"(epoch & 255u) : "memory");
}
__device__ __forceinline__ unsigned get_flag(int slot, int byte) {
  unsigned v; asm volatile("ld.relaxed.gpu.global.u8 %0, [%1];" : "=r"(v) : "l"(g_flags + slot * 256 + byte) : "memory"); return v;
}
__device__ __forceinline__ void publish(int slot, int byte, unsigned epoch) {
  asm volatile("fence.acq_rel.gpu;" ::: "memory");
  set_flag(slot, byte, epoch);
}
__device__ __forceinline__ float sum8(uint4 v) {
  return ((bf_lo(v.x) + bf_hi(v.x)) + (bf_lo(v.y) + bf_hi(v.y))) + ((bf_lo(v.z) + bf_hi(v.z)) + (bf_lo(v.w) + bf_hi(v.w)));
}
__device__ __forceinline__ uint4 ldg128(const void* p) {
  uint4 v; asm volatile("ld.global.nc.v4.u32 {%0,%1,%2,%3}, [%4];" : "=r"(v.x), "=r"(v.y), "=r"(v.z), "=r"(v.w) : "l"(p)); return v;
}

__device__ __forceinline__ void ln_rows(const uint4 (&rv)[5], uint32_t buf, int cta, unsigned epoch) {
  const int t = threadIdx.x - 128, row = cta * 16 + (t >> 4), c = t & 15;
  const float sh = __shfl_sync(0xffffffffu, bf_lo(rv[0].x), t & 16);
  float d[40], s = 0.f, q = 0.f;
  #pragma unroll
  for (int j = 0; j < 5; j++) {
    const uint32_t u[4] = {rv[j].x, rv[j].y, rv[j].z, rv[j].w};
    #pragma unroll
    for (int e = 0; e < 4; e++) {
      const float d0 = bf_lo(u[e]) - sh, d1 = bf_hi(u[e]) - sh;
      d[j * 8 + e * 2] = d0; d[j * 8 + e * 2 + 1] = d1;
      s += d0 + d1; q = fmaf(d0, d0, q); q = fmaf(d1, d1, q);
    }
  }
  #pragma unroll
  for (int o = 1; o < 16; o <<= 1) { s += __shfl_xor_sync(0xffffffffu, s, o); q += __shfl_xor_sync(0xffffffffu, q, o); }
  const float md = s * (1.f / DM);
  const float r = rsqrtf(fmaxf(fmaf(q, 1.f / DM, -md * md), 0.f) + LN_EPS), o = -md * r;
  if (c == 0) st_tag2(&g_xstat[row], __float_as_uint(r), (__float_as_uint(-(md + sh) * r) & ~255u) | (epoch & 255u));
  #pragma unroll
  for (int j = 0; j < 5; j++) {
    const float* a = &d[j * 8];
    sts128(buf + (t >> 4) * 1280 + (c + 16 * j) * 16,
           pack_bf16(fmaf(a[0], r, o), fmaf(a[1], r, o)), pack_bf16(fmaf(a[2], r, o), fmaf(a[3], r, o)),
           pack_bf16(fmaf(a[4], r, o), fmaf(a[5], r, o)), pack_bf16(fmaf(a[6], r, o), fmaf(a[7], r, o)));
  }
  fence_async_smem();
  bar_arrive<BAR_LN>(288);
}

__device__ __forceinline__ void weight_sums(const bf16* __restrict__ win, const bf16* __restrict__ wdre, int j, unsigned epoch) {
  const int t = threadIdx.x & 127, w = t >> 5, l = t & 31;
  const int cj = min(j, 59), cg = cj % 12, rg = cj / 12, wr = j * 10 + min(t >> 3, 9);
  uint4 cv[8], rv[10];
  #pragma unroll
  for (int i = 0; i < 8; i++) cv[i] = ldg128(reinterpret_cast<const uint4*>(win + (size_t)(rg * 128 + w * 32 + i * 4 + (l >> 3)) * FF + FH + cg * 64) + (l & 7));
  #pragma unroll
  for (int i = 0; i < 10; i++) rv[i] = ldg128(reinterpret_cast<const uint4*>(wdre + (size_t)wr * DM) + (l & 7) + 8 * i);
  float v[8];
  #pragma unroll
  for (int e = 0; e < 8; e++) v[e] = 0.f;
  #pragma unroll
  for (int i = 0; i < 8; i++) {
    v[0] += bf_lo(cv[i].x); v[1] += bf_hi(cv[i].x); v[2] += bf_lo(cv[i].y); v[3] += bf_hi(cv[i].y);
    v[4] += bf_lo(cv[i].z); v[5] += bf_hi(cv[i].z); v[6] += bf_lo(cv[i].w); v[7] += bf_hi(cv[i].w);
  }
  #pragma unroll
  for (int st = 0; st < 2; st++) {
    const int n = 4 >> st;
    const bool up = (l & (4 * n)) != 0;
    #pragma unroll
    for (int e = 0; e < 4; e++)
      if (e < n) { const float keep = up ? v[e + n] : v[e], send = up ? v[e] : v[e + n]; v[e] = keep + __shfl_xor_sync(0xffffffffu, send, 4 * n); }
  }
  float* red = reinterpret_cast<float*>(smem + RED_OFF);
  *reinterpret_cast<float2*>(red + w * 64 + (l & 7) * 8 + (l >> 3) * 2) = make_float2(v[0], v[1]);
  float s = 0.f;
  #pragma unroll
  for (int i = 0; i < 10; i++) s += sum8(rv[i]);
  #pragma unroll
  for (int o = 1; o < 8; o <<= 1) s += __shfl_xor_sync(0xffffffffu, s, o);
  if ((l & 7) == 0) st_tag2(&g_csum[5 * FH + wr], __float_as_uint(s), epoch);
  bar_sync<BAR_WG1>(128);
  if (t < 64) st_tag2(&g_csum[rg * FH + cg * 64 + t], __float_as_uint((red[t] + red[64 + t]) + (red[128 + t] + red[192 + t])), epoch);
}

__device__ __forceinline__ void gather96(const uint2* src, float* dst, unsigned epoch) {
  unsigned it = 0;
  while (true) {
    bool ok = true;
    uint2 u[15];
    #pragma unroll
    for (int j = 0; j < 15; j++) u[j] = ld_tag2(src + (j % 5) * FH + (j / 5) * 32);
    #pragma unroll
    for (int j = 0; j < 15; j++) ok = ok && u[j].y == epoch;
    #pragma unroll
    for (int j = 0; j < 3; j++)
      dst[j * 32] = ((__uint_as_float(u[j * 5].x) + __uint_as_float(u[j * 5 + 1].x)) + (__uint_as_float(u[j * 5 + 2].x) + __uint_as_float(u[j * 5 + 3].x))) + __uint_as_float(u[j * 5 + 4].x);
    if (ok || ++it > POLL_LIMIT) break;
    __nanosleep(2 * POLL_NS);
  }
}

__device__ __forceinline__ void a_entry(int g, int grp, int ct, int& mi, int& kb) {
  if (g < 10) { mi = M_X; kb = g; }
  else if (g < 20) { mi = M_XN; kb = g - 10; }
  else if (g < 52) { mi = grp == 0 ? M_WSP : M_WSRE; kb = g - 20; }
  else if (grp == 0) {
    if (g < 52 + NX) { mi = M_WSIM; kb = g - 52 + 32 - NX; }
    else {
      const int i = g - 52 - NX;
      mi = M_H; kb = i < 3 ? ct * 3 + i : i < 6 ? (ct ^ 1) * 3 + i - 3 : ((ct >> 1) ^ 1) * 6 + i - 6;
    }
  } else {
    if (g < 84 - NX) { mi = M_WSIM; kb = g - 52; }
    else { mi = M_H; kb = ((ct >> 1) ^ 1) * 6 + g - (84 - NX) + 6 - NO; }
  }
}

__global__ void __cluster_dims__(2, 1, 1) __launch_bounds__(384, 1)
fused_kernel(const __grid_constant__ Maps maps, const bf16* __restrict__ x, const bf16* __restrict__ win, const bf16* __restrict__ wdre,
             const bf16* __restrict__ bsp, const bf16* __restrict__ wout, bf16* __restrict__ out) {
  const uint32_t sbase = smem_u32(smem);
  const uint32_t full0 = sbase + BAR_OFF, empty0 = full0 + 8 * MAXST, dep0 = empty0 + 8 * MAXST, ring = sbase + RING_OFF;
  const int tid = threadIdx.x, wg = __shfl_sync(0xffffffffu, tid >> 7, 0);
  if (blockIdx.x < 4) {
    if (tid == 0) {
      const unsigned epoch = (ld_relaxed(&g_done) >> 7) + 1u;
      for (int s = 0; s < 4; s++) mbar_init(sbase + 8 * s, 1);
      asm volatile("fence.mbarrier_init.release.cluster;" ::: "memory");
      __nanosleep(HELP_NS);
      const char* src = reinterpret_cast<const char*>(x) + (size_t)blockIdx.x * 655360;
      char* dst = reinterpret_cast<char*>(out) + (size_t)blockIdx.x * 655360;
      #pragma unroll 1
      for (int i = 0; i < 16 + 3; i++) {
        if (i < 16) {
          if (i >= 4) asm volatile("cp.async.bulk.wait_group.read 0;" ::: "memory");
          mbar_expect_tx(sbase + 8 * (i & 3), 40960);
          asm volatile("cp.async.bulk.shared::cluster.global.mbarrier::complete_tx::bytes [%0], [%1], 40960, [%2];"
                       :: "r"(sbase + 1024 + (i & 3) * 40960), "l"(src + (size_t)i * 40960), "r"(sbase + 8 * (i & 3)) : "memory");
        }
        if (i >= 3) {
          const int j = i - 3;
          mbar_wait(sbase + 8 * (j & 3), (j >> 2) & 1);
          asm volatile("cp.async.bulk.global.shared::cta.bulk_group [%0], [%1], 40960;" :: "l"(dst + (size_t)j * 40960), "r"(sbase + 1024 + (j & 3) * 40960) : "memory");
          bulk_commit();
        }
      }
      bulk_wait_all();
      for (int r = 0; r < 4; r++) set_flag(F_Y + blockIdx.x * 4 + r, 0, epoch);
    }
    return;
  }
  const int cta = blockIdx.x - 4, rank = cta & 1, grp = (cta >> 1) & 1, rb = cta >> 3, ct = ((cta >> 2) & 1) * 2 + rank;
  const int total = grp == 0 ? KB_A : KB_B, gh = grp == 0 ? 52 + NX : 84 - NX;
  const uint32_t stage_bytes = grp == 0 ? STAGE_A : STAGE_B;
  const int nst = grp == 0 ? NST_A : NST_B;
  const uint32_t buf = ring + nst * stage_bytes;

  uint4 rv[5];
  if (wg != 0) {
    #pragma unroll
    for (int j = 0; j < 5; j++) rv[j] = ldg128(reinterpret_cast<const uint4*>(x + (size_t)(cta * 16 + ((tid - 128) >> 4)) * DM) + (tid & 15) + 16 * j);
  }
  const unsigned epoch = (ld_relaxed(&g_done) >> 7) + 1u;
  if (tid == 0) {
    TS(0, 0);
    for (int s = 0; s < MAXST; s++) { mbar_init(full0 + 8 * s, 2); mbar_init(empty0 + 8 * s, 4); mbar_init(dep0 + 8 * s, 1); }
    *reinterpret_cast<volatile int*>(smem + READY_OFF) = 0;
    asm volatile("fence.mbarrier_init.release.cluster;" ::: "memory");
  }
  __syncthreads();
  asm volatile("barrier.cluster.arrive.relaxed.aligned;" ::: "memory");

  if (wg == 0) {
    asm volatile("setmaxnreg.dec.sync.aligned.u32 40;");
    const int warp = tid >> 5, lane = tid & 31;
    if (warp == 0) {
      const int row = rb * 128;
      if (lane == 0) {
        for (int g = 0; g < nst; g++) {
          mbar_expect_tx(full0 + 8 * g, A_BYTES);
          tma_load_2d(ring + g * stage_bytes, &maps.m[M_X], full0 + 8 * g, g * 64, row);
          tma_load_2d(ring + g * stage_bytes + 8192, &maps.m[M_X], full0 + 8 * g, g * 64, row + 64);
        }
      }
      __syncwarp();
      cluster_wait();
      if (lane == 0) {
        int s = 0, ph = 0;
        #pragma unroll 1
        for (int g = nst; g < total; g++) {
          int mi, kb;
          a_entry(g, grp, ct, mi, kb);
          if (g == 10 || g == gh + 6 - 6 * grp || (grp == 0 && g == gh + 3)) {
            TS(0, g > 10 ? 3 : 1);
            mbar_wait(dep0 + (g == 10 ? 0 : g == gh + 6 - 6 * grp ? 24 : 8), 0);
            fence_async_global();
            TS(0, g > 10 ? 4 : 2);
          }
          mbar_wait(empty0 + 8 * s, ph);
          if (grp == 0 && g >= gh && g < gh + 6) {
            if (g < gh + 3) {
              mbar_arrive(full0 + 8 * s);
            } else {
              mbar_expect_tx(full0 + 8 * s, A_BYTES);
              tma_load_2d(ring + s * stage_bytes, &maps.m[mi], full0 + 8 * s, kb * 64, row);
              tma_load_2d(ring + s * stage_bytes + 8192, &maps.m[mi], full0 + 8 * s, kb * 64, row + 64);
            }
          } else {
            mbar_expect_tx(full0 + 8 * s, A_BYTES);
            tma_load_2d_mc(ring + s * stage_bytes + rank * 8192, &maps.m[mi], full0 + 8 * s, kb * 64, row + rank * 64, 3);
          }
          if (++s == nst) { s = 0; ph ^= 1; }
          if (g + PF_D < gh) {
            a_entry(g + PF_D, grp, ct, mi, kb);
            if (mi >= M_WSRE && (kb & 1) == (ct >> 1))
              asm volatile("cp.async.bulk.prefetch.tensor.2d.L2.global.tile [%0, {%1, %2}];" :: "l"((uint64_t)&maps.m[mi]), "r"(kb * 64), "r"(row + rank * 64) : "memory");
          }
        }
        TS(0, 5);
      }
    } else if (warp == 1) {
      if (lane == 0) {
        int s = 0, ph = 1;
        int have = 0;
        #pragma unroll 1
        for (int g = 0; g < total; g++) {
          int mi, kb, c;
          a_entry(g, grp, ct, mi, kb);
          const bool nmaj = g >= gh || (grp == 0 && g < 52);
          uint32_t bytes = 20480;
          if (g >= gh) { mi = M_WOUT; c = ct * 5; }
          else if (g >= 52) { mi = M_AB; c = DM + ct * 160; }
          else if (grp == 0) { mi = g < 20 ? M_WIN3 : M_Z23; c = 3 * ct + (g < 10 ? 12 : 0); bytes = 24576; }
          else { mi = g < 10 ? M_WDRE : g < 20 ? M_WDIM : M_AB; c = ct * 160; }
          if (g >= 20 && g < 52 && ((g - 20) >> 1) >= have) {
            if (g == 20) TS(1, 0);
            unsigned it = 0;
            while ((have = *reinterpret_cast<volatile int*>(smem + READY_OFF)) <= ((g - 20) >> 1) && ++it < 50 * POLL_LIMIT) {}
            fence_async_global();
            if (g == 20) { TS(1, 1); TC(1); }
          }
          if (g == 52) { TS(1, 2); mbar_wait(dep0 + 16, 0); fence_async_global(); TS(1, 3); TC(2); }
          const uint32_t dst = ring + s * stage_bytes + A_BYTES, fb = full0 + 8 * s;
          mbar_wait(empty0 + 8 * s, ph);
          if (++s == nst) { s = 0; ph ^= 1; }
          mbar_expect_tx(fb, bytes);
          if (nmaj) tma_load_3d(dst, &maps.m[mi], fb, 0, kb * 64, c);
          else tma_load_2d(dst, &maps.m[mi], fb, kb * 64, c);
        }
      }
      __syncwarp();
      cluster_wait();
    } else if (warp == 2) {
      if (lane < M_COUNT) asm volatile("prefetch.tensormap [%0];" :: "l"((uint64_t)&maps.m[lane]) : "memory");
      cluster_wait();
      {
        unsigned it = 0;
        uint2 v[4];
        while (true) {
          bool ok = true;
          #pragma unroll
          for (int i = 0; i < 4; i++) { v[i] = ld_tag2(&g_xstat[rb * 128 + i * 32 + lane]); ok = ok && ((v[i].y ^ epoch) & 255u) == 0; }
          if (ok || ++it > POLL_LIMIT) break;
          __nanosleep(POLL_NS);
        }
        #pragma unroll
        for (int i = 0; i < 4; i++) reinterpret_cast<uint2*>(smem + ROWSTAT_OFF)[i * 32 + lane] = make_uint2(v[i].x, v[i].y & ~255u);
        __syncwarp();
        TS(0, 6);
        if (grp == 0) bar_arrive<BAR_STATS>(320); else bar_arrive<BAR_STATS>(192);
      }
      #pragma unroll 1
      for (int i = 0; i < 5; i++) {
        const int d = i == 3 ? 4 : i == 4 ? 3 : i;
        const int slot = d == 0 ? F_XN + rb : d == 4 ? F_Y + rb : d == 3 ? F_H + rb : d == 2 ? F_B + ct : grp == 0 ? F_Z + ct : F_A + ct;
        const int byte = d == 0 ? lane & 7 : d == 4 ? 0 : d == 3 ? lane & 3 : lane & 15;
        unsigned it = 0, m;
        while ((m = __ballot_sync(0xffffffffu, get_flag(slot, byte) != (epoch & 255u))) != 0 && ++it < POLL_LIMIT) {
          if (d == 1 && lane == 0) *reinterpret_cast<volatile int*>(smem + READY_OFF) = __ffs(m) - 1;
          __nanosleep(WATCH_NS);
        }
        if (d == 1 && lane == 0) *reinterpret_cast<volatile int*>(smem + READY_OFF) = 16;
        if (d < 4) TS(0, 8 + d * 2); else TS(0, 7);
        fence_async_global();
        __syncwarp();
        if (lane == 0 && d != 1) mbar_arrive(dep0 + 8 * d);
        if (d == 2 && lane < 30) {
          asm volatile("prefetch.global.L2 [%0];" :: "l"(wout + (size_t)cta * 6 * DM + lane * 128));
          asm volatile("prefetch.global.L2 [%0];" :: "l"(wout + (size_t)cta * 6 * DM + lane * 128 + 64));
        }
      }
    } else {
      cluster_wait();
      bar_sync<BAR_LN>(288);
      if (lane == 0) {
        TS(1, 5);
        asm volatile("cp.async.bulk.global.shared::cta.bulk_group [%0], [%1], 20480;" :: "l"(g_xn + (size_t)cta * 16 * DM), "r"(buf) : "memory");
        bulk_commit();
        bulk_wait_all();
        set_flag(F_XN + rb, cta & 7, epoch);
        TS(1, 6);
      }
      __syncwarp();
      if (grp == 0) {
        #pragma unroll 1
        for (int i = 0; i < 2; i++) gather96(&g_csum[ct * 192 + i * 96 + lane], reinterpret_cast<float*>(smem + COLSUM_OFF) + i * 96 + lane, epoch);
      } else {
        unsigned it = 0;
        while (true) {
          bool ok = true;
          #pragma unroll
          for (int j = 0; j < 5; j++) {
            const uint2 u = ld_tag2(&g_csum[5 * FH + ct * 160 + j * 32 + lane]);
            ok = ok && u.y == epoch;
            reinterpret_cast<uint32_t*>(smem + COLSUM_OFF)[j * 32 + lane] = u.x;
          }
          if (ok || ++it > POLL_LIMIT) break;
          __nanosleep(2 * POLL_NS);
        }
      }
      __syncwarp();
      TS(1, 4);
      if (grp == 0) {
        bar_arrive<BAR_STATS>(320);
        bar_sync<BAR_PUB1>(160);
        if (lane == 0) set_flag(F_Z + ct, rb, epoch);
        TS(1, 8);
        __syncwarp();
        bar_arrive<BAR_BUF>(160);
      } else {
        bar_arrive<BAR_STATS>(192);
        bar_sync<BAR_PUB2>(160);
        if (lane == 0) set_flag(F_A + ct, rb, epoch);
        TS(1, 9);
        __syncwarp();
      }
      bar_sync<BAR_PUB1>(160);
      if (lane == 0) {
        set_flag(grp == 0 ? F_H + rb : F_B + ct, grp == 0 ? ct : rb, epoch);
        if (grp == 0) mbar_arrive_cluster(dep0 + 8, rank ^ 1);
      }
      TS(1, 10);
      __syncwarp();
      bar_arrive<BAR_BUF>(160);
    }
  } else {
    asm volatile("setmaxnreg.inc.sync.aligned.u32 232;");
    const int t = tid & 127, w = t >> 5, l = t & 31;
    ln_rows(rv, buf, cta, epoch);
    TS(wg + 1, 0);
    cluster_wait();
    const uint32_t st_base = buf + (w * 16 + ((l >> 3) & 1) * 8 + (l & 7)) * 128;
    const uint32_t st_x = ((l >> 4) ^ (l & 7)) << 4;
    const float2* rs = reinterpret_cast<const float2*>(smem + ROWSTAT_OFF) + w * 16 + (l >> 2);
    const float2* cs = reinterpret_cast<const float2*>(smem + COLSUM_OFF) + (l & 3);
    if (grp == 0) {
      {
        const int mb = wg - 1;
        float acc[1][96];
        zero(acc);
        mainloop<192, 1, 1, false, 0>(acc, sbase, 0, 0, 10, mb);
        drain(acc, sbase, 0, 9);
        TS(wg + 1, 1);
        bar_sync<BAR_STATS>(320);
        const float2 s0 = rs[mb * 64], s1 = rs[mb * 64 + 8];
        const float nm[2] = {s0.y / s0.x, s1.y / s1.x}, hr[2] = {0.5f * s0.x, 0.5f * s1.x};
        const float k1[2] = {0.7978845608f * s0.x, 0.7978845608f * s1.x};
        const float k2[2] = {0.0356774081f * s0.x * s0.x * s0.x, 0.0356774081f * s1.x * s1.x * s1.x};
        float sm0 = 0.f, sm1 = 0.f, q0 = 0.f, q1 = 0.f;
        #pragma unroll
        for (int jj = 0; jj < 12; jj++) {
          float u[8];
          #pragma unroll
          for (int hf = 0; hf < 2; hf++) {
            const float2 c = cs[jj * 8 + hf * 4];
            #pragma unroll
            for (int e = 0; e < 4; e++) {
              const float wv = fmaf(nm[e >> 1], (e & 1) ? c.y : c.x, acc[0][8 * jj + 4 * hf + e]);
              float th; asm("tanh.approx.f32 %0, %1;" : "=f"(th) : "f"(wv * fmaf(k2[e >> 1], wv * wv, k1[e >> 1])));
              const float hv = hr[e >> 1] * wv;
              u[4 * hf + e] = fmaf(hv, th, hv);
            }
            sm0 += u[4 * hf] + u[4 * hf + 1]; q0 = fmaf(u[4 * hf], u[4 * hf], q0); q0 = fmaf(u[4 * hf + 1], u[4 * hf + 1], q0);
            sm1 += u[4 * hf + 2] + u[4 * hf + 3]; q1 = fmaf(u[4 * hf + 2], u[4 * hf + 2], q1); q1 = fmaf(u[4 * hf + 3], u[4 * hf + 3], q1);
          }
          stsm4(st_base + mb * 24576 + (jj >> 2) * 8192 + (st_x ^ ((jj & 3) << 5)),
                pack_bf16(u[0], u[1]), pack_bf16(u[2], u[3]), pack_bf16(u[4], u[5]), pack_bf16(u[6], u[7]));
        }
        #pragma unroll
        for (int o = 1; o < 4; o <<= 1) {
          sm0 += __shfl_xor_sync(0xffffffffu, sm0, o); q0 += __shfl_xor_sync(0xffffffffu, q0, o);
          sm1 += __shfl_xor_sync(0xffffffffu, sm1, o); q1 += __shfl_xor_sync(0xffffffffu, q1, o);
        }
        if ((l & 3) < 2) {
          const float sm = (l & 1) ? sm1 : sm0, sv = (l & 1) ? q1 : q0;
          const int row = mb * 64 + w * 16 + (l & 1) * 8 + (l >> 2);
          const float mu = sm * (1.f / 192), m2 = fmaxf(sv - sm * mu, 0.f);
          st_tag2(&g_zstat[(rb * 4 + ct) * 128 + row], __float_as_uint(mu), (__float_as_uint(m2) & ~255u) | (epoch & 255u));
          reinterpret_cast<float2*>(smem + ZSTAT_OFF)[row] = make_float2(mu, m2);
        }
        TS(wg + 1, 4);
      }
      float acc[2][96];
      if (wg == 1) {
        bar_sync<BAR_U>(256);
        uint2 v[3];
        unsigned n = 0;
        while (true) {
          bool ok = true;
          #pragma unroll
          for (int j = 0; j < 3; j++) { v[j] = ld_tag2(&g_zstat[(rb * 4 + ((ct + 1 + j) & 3)) * 128 + t]); ok = ok && ((v[j].y ^ epoch) & 255u) == 0; }
          if (ok || ++n > POLL_LIMIT) break;
          __nanosleep(POLL_NS);
        }
        const float2 own = reinterpret_cast<const float2*>(smem + ZSTAT_OFF)[t];
        const float m0 = __uint_as_float(v[0].x), m1 = __uint_as_float(v[1].x), m3 = __uint_as_float(v[2].x);
        const float mean = 0.25f * ((own.x + m0) + (m1 + m3));
        const float d = (own.x - mean) * (own.x - mean) + (m0 - mean) * (m0 - mean) + (m1 - mean) * (m1 - mean) + (m3 - mean) * (m3 - mean);
        const float var = fmaf(192.f, d, (own.y + __uint_as_float(v[0].y & ~255u)) + (__uint_as_float(v[1].y & ~255u) + __uint_as_float(v[2].y & ~255u)));
        const float r = rsqrtf(var * (1.f / FH) + LN_EPS);
        TS(2, 5);
        const uint32_t rbase = buf + (t >> 6) * 24576 + (t & 63) * 128;
        const uint32_t m2 = pack_bf16(-mean, -mean), r2 = pack_bf16(r, r);
        const float res = (-mean - bf_lo(m2)) * r;
        const uint32_t e2 = pack_bf16(res, res);
        #pragma unroll 1
        for (int c = 0; c < 3; c++) {
          uint4 z[8];
          #pragma unroll
          for (int i = 0; i < 8; i++) z[i] = lds128(rbase + c * 8192 + (((i ^ l) & 7) << 4));
          #pragma unroll
          for (int i = 0; i < 8; i++)
            sts128(rbase + c * 8192 + (((i ^ l) & 7) << 4), hfma2_bf16(hadd2_bf16(z[i].x, m2), r2, e2), hfma2_bf16(hadd2_bf16(z[i].y, m2), r2, e2),
                   hfma2_bf16(hadd2_bf16(z[i].z, m2), r2, e2), hfma2_bf16(hadd2_bf16(z[i].w, m2), r2, e2));
          fence_async_smem();
          __syncwarp();
          if (l == 0) {
            tma_store_2d(&maps.m[M_ZS], buf + (w >> 1) * 24576 + c * 8192 + (w & 1) * 4096, ct * 192 + c * 64, rb * 128 + w * 32);
            bulk_commit();
          }
        }
        TS(2, 6);
        if (l == 0) bulk_wait_all();
        __syncwarp();
        bar_arrive<BAR_PUB1>(160);
        {
          const bf16* bp = bsp + rb * 128 + w * 16 + (l >> 2);
          const float bb[4] = {__bfloat162float(bp[0]), __bfloat162float(bp[8]), __bfloat162float(bp[64]), __bfloat162float(bp[72])};
          #pragma unroll
          for (int i = 0; i < 96; i++) { acc[0][i] = bb[(i >> 1) & 1]; acc[1][i] = bb[2 + ((i >> 1) & 1)]; }
          pin(acc);
        }
        bar_sync<BAR_ORD2>(256);
        mainloop<192, 2, 1, false, BAR_ORD1>(acc, sbase, 0, 20, 32);
        bar_sync<BAR_Z1>(256);
        uint32_t z[6][4][4];
        #pragma unroll
        for (int i = 0; i < ZPRE; i++) ldsm4(st_base + (i >> 2) * 8192 + (st_x ^ ((i & 3) << 5)), z[i >> 2][i & 3][0], z[i >> 2][i & 3][1], z[i >> 2][i & 3][2], z[i >> 2][i & 3][3]);
        drain(acc, sbase, 0, 51);
        TS(2, 7);
        #pragma unroll
        for (int bx = 0; bx < 6; bx++) {
          if (bx >= 1) {
            #pragma unroll
            for (int i = ZPRE + (bx - 1) * 10; i < ZPRE + bx * 10; i++)
              if (i < 24) ldsm4(st_base + (i >> 2) * 8192 + (st_x ^ ((i & 3) << 5)), z[i >> 2][i & 3][0], z[i >> 2][i & 3][1], z[i >> 2][i & 3][2], z[i >> 2][i & 3][3]);
          }
          #pragma unroll
          for (int i = 0; i < 4; i++) {
            const float* a = &acc[bx / 3][8 * ((bx % 3) * 4 + i)];
            const uint32_t* zz = z[bx][i];
            stsm4(st_base + bx * 8192 + (st_x ^ (i << 5)),
                  hmul2_bf16(zz[0], pack_bf16(a[0], a[1])), hmul2_bf16(zz[1], pack_bf16(a[2], a[3])),
                  hmul2_bf16(zz[2], pack_bf16(a[4], a[5])), hmul2_bf16(zz[3], pack_bf16(a[6], a[7])));

          }
          if (bx % 3 == 2) {
            fence_async_smem();
            __syncwarp();
            if (l < 3) {
              tma_store_2d(&maps.m[M_HS], buf + (bx - 2 + l) * 8192 + w * 2048, ct * 192 + l * 64, rb * 128 + (bx / 3) * 64 + w * 16);
              bulk_commit();
            }
          }
        }
        bar_arrive<BAR_U>(256);
        TS(2, 8);
        if (l < 3) bulk_wait_all();
        __syncwarp();
        bar_arrive<BAR_PUB1>(160);
        TS(2, 9);
        return;
      }
      bar_arrive<BAR_U>(256);
      zero(acc);
      mainloop<192, 2, 1, false, BAR_ORD2>(acc, sbase, 0, 10, 10);
      drain(acc, sbase, 0, 19);
      TS(3, 2);
      bar_sync<BAR_BUF>(160);
      #pragma unroll
      for (int mi = 0; mi < 2; mi++)
        #pragma unroll
        for (int jj = 0; jj < 12; jj++) {
          const float* a = &acc[mi][8 * jj];
          stsm4(st_base + mi * 24576 + (jj >> 2) * 8192 + (st_x ^ ((jj & 3) << 5)),
                pack_bf16(a[0], a[1]), pack_bf16(a[2], a[3]), pack_bf16(a[4], a[5]), pack_bf16(a[6], a[7]));
        }
      __syncwarp();
      TS(3, 3);
      const uint32_t rbase = buf + (l >> 4) * 24576 + (w * 16 + (l & 15)) * 128;
      #pragma unroll 1
      for (int c2 = 0; c2 < 12; c2++) {
        const uint32_t ab = rbase + (c2 >> 2) * 8192;
        uint4 v[2];
        #pragma unroll
        for (int i = 0; i < 2; i++) v[i] = lds128(ab + (((((c2 & 3) * 2 + i) ^ l) & 7) << 4));
        #pragma unroll
        for (int i = 0; i < 2; i++)
          sts128(ab + (((((c2 & 3) * 2 + i) ^ l) & 7) << 4),
                 pack_bf16(gelu_tanh(bf_lo(v[i].x)), gelu_tanh(bf_hi(v[i].x))), pack_bf16(gelu_tanh(bf_lo(v[i].y)), gelu_tanh(bf_hi(v[i].y))),
                 pack_bf16(gelu_tanh(bf_lo(v[i].z)), gelu_tanh(bf_hi(v[i].z))), pack_bf16(gelu_tanh(bf_lo(v[i].w)), gelu_tanh(bf_hi(v[i].w))));
        __nanosleep(Z1_NS);
      }
      TS(3, 5);
      bar_arrive<BAR_Z1>(256);
    }
    float acc[2][80];
    if (grp == 1) {
      zero(acc);
      if (wg == 2) {
        mainloop<160, 2, 0, false, BAR_ORD2>(acc, sbase, 1, 0, 10);
      } else {
        weight_sums(win, wdre, rb * 4 + ct, epoch);
        TS(2, 1);
        bar_sync<BAR_ORD2>(256);
        mainloop<160, 2, 0, false, BAR_ORD1>(acc, sbase, 1, 10, 10);
      }
      drain(acc, sbase, 1, wg == 2 ? 9 : 19);
      TS(wg + 1, wg == 1 ? 7 : 2);
      if (wg == 1) bar_sync<BAR_Z1>(256); else bar_sync<BAR_STATS>(192);
      const uint32_t tb = buf + ((l >> 4) * 8 + (l & 7)) * 128 + (((w * 2 + ((l >> 3) & 1)) ^ (l & 7)) << 4);
      float2 st[4];
      #pragma unroll
      for (int r = 0; r < 4; r++) st[r] = wg == 2 ? rs[(r >> 1) * 64 + (r & 1) * 8] : make_float2(-1.f, 0.f);
      #pragma unroll
      for (int jj = 0; jj < 10; jj++) {
        const float2 c0 = cs[jj * 8], c1 = cs[jj * 8 + 4];
        #pragma unroll
        for (int mi = 0; mi < 2; mi++) {
          const float* a = &acc[mi][8 * jj];
          const float2 s0 = st[mi * 2], s1 = st[mi * 2 + 1];
          stsm4_t(tb + mi * 20480 + jj * 2048,
                  pack_bf16(fmaf(a[0], s0.x, s0.y * c0.x), fmaf(a[1], s0.x, s0.y * c0.y)), pack_bf16(fmaf(a[2], s1.x, s1.y * c0.x), fmaf(a[3], s1.x, s1.y * c0.y)),
                  pack_bf16(fmaf(a[4], s0.x, s0.y * c1.x), fmaf(a[5], s0.x, s0.y * c1.y)), pack_bf16(fmaf(a[6], s1.x, s1.y * c1.x), fmaf(a[7], s1.x, s1.y * c1.y)));
        }
      }
      fence_async_smem();
      if (wg == 1) bar_sync<BAR_WG1>(128); else bar_sync<BAR_WG2>(128);
      TS(wg + 1, wg == 1 ? 8 : 6);
      if (l < 2) {
        tma_store_2d(&maps.m[M_ABS], buf + l * 20480 + w * 5120, rb * 128 + l * 64, (2 - wg) * DM + ct * 160 + w * 40);
        bulk_commit();
        bulk_wait_all();
      }
      __syncwarp();
      TS(wg + 1, wg == 1 ? 9 : 10);
      if (wg == 1) {
        bar_arrive<BAR_PUB1>(160);
        return;
      }
      bar_arrive<BAR_PUB2>(160);
      bar_arrive<BAR_Z1>(256);
    }
    zero(acc);
    bar_sync<BAR_ORD1>(256);
    mainloop<160, 2, 0, false, 0>(acc, sbase, grp, grp == 0 ? 52 : 20, grp == 0 ? NX : 64 - NX);
    if (grp == 0) {
      bar_sync<BAR_U>(256);
      mainloop<160, 2, 2, true, 0, true>(acc, sbase, 0, 52 + NX, 3);
    }
    mainloop<160, 2, 2, true, 0>(acc, sbase, grp, gh + 3 - 3 * grp, total - gh - 3 + 3 * grp);
    const uint32_t slab = buf + w * (16 * 320);
    const uint32_t addr = slab + (((l >> 3) & 1) * 8 + (l & 7)) * 320 + (l >> 4) * 16;
    bar_sync<BAR_BUF>(160);
    mbar_wait(dep0 + 32, 0);
    drain(acc, sbase, grp, total - 1);
    TS(3, 12);
    #pragma unroll
    for (int mi = 0; mi < 2; mi++) {
      #pragma unroll
      for (int jj = 0; jj < 10; jj++) {
        const float* a = &acc[mi][8 * jj];
        stsm4(addr + mi * 20480 + jj * 32, pack_bf16(a[0], a[1]), pack_bf16(a[2], a[3]), pack_bf16(a[4], a[5]), pack_bf16(a[6], a[7]));
      }
      fence_async_smem();
      __syncwarp();
      if (l == 0) {
        tma_reduce_2d(&maps.m[M_OUT], slab + mi * 20480, ct * 160, rb * 128 + mi * 64 + w * 16);
        bulk_commit();
      }
    }
    TS(3, 13);
    if (l == 0) {
      bulk_wait_read();
      if (w == 0) atomicAdd(&g_done, 1u);
    }
    TS(3, 15);
  }
}

typedef CUresult (*EncodeFn)(CUtensorMap*, CUtensorMapDataType, cuuint32_t, void*, const cuuint64_t*, const cuuint64_t*,
                             const cuuint32_t*, const cuuint32_t*, CUtensorMapInterleave, CUtensorMapSwizzle,
                             CUtensorMapL2promotion, CUtensorMapFloatOOBfill);

void make2d(EncodeFn enc, CUtensorMap* m, const void* p, uint64_t cols, uint64_t rows, uint32_t bc, uint32_t br, bool swz = true) {
  cuuint64_t gd[2] = {cols, rows}, gs[1] = {cols * 2};
  cuuint32_t bd[2] = {bc, br}, es[2] = {1, 1};
  enc(m, CU_TENSOR_MAP_DATA_TYPE_BFLOAT16, 2, const_cast<void*>(p), gd, gs, bd, es, CU_TENSOR_MAP_INTERLEAVE_NONE,
      swz ? CU_TENSOR_MAP_SWIZZLE_128B : CU_TENSOR_MAP_SWIZZLE_NONE, CU_TENSOR_MAP_L2_PROMOTION_L2_128B, CU_TENSOR_MAP_FLOAT_OOB_FILL_NONE);
}
void make3d(EncodeFn enc, CUtensorMap* m, const void* p, uint64_t cols, uint64_t rows, uint32_t cw, uint32_t nc, uint32_t br = 64) {
  cuuint64_t gd[3] = {cw, rows, cols / cw}, gs[2] = {cols * 2, cw * 2};
  cuuint32_t bd[3] = {cw, br, nc}, es[3] = {1, 1, 1};
  enc(m, CU_TENSOR_MAP_DATA_TYPE_BFLOAT16, 3, const_cast<void*>(p), gd, gs, bd, es, CU_TENSOR_MAP_INTERLEAVE_NONE,
      cw == 64 ? CU_TENSOR_MAP_SWIZZLE_128B : CU_TENSOR_MAP_SWIZZLE_64B, CU_TENSOR_MAP_L2_PROMOTION_L2_128B, CU_TENSOR_MAP_FLOAT_OOB_FILL_NONE);
}

}

extern "C" void kernel_launch(void* const* d_in, const int* in_sizes, int n_in, void* d_out, int out_size) {
  const bf16* x = (const bf16*)d_in[0];
  const bf16* wsre = (const bf16*)d_in[1];
  const bf16* wsim = (const bf16*)d_in[2];
  const bf16* wdre = (const bf16*)d_in[3];
  const bf16* wdim = (const bf16*)d_in[4];
  const bf16* win = (const bf16*)d_in[6];
  const bf16* wsp = (const bf16*)d_in[7];
  const bf16* bsp = (const bf16*)d_in[8];
  const bf16* wout = (const bf16*)d_in[9];

  void* fn = nullptr;
  cudaDriverEntryPointQueryResult qr;
  cudaGetDriverEntryPoint("cuTensorMapEncodeTiled", &fn, cudaEnableDefault, &qr);
  EncodeFn enc = (EncodeFn)fn;
  void *abT, *z2, *h, *xn;
  cudaGetSymbolAddress(&xn, g_xn);
  cudaGetSymbolAddress(&abT, g_abT);
  cudaGetSymbolAddress(&z2, g_z2);
  cudaGetSymbolAddress(&h, g_h);

  Maps maps;
  make2d(enc, &maps.m[M_X], x, DM, SEQ, 64, 64);
  make2d(enc, &maps.m[M_XN], xn, DM, SEQ, 64, 64);
  make2d(enc, &maps.m[M_WSRE], wsre, SEQ, SEQ, 64, 64);
  make2d(enc, &maps.m[M_WSIM], wsim, SEQ, SEQ, 64, 64);
  make2d(enc, &maps.m[M_WSP], wsp, SEQ, SEQ, 64, 64);
  make2d(enc, &maps.m[M_H], h, FH, SEQ, 64, 64);
  make3d(enc, &maps.m[M_WIN3], win, FF, DM, 64, 3);
  make3d(enc, &maps.m[M_Z23], z2, FH, SEQ, 64, 3);
  make2d(enc, &maps.m[M_WDRE], wdre, DM, DM, 64, 160);
  make2d(enc, &maps.m[M_WDIM], wdim, DM, DM, 64, 160);
  make2d(enc, &maps.m[M_AB], abT, SEQ, 2 * DM, 64, 160);
  make3d(enc, &maps.m[M_WOUT], wout, DM, FH, 32, 5);
  make2d(enc, &maps.m[M_HS], h, FH, SEQ, 64, 16);
  make2d(enc, &maps.m[M_ZS], z2, FH, SEQ, 64, 32);
  make2d(enc, &maps.m[M_ABS], abT, SEQ, 2 * DM, 64, 40);
  make2d(enc, &maps.m[M_OUT], d_out, DM, SEQ, 160, 16, false);

  cudaFuncSetAttribute(fused_kernel, cudaFuncAttributeMaxDynamicSharedMemorySize, SMEM_BYTES);
  fused_kernel<<<132, 384, SMEM_BYTES>>>(maps, x, win, wdre, bsp, wout, (bf16*)d_out);
}
```

```cpp
#include <cuda_runtime.h>
#include <cuda_bf16.h>
#include <cuda.h>
#include <stdint.h>

namespace {

typedef __nv_bfloat16 bf16;

constexpr int SEQ = 2048, DM = 640, FF = 1536, FH = 768;
#define NOV 3
#define NXV 5
constexpr int NX = NXV;
constexpr int NO = NOV;
constexpr int NST_A = 4, NST_B = 5, MAXST = 5;
constexpr int A_BYTES = 16384;
constexpr int BAR_OFF = 0;
constexpr int READY_OFF = 128;
constexpr int COLSUM_OFF = 256;
constexpr int ROWSTAT_OFF = 1024;
constexpr int ZSTAT_OFF = 2048;
constexpr int RED_OFF = 3072;
constexpr int RING_OFF = 4096;
constexpr int STAGE_A = 40960, STAGE_B = 36864;
constexpr int SMEM_BYTES = RING_OFF + 5 * STAGE_B + 40960;
constexpr int KB_A = 52 + NX + 12 - NO;
constexpr int KB_B = 84 - NX + NO;
constexpr float LN_EPS = 1e-5f;
constexpr unsigned POLL_LIMIT = 100000;
constexpr unsigned POLL_NS = 100, WATCH_NS = 40;
constexpr unsigned Z1_NS = 600;
constexpr int PF_D = 8;
constexpr int ZPRE = 6;

#define ST_A 0
#define ST_B 400
#define HELP_NS 4000
constexpr int BAR_ORD1 = 1, BAR_ORD2 = 2, BAR_WG1 = 3, BAR_WG2 = 4, BAR_LN = 5, BAR_BUF = 6, BAR_Z1 = 7, BAR_PUB1 = 8, BAR_PUB2 = 9,
              BAR_STATS = 10, BAR_U = 11;

enum { M_X, M_XN, M_WSRE, M_WSIM, M_WSP, M_H, M_WIN3, M_Z23, M_WDRE, M_WDIM, M_AB, M_WOUT, M_OUT, M_HS, M_ZS, M_ABS, M_COUNT };
struct Maps { CUtensorMap m[M_COUNT]; };

__device__ __align__(1024) bf16 g_abT[2 * DM * SEQ];
__device__ __align__(1024) bf16 g_z2[SEQ * FH];
__device__ __align__(1024) bf16 g_h[SEQ * FH];
__device__ __align__(1024) bf16 g_xn[SEQ * DM];
__device__ __align__(16) uint2 g_xstat[SEQ];
__device__ __align__(16) uint2 g_csum[5 * FH + DM];
__device__ __align__(16) uint2 g_zstat[64 * 128];
__device__ __align__(256) unsigned char g_flags[108 * 256];
constexpr int F_A = 0, F_B = 4, F_Z = 8, F_H = 12, F_XN = 28, F_Y = 44;
__device__ unsigned g_done;
#define TS(role, ev)
#define TC(i)

extern __shared__ __align__(1024) uint8_t smem[];

__device__ __forceinline__ uint32_t smem_u32(const void* p) { return (uint32_t)__cvta_generic_to_shared(p); }
__device__ __forceinline__ void mbar_init(uint32_t bar, uint32_t cnt) { asm volatile("mbarrier.init.shared::cta.b64 [%0], %1;" :: "r"(bar), "r"(cnt)); }
__device__ __forceinline__ void mbar_expect_tx(uint32_t bar, uint32_t bytes) { asm volatile("mbarrier.arrive.expect_tx.shared::cta.b64 _, [%0], %1;" :: "r"(bar), "r"(bytes) : "memory"); }
__device__ __forceinline__ void mbar_arrive(uint32_t bar) { asm volatile("mbarrier.arrive.shared::cta.b64 _, [%0];" :: "r"(bar) : "memory"); }
__device__ __forceinline__ void mbar_arrive_cluster(uint32_t bar, uint32_t cta) {
  asm volatile("{\n.reg .b32 ra;\nmapa.shared::cluster.u32 ra, %0, %1;\nmbarrier.arrive.shared::cluster.b64 _, [ra];\n}" :: "r"(bar), "r"(cta) : "memory");
}
__device__ __forceinline__ void mbar_wait(uint32_t bar, uint32_t parity) {
  asm volatile("{\n.reg .pred p;\n.reg .u32 n;\nmov.u32 n, 0;\n"
               "LW: mbarrier.try_wait.parity.shared::cta.b64 p, [%0], %1, 2000;\n@p bra LD;\n"
               "add.u32 n, n, 1;\nsetp.lt.u32 p, n, 20000;\n@p bra LW;\nLD:\n}" :: "r"(bar), "r"(parity) : "memory");
}
__device__ __forceinline__ void tma_load_2d(uint32_t dst, const CUtensorMap* map, uint32_t bar, int c0, int c1) {
  asm volatile("cp.async.bulk.tensor.2d.shared::cluster.global.mbarrier::complete_tx::bytes [%0], [%1, {%3, %4}], [%2];"
    :: "r"(dst), "l"((uint64_t)map), "r"(bar), "r"(c0), "r"(c1) : "memory");
}
__device__ __forceinline__ void tma_load_3d(uint32_t dst, const CUtensorMap* map, uint32_t bar, int c0, int c1, int c2) {
  asm volatile("cp.async.bulk.tensor.3d.shared::cluster.global.mbarrier::complete_tx::bytes [%0], [%1, {%3, %4, %5}], [%2];"
    :: "r"(dst), "l"((uint64_t)map), "r"(bar), "r"(c0), "r"(c1), "r"(c2) : "memory");
}
__device__ __forceinline__ void tma_load_2d_mc(uint32_t dst, const CUtensorMap* map, uint32_t bar, int c0, int c1, uint16_t mask) {
  asm volatile("cp.async.bulk.tensor.2d.shared::cluster.global.mbarrier::complete_tx::bytes.multicast::cluster [%0], [%1, {%3, %4}], [%2], %5;"
    :: "r"(dst), "l"((uint64_t)map), "r"(bar), "r"(c0), "r"(c1), "h"(mask) : "memory");
}
__device__ __forceinline__ void tma_store_2d(const CUtensorMap* map, uint32_t src, int c0, int c1) {
  asm volatile("cp.async.bulk.tensor.2d.global.shared::cta.bulk_group [%0, {%2, %3}], [%1];"
    :: "l"((uint64_t)map), "r"(src), "r"(c0), "r"(c1) : "memory");
}
__device__ __forceinline__ void tma_reduce_2d(const CUtensorMap* map, uint32_t src, int c0, int c1) {
  asm volatile("cp.reduce.async.bulk.tensor.2d.global.shared::cta.add.tile.bulk_group [%0, {%2, %3}], [%1];"
    :: "l"((uint64_t)map), "r"(src), "r"(c0), "r"(c1) : "memory");
}
__device__ __forceinline__ void bulk_wait_all() { asm volatile("cp.async.bulk.wait_group 0;" ::: "memory"); }
__device__ __forceinline__ void bulk_commit() { asm volatile("cp.async.bulk.commit_group;" ::: "memory"); }
__device__ __forceinline__ void bulk_wait_read() { asm volatile("cp.async.bulk.wait_group.read 0;" ::: "memory"); }
__device__ __forceinline__ void fence_async_smem() { asm volatile("fence.proxy.async.shared::cta;" ::: "memory"); }
__device__ __forceinline__ void fence_async_global() { asm volatile("fence.proxy.async.global;" ::: "memory"); }
__device__ __forceinline__ void wgmma_fence() { asm volatile("wgmma.fence.sync.aligned;" ::: "memory"); }
__device__ __forceinline__ void wgmma_commit() { asm volatile("wgmma.commit_group.sync.aligned;" ::: "memory"); }
template<int N> __device__ __forceinline__ void wgmma_wait() { asm volatile("wgmma.wait_group.sync.aligned %0;" :: "n"(N) : "memory"); }
template<int ID> __device__ __forceinline__ void bar_sync(int n) { asm volatile("bar.sync %0, %1;" :: "n"(ID), "r"(n) : "memory"); }
template<int ID> __device__ __forceinline__ void bar_arrive(int n) { asm volatile("bar.arrive %0, %1;" :: "n"(ID), "r"(n) : "memory"); }
__device__ __forceinline__ void cluster_wait() { asm volatile("barrier.cluster.wait.aligned;" ::: "memory"); }
__device__ __forceinline__ uint64_t desc64(uint32_t lo, uint32_t hi) { return (uint64_t)lo | ((uint64_t)hi << 32); }
__device__ __forceinline__ uint2 ld_tag2(const uint2* p) {
  uint2 v; asm volatile("ld.relaxed.gpu.global.v2.u32 {%0,%1}, [%2];" : "=r"(v.x), "=r"(v.y) : "l"(p) : "memory"); return v;
}
__device__ __forceinline__ void st_tag2(uint2* p, uint32_t a, uint32_t b) {
  asm volatile("st.relaxed.gpu.global.v2.u32 [%0], {%1,%2};" :: "l"(p), "r"(a), "r"(b) : "memory");
}
__device__ __forceinline__ void stg128(void* p, uint4 v) {
  asm volatile("st.global.v4.u32 [%0], {%1,%2,%3,%4};" :: "l"(p), "r"(v.x), "r"(v.y), "r"(v.z), "r"(v.w));
}
__device__ __forceinline__ unsigned ld_relaxed(const unsigned* p) {
  unsigned v; asm volatile("ld.relaxed.gpu.global.u32 %0, [%1];" : "=r"(v) : "l"(p) : "memory"); return v;
}
__device__ __forceinline__ uint32_t pack_bf16(float lo, float hi) {
  uint32_t r; asm("cvt.rn.bf16x2.f32 %0, %1, %2;" : "=r"(r) : "f"(hi), "f"(lo)); return r;
}
__device__ __forceinline__ float bf_lo(uint32_t v) { return __uint_as_float(v << 16); }
__device__ __forceinline__ float bf_hi(uint32_t v) { return __uint_as_float(v & 0xFFFF0000u); }
__device__ __forceinline__ void stsm4(uint32_t addr, uint32_t a, uint32_t b, uint32_t c, uint32_t d) {
  asm volatile("stmatrix.sync.aligned.m8n8.x4.shared.b16 [%0], {%1,%2,%3,%4};" :: "r"(addr), "r"(a), "r"(b), "r"(c), "r"(d));
}
__device__ __forceinline__ void stsm4_t(uint32_t addr, uint32_t a, uint32_t b, uint32_t c, uint32_t d) {
  asm volatile("stmatrix.sync.aligned.m8n8.x4.trans.shared.b16 [%0], {%1,%2,%3,%4};" :: "r"(addr), "r"(a), "r"(b), "r"(c), "r"(d));
}
__device__ __forceinline__ void ldsm4(uint32_t addr, uint32_t& a, uint32_t& b, uint32_t& c, uint32_t& d) {
  asm volatile("ldmatrix.sync.aligned.m8n8.x4.shared.b16 {%0,%1,%2,%3}, [%4];" : "=r"(a), "=r"(b), "=r"(c), "=r"(d) : "r"(addr));
}
__device__ __forceinline__ uint4 lds128(uint32_t a) {
  uint4 v; asm volatile("ld.shared.v4.u32 {%0,%1,%2,%3}, [%4];" : "=r"(v.x), "=r"(v.y), "=r"(v.z), "=r"(v.w) : "r"(a)); return v;
}
__device__ __forceinline__ void sts128(uint32_t a, uint32_t x, uint32_t y, uint32_t z, uint32_t w) {
  asm volatile("st.shared.v4.u32 [%0], {%1,%2,%3,%4};" :: "r"(a), "r"(x), "r"(y), "r"(z), "r"(w));
}
__device__ __forceinline__ uint32_t hmul2_bf16(uint32_t a, uint32_t b) {
  uint32_t r; asm("mul.rn.bf16x2 %0, %1, %2;" : "=r"(r) : "r"(a), "r"(b)); return r;
}
__device__ __forceinline__ uint32_t hadd2_bf16(uint32_t a, uint32_t b) {
  uint32_t r; asm("add.rn.bf16x2 %0, %1, %2;" : "=r"(r) : "r"(a), "r"(b)); return r;
}
__device__ __forceinline__ uint32_t hfma2_bf16(uint32_t a, uint32_t b, uint32_t c) {
  uint32_t r; asm("fma.rn.bf16x2 %0, %1, %2, %3;" : "=r"(r) : "r"(a), "r"(b), "r"(c)); return r;
}
__device__ __forceinline__ float gelu_tanh(float v) {
  float u = v * fmaf(0.0356774081f, v * v, 0.7978845608f);
  float t; asm("tanh.approx.f32 %0, %1;" : "=f"(t) : "f"(u));
  float hv = 0.5f * v;
  return fmaf(hv, t, hv);
}

template<int TB>
__device__ __forceinline__ void wgmma_n192(float (&d)[96], uint64_t da, uint64_t db, int scale_d) {
  asm volatile("{\n.reg .pred p;\nsetp.ne.b32 p, %98, 0;\n"
   "wgmma.mma_async.sync.aligned.m64n192k16.f32.bf16.bf16 {%0,%1,%2,%3,%4,%5,%6,%7,%8,%9,%10,%11,%12,%13,%14,%15,%16,%17,%18,%19,%20,%21,%22,%23,%24,%25,%26,%27,%28,%29,%30,%31,%32,%33,%34,%35,%36,%37,%38,%39,%40,%41,%42,%43,%44,%45,%46,%47,%48,%49,%50,%51,%52,%53,%54,%55,%56,%57,%58,%59,%60,%61,%62,%63,%64,%65,%66,%67,%68,%69,%70,%71,%72,%73,%74,%75,%76,%77,%78,%79,%80,%81,%82,%83,%84,%85,%86,%87,%88,%89,%90,%91,%92,%93,%94,%95}, %96, %97, p, 1, 1, 0, %99;\n}"
   : "+f"(d[0]),"+f"(d[1]),"+f"(d[2]),"+f"(d[3]),"+f"(d[4]),"+f"(d[5]),"+f"(d[6]),"+f"(d[7]),"+f"(d[8]),"+f"(d[9]),"+f"(d[10]),"+f"(d[11]),"+f"(d[12]),"+f"(d[13]),"+f"(d[14]),"+f"(d[15]),"+f"(d[16]),"+f"(d[17]),"+f"(d[18]),"+f"(d[19]),"+f"(d[20]),"+f"(d[21]),"+f"(d[22]),"+f"(d[23]),"+f"(d[24]),"+f"(d[25]),"+f"(d[26]),"+f"(d[27]),"+f"(d[28]),"+f"(d[29]),"+f"(d[30]),"+f"(d[31]),"+f"(d[32]),"+f"(d[33]),"+f"(d[34]),"+f"(d[35]),"+f"(d[36]),"+f"(d[37]),"+f"(d[38]),"+f"(d[39]),"+f"(d[40]),"+f"(d[41]),"+f"(d[42]),"+f"(d[43]),"+f"(d[44]),"+f"(d[45]),"+f"(d[46]),"+f"(d[47]),"+f"(d[48]),"+f"(d[49]),"+f"(d[50]),"+f"(d[51]),"+f"(d[52]),"+f"(d[53]),"+f"(d[54]),"+f"(d[55]),"+f"(d[56]),"+f"(d[57]),"+f"(d[58]),"+f"(d[59]),"+f"(d[60]),"+f"(d[61]),"+f"(d[62]),"+f"(d[63]),"+f"(d[64]),"+f"(d[65]),"+f"(d[66]),"+f"(d[67]),"+f"(d[68]),"+f"(d[69]),"+f"(d[70]),"+f"(d[71]),"+f"(d[72]),"+f"(d[73]),"+f"(d[74]),"+f"(d[75]),"+f"(d[76]),"+f"(d[77]),"+f"(d[78]),"+f"(d[79]),"+f"(d[80]),"+f"(d[81]),"+f"(d[82]),"+f"(d[83]),"+f"(d[84]),"+f"(d[85]),"+f"(d[86]),"+f"(d[87]),"+f"(d[88]),"+f"(d[89]),"+f"(d[90]),"+f"(d[91]),"+f"(d[92]),"+f"(d[93]),"+f"(d[94]),"+f"(d[95])
   : "l"(da), "l"(db), "r"(scale_d), "n"(TB));
}
template<int TB>
__device__ __forceinline__ void wgmma_n160(float (&d)[80], uint64_t da, uint64_t db, int scale_d) {
  asm volatile("{\n.reg .pred p;\nsetp.ne.b32 p, %82, 0;\n"
   "wgmma.mma_async.sync.aligned.m64n160k16.f32.bf16.bf16 {%0,%1,%2,%3,%4,%5,%6,%7,%8,%9,%10,%11,%12,%13,%14,%15,%16,%17,%18,%19,%20,%21,%22,%23,%24,%25,%26,%27,%28,%29,%30,%31,%32,%33,%34,%35,%36,%37,%38,%39,%40,%41,%42,%43,%44,%45,%46,%47,%48,%49,%50,%51,%52,%53,%54,%55,%56,%57,%58,%59,%60,%61,%62,%63,%64,%65,%66,%67,%68,%69,%70,%71,%72,%73,%74,%75,%76,%77,%78,%79}, %80, %81, p, 1, 1, 0, %83;\n}"
   : "+f"(d[0]),"+f"(d[1]),"+f"(d[2]),"+f"(d[3]),"+f"(d[4]),"+f"(d[5]),"+f"(d[6]),"+f"(d[7]),"+f"(d[8]),"+f"(d[9]),"+f"(d[10]),"+f"(d[11]),"+f"(d[12]),"+f"(d[13]),"+f"(d[14]),"+f"(d[15]),"+f"(d[16]),"+f"(d[17]),"+f"(d[18]),"+f"(d[19]),"+f"(d[20]),"+f"(d[21]),"+f"(d[22]),"+f"(d[23]),"+f"(d[24]),"+f"(d[25]),"+f"(d[26]),"+f"(d[27]),"+f"(d[28]),"+f"(d[29]),"+f"(d[30]),"+f"(d[31]),"+f"(d[32]),"+f"(d[33]),"+f"(d[34]),"+f"(d[35]),"+f"(d[36]),"+f"(d[37]),"+f"(d[38]),"+f"(d[39]),"+f"(d[40]),"+f"(d[41]),"+f"(d[42]),"+f"(d[43]),"+f"(d[44]),"+f"(d[45]),"+f"(d[46]),"+f"(d[47]),"+f"(d[48]),"+f"(d[49]),"+f"(d[50]),"+f"(d[51]),"+f"(d[52]),"+f"(d[53]),"+f"(d[54]),"+f"(d[55]),"+f"(d[56]),"+f"(d[57]),"+f"(d[58]),"+f"(d[59]),"+f"(d[60]),"+f"(d[61]),"+f"(d[62]),"+f"(d[63]),"+f"(d[64]),"+f"(d[65]),"+f"(d[66]),"+f"(d[67]),"+f"(d[68]),"+f"(d[69]),"+f"(d[70]),"+f"(d[71]),"+f"(d[72]),"+f"(d[73]),"+f"(d[74]),"+f"(d[75]),"+f"(d[76]),"+f"(d[77]),"+f"(d[78]),"+f"(d[79])
   : "l"(da), "l"(db), "r"(scale_d), "n"(TB));
}

template<int N, int TB>
__device__ __forceinline__ void wgmma_n(float (&d)[N / 2], uint64_t da, uint64_t db) {
  if constexpr (N == 192) wgmma_n192<TB>(d, da, db, 1); else wgmma_n160<TB>(d, da, db, 1);
}

template<int M, int R>
__device__ __forceinline__ void pin(float (&acc)[M][R]) {
  #pragma unroll
  for (int mi = 0; mi < M; mi++)
    #pragma unroll
    for (int i = 0; i < R; i++) asm volatile("" : "+f"(acc[mi][i]) :: "memory");
}
template<int M, int R>
__device__ __forceinline__ void zero(float (&acc)[M][R]) {
  #pragma unroll
  for (int mi = 0; mi < M; mi++)
    #pragma unroll
    for (int i = 0; i < R; i++) acc[mi][i] = 0.f;
  pin(acc);
}

template<int N, int M, int TB, bool CONT, int ORD_BAR, bool AOWN = false>
__device__ __forceinline__ void mainloop(float (&acc)[M][N / 2], uint32_t sbase, int grp, int g0, int nk, int m0 = 0) {
  const uint32_t full0 = sbase + BAR_OFF, empty0 = full0 + 8 * MAXST, ring = sbase + RING_OFF;
  const int nst = grp == 0 ? NST_A : NST_B, total = grp == 0 ? KB_A : KB_B;
  const uint32_t sstep = (grp == 0 ? STAGE_A : STAGE_B) >> 4;
  const int t = threadIdx.x & 127;
  const uint32_t da0 = (((ring + m0 * 8192) & 0x3FFFF) >> 4) | 0x10000u;
  const uint32_t db0 = (((ring + A_BYTES) & 0x3FFFF) >> 4) | ((TB == 2 ? 256u : TB ? 512u : 1u) << 16);
  constexpr uint32_t HI_A = 0x40000040u, HI_B = TB == 2 ? 0x80000020u : 0x40000040u;
  int s = g0 % nst, ph = (g0 / nst) & 1, ps = s == 0 ? nst - 1 : s - 1;
  #pragma unroll 1
  for (int g = g0; g < g0 + nk; g++) {
    const uint32_t so = s * sstep;
    mbar_wait(full0 + 8 * s, ph);
    wgmma_fence();
    #pragma unroll
    for (int k = 0; k < 4; k++) {
      const uint64_t db = desc64(db0 + so + (TB == 2 ? k * 64 : TB ? k * 128 : k * 2), HI_B);
      #pragma unroll
      for (int mi = 0; mi < M; mi++)
        wgmma_n<N, TB != 0>(acc[mi], desc64(AOWN ? da0 + ((NST_A * STAGE_A) >> 4) + (g - g0) * 512 + mi * 1536 + k * 2 : da0 + so + mi * 512 + k * 2, HI_A), db);
    }
    wgmma_commit();
    if (ORD_BAR != 0 && g == g0 + nk - 1) bar_arrive<ORD_BAR>(256);
    wgmma_wait<1>();
    if (t < 2 * M && (CONT || g > g0) && g - 1 + nst < total) mbar_arrive_cluster(empty0 + 8 * ps, t & 1);
    ps = s;
    if (++s == nst) { s = 0; ph ^= 1; }
  }
}
template<int M, int R>
__device__ __forceinline__ void drain(float (&acc)[M][R], uint32_t sbase, int grp, int glast) {
  wgmma_wait<0>();
  pin(acc);
  const int t = threadIdx.x & 127;
  const int nst = grp == 0 ? NST_A : NST_B, total = grp == 0 ? KB_A : KB_B;
  if (t < 2 * M && glast + nst < total) mbar_arrive_cluster(sbase + BAR_OFF + 8 * MAXST + 8 * (glast % nst), t & 1);
}

__device__ __forceinline__ void set_flag(int slot, int byte, unsigned epoch) {
  asm volatile("st.relaxed.gpu.global.u8 [%0], %1;" :: "l"(g_flags + slot * 256 + byte), "r"(epoch & 255u) : "memory");
}
__device__ __forceinline__ unsigned get_flag(int slot, int byte) {
  unsigned v; asm volatile("ld.relaxed.gpu.global.u8 %0, [%1];" : "=r"(v) : "l"(g_flags + slot * 256 + byte) : "memory"); return v;
}
__device__ __forceinline__ void publish(int slot, int byte, unsigned epoch) {
  asm volatile("fence.acq_rel.gpu;" ::: "memory");
  set_flag(slot, byte, epoch);
}
__device__ __forceinline__ float sum8(uint4 v) {
  return ((bf_lo(v.x) + bf_hi(v.x)) + (bf_lo(v.y) + bf_hi(v.y))) + ((bf_lo(v.z) + bf_hi(v.z)) + (bf_lo(v.w) + bf_hi(v.w)));
}
__device__ __forceinline__ uint4 ldg128(const void* p) {
  uint4 v; asm volatile("ld.global.nc.v4.u32 {%0,%1,%2,%3}, [%4];" : "=r"(v.x), "=r"(v.y), "=r"(v.z), "=r"(v.w) : "l"(p)); return v;
}

__device__ __forceinline__ void ln_rows(const uint4 (&rv)[5], uint32_t buf, int cta, unsigned epoch) {
  const int t = threadIdx.x - 128, row = cta * 16 + (t >> 4), c = t & 15;
  const float sh = __shfl_sync(0xffffffffu, bf_lo(rv[0].x), t & 16);
  float d[40], s = 0.f, q = 0.f;
  #pragma unroll
  for (int j = 0; j < 5; j++) {
    const uint32_t u[4] = {rv[j].x, rv[j].y, rv[j].z, rv[j].w};
    #pragma unroll
    for (int e = 0; e < 4; e++) {
      const float d0 = bf_lo(u[e]) - sh, d1 = bf_hi(u[e]) - sh;
      d[j * 8 + e * 2] = d0; d[j * 8 + e * 2 + 1] = d1;
      s += d0 + d1; q = fmaf(d0, d0, q); q = fmaf(d1, d1, q);
    }
  }
  #pragma unroll
  for (int o = 1; o < 16; o <<= 1) { s += __shfl_xor_sync(0xffffffffu, s, o); q += __shfl_xor_sync(0xffffffffu, q, o); }
  const float md = s * (1.f / DM);
  const float r = rsqrtf(fmaxf(fmaf(q, 1.f / DM, -md * md), 0.f) + LN_EPS), o = -md * r;
  if (c == 0) st_tag2(&g_xstat[row], __float_as_uint(r), (__float_as_uint(-(md + sh) * r) & ~255u) | (epoch & 255u));
  #pragma unroll
  for (int j = 0; j < 5; j++) {
    const float* a = &d[j * 8];
    sts128(buf + (t >> 4) * 1280 + (c + 16 * j) * 16,
           pack_bf16(fmaf(a[0], r, o), fmaf(a[1], r, o)), pack_bf16(fmaf(a[2], r, o), fmaf(a[3], r, o)),
           pack_bf16(fmaf(a[4], r, o), fmaf(a[5], r, o)), pack_bf16(fmaf(a[6], r, o), fmaf(a[7], r, o)));
  }
  fence_async_smem();
  bar_arrive<BAR_LN>(288);
}

__device__ __forceinline__ void weight_sums(const bf16* __restrict__ win, const bf16* __restrict__ wdre, int j, unsigned epoch) {
  const int t = threadIdx.x & 127, w = t >> 5, l = t & 31;
  const int cj = min(j, 59), cg = cj % 12, rg = cj / 12, wr = j * 10 + min(t >> 3, 9);
  uint4 cv[8], rv[10];
  #pragma unroll
  for (int i = 0; i < 8; i++) cv[i] = ldg128(reinterpret_cast<const uint4*>(win + (size_t)(rg * 128 + w * 32 + i * 4 + (l >> 3)) * FF + FH + cg * 64) + (l & 7));
  #pragma unroll
  for (int i = 0; i < 10; i++) rv[i] = ldg128(reinterpret_cast<const uint4*>(wdre + (size_t)wr * DM) + (l & 7) + 8 * i);
  float v[8];
  #pragma unroll
  for (int e = 0; e < 8; e++) v[e] = 0.f;
  #pragma unroll
  for (int i = 0; i < 8; i++) {
    v[0] += bf_lo(cv[i].x); v[1] += bf_hi(cv[i].x); v[2] += bf_lo(cv[i].y); v[3] += bf_hi(cv[i].y);
    v[4] += bf_lo(cv[i].z); v[5] += bf_hi(cv[i].z); v[6] += bf_lo(cv[i].w); v[7] += bf_hi(cv[i].w);
  }
  #pragma unroll
  for (int st = 0; st < 2; st++) {
    const int n = 4 >> st;
    const bool up = (l & (4 * n)) != 0;
    #pragma unroll
    for (int e = 0; e < 4; e++)
      if (e < n) { const float keep = up ? v[e + n] : v[e], send = up ? v[e] : v[e + n]; v[e] = keep + __shfl_xor_sync(0xffffffffu, send, 4 * n); }
  }
  float* red = reinterpret_cast<float*>(smem + RED_OFF);
  *reinterpret_cast<float2*>(red + w * 64 + (l & 7) * 8 + (l >> 3) * 2) = make_float2(v[0], v[1]);
  float s = 0.f;
  #pragma unroll
  for (int i = 0; i < 10; i++) s += sum8(rv[i]);
  #pragma unroll
  for (int o = 1; o < 8; o <<= 1) s += __shfl_xor_sync(0xffffffffu, s, o);
  if ((l & 7) == 0) st_tag2(&g_csum[5 * FH + wr], __float_as_uint(s), epoch);
  bar_sync<BAR_WG1>(128);
  if (t < 64) st_tag2(&g_csum[rg * FH + cg * 64 + t], __float_as_uint((red[t] + red[64 + t]) + (red[128 + t] + red[192 + t])), epoch);
}

__device__ __forceinline__ void gather96(const uint2* src, float* dst, unsigned epoch) {
  unsigned it = 0;
  while (true) {
    bool ok = true;
    uint2 u[15];
    #pragma unroll
    for (int j = 0; j < 15; j++) u[j] = ld_tag2(src + (j % 5) * FH + (j / 5) * 32);
    #pragma unroll
    for (int j = 0; j < 15; j++) ok = ok && u[j].y == epoch;
    #pragma unroll
    for (int j = 0; j < 3; j++)
      dst[j * 32] = ((__uint_as_float(u[j * 5].x) + __uint_as_float(u[j * 5 + 1].x)) + (__uint_as_float(u[j * 5 + 2].x) + __uint_as_float(u[j * 5 + 3].x))) + __uint_as_float(u[j * 5 + 4].x);
    if (ok || ++it > POLL_LIMIT) break;
    __nanosleep(2 * POLL_NS);
  }
}

__device__ __forceinline__ void a_entry(int g, int grp, int ct, int& mi, int& kb) {
  if (g < 10) { mi = M_X; kb = g; }
  else if (g < 20) { mi = M_XN; kb = g - 10; }
  else if (g < 52) { mi = grp == 0 ? M_WSP : M_WSRE; kb = g - 20; }
  else if (grp == 0) {
    if (g < 52 + NX) { mi = M_WSIM; kb = g - 52 + 32 - NX; }
    else {
      const int i = g - 52 - NX;
      mi = M_H; kb = i < 3 ? ct * 3 + i : i < 6 ? (ct ^ 1) * 3 + i - 3 : ((ct >> 1) ^ 1) * 6 + i - 6;
    }
  } else {
    if (g < 84 - NX) { mi = M_WSIM; kb = g - 52; }
    else { mi = M_H; kb = ((ct >> 1) ^ 1) * 6 + g - (84 - NX) + 6 - NO; }
  }
}

__global__ void __cluster_dims__(2, 1, 1) __launch_bounds__(384, 1)
fused_kernel(const __grid_constant__ Maps maps, const bf16* __restrict__ x, const bf16* __restrict__ win, const bf16* __restrict__ wdre,
             const bf16* __restrict__ bsp, const bf16* __restrict__ wout, bf16* __restrict__ out) {
  const uint32_t sbase = smem_u32(smem);
  const uint32_t full0 = sbase + BAR_OFF, empty0 = full0 + 8 * MAXST, dep0 = empty0 + 8 * MAXST, ring = sbase + RING_OFF;
  const int tid = threadIdx.x, wg = __shfl_sync(0xffffffffu, tid >> 7, 0);
  if (blockIdx.x < 4) {
    if (tid == 0) {
      const unsigned epoch = (ld_relaxed(&g_done) >> 7) + 1u;
      for (int s = 0; s < 4; s++) mbar_init(sbase + 8 * s, 1);
      asm volatile("fence.mbarrier_init.release.cluster;" ::: "memory");
      __nanosleep(HELP_NS);
      const char* src = reinterpret_cast<const char*>(x) + (size_t)blockIdx.x * 655360;
      char* dst = reinterpret_cast<char*>(out) + (size_t)blockIdx.x * 655360;
      #pragma unroll 1
      for (int i = 0; i < 16 + 3; i++) {
        if (i < 16) {
          if (i >= 4) asm volatile("cp.async.bulk.wait_group.read 0;" ::: "memory");
          mbar_expect_tx(sbase + 8 * (i & 3), 40960);
          asm volatile("cp.async.bulk.shared::cluster.global.mbarrier::complete_tx::bytes [%0], [%1], 40960, [%2];"
                       :: "r"(sbase + 1024 + (i & 3) * 40960), "l"(src + (size_t)i * 40960), "r"(sbase + 8 * (i & 3)) : "memory");
        }
        if (i >= 3) {
          const int j = i - 3;
          mbar_wait(sbase + 8 * (j & 3), (j >> 2) & 1);
          asm volatile("cp.async.bulk.global.shared::cta.bulk_group [%0], [%1], 40960;" :: "l"(dst + (size_t)j * 40960), "r"(sbase + 1024 + (j & 3) * 40960) : "memory");
          bulk_commit();
        }
      }
      bulk_wait_all();
      for (int r = 0; r < 4; r++) set_flag(F_Y + blockIdx.x * 4 + r, 0, epoch);
    }
    return;
  }
  const int cta = blockIdx.x - 4, rank = cta & 1, grp = (cta >> 1) & 1, rb = cta >> 3, ct = ((cta >> 2) & 1) * 2 + rank;
  const int total = grp == 0 ? KB_A : KB_B, gh = grp == 0 ? 52 + NX : 84 - NX;
  const uint32_t stage_bytes = grp == 0 ? STAGE_A : STAGE_B;
  const int nst = grp == 0 ? NST_A : NST_B;
  const uint32_t buf = ring + nst * stage_bytes;

  uint4 rv[5];
  if (wg != 0) {
    #pragma unroll
    for (int j = 0; j < 5; j++) rv[j] = ldg128(reinterpret_cast<const uint4*>(x + (size_t)(cta * 16 + ((tid - 128) >> 4)) * DM) + (tid & 15) + 16 * j);
  }
  const unsigned epoch = (ld_relaxed(&g_done) >> 7) + 1u;
  if (tid == 0) {
    TS(0, 0);
    for (int s = 0; s < MAXST; s++) { mbar_init(full0 + 8 * s, 2); mbar_init(empty0 + 8 * s, 4); mbar_init(dep0 + 8 * s, 1); }
    *reinterpret_cast<volatile int*>(smem + READY_OFF) = 0;
    asm volatile("fence.mbarrier_init.release.cluster;" ::: "memory");
  }
  __syncthreads();
  asm volatile("barrier.cluster.arrive.relaxed.aligned;" ::: "memory");

  if (wg == 0) {
    asm volatile("setmaxnreg.dec.sync.aligned.u32 40;");
    const int warp = tid >> 5, lane = tid & 31;
    if (warp == 0) {
      const int row = rb * 128;
      if (lane == 0) {
        for (int g = 0; g < nst; g++) {
          mbar_expect_tx(full0 + 8 * g, A_BYTES);
          tma_load_2d(ring + g * stage_bytes, &maps.m[M_X], full0 + 8 * g, g * 64, row);
          tma_load_2d(ring + g * stage_bytes + 8192, &maps.m[M_X], full0 + 8 * g, g * 64, row + 64);
        }
      }
      __syncwarp();
      cluster_wait();
      if (lane == 0) {
        int s = 0, ph = 0;
        #pragma unroll 1
        for (int g = nst; g < total; g++) {
          int mi, kb;
          a_entry(g, grp, ct, mi, kb);
          if (g == 10 || g == gh + 6 - 6 * grp || (grp == 0 && g == gh + 3)) {
            TS(0, g > 10 ? 3 : 1);
            mbar_wait(dep0 + (g == 10 ? 0 : g == gh + 6 - 6 * grp ? 24 : 8), 0);
            fence_async_global();
            TS(0, g > 10 ? 4 : 2);
          }
          mbar_wait(empty0 + 8 * s, ph);
          if (grp == 0 && g >= gh && g < gh + 6) {
            if (g < gh + 3) {
              mbar_arrive(full0 + 8 * s);
            } else {
              mbar_expect_tx(full0 + 8 * s, A_BYTES);
              tma_load_2d(ring + s * stage_bytes, &maps.m[mi], full0 + 8 * s, kb * 64, row);
              tma_load_2d(ring + s * stage_bytes + 8192, &maps.m[mi], full0 + 8 * s, kb * 64, row + 64);
            }
          } else {
            mbar_expect_tx(full0 + 8 * s, A_BYTES);
            tma_load_2d_mc(ring + s * stage_bytes + rank * 8192, &maps.m[mi], full0 + 8 * s, kb * 64, row + rank * 64, 3);
          }
          if (++s == nst) { s = 0; ph ^= 1; }
          if (g + PF_D < gh) {
            a_entry(g + PF_D, grp, ct, mi, kb);
            if (mi >= M_WSRE && (kb & 1) == (ct >> 1))
              asm volatile("cp.async.bulk.prefetch.tensor.2d.L2.global.tile [%0, {%1, %2}];" :: "l"((uint64_t)&maps.m[mi]), "r"(kb * 64), "r"(row + rank * 64) : "memory");
          }
        }
        TS(0, 5);
      }
    } else if (warp == 1) {
      if (lane == 0) {
        int s = 0, ph = 1;
        int have = 0;
        #pragma unroll 1
        for (int g = 0; g < total; g++) {
          int mi, kb, c;
          a_entry(g, grp, ct, mi, kb);
          const bool nmaj = g >= gh || (grp == 0 && g < 52);
          uint32_t bytes = 20480;
          if (g >= gh) { mi = M_WOUT; c = ct * 5; }
          else if (g >= 52) { mi = M_AB; c = DM + ct * 160; }
          else if (grp == 0) { mi = g < 20 ? M_WIN3 : M_Z23; c = 3 * ct + (g < 10 ? 12 : 0); bytes = 24576; }
          else { mi = g < 10 ? M_WDRE : g < 20 ? M_WDIM : M_AB; c = ct * 160; }
          if (g >= 20 && g < 52 && ((g - 20) >> 1) >= have) {
            if (g == 20) TS(1, 0);
            unsigned it = 0;
            while ((have = *reinterpret_cast<volatile int*>(smem + READY_OFF)) <= ((g - 20) >> 1) && ++it < 50 * POLL_LIMIT) {}
            fence_async_global();
            if (g == 20) { TS(1, 1); TC(1); }
          }
          if (g == 52) { TS(1, 2); mbar_wait(dep0 + 16, 0); fence_async_global(); TS(1, 3); TC(2); }
          const uint32_t dst = ring + s * stage_bytes + A_BYTES, fb = full0 + 8 * s;
          mbar_wait(empty0 + 8 * s, ph);
          if (++s == nst) { s = 0; ph ^= 1; }
          mbar_expect_tx(fb, bytes);
          if (nmaj) tma_load_3d(dst, &maps.m[mi], fb, 0, kb * 64, c);
          else tma_load_2d(dst, &maps.m[mi], fb, kb * 64, c);
        }
      }
      __syncwarp();
      cluster_wait();
    } else if (warp == 2) {
      if (lane < M_COUNT) asm volatile("prefetch.tensormap [%0];" :: "l"((uint64_t)&maps.m[lane]) : "memory");
      cluster_wait();
      {
        unsigned it = 0;
        uint2 v[4];
        while (true) {
          bool ok = true;
          #pragma unroll
          for (int i = 0; i < 4; i++) { v[i] = ld_tag2(&g_xstat[rb * 128 + i * 32 + lane]); ok = ok && ((v[i].y ^ epoch) & 255u) == 0; }
          if (ok || ++it > POLL_LIMIT) break;
          __nanosleep(POLL_NS);
        }
        #pragma unroll
        for (int i = 0; i < 4; i++) reinterpret_cast<uint2*>(smem + ROWSTAT_OFF)[i * 32 + lane] = make_uint2(v[i].x, v[i].y & ~255u);
        __syncwarp();
        TS(0, 6);
        if (grp == 0) bar_arrive<BAR_STATS>(320); else bar_arrive<BAR_STATS>(192);
      }
      const int hsrc = ((ct >> 1) ^ 1) * 2 + (grp == 0 ? (NO >= 3 ? 0 : lane & 1) : (NO <= 3 ? 1 : lane & 1));
      #pragma unroll 1
      for (int i = 0; i < 5; i++) {
        const int d = i == 3 ? 4 : i == 4 ? 3 : i;
        const int slot = d == 0 ? F_XN + rb : d == 4 ? F_Y + rb : d == 3 ? F_H + rb : d == 2 ? F_B + ct : grp == 0 ? F_Z + ct : F_A + ct;
        const int byte = d == 0 ? lane & 7 : d == 4 ? 0 : d == 3 ? hsrc : lane & 15;
        unsigned it = 0, m;
        while ((m = __ballot_sync(0xffffffffu, get_flag(slot, byte) != (epoch & 255u))) != 0 && ++it < POLL_LIMIT) {
          if (d == 1 && lane == 0) *reinterpret_cast<volatile int*>(smem + READY_OFF) = __ffs(m) - 1;
          __nanosleep(WATCH_NS);
        }
        if (d == 1 && lane == 0) *reinterpret_cast<volatile int*>(smem + READY_OFF) = 16;
        if (d < 4) TS(0, 8 + d * 2); else TS(0, 7);
        fence_async_global();
        __syncwarp();
        if (lane == 0 && d != 1) mbar_arrive(dep0 + 8 * d);
        if (d == 2 && lane < 30) {
          asm volatile("prefetch.global.L2 [%0];" :: "l"(wout + (size_t)cta * 6 * DM + lane * 128));
          asm volatile("prefetch.global.L2 [%0];" :: "l"(wout + (size_t)cta * 6 * DM + lane * 128 + 64));
        }
      }
    } else {
      cluster_wait();
      bar_sync<BAR_LN>(288);
      if (lane == 0) {
        TS(1, 5);
        asm volatile("cp.async.bulk.global.shared::cta.bulk_group [%0], [%1], 20480;" :: "l"(g_xn + (size_t)cta * 16 * DM), "r"(buf) : "memory");
        bulk_commit();
        bulk_wait_all();
        set_flag(F_XN + rb, cta & 7, epoch);
        TS(1, 6);
      }
      __syncwarp();
      if (grp == 0) {
        #pragma unroll 1
        for (int i = 0; i < 2; i++) gather96(&g_csum[ct * 192 + i * 96 + lane], reinterpret_cast<float*>(smem + COLSUM_OFF) + i * 96 + lane, epoch);
      } else {
        unsigned it = 0;
        while (true) {
          bool ok = true;
          #pragma unroll
          for (int j = 0; j < 5; j++) {
            const uint2 u = ld_tag2(&g_csum[5 * FH + ct * 160 + j * 32 + lane]);
            ok = ok && u.y == epoch;
            reinterpret_cast<uint32_t*>(smem + COLSUM_OFF)[j * 32 + lane] = u.x;
          }
          if (ok || ++it > POLL_LIMIT) break;
          __nanosleep(2 * POLL_NS);
        }
      }
      __syncwarp();
      TS(1, 4);
      if (grp == 0) {
        bar_arrive<BAR_STATS>(320);
        bar_sync<BAR_PUB1>(160);
        if (lane == 0) set_flag(F_Z + ct, rb, epoch);
        TS(1, 8);
        __syncwarp();
        bar_arrive<BAR_BUF>(160);
      } else {
        bar_arrive<BAR_STATS>(192);
        bar_sync<BAR_PUB2>(160);
        if (lane == 0) set_flag(F_A + ct, rb, epoch);
        TS(1, 9);
        __syncwarp();
      }
      bar_sync<BAR_PUB1>(160);
      if (lane == 0) {
        set_flag(grp == 0 ? F_H + rb : F_B + ct, grp == 0 ? ct : rb, epoch);
        if (grp == 0) mbar_arrive_cluster(dep0 + 8, rank ^ 1);
      }
      TS(1, 10);
      __syncwarp();
      bar_arrive<BAR_BUF>(160);
    }
  } else {
    asm volatile("setmaxnreg.inc.sync.aligned.u32 232;");
    const int t = tid & 127, w = t >> 5, l = t & 31;
    ln_rows(rv, buf, cta, epoch);
    TS(wg + 1, 0);
    cluster_wait();
    const uint32_t st_base = buf + (w * 16 + ((l >> 3) & 1) * 8 + (l & 7)) * 128;
    const uint32_t st_x = ((l >> 4) ^ (l & 7)) << 4;
    const float2* rs = reinterpret_cast<const float2*>(smem + ROWSTAT_OFF) + w * 16 + (l >> 2);
    const float2* cs = reinterpret_cast<const float2*>(smem + COLSUM_OFF) + (l & 3);
    if (grp == 0) {
      {
        const int mb = wg - 1;
        float acc[1][96];
        zero(acc);
        mainloop<192, 1, 1, false, 0>(acc, sbase, 0, 0, 10, mb);
        drain(acc, sbase, 0, 9);
        TS(wg + 1, 1);
        bar_sync<BAR_STATS>(320);
        const float2 s0 = rs[mb * 64], s1 = rs[mb * 64 + 8];
        const float nm[2] = {s0.y / s0.x, s1.y / s1.x}, hr[2] = {0.5f * s0.x, 0.5f * s1.x};
        const float k1[2] = {0.7978845608f * s0.x, 0.7978845608f * s1.x};
        const float k2[2] = {0.0356774081f * s0.x * s0.x * s0.x, 0.0356774081f * s1.x * s1.x * s1.x};
        float sm0 = 0.f, sm1 = 0.f, q0 = 0.f, q1 = 0.f;
        #pragma unroll
        for (int jj = 0; jj < 12; jj++) {
          float u[8];
          #pragma unroll
          for (int hf = 0; hf < 2; hf++) {
            const float2 c = cs[jj * 8 + hf * 4];
            #pragma unroll
            for (int e = 0; e < 4; e++) {
              const float wv = fmaf(nm[e >> 1], (e & 1) ? c.y : c.x, acc[0][8 * jj + 4 * hf + e]);
              float th; asm("tanh.approx.f32 %0, %1;" : "=f"(th) : "f"(wv * fmaf(k2[e >> 1], wv * wv, k1[e >> 1])));
              const float hv = hr[e >> 1] * wv;
              u[4 * hf + e] = fmaf(hv, th, hv);
            }
            sm0 += u[4 * hf] + u[4 * hf + 1]; q0 = fmaf(u[4 * hf], u[4 * hf], q0); q0 = fmaf(u[4 * hf + 1], u[4 * hf + 1], q0);
            sm1 += u[4 * hf + 2] + u[4 * hf + 3]; q1 = fmaf(u[4 * hf + 2], u[4 * hf + 2], q1); q1 = fmaf(u[4 * hf + 3], u[4 * hf + 3], q1);
          }
          stsm4(st_base + mb * 24576 + (jj >> 2) * 8192 + (st_x ^ ((jj & 3) << 5)),
                pack_bf16(u[0], u[1]), pack_bf16(u[2], u[3]), pack_bf16(u[4], u[5]), pack_bf16(u[6], u[7]));
        }
        #pragma unroll
        for (int o = 1; o < 4; o <<= 1) {
          sm0 += __shfl_xor_sync(0xffffffffu, sm0, o); q0 += __shfl_xor_sync(0xffffffffu, q0, o);
          sm1 += __shfl_xor_sync(0xffffffffu, sm1, o); q1 += __shfl_xor_sync(0xffffffffu, q1, o);
        }
        if ((l & 3) < 2) {
          const float sm = (l & 1) ? sm1 : sm0, sv = (l & 1) ? q1 : q0;
          const int row = mb * 64 + w * 16 + (l & 1) * 8 + (l >> 2);
          const float mu = sm * (1.f / 192), m2 = fmaxf(sv - sm * mu, 0.f);
          st_tag2(&g_zstat[(rb * 4 + ct) * 128 + row], __float_as_uint(mu), (__float_as_uint(m2) & ~255u) | (epoch & 255u));
          reinterpret_cast<float2*>(smem + ZSTAT_OFF)[row] = make_float2(mu, m2);
        }
        TS(wg + 1, 4);
      }
      float acc[2][96];
      if (wg == 1) {
        bar_sync<BAR_U>(256);
        uint2 v[3];
        unsigned n = 0;
        while (true) {
          bool ok = true;
          #pragma unroll
          for (int j = 0; j < 3; j++) { v[j] = ld_tag2(&g_zstat[(rb * 4 + ((ct + 1 + j) & 3)) * 128 + t]); ok = ok && ((v[j].y ^ epoch) & 255u) == 0; }
          if (ok || ++n > POLL_LIMIT) break;
          __nanosleep(POLL_NS);
        }
        const float2 own = reinterpret_cast<const float2*>(smem + ZSTAT_OFF)[t];
        const float m0 = __uint_as_float(v[0].x), m1 = __uint_as_float(v[1].x), m3 = __uint_as_float(v[2].x);
        const float mean = 0.25f * ((own.x + m0) + (m1 + m3));
        const float d = (own.x - mean) * (own.x - mean) + (m0 - mean) * (m0 - mean) + (m1 - mean) * (m1 - mean) + (m3 - mean) * (m3 - mean);
        const float var = fmaf(192.f, d, (own.y + __uint_as_float(v[0].y & ~255u)) + (__uint_as_float(v[1].y & ~255u) + __uint_as_float(v[2].y & ~255u)));
        const float r = rsqrtf(var * (1.f / FH) + LN_EPS);
        TS(2, 5);
        const uint32_t rbase = buf + (t >> 6) * 24576 + (t & 63) * 128;
        const uint32_t m2 = pack_bf16(-mean, -mean), r2 = pack_bf16(r, r);
        const float res = (-mean - bf_lo(m2)) * r;
        const uint32_t e2 = pack_bf16(res, res);
        #pragma unroll 1
        for (int c = 0; c < 3; c++) {
          uint4 z[8];
          #pragma unroll
          for (int i = 0; i < 8; i++) z[i] = lds128(rbase + c * 8192 + (((i ^ l) & 7) << 4));
          #pragma unroll
          for (int i = 0; i < 8; i++)
            sts128(rbase + c * 8192 + (((i ^ l) & 7) << 4), hfma2_bf16(hadd2_bf16(z[i].x, m2), r2, e2), hfma2_bf16(hadd2_bf16(z[i].y, m2), r2, e2),
                   hfma2_bf16(hadd2_bf16(z[i].z, m2), r2, e2), hfma2_bf16(hadd2_bf16(z[i].w, m2), r2, e2));
          fence_async_smem();
          __syncwarp();
          if (l == 0) {
            tma_store_2d(&maps.m[M_ZS], buf + (w >> 1) * 24576 + c * 8192 + (w & 1) * 4096, ct * 192 + c * 64, rb * 128 + w * 32);
            bulk_commit();
          }
        }
        TS(2, 6);
        if (l == 0) bulk_wait_all();
        __syncwarp();
        bar_arrive<BAR_PUB1>(160);
        {
          const bf16* bp = bsp + rb * 128 + w * 16 + (l >> 2);
          const float bb[4] = {__bfloat162float(bp[0]), __bfloat162float(bp[8]), __bfloat162float(bp[64]), __bfloat162float(bp[72])};
          #pragma unroll
          for (int i = 0; i < 96; i++) { acc[0][i] = bb[(i >> 1) & 1]; acc[1][i] = bb[2 + ((i >> 1) & 1)]; }
          pin(acc);
        }
        bar_sync<BAR_ORD2>(256);
        mainloop<192, 2, 1, false, BAR_ORD1>(acc, sbase, 0, 20, 32);
        bar_sync<BAR_Z1>(256);
        uint32_t z[6][4][4];
        #pragma unroll
        for (int i = 0; i < ZPRE; i++) ldsm4(st_base + (i >> 2) * 8192 + (st_x ^ ((i & 3) << 5)), z[i >> 2][i & 3][0], z[i >> 2][i & 3][1], z[i >> 2][i & 3][2], z[i >> 2][i & 3][3]);
        drain(acc, sbase, 0, 51);
        TS(2, 7);
        #pragma unroll
        for (int bx = 0; bx < 6; bx++) {
          if (bx >= 1) {
            #pragma unroll
            for (int i = ZPRE + (bx - 1) * 10; i < ZPRE + bx * 10; i++)
              if (i < 24) ldsm4(st_base + (i >> 2) * 8192 + (st_x ^ ((i & 3) << 5)), z[i >> 2][i & 3][0], z[i >> 2][i & 3][1], z[i >> 2][i & 3][2], z[i >> 2][i & 3][3]);
          }
          #pragma unroll
          for (int i = 0; i < 4; i++) {
            const float* a = &acc[bx / 3][8 * ((bx % 3) * 4 + i)];
            const uint32_t* zz = z[bx][i];
            stsm4(st_base + bx * 8192 + (st_x ^ (i << 5)),
                  hmul2_bf16(zz[0], pack_bf16(a[0], a[1])), hmul2_bf16(zz[1], pack_bf16(a[2], a[3])),
                  hmul2_bf16(zz[2], pack_bf16(a[4], a[5])), hmul2_bf16(zz[3], pack_bf16(a[6], a[7])));

          }
          if (bx % 3 == 2) {
            fence_async_smem();
            __syncwarp();
            if (l < 3) {
              tma_store_2d(&maps.m[M_HS], buf + (bx - 2 + l) * 8192 + w * 2048, ct * 192 + l * 64, rb * 128 + (bx / 3) * 64 + w * 16);
              bulk_commit();
            }
          }
        }
        bar_arrive<BAR_U>(256);
        TS(2, 8);
        if (l < 3) bulk_wait_all();
        __syncwarp();
        bar_arrive<BAR_PUB1>(160);
        TS(2, 9);
        return;
      }
      bar_arrive<BAR_U>(256);
      zero(acc);
      mainloop<192, 2, 1, false, BAR_ORD2>(acc, sbase, 0, 10, 10);
      drain(acc, sbase, 0, 19);
      TS(3, 2);
      bar_sync<BAR_BUF>(160);
      #pragma unroll
      for (int mi = 0; mi < 2; mi++)
        #pragma unroll
        for (int jj = 0; jj < 12; jj++) {
          const float* a = &acc[mi][8 * jj];
          stsm4(st_base + mi * 24576 + (jj >> 2) * 8192 + (st_x ^ ((jj & 3) << 5)),
                pack_bf16(a[0], a[1]), pack_bf16(a[2], a[3]), pack_bf16(a[4], a[5]), pack_bf16(a[6], a[7]));
        }
      __syncwarp();
      TS(3, 3);
      const uint32_t rbase = buf + (l >> 4) * 24576 + (w * 16 + (l & 15)) * 128;
      #pragma unroll 1
      for (int c2 = 0; c2 < 12; c2++) {
        const uint32_t ab = rbase + (c2 >> 2) * 8192;
        uint4 v[2];
        #pragma unroll
        for (int i = 0; i < 2; i++) v[i] = lds128(ab + (((((c2 & 3) * 2 + i) ^ l) & 7) << 4));
        #pragma unroll
        for (int i = 0; i < 2; i++)
          sts128(ab + (((((c2 & 3) * 2 + i) ^ l) & 7) << 4),
                 pack_bf16(gelu_tanh(bf_lo(v[i].x)), gelu_tanh(bf_hi(v[i].x))), pack_bf16(gelu_tanh(bf_lo(v[i].y)), gelu_tanh(bf_hi(v[i].y))),
                 pack_bf16(gelu_tanh(bf_lo(v[i].z)), gelu_tanh(bf_hi(v[i].z))), pack_bf16(gelu_tanh(bf_lo(v[i].w)), gelu_tanh(bf_hi(v[i].w))));
        __nanosleep(Z1_NS);
      }
      TS(3, 5);
      bar_arrive<BAR_Z1>(256);
    }
    float acc[2][80];
    if (grp == 1) {
      zero(acc);
      if (wg == 2) {
        mainloop<160, 2, 0, false, BAR_ORD2>(acc, sbase, 1, 0, 10);
      } else {
        weight_sums(win, wdre, rb * 4 + ct, epoch);
        TS(2, 1);
        bar_sync<BAR_ORD2>(256);
        mainloop<160, 2, 0, false, BAR_ORD1>(acc, sbase, 1, 10, 10);
      }
      drain(acc, sbase, 1, wg == 2 ? 9 : 19);
      TS(wg + 1, wg == 1 ? 7 : 2);
      if (wg == 1) bar_sync<BAR_Z1>(256); else bar_sync<BAR_STATS>(192);
      const uint32_t tb = buf + ((l >> 4) * 8 + (l & 7)) * 128 + (((w * 2 + ((l >> 3) & 1)) ^ (l & 7)) << 4);
      float2 st[4];
      #pragma unroll
      for (int r = 0; r < 4; r++) st[r] = wg == 2 ? rs[(r >> 1) * 64 + (r & 1) * 8] : make_float2(-1.f, 0.f);
      #pragma unroll
      for (int jj = 0; jj < 10; jj++) {
        const float2 c0 = cs[jj * 8], c1 = cs[jj * 8 + 4];
        #pragma unroll
        for (int mi = 0; mi < 2; mi++) {
          const float* a = &acc[mi][8 * jj];
          const float2 s0 = st[mi * 2], s1 = st[mi * 2 + 1];
          stsm4_t(tb + mi * 20480 + jj * 2048,
                  pack_bf16(fmaf(a[0], s0.x, s0.y * c0.x), fmaf(a[1], s0.x, s0.y * c0.y)), pack_bf16(fmaf(a[2], s1.x, s1.y * c0.x), fmaf(a[3], s1.x, s1.y * c0.y)),
                  pack_bf16(fmaf(a[4], s0.x, s0.y * c1.x), fmaf(a[5], s0.x, s0.y * c1.y)), pack_bf16(fmaf(a[6], s1.x, s1.y * c1.x), fmaf(a[7], s1.x, s1.y * c1.y)));
        }
      }
      fence_async_smem();
      if (wg == 1) bar_sync<BAR_WG1>(128); else bar_sync<BAR_WG2>(128);
      TS(wg + 1, wg == 1 ? 8 : 6);
      if (l == 0) {
        #pragma unroll 1
        for (int i = 0; i < 2; i++) {
          const unsigned d = wg == 2 ? ST_A : ST_B;
          if (d) __nanosleep(i == 0 ? w * d : 3 * d);
          tma_store_2d(&maps.m[M_ABS], buf + i * 20480 + w * 5120, rb * 128 + i * 64, (2 - wg) * DM + ct * 160 + w * 40);
          bulk_commit();
        }
        bulk_wait_all();
      }
      __syncwarp();
      TS(wg + 1, wg == 1 ? 9 : 10);
      if (wg == 1) {
        bar_arrive<BAR_PUB1>(160);
        return;
      }
      bar_arrive<BAR_PUB2>(160);
      bar_arrive<BAR_Z1>(256);
    }
    zero(acc);
    bar_sync<BAR_ORD1>(256);
    mainloop<160, 2, 0, false, 0>(acc, sbase, grp, grp == 0 ? 52 : 20, grp == 0 ? NX : 64 - NX);
    if (grp == 0) {
      bar_sync<BAR_U>(256);
      mainloop<160, 2, 2, true, 0, true>(acc, sbase, 0, 52 + NX, 3);
    }
    mainloop<160, 2, 2, true, 0>(acc, sbase, grp, gh + 3 - 3 * grp, total - gh - 3 + 3 * grp);
    const uint32_t slab = buf + w * (16 * 320);
    const uint32_t addr = slab + (((l >> 3) & 1) * 8 + (l & 7)) * 320 + (l >> 4) * 16;
    bar_sync<BAR_BUF>(160);
    mbar_wait(dep0 + 32, 0);
    drain(acc, sbase, grp, total - 1);
    TS(3, 12);
    #pragma unroll
    for (int mi = 0; mi < 2; mi++) {
      #pragma unroll
      for (int jj = 0; jj < 10; jj++) {
        const float* a = &acc[mi][8 * jj];
        stsm4(addr + mi * 20480 + jj * 32, pack_bf16(a[0], a[1]), pack_bf16(a[2], a[3]), pack_bf16(a[4], a[5]), pack_bf16(a[6], a[7]));
      }
      fence_async_smem();
      __syncwarp();
      if (l == 0) {
        tma_reduce_2d(&maps.m[M_OUT], slab + mi * 20480, ct * 160, rb * 128 + mi * 64 + w * 16);
        bulk_commit();
      }
    }
    TS(3, 13);
    if (l == 0) {
      bulk_wait_read();
      if (w == 0) atomicAdd(&g_done, 1u);
    }
    TS(3, 15);
  }
}

typedef CUresult (*EncodeFn)(CUtensorMap*, CUtensorMapDataType, cuuint32_t, void*, const cuuint64_t*, const cuuint64_t*,
                             const cuuint32_t*, const cuuint32_t*, CUtensorMapInterleave, CUtensorMapSwizzle,
                             CUtensorMapL2promotion, CUtensorMapFloatOOBfill);

void make2d(EncodeFn enc, CUtensorMap* m, const void* p, uint64_t cols, uint64_t rows, uint32_t bc, uint32_t br, bool swz = true) {
  cuuint64_t gd[2] = {cols, rows}, gs[1] = {cols * 2};
  cuuint32_t bd[2] = {bc, br}, es[2] = {1, 1};
  enc(m, CU_TENSOR_MAP_DATA_TYPE_BFLOAT16, 2, const_cast<void*>(p), gd, gs, bd, es, CU_TENSOR_MAP_INTERLEAVE_NONE,
      swz ? CU_TENSOR_MAP_SWIZZLE_128B : CU_TENSOR_MAP_SWIZZLE_NONE, CU_TENSOR_MAP_L2_PROMOTION_L2_128B, CU_TENSOR_MAP_FLOAT_OOB_FILL_NONE);
}
void make3d(EncodeFn enc, CUtensorMap* m, const void* p, uint64_t cols, uint64_t rows, uint32_t cw, uint32_t nc, uint32_t br = 64) {
  cuuint64_t gd[3] = {cw, rows, cols / cw}, gs[2] = {cols * 2, cw * 2};
  cuuint32_t bd[3] = {cw, br, nc}, es[3] = {1, 1, 1};
  enc(m, CU_TENSOR_MAP_DATA_TYPE_BFLOAT16, 3, const_cast<void*>(p), gd, gs, bd, es, CU_TENSOR_MAP_INTERLEAVE_NONE,
      cw == 64 ? CU_TENSOR_MAP_SWIZZLE_128B : CU_TENSOR_MAP_SWIZZLE_64B, CU_TENSOR_MAP_L2_PROMOTION_L2_128B, CU_TENSOR_MAP_FLOAT_OOB_FILL_NONE);
}

}

extern "C" void kernel_launch(void* const* d_in, const int* in_sizes, int n_in, void* d_out, int out_size) {
  const bf16* x = (const bf16*)d_in[0];
  const bf16* wsre = (const bf16*)d_in[1];
  const bf16* wsim = (const bf16*)d_in[2];
  const bf16* wdre = (const bf16*)d_in[3];
  const bf16* wdim = (const bf16*)d_in[4];
  const bf16* win = (const bf16*)d_in[6];
  const bf16* wsp = (const bf16*)d_in[7];
  const bf16* bsp = (const bf16*)d_in[8];
  const bf16* wout = (const bf16*)d_in[9];

  void* fn = nullptr;
  cudaDriverEntryPointQueryResult qr;
  cudaGetDriverEntryPoint("cuTensorMapEncodeTiled", &fn, cudaEnableDefault, &qr);
  EncodeFn enc = (EncodeFn)fn;
  void *abT, *z2, *h, *xn;
  cudaGetSymbolAddress(&xn, g_xn);
  cudaGetSymbolAddress(&abT, g_abT);
  cudaGetSymbolAddress(&z2, g_z2);
  cudaGetSymbolAddress(&h, g_h);

  Maps maps;
  make2d(enc, &maps.m[M_X], x, DM, SEQ, 64, 64);
  make2d(enc, &maps.m[M_XN], xn, DM, SEQ, 64, 64);
  make2d(enc, &maps.m[M_WSRE], wsre, SEQ, SEQ, 64, 64);
  make2d(enc, &maps.m[M_WSIM], wsim, SEQ, SEQ, 64, 64);
  make2d(enc, &maps.m[M_WSP], wsp, SEQ, SEQ, 64, 64);
  make2d(enc, &maps.m[M_H], h, FH, SEQ, 64, 64);
  make3d(enc, &maps.m[M_WIN3], win, FF, DM, 64, 3);
  make3d(enc, &maps.m[M_Z23], z2, FH, SEQ, 64, 3);
  make2d(enc, &maps.m[M_WDRE], wdre, DM, DM, 64, 160);
  make2d(enc, &maps.m[M_WDIM], wdim, DM, DM, 64, 160);
  make2d(enc, &maps.m[M_AB], abT, SEQ, 2 * DM, 64, 160);
  make3d(enc, &maps.m[M_WOUT], wout, DM, FH, 32, 5);
  make2d(enc, &maps.m[M_HS], h, FH, SEQ, 64, 16);
  make2d(enc, &maps.m[M_ZS], z2, FH, SEQ, 64, 32);
  make2d(enc, &maps.m[M_ABS], abT, SEQ, 2 * DM, 64, 40);
  make2d(enc, &maps.m[M_OUT], d_out, DM, SEQ, 160, 16, false);

  cudaFuncSetAttribute(fused_kernel, cudaFuncAttributeMaxDynamicSharedMemorySize, SMEM_BYTES);
  fused_kernel<<<132, 384, SMEM_BYTES>>>(maps, x, win, wdre, bsp, wout, (bf16*)d_out);
}
```

```cpp
#include <cuda_runtime.h>
#include <cuda_bf16.h>
#include <cuda.h>
#include <stdint.h>

namespace {

typedef __nv_bfloat16 bf16;

constexpr int SEQ = 2048, DM = 640, FF = 1536, FH = 768;
#define NOV 3
#define NXV 5
constexpr int NX = NXV;
constexpr int NO = NOV;
constexpr int NST_A = 4, NST_B = 5, MAXST = 5;
constexpr int A_BYTES = 16384;
constexpr int BAR_OFF = 0;
constexpr int READY_OFF = 128;
constexpr int COLSUM_OFF = 256;
constexpr int ROWSTAT_OFF = 1024;
constexpr int ZSTAT_OFF = 2048;
constexpr int RED_OFF = 3072;
constexpr int RING_OFF = 4096;
constexpr int STAGE_A = 40960, STAGE_B = 36864;
constexpr int SMEM_BYTES = RING_OFF + 5 * STAGE_B + 40960;
constexpr int KB_A = 52 + NX + 12 - NO;
constexpr int KB_B = 84 - NX + NO;
constexpr float LN_EPS = 1e-5f;
constexpr unsigned POLL_LIMIT = 100000;
constexpr unsigned POLL_NS = 100, WATCH_NS = 40;
constexpr unsigned Z1_NS = 600;
constexpr int PF_D = 8;
constexpr int ZPRE = 6;

#define ST_A 0
#define ST_B 400
#define HELP_NS 4000
constexpr int BAR_ORD1 = 1, BAR_ORD2 = 2, BAR_WG1 = 3, BAR_WG2 = 4, BAR_LN = 5, BAR_BUF = 6, BAR_Z1 = 7, BAR_PUB1 = 8, BAR_PUB2 = 9,
              BAR_STATS = 10, BAR_U = 11;

enum { M_X, M_XN, M_WSRE, M_WSIM, M_WSP, M_H, M_WIN3, M_Z23, M_WDRE, M_WDIM, M_AB, M_WOUT, M_OUT, M_HS, M_ZS, M_ABS, M_COUNT };
struct Maps { CUtensorMap m[M_COUNT]; };

__device__ __align__(1024) bf16 g_abT[2 * DM * SEQ];
__device__ __align__(1024) bf16 g_z2[SEQ * FH];
__device__ __align__(1024) bf16 g_h[SEQ * FH];
__device__ __align__(1024) bf16 g_xn[SEQ * DM];
__device__ __align__(16) uint2 g_xstat[SEQ];
__device__ __align__(16) uint2 g_csum[5 * FH + DM];
__device__ __align__(16) uint2 g_zstat[64 * 128];
__device__ __align__(256) unsigned char g_flags[108 * 256];
constexpr int F_A = 0, F_B = 4, F_Z = 8, F_H = 12, F_XN = 28, F_Y = 44;
__device__ unsigned g_done;
#define TS(role, ev)
#define TC(i)

extern __shared__ __align__(1024) uint8_t smem[];

__device__ __forceinline__ uint32_t smem_u32(const void* p) { return (uint32_t)__cvta_generic_to_shared(p); }
__device__ __forceinline__ void mbar_init(uint32_t bar, uint32_t cnt) { asm volatile("mbarrier.init.shared::cta.b64 [%0], %1;" :: "r"(bar), "r"(cnt)); }
__device__ __forceinline__ void mbar_expect_tx(uint32_t bar, uint32_t bytes) { asm volatile("mbarrier.arrive.expect_tx.shared::cta.b64 _, [%0], %1;" :: "r"(bar), "r"(bytes) : "memory"); }
__device__ __forceinline__ void mbar_arrive(uint32_t bar) { asm volatile("mbarrier.arrive.shared::cta.b64 _, [%0];" :: "r"(bar) : "memory"); }
__device__ __forceinline__ void mbar_arrive_cluster(uint32_t bar, uint32_t cta) {
  asm volatile("{\n.reg .b32 ra;\nmapa.shared::cluster.u32 ra, %0, %1;\nmbarrier.arrive.shared::cluster.b64 _, [ra];\n}" :: "r"(bar), "r"(cta) : "memory");
}
__device__ __forceinline__ void mbar_wait(uint32_t bar, uint32_t parity) {
  asm volatile("{\n.reg .pred p;\n.reg .u32 n;\nmov.u32 n, 0;\n"
               "LW: mbarrier.try_wait.parity.shared::cta.b64 p, [%0], %1, 2000;\n@p bra LD;\n"
               "add.u32 n, n, 1;\nsetp.lt.u32 p, n, 20000;\n@p bra LW;\nLD:\n}" :: "r"(bar), "r"(parity) : "memory");
}
__device__ __forceinline__ void tma_load_2d(uint32_t dst, const CUtensorMap* map, uint32_t bar, int c0, int c1) {
  asm volatile("cp.async.bulk.tensor.2d.shared::cluster.global.mbarrier::complete_tx::bytes [%0], [%1, {%3, %4}], [%2];"
    :: "r"(dst), "l"((uint64_t)map), "r"(bar), "r"(c0), "r"(c1) : "memory");
}
__device__ __forceinline__ void tma_load_3d(uint32_t dst, const CUtensorMap* map, uint32_t bar, int c0, int c1, int c2) {
  asm volatile("cp.async.bulk.tensor.3d.shared::cluster.global.mbarrier::complete_tx::bytes [%0], [%1, {%3, %4, %5}], [%2];"
    :: "r"(dst), "l"((uint64_t)map), "r"(bar), "r"(c0), "r"(c1), "r"(c2) : "memory");
}
__device__ __forceinline__ void tma_load_2d_mc(uint32_t dst, const CUtensorMap* map, uint32_t bar, int c0, int c1, uint16_t mask) {
  asm volatile("cp.async.bulk.tensor.2d.shared::cluster.global.mbarrier::complete_tx::bytes.multicast::cluster [%0], [%1, {%3, %4}], [%2], %5;"
    :: "r"(dst), "l"((uint64_t)map), "r"(bar), "r"(c0), "r"(c1), "h"(mask) : "memory");
}
__device__ __forceinline__ void tma_store_2d(const CUtensorMap* map, uint32_t src, int c0, int c1) {
  asm volatile("cp.async.bulk.tensor.2d.global.shared::cta.bulk_group [%0, {%2, %3}], [%1];"
    :: "l"((uint64_t)map), "r"(src), "r"(c0), "r"(c1) : "memory");
}
__device__ __forceinline__ void tma_reduce_2d(const CUtensorMap* map, uint32_t src, int c0, int c1) {
  asm volatile("cp.reduce.async.bulk.tensor.2d.global.shared::cta.add.tile.bulk_group [%0, {%2, %3}], [%1];"
    :: "l"((uint64_t)map), "r"(src), "r"(c0), "r"(c1) : "memory");
}
__device__ __forceinline__ void bulk_wait_all() { asm volatile("cp.async.bulk.wait_group 0;" ::: "memory"); }
__device__ __forceinline__ void bulk_commit() { asm volatile("cp.async.bulk.commit_group;" ::: "memory"); }
__device__ __forceinline__ void bulk_wait_read() { asm volatile("cp.async.bulk.wait_group.read 0;" ::: "memory"); }
__device__ __forceinline__ void fence_async_smem() { asm volatile("fence.proxy.async.shared::cta;" ::: "memory"); }
__device__ __forceinline__ void fence_async_global() { asm volatile("fence.proxy.async.global;" ::: "memory"); }
__device__ __forceinline__ void wgmma_fence() { asm volatile("wgmma.fence.sync.aligned;" ::: "memory"); }
__device__ __forceinline__ void wgmma_commit() { asm volatile("wgmma.commit_group.sync.aligned;" ::: "memory"); }
template<int N> __device__ __forceinline__ void wgmma_wait() { asm volatile("wgmma.wait_group.sync.aligned %0;" :: "n"(N) : "memory"); }
template<int ID> __device__ __forceinline__ void bar_sync(int n) { asm volatile("bar.sync %0, %1;" :: "n"(ID), "r"(n) : "memory"); }
template<int ID> __device__ __forceinline__ void bar_arrive(int n) { asm volatile("bar.arrive %0, %1;" :: "n"(ID), "r"(n) : "memory"); }
__device__ __forceinline__ void cluster_wait() { asm volatile("barrier.cluster.wait.aligned;" ::: "memory"); }
__device__ __forceinline__ uint64_t desc64(uint32_t lo, uint32_t hi) { return (uint64_t)lo | ((uint64_t)hi << 32); }
__device__ __forceinline__ uint2 ld_tag2(const uint2* p) {
  uint2 v; asm volatile("ld.relaxed.gpu.global.v2.u32 {%0,%1}, [%2];" : "=r"(v.x), "=r"(v.y) : "l"(p) : "memory"); return v;
}
__device__ __forceinline__ void st_tag2(uint2* p, uint32_t a, uint32_t b) {
  asm volatile("st.relaxed.gpu.global.v2.u32 [%0], {%1,%2};" :: "l"(p), "r"(a), "r"(b) : "memory");
}
__device__ __forceinline__ void stg128(void* p, uint4 v) {
  asm volatile("st.global.v4.u32 [%0], {%1,%2,%3,%4};" :: "l"(p), "r"(v.x), "r"(v.y), "r"(v.z), "r"(v.w));
}
__device__ __forceinline__ unsigned ld_relaxed(const unsigned* p) {
  unsigned v; asm volatile("ld.relaxed.gpu.global.u32 %0, [%1];" : "=r"(v) : "l"(p) : "memory"); return v;
}
__device__ __forceinline__ uint32_t pack_bf16(float lo, float hi) {
  uint32_t r; asm("cvt.rn.bf16x2.f32 %0, %1, %2;" : "=r"(r) : "f"(hi), "f"(lo)); return r;
}
__device__ __forceinline__ float bf_lo(uint32_t v) { return __uint_as_float(v << 16); }
__device__ __forceinline__ float bf_hi(uint32_t v) { return __uint_as_float(v & 0xFFFF0000u); }
__device__ __forceinline__ void stsm4(uint32_t addr, uint32_t a, uint32_t b, uint32_t c, uint32_t d) {
  asm volatile("stmatrix.sync.aligned.m8n8.x4.shared.b16 [%0], {%1,%2,%3,%4};" :: "r"(addr), "r"(a), "r"(b), "r"(c), "r"(d));
}
__device__ __forceinline__ void stsm4_t(uint32_t addr, uint32_t a, uint32_t b, uint32_t c, uint32_t d) {
  asm volatile("stmatrix.sync.aligned.m8n8.x4.trans.shared.b16 [%0], {%1,%2,%3,%4};" :: "r"(addr), "r"(a), "r"(b), "r"(c), "r"(d));
}
__device__ __forceinline__ void ldsm4(uint32_t addr, uint32_t& a, uint32_t& b, uint32_t& c, uint32_t& d) {
  asm volatile("ldmatrix.sync.aligned.m8n8.x4.shared.b16 {%0,%1,%2,%3}, [%4];" : "=r"(a), "=r"(b), "=r"(c), "=r"(d) : "r"(addr));
}
__device__ __forceinline__ uint4 lds128(uint32_t a) {
  uint4 v; asm volatile("ld.shared.v4.u32 {%0,%1,%2,%3}, [%4];" : "=r"(v.x), "=r"(v.y), "=r"(v.z), "=r"(v.w) : "r"(a)); return v;
}
__device__ __forceinline__ void sts128(uint32_t a, uint32_t x, uint32_t y, uint32_t z, uint32_t w) {
  asm volatile("st.shared.v4.u32 [%0], {%1,%2,%3,%4};" :: "r"(a), "r"(x), "r"(y), "r"(z), "r"(w));
}
__device__ __forceinline__ uint32_t hmul2_bf16(uint32_t a, uint32_t b) {
  uint32_t r; asm("mul.rn.bf16x2 %0, %1, %2;" : "=r"(r) : "r"(a), "r"(b)); return r;
}
__device__ __forceinline__ uint32_t hadd2_bf16(uint32_t a, uint32_t b) {
  uint32_t r; asm("add.rn.bf16x2 %0, %1, %2;" : "=r"(r) : "r"(a), "r"(b)); return r;
}
__device__ __forceinline__ uint32_t hfma2_bf16(uint32_t a, uint32_t b, uint32_t c) {
  uint32_t r; asm("fma.rn.bf16x2 %0, %1, %2, %3;" : "=r"(r) : "r"(a), "r"(b), "r"(c)); return r;
}
__device__ __forceinline__ float gelu_tanh(float v) {
  float u = v * fmaf(0.0356774081f, v * v, 0.7978845608f);
  float t; asm("tanh.approx.f32 %0, %1;" : "=f"(t) : "f"(u));
  float hv = 0.5f * v;
  return fmaf(hv, t, hv);
}

template<int TB>
__device__ __forceinline__ void wgmma_n192(float (&d)[96], uint64_t da, uint64_t db, int scale_d) {
  asm volatile("{\n.reg .pred p;\nsetp.ne.b32 p, %98, 0;\n"
   "wgmma.mma_async.sync.aligned.m64n192k16.f32.bf16.bf16 {%0,%1,%2,%3,%4,%5,%6,%7,%8,%9,%10,%11,%12,%13,%14,%15,%16,%17,%18,%19,%20,%21,%22,%23,%24,%25,%26,%27,%28,%29,%30,%31,%32,%33,%34,%35,%36,%37,%38,%39,%40,%41,%42,%43,%44,%45,%46,%47,%48,%49,%50,%51,%52,%53,%54,%55,%56,%57,%58,%59,%60,%61,%62,%63,%64,%65,%66,%67,%68,%69,%70,%71,%72,%73,%74,%75,%76,%77,%78,%79,%80,%81,%82,%83,%84,%85,%86,%87,%88,%89,%90,%91,%92,%93,%94,%95}, %96, %97, p, 1, 1, 0, %99;\n}"
   : "+f"(d[0]),"+f"(d[1]),"+f"(d[2]),"+f"(d[3]),"+f"(d[4]),"+f"(d[5]),"+f"(d[6]),"+f"(d[7]),"+f"(d[8]),"+f"(d[9]),"+f"(d[10]),"+f"(d[11]),"+f"(d[12]),"+f"(d[13]),"+f"(d[14]),"+f"(d[15]),"+f"(d[16]),"+f"(d[17]),"+f"(d[18]),"+f"(d[19]),"+f"(d[20]),"+f"(d[21]),"+f"(d[22]),"+f"(d[23]),"+f"(d[24]),"+f"(d[25]),"+f"(d[26]),"+f"(d[27]),"+f"(d[28]),"+f"(d[29]),"+f"(d[30]),"+f"(d[31]),"+f"(d[32]),"+f"(d[33]),"+f"(d[34]),"+f"(d[35]),"+f"(d[36]),"+f"(d[37]),"+f"(d[38]),"+f"(d[39]),"+f"(d[40]),"+f"(d[41]),"+f"(d[42]),"+f"(d[43]),"+f"(d[44]),"+f"(d[45]),"+f"(d[46]),"+f"(d[47]),"+f"(d[48]),"+f"(d[49]),"+f"(d[50]),"+f"(d[51]),"+f"(d[52]),"+f"(d[53]),"+f"(d[54]),"+f"(d[55]),"+f"(d[56]),"+f"(d[57]),"+f"(d[58]),"+f"(d[59]),"+f"(d[60]),"+f"(d[61]),"+f"(d[62]),"+f"(d[63]),"+f"(d[64]),"+f"(d[65]),"+f"(d[66]),"+f"(d[67]),"+f"(d[68]),"+f"(d[69]),"+f"(d[70]),"+f"(d[71]),"+f"(d[72]),"+f"(d[73]),"+f"(d[74]),"+f"(d[75]),"+f"(d[76]),"+f"(d[77]),"+f"(d[78]),"+f"(d[79]),"+f"(d[80]),"+f"(d[81]),"+f"(d[82]),"+f"(d[83]),"+f"(d[84]),"+f"(d[85]),"+f"(d[86]),"+f"(d[87]),"+f"(d[88]),"+f"(d[89]),"+f"(d[90]),"+f"(d[91]),"+f"(d[92]),"+f"(d[93]),"+f"(d[94]),"+f"(d[95])
   : "l"(da), "l"(db), "r"(scale_d), "n"(TB));
}
template<int TB>
__device__ __forceinline__ void wgmma_n160(float (&d)[80], uint64_t da, uint64_t db, int scale_d) {
  asm volatile("{\n.reg .pred p;\nsetp.ne.b32 p, %82, 0;\n"
   "wgmma.mma_async.sync.aligned.m64n160k16.f32.bf16.bf16 {%0,%1,%2,%3,%4,%5,%6,%7,%8,%9,%10,%11,%12,%13,%14,%15,%16,%17,%18,%19,%20,%21,%22,%23,%24,%25,%26,%27,%28,%29,%30,%31,%32,%33,%34,%35,%36,%37,%38,%39,%40,%41,%42,%43,%44,%45,%46,%47,%48,%49,%50,%51,%52,%53,%54,%55,%56,%57,%58,%59,%60,%61,%62,%63,%64,%65,%66,%67,%68,%69,%70,%71,%72,%73,%74,%75,%76,%77,%78,%79}, %80, %81, p, 1, 1, 0, %83;\n}"
   : "+f"(d[0]),"+f"(d[1]),"+f"(d[2]),"+f"(d[3]),"+f"(d[4]),"+f"(d[5]),"+f"(d[6]),"+f"(d[7]),"+f"(d[8]),"+f"(d[9]),"+f"(d[10]),"+f"(d[11]),"+f"(d[12]),"+f"(d[13]),"+f"(d[14]),"+f"(d[15]),"+f"(d[16]),"+f"(d[17]),"+f"(d[18]),"+f"(d[19]),"+f"(d[20]),"+f"(d[21]),"+f"(d[22]),"+f"(d[23]),"+f"(d[24]),"+f"(d[25]),"+f"(d[26]),"+f"(d[27]),"+f"(d[28]),"+f"(d[29]),"+f"(d[30]),"+f"(d[31]),"+f"(d[32]),"+f"(d[33]),"+f"(d[34]),"+f"(d[35]),"+f"(d[36]),"+f"(d[37]),"+f"(d[38]),"+f"(d[39]),"+f"(d[40]),"+f"(d[41]),"+f"(d[42]),"+f"(d[43]),"+f"(d[44]),"+f"(d[45]),"+f"(d[46]),"+f"(d[47]),"+f"(d[48]),"+f"(d[49]),"+f"(d[50]),"+f"(d[51]),"+f"(d[52]),"+f"(d[53]),"+f"(d[54]),"+f"(d[55]),"+f"(d[56]),"+f"(d[57]),"+f"(d[58]),"+f"(d[59]),"+f"(d[60]),"+f"(d[61]),"+f"(d[62]),"+f"(d[63]),"+f"(d[64]),"+f"(d[65]),"+f"(d[66]),"+f"(d[67]),"+f"(d[68]),"+f"(d[69]),"+f"(d[70]),"+f"(d[71]),"+f"(d[72]),"+f"(d[73]),"+f"(d[74]),"+f"(d[75]),"+f"(d[76]),"+f"(d[77]),"+f"(d[78]),"+f"(d[79])
   : "l"(da), "l"(db), "r"(scale_d), "n"(TB));
}

template<int N, int TB>
__device__ __forceinline__ void wgmma_n(float (&d)[N / 2], uint64_t da, uint64_t db) {
  if constexpr (N == 192) wgmma_n192<TB>(d, da, db, 1); else wgmma_n160<TB>(d, da, db, 1);
}

template<int M, int R>
__device__ __forceinline__ void pin(float (&acc)[M][R]) {
  #pragma unroll
  for (int mi = 0; mi < M; mi++)
    #pragma unroll
    for (int i = 0; i < R; i++) asm volatile("" : "+f"(acc[mi][i]) :: "memory");
}
template<int M, int R>
__device__ __forceinline__ void zero(float (&acc)[M][R]) {
  #pragma unroll
  for (int mi = 0; mi < M; mi++)
    #pragma unroll
    for (int i = 0; i < R; i++) acc[mi][i] = 0.f;
  pin(acc);
}

template<int N, int M, int TB, bool CONT, int ORD_BAR, bool AOWN = false>
__device__ __forceinline__ void mainloop(float (&acc)[M][N / 2], uint32_t sbase, int grp, int g0, int nk, int m0 = 0) {
  const uint32_t full0 = sbase + BAR_OFF, empty0 = full0 + 8 * MAXST, ring = sbase + RING_OFF;
  const int nst = grp == 0 ? NST_A : NST_B, total = grp == 0 ? KB_A : KB_B;
  const uint32_t sstep = (grp == 0 ? STAGE_A : STAGE_B) >> 4;
  const int t = threadIdx.x & 127;
  const uint32_t da0 = (((ring + m0 * 8192) & 0x3FFFF) >> 4) | 0x10000u;
  const uint32_t db0 = (((ring + A_BYTES) & 0x3FFFF) >> 4) | ((TB == 2 ? 256u : TB ? 512u : 1u) << 16);
  constexpr uint32_t HI_A = 0x40000040u, HI_B = TB == 2 ? 0x80000020u : 0x40000040u;
  int s = g0 % nst, ph = (g0 / nst) & 1, ps = s == 0 ? nst - 1 : s - 1;
  #pragma unroll 1
  for (int g = g0; g < g0 + nk; g++) {
    const uint32_t so = s * sstep;
    mbar_wait(full0 + 8 * s, ph);
    wgmma_fence();
    #pragma unroll
    for (int k = 0; k < 4; k++) {
      const uint64_t db = desc64(db0 + so + (TB == 2 ? k * 64 : TB ? k * 128 : k * 2), HI_B);
      #pragma unroll
      for (int mi = 0; mi < M; mi++)
        wgmma_n<N, TB != 0>(acc[mi], desc64(AOWN ? da0 + ((NST_A * STAGE_A) >> 4) + (g - g0) * 512 + mi * 1536 + k * 2 : da0 + so + mi * 512 + k * 2, HI_A), db);
    }
    wgmma_commit();
    if (ORD_BAR != 0 && g == g0 + nk - 1) bar_arrive<ORD_BAR>(256);
    wgmma_wait<1>();
    if (t < 2 * M && (CONT || g > g0) && g - 1 + nst < total) mbar_arrive_cluster(empty0 + 8 * ps, t & 1);
    ps = s;
    if (++s == nst) { s = 0; ph ^= 1; }
  }
}
template<int M, int R>
__device__ __forceinline__ void drain(float (&acc)[M][R], uint32_t sbase, int grp, int glast) {
  wgmma_wait<0>();
  pin(acc);
  const int t = threadIdx.x & 127;
  const int nst = grp == 0 ? NST_A : NST_B, total = grp == 0 ? KB_A : KB_B;
  if (t < 2 * M && glast + nst < total) mbar_arrive_cluster(sbase + BAR_OFF + 8 * MAXST + 8 * (glast % nst), t & 1);
}

__device__ __forceinline__ void set_flag(int slot, int byte, unsigned epoch) {
  asm volatile("st.relaxed.gpu.global.u8 [%0], %1;" :: "l"(g_flags + slot * 256 + byte), "r"(epoch & 255u) : "memory");
}
__device__ __forceinline__ unsigned get_flag(int slot, int byte) {
  unsigned v; asm volatile("ld.relaxed.gpu.global.u8 %0, [%1];" : "=r"(v) : "l"(g_flags + slot * 256 + byte) : "memory"); return v;
}
__device__ __forceinline__ void publish(int slot, int byte, unsigned epoch) {
  asm volatile("fence.acq_rel.gpu;" ::: "memory");
  set_flag(slot, byte, epoch);
}
__device__ __forceinline__ float sum8(uint4 v) {
  return ((bf_lo(v.x) + bf_hi(v.x)) + (bf_lo(v.y) + bf_hi(v.y))) + ((bf_lo(v.z) + bf_hi(v.z)) + (bf_lo(v.w) + bf_hi(v.w)));
}
__device__ __forceinline__ uint4 ldg128(const void* p) {
  uint4 v; asm volatile("ld.global.nc.v4.u32 {%0,%1,%2,%3}, [%4];" : "=r"(v.x), "=r"(v.y), "=r"(v.z), "=r"(v.w) : "l"(p)); return v;
}

__device__ __forceinline__ void ln_rows(const uint4 (&rv)[5], uint32_t buf, int cta, unsigned epoch) {
  const int t = threadIdx.x - 128, row = cta * 16 + (t >> 4), c = t & 15;
  const float sh = __shfl_sync(0xffffffffu, bf_lo(rv[0].x), t & 16);
  float d[40], s = 0.f, q = 0.f;
  #pragma unroll
  for (int j = 0; j < 5; j++) {
    const uint32_t u[4] = {rv[j].x, rv[j].y, rv[j].z, rv[j].w};
    #pragma unroll
    for (int e = 0; e < 4; e++) {
      const float d0 = bf_lo(u[e]) - sh, d1 = bf_hi(u[e]) - sh;
      d[j * 8 + e * 2] = d0; d[j * 8 + e * 2 + 1] = d1;
      s += d0 + d1; q = fmaf(d0, d0, q); q = fmaf(d1, d1, q);
    }
  }
  #pragma unroll
  for (int o = 1; o < 16; o <<= 1) { s += __shfl_xor_sync(0xffffffffu, s, o); q += __shfl_xor_sync(0xffffffffu, q, o); }
  const float md = s * (1.f / DM);
  const float r = rsqrtf(fmaxf(fmaf(q, 1.f / DM, -md * md), 0.f) + LN_EPS), o = -md * r;
  if (c == 0) st_tag2(&g_xstat[row], __float_as_uint(r), (__float_as_uint(-(md + sh) * r) & ~255u) | (epoch & 255u));
  #pragma unroll
  for (int j = 0; j < 5; j++) {
    const float* a = &d[j * 8];
    sts128(buf + (t >> 4) * 1280 + (c + 16 * j) * 16,
           pack_bf16(fmaf(a[0], r, o), fmaf(a[1], r, o)), pack_bf16(fmaf(a[2], r, o), fmaf(a[3], r, o)),
           pack_bf16(fmaf(a[4], r, o), fmaf(a[5], r, o)), pack_bf16(fmaf(a[6], r, o), fmaf(a[7], r, o)));
  }
  fence_async_smem();
  bar_arrive<BAR_LN>(288);
}

__device__ __forceinline__ void weight_sums(const bf16* __restrict__ win, const bf16* __restrict__ wdre, int j, unsigned epoch) {
  const int t = threadIdx.x & 127, w = t >> 5, l = t & 31;
  const int cj = min(j, 59), cg = cj % 12, rg = cj / 12, wr = j * 10 + min(t >> 3, 9);
  uint4 cv[8], rv[10];
  #pragma unroll
  for (int i = 0; i < 8; i++) cv[i] = ldg128(reinterpret_cast<const uint4*>(win + (size_t)(rg * 128 + w * 32 + i * 4 + (l >> 3)) * FF + FH + cg * 64) + (l & 7));
  #pragma unroll
  for (int i = 0; i < 10; i++) rv[i] = ldg128(reinterpret_cast<const uint4*>(wdre + (size_t)wr * DM) + (l & 7) + 8 * i);
  float v[8];
  #pragma unroll
  for (int e = 0; e < 8; e++) v[e] = 0.f;
  #pragma unroll
  for (int i = 0; i < 8; i++) {
    v[0] += bf_lo(cv[i].x); v[1] += bf_hi(cv[i].x); v[2] += bf_lo(cv[i].y); v[3] += bf_hi(cv[i].y);
    v[4] += bf_lo(cv[i].z); v[5] += bf_hi(cv[i].z); v[6] += bf_lo(cv[i].w); v[7] += bf_hi(cv[i].w);
  }
  #pragma unroll
  for (int st = 0; st < 2; st++) {
    const int n = 4 >> st;
    const bool up = (l & (4 * n)) != 0;
    #pragma unroll
    for (int e = 0; e < 4; e++)
      if (e < n) { const float keep = up ? v[e + n] : v[e], send = up ? v[e] : v[e + n]; v[e] = keep + __shfl_xor_sync(0xffffffffu, send, 4 * n); }
  }
  float* red = reinterpret_cast<float*>(smem + RED_OFF);
  *reinterpret_cast<float2*>(red + w * 64 + (l & 7) * 8 + (l >> 3) * 2) = make_float2(v[0], v[1]);
  float s = 0.f;
  #pragma unroll
  for (int i = 0; i < 10; i++) s += sum8(rv[i]);
  #pragma unroll
  for (int o = 1; o < 8; o <<= 1) s += __shfl_xor_sync(0xffffffffu, s, o);
  if ((l & 7) == 0) st_tag2(&g_csum[5 * FH + wr], __float_as_uint(s), epoch);
  bar_sync<BAR_WG1>(128);
  if (t < 64) st_tag2(&g_csum[rg * FH + cg * 64 + t], __float_as_uint((red[t] + red[64 + t]) + (red[128 + t] + red[192 + t])), epoch);
}

__device__ __forceinline__ void gather96(const uint2* src, float* dst, unsigned epoch) {
  unsigned it = 0;
  while (true) {
    bool ok = true;
    uint2 u[15];
    #pragma unroll
    for (int j = 0; j < 15; j++) u[j] = ld_tag2(src + (j % 5) * FH + (j / 5) * 32);
    #pragma unroll
    for (int j = 0; j < 15; j++) ok = ok && u[j].y == epoch;
    #pragma unroll
    for (int j = 0; j < 3; j++)
      dst[j * 32] = ((__uint_as_float(u[j * 5].x) + __uint_as_float(u[j * 5 + 1].x)) + (__uint_as_float(u[j * 5 + 2].x) + __uint_as_float(u[j * 5 + 3].x))) + __uint_as_float(u[j * 5 + 4].x);
    if (ok || ++it > POLL_LIMIT) break;
    __nanosleep(2 * POLL_NS);
  }
}

__device__ __forceinline__ void a_entry(int g, int grp, int ct, int& mi, int& kb) {
  if (g < 10) { mi = M_X; kb = g; }
  else if (g < 20) { mi = M_XN; kb = g - 10; }
  else if (g < 52) { mi = grp == 0 ? M_WSP : M_WSRE; kb = g - 20; }
  else if (grp == 0) {
    if (g < 52 + NX) { mi = M_WSIM; kb = g - 52 + 32 - NX; }
    else {
      const int i = g - 52 - NX;
      mi = M_H; kb = i < 3 ? ct * 3 + i : i < 6 ? (ct ^ 1) * 3 + i - 3 : ((ct >> 1) ^ 1) * 6 + i - 6;
    }
  } else {
    if (g < 84 - NX) { mi = M_WSIM; kb = g - 52; }
    else { mi = M_H; kb = ((ct >> 1) ^ 1) * 6 + g - (84 - NX) + 6 - NO; }
  }
}

__global__ void __cluster_dims__(2, 1, 1) __launch_bounds__(384, 1)
fused_kernel(const __grid_constant__ Maps maps, const bf16* __restrict__ x, const bf16* __restrict__ win, const bf16* __restrict__ wdre,
             const bf16* __restrict__ bsp, const bf16* __restrict__ wout, bf16* __restrict__ out) {
  const uint32_t sbase = smem_u32(smem);
  const uint32_t full0 = sbase + BAR_OFF, empty0 = full0 + 8 * MAXST, dep0 = empty0 + 8 * MAXST, ring = sbase + RING_OFF;
  const int tid = threadIdx.x, wg = __shfl_sync(0xffffffffu, tid >> 7, 0);
  if (blockIdx.x < 4) {
    if (tid == 0) {
      const unsigned epoch = (ld_relaxed(&g_done) >> 7) + 1u;
      for (int s = 0; s < 4; s++) mbar_init(sbase + 8 * s, 1);
      asm volatile("fence.mbarrier_init.release.cluster;" ::: "memory");
      __nanosleep(HELP_NS);
      const char* src = reinterpret_cast<const char*>(x) + (size_t)blockIdx.x * 655360;
      char* dst = reinterpret_cast<char*>(out) + (size_t)blockIdx.x * 655360;
      #pragma unroll 1
      for (int i = 0; i < 16 + 3; i++) {
        if (i < 16) {
          if (i >= 4) asm volatile("cp.async.bulk.wait_group.read 0;" ::: "memory");
          mbar_expect_tx(sbase + 8 * (i & 3), 40960);
          asm volatile("cp.async.bulk.shared::cluster.global.mbarrier::complete_tx::bytes [%0], [%1], 40960, [%2];"
                       :: "r"(sbase + 1024 + (i & 3) * 40960), "l"(src + (size_t)i * 40960), "r"(sbase + 8 * (i & 3)) : "memory");
        }
        if (i >= 3) {
          const int j = i - 3;
          mbar_wait(sbase + 8 * (j & 3), (j >> 2) & 1);
          asm volatile("cp.async.bulk.global.shared::cta.bulk_group [%0], [%1], 40960;" :: "l"(dst + (size_t)j * 40960), "r"(sbase + 1024 + (j & 3) * 40960) : "memory");
          bulk_commit();
        }
      }
      bulk_wait_all();
      for (int r = 0; r < 4; r++) set_flag(F_Y + blockIdx.x * 4 + r, 0, epoch);
    }
    return;
  }
  const int cta = blockIdx.x - 4, rank = cta & 1, grp = (cta >> 1) & 1, rb = cta >> 3, ct = ((cta >> 2) & 1) * 2 + rank;
  const int total = grp == 0 ? KB_A : KB_B, gh = grp == 0 ? 52 + NX : 84 - NX;
  const uint32_t stage_bytes = grp == 0 ? STAGE_A : STAGE_B;
  const int nst = grp == 0 ? NST_A : NST_B;
  const uint32_t buf = ring + nst * stage_bytes;

  uint4 rv[5];
  if (wg != 0) {
    #pragma unroll
    for (int j = 0; j < 5; j++) rv[j] = ldg128(reinterpret_cast<const uint4*>(x + (size_t)(cta * 16 + ((tid - 128) >> 4)) * DM) + (tid & 15) + 16 * j);
  }
  const unsigned epoch = (ld_relaxed(&g_done) >> 7) + 1u;
  if (tid == 0) {
    TS(0, 0);
    for (int s = 0; s < MAXST; s++) { mbar_init(full0 + 8 * s, 2); mbar_init(empty0 + 8 * s, 4); mbar_init(dep0 + 8 * s, 1); }
    *reinterpret_cast<volatile int*>(smem + READY_OFF) = 0;
    asm volatile("fence.mbarrier_init.release.cluster;" ::: "memory");
  }
  __syncthreads();
  asm volatile("barrier.cluster.arrive.relaxed.aligned;" ::: "memory");

  if (wg == 0) {
    asm volatile("setmaxnreg.dec.sync.aligned.u32 40;");
    const int warp = tid >> 5, lane = tid & 31;
    if (warp == 0) {
      const int row = rb * 128;
      if (lane == 0) {
        for (int g = 0; g < nst; g++) {
          mbar_expect_tx(full0 + 8 * g, A_BYTES);
          tma_load_2d(ring + g * stage_bytes, &maps.m[M_X], full0 + 8 * g, g * 64, row);
          tma_load_2d(ring + g * stage_bytes + 8192, &maps.m[M_X], full0 + 8 * g, g * 64, row + 64);
        }
      }
      __syncwarp();
      cluster_wait();
      if (lane == 0) {
        int s = 0, ph = 0;
        #pragma unroll 1
        for (int g = nst; g < total; g++) {
          int mi, kb;
          a_entry(g, grp, ct, mi, kb);
          if (g == 10 || g == gh + 6 - 6 * grp || (grp == 0 && g == gh + 3)) {
            TS(0, g > 10 ? 3 : 1);
            mbar_wait(dep0 + (g == 10 ? 0 : g == gh + 6 - 6 * grp ? 24 : 8), 0);
            fence_async_global();
            TS(0, g > 10 ? 4 : 2);
          }
          mbar_wait(empty0 + 8 * s, ph);
          if (grp == 0 && g >= gh && g < gh + 6) {
            if (g < gh + 3) {
              mbar_arrive(full0 + 8 * s);
            } else {
              mbar_expect_tx(full0 + 8 * s, A_BYTES);
              tma_load_2d(ring + s * stage_bytes, &maps.m[mi], full0 + 8 * s, kb * 64, row);
              tma_load_2d(ring + s * stage_bytes + 8192, &maps.m[mi], full0 + 8 * s, kb * 64, row + 64);
            }
          } else {
            mbar_expect_tx(full0 + 8 * s, A_BYTES);
            tma_load_2d_mc(ring + s * stage_bytes + rank * 8192, &maps.m[mi], full0 + 8 * s, kb * 64, row + rank * 64, 3);
          }
          if (++s == nst) { s = 0; ph ^= 1; }
          if (g + PF_D < gh) {
            a_entry(g + PF_D, grp, ct, mi, kb);
            if (mi >= M_WSRE && (kb & 1) == (ct >> 1))
              asm volatile("cp.async.bulk.prefetch.tensor.2d.L2.global.tile [%0, {%1, %2}];" :: "l"((uint64_t)&maps.m[mi]), "r"(kb * 64), "r"(row + rank * 64) : "memory");
          }
        }
        TS(0, 5);
      }
    } else if (warp == 1) {
      if (lane == 0) {
        int s = 0, ph = 1;
        int have = 0;
        #pragma unroll 1
        for (int g = 0; g < total; g++) {
          int mi, kb, c;
          a_entry(g, grp, ct, mi, kb);
          const bool nmaj = g >= gh || (grp == 0 && g < 52);
          uint32_t bytes = 20480;
          if (g >= gh) { mi = M_WOUT; c = ct * 5; }
          else if (g >= 52) { mi = M_AB; c = DM + ct * 160; }
          else if (grp == 0) { mi = g < 20 ? M_WIN3 : M_Z23; c = 3 * ct + (g < 10 ? 12 : 0); bytes = 24576; }
          else { mi = g < 10 ? M_WDRE : g < 20 ? M_WDIM : M_AB; c = ct * 160; }
          if (g >= 20 && g < 52 && ((g - 20) >> 1) >= have) {
            if (g == 20) TS(1, 0);
            unsigned it = 0;
            while ((have = *reinterpret_cast<volatile int*>(smem + READY_OFF)) <= ((g - 20) >> 1) && ++it < 50 * POLL_LIMIT) {}
            fence_async_global();
            if (g == 20) { TS(1, 1); TC(1); }
          }
          if (g == 52) { TS(1, 2); mbar_wait(dep0 + 16, 0); fence_async_global(); TS(1, 3); TC(2); }
          const uint32_t dst = ring + s * stage_bytes + A_BYTES, fb = full0 + 8 * s;
          mbar_wait(empty0 + 8 * s, ph);
          if (++s == nst) { s = 0; ph ^= 1; }
          mbar_expect_tx(fb, bytes);
          if (nmaj) tma_load_3d(dst, &maps.m[mi], fb, 0, kb * 64, c);
          else tma_load_2d(dst, &maps.m[mi], fb, kb * 64, c);
        }
      }
      __syncwarp();
      cluster_wait();
    } else if (warp == 2) {
      if (lane < M_COUNT) asm volatile("prefetch.tensormap [%0];" :: "l"((uint64_t)&maps.m[lane]) : "memory");
      cluster_wait();
      {
        unsigned it = 0;
        uint2 v[4];
        while (true) {
          bool ok = true;
          #pragma unroll
          for (int i = 0; i < 4; i++) { v[i] = ld_tag2(&g_xstat[rb * 128 + i * 32 + lane]); ok = ok && ((v[i].y ^ epoch) & 255u) == 0; }
          if (ok || ++it > POLL_LIMIT) break;
          __nanosleep(POLL_NS);
        }
        #pragma unroll
        for (int i = 0; i < 4; i++) reinterpret_cast<uint2*>(smem + ROWSTAT_OFF)[i * 32 + lane] = make_uint2(v[i].x, v[i].y & ~255u);
        __syncwarp();
        TS(0, 6);
      }
      const int hsrc = ((ct >> 1) ^ 1) * 2 + (grp == 0 ? (NO >= 3 ? 0 : lane & 1) : (NO <= 3 ? 1 : lane & 1));
      #pragma unroll 1
      for (int i = 0; i < 5; i++) {
        const int d = i == 3 ? 4 : i == 4 ? 3 : i;
        const int slot = d == 0 ? F_XN + rb : d == 4 ? F_Y + rb : d == 3 ? F_H + rb : d == 2 ? F_B + ct : grp == 0 ? F_Z + ct : F_A + ct;
        const int byte = d == 0 ? lane & 7 : d == 4 ? 0 : d == 3 ? hsrc : lane & 15;
        unsigned it = 0, m;
        while ((m = __ballot_sync(0xffffffffu, get_flag(slot, byte) != (epoch & 255u))) != 0 && ++it < POLL_LIMIT) {
          if (d == 1 && lane == 0) *reinterpret_cast<volatile int*>(smem + READY_OFF) = __ffs(m) - 1;
          __nanosleep(WATCH_NS);
        }
        if (d == 1 && lane == 0) *reinterpret_cast<volatile int*>(smem + READY_OFF) = 16;
        if (d < 4) TS(0, 8 + d * 2); else TS(0, 7);
        fence_async_global();
        __syncwarp();
        if (lane == 0 && d != 1) mbar_arrive(dep0 + 8 * d);
        if (d == 0) {
          if (grp == 0) {
            gather96(&g_csum[ct * 192 + 96 + lane], reinterpret_cast<float*>(smem + COLSUM_OFF) + 96 + lane, epoch);
            __syncwarp();
            bar_arrive<BAR_STATS>(320);
          } else {
            bar_arrive<BAR_STATS>(192);
          }
        }
        if (d == 2 && lane < 30) {
          asm volatile("prefetch.global.L2 [%0];" :: "l"(wout + (size_t)cta * 6 * DM + lane * 128));
          asm volatile("prefetch.global.L2 [%0];" :: "l"(wout + (size_t)cta * 6 * DM + lane * 128 + 64));
        }
      }
    } else {
      cluster_wait();
      bar_sync<BAR_LN>(288);
      if (lane == 0) {
        TS(1, 5);
        asm volatile("cp.async.bulk.global.shared::cta.bulk_group [%0], [%1], 20480;" :: "l"(g_xn + (size_t)cta * 16 * DM), "r"(buf) : "memory");
        bulk_commit();
        bulk_wait_all();
        set_flag(F_XN + rb, cta & 7, epoch);
        TS(1, 6);
      }
      __syncwarp();
      if (grp == 0) {
        gather96(&g_csum[ct * 192 + lane], reinterpret_cast<float*>(smem + COLSUM_OFF) + lane, epoch);
      } else {
        unsigned it = 0;
        while (true) {
          bool ok = true;
          #pragma unroll
          for (int j = 0; j < 5; j++) {
            const uint2 u = ld_tag2(&g_csum[5 * FH + ct * 160 + j * 32 + lane]);
            ok = ok && u.y == epoch;
            reinterpret_cast<uint32_t*>(smem + COLSUM_OFF)[j * 32 + lane] = u.x;
          }
          if (ok || ++it > POLL_LIMIT) break;
          __nanosleep(2 * POLL_NS);
        }
      }
      __syncwarp();
      TS(1, 4);
      if (grp == 0) {
        bar_arrive<BAR_STATS>(320);
        bar_sync<BAR_PUB1>(160);
        if (lane == 0) set_flag(F_Z + ct, rb, epoch);
        TS(1, 8);
        __syncwarp();
        bar_arrive<BAR_BUF>(160);
      } else {
        bar_arrive<BAR_STATS>(192);
        bar_sync<BAR_PUB2>(160);
        if (lane == 0) set_flag(F_A + ct, rb, epoch);
        TS(1, 9);
        __syncwarp();
      }
      bar_sync<BAR_PUB1>(160);
      if (lane == 0) {
        set_flag(grp == 0 ? F_H + rb : F_B + ct, grp == 0 ? ct : rb, epoch);
        if (grp == 0) mbar_arrive_cluster(dep0 + 8, rank ^ 1);
      }
      TS(1, 10);
      __syncwarp();
      bar_arrive<BAR_BUF>(160);
    }
  } else {
    asm volatile("setmaxnreg.inc.sync.aligned.u32 232;");
    const int t = tid & 127, w = t >> 5, l = t & 31;
    ln_rows(rv, buf, cta, epoch);
    TS(wg + 1, 0);
    cluster_wait();
    const uint32_t st_base = buf + (w * 16 + ((l >> 3) & 1) * 8 + (l & 7)) * 128;
    const uint32_t st_x = ((l >> 4) ^ (l & 7)) << 4;
    const float2* rs = reinterpret_cast<const float2*>(smem + ROWSTAT_OFF) + w * 16 + (l >> 2);
    const float2* cs = reinterpret_cast<const float2*>(smem + COLSUM_OFF) + (l & 3);
    if (grp == 0) {
      {
        const int mb = wg - 1;
        float acc[1][96];
        zero(acc);
        mainloop<192, 1, 1, false, 0>(acc, sbase, 0, 0, 10, mb);
        drain(acc, sbase, 0, 9);
        TS(wg + 1, 1);
        bar_sync<BAR_STATS>(320);
        const float2 s0 = rs[mb * 64], s1 = rs[mb * 64 + 8];
        const float nm[2] = {s0.y / s0.x, s1.y / s1.x}, hr[2] = {0.5f * s0.x, 0.5f * s1.x};
        const float k1[2] = {0.7978845608f * s0.x, 0.7978845608f * s1.x};
        const float k2[2] = {0.0356774081f * s0.x * s0.x * s0.x, 0.0356774081f * s1.x * s1.x * s1.x};
        float sm0 = 0.f, sm1 = 0.f, q0 = 0.f, q1 = 0.f;
        #pragma unroll 1
        for (int bx = 0; bx < 3; bx++) {
          #pragma unroll
          for (int jj = 0; jj < 4; jj++) {
            float u[8];
            #pragma unroll
            for (int hf = 0; hf < 2; hf++) {
              const float2 c = cs[bx * 32 + jj * 8 + hf * 4];
              #pragma unroll
              for (int e = 0; e < 4; e++) {
                const float wv = fmaf(nm[e >> 1], (e & 1) ? c.y : c.x, acc[0][8 * jj + 4 * hf + e]);
                float th; asm("tanh.approx.f32 %0, %1;" : "=f"(th) : "f"(wv * fmaf(k2[e >> 1], wv * wv, k1[e >> 1])));
                const float hv = hr[e >> 1] * wv;
                u[4 * hf + e] = fmaf(hv, th, hv);
              }
              sm0 += u[4 * hf] + u[4 * hf + 1]; q0 = fmaf(u[4 * hf], u[4 * hf], q0); q0 = fmaf(u[4 * hf + 1], u[4 * hf + 1], q0);
              sm1 += u[4 * hf + 2] + u[4 * hf + 3]; q1 = fmaf(u[4 * hf + 2], u[4 * hf + 2], q1); q1 = fmaf(u[4 * hf + 3], u[4 * hf + 3], q1);
            }
            stsm4(st_base + mb * 24576 + bx * 8192 + (st_x ^ (jj << 5)),
                  pack_bf16(u[0], u[1]), pack_bf16(u[2], u[3]), pack_bf16(u[4], u[5]), pack_bf16(u[6], u[7]));
          }
          #pragma unroll
          for (int i = 0; i < 64; i++) acc[0][i] = acc[0][i + 32];
        }
        #pragma unroll
        for (int o = 1; o < 4; o <<= 1) {
          sm0 += __shfl_xor_sync(0xffffffffu, sm0, o); q0 += __shfl_xor_sync(0xffffffffu, q0, o);
          sm1 += __shfl_xor_sync(0xffffffffu, sm1, o); q1 += __shfl_xor_sync(0xffffffffu, q1, o);
        }
        if ((l & 3) < 2) {
          const float sm = (l & 1) ? sm1 : sm0, sv = (l & 1) ? q1 : q0;
          const int row = mb * 64 + w * 16 + (l & 1) * 8 + (l >> 2);
          const float mu = sm * (1.f / 192), m2 = fmaxf(sv - sm * mu, 0.f);
          st_tag2(&g_zstat[(rb * 4 + ct) * 128 + row], __float_as_uint(mu), (__float_as_uint(m2) & ~255u) | (epoch & 255u));
          reinterpret_cast<float2*>(smem + ZSTAT_OFF)[row] = make_float2(mu, m2);
        }
        TS(wg + 1, 4);
      }
      float acc[2][96];
      if (wg == 1) {
        bar_sync<BAR_U>(256);
        uint2 v[3];
        unsigned n = 0;
        while (true) {
          bool ok = true;
          #pragma unroll
          for (int j = 0; j < 3; j++) { v[j] = ld_tag2(&g_zstat[(rb * 4 + ((ct + 1 + j) & 3)) * 128 + t]); ok = ok && ((v[j].y ^ epoch) & 255u) == 0; }
          if (ok || ++n > POLL_LIMIT) break;
          __nanosleep(POLL_NS);
        }
        const float2 own = reinterpret_cast<const float2*>(smem + ZSTAT_OFF)[t];
        const float m0 = __uint_as_float(v[0].x), m1 = __uint_as_float(v[1].x), m3 = __uint_as_float(v[2].x);
        const float mean = 0.25f * ((own.x + m0) + (m1 + m3));
        const float d = (own.x - mean) * (own.x - mean) + (m0 - mean) * (m0 - mean) + (m1 - mean) * (m1 - mean) + (m3 - mean) * (m3 - mean);
        const float var = fmaf(192.f, d, (own.y + __uint_as_float(v[0].y & ~255u)) + (__uint_as_float(v[1].y & ~255u) + __uint_as_float(v[2].y & ~255u)));
        const float r = rsqrtf(var * (1.f / FH) + LN_EPS);
        TS(2, 5);
        const uint32_t rbase = buf + (t >> 6) * 24576 + (t & 63) * 128;
        const uint32_t m2 = pack_bf16(-mean, -mean), r2 = pack_bf16(r, r);
        const float res = (-mean - bf_lo(m2)) * r;
        const uint32_t e2 = pack_bf16(res, res);
        #pragma unroll 1
        for (int c = 0; c < 3; c++) {
          uint4 z[8];
          #pragma unroll
          for (int i = 0; i < 8; i++) z[i] = lds128(rbase + c * 8192 + (((i ^ l) & 7) << 4));
          #pragma unroll
          for (int i = 0; i < 8; i++)
            sts128(rbase + c * 8192 + (((i ^ l) & 7) << 4), hfma2_bf16(hadd2_bf16(z[i].x, m2), r2, e2), hfma2_bf16(hadd2_bf16(z[i].y, m2), r2, e2),
                   hfma2_bf16(hadd2_bf16(z[i].z, m2), r2, e2), hfma2_bf16(hadd2_bf16(z[i].w, m2), r2, e2));
          fence_async_smem();
          __syncwarp();
          if (l == 0) {
            tma_store_2d(&maps.m[M_ZS], buf + (w >> 1) * 24576 + c * 8192 + (w & 1) * 4096, ct * 192 + c * 64, rb * 128 + w * 32);
            bulk_commit();
          }
        }
        TS(2, 6);
        if (l == 0) bulk_wait_all();
        __syncwarp();
        bar_arrive<BAR_PUB1>(160);
        {
          const bf16* bp = bsp + rb * 128 + w * 16 + (l >> 2);
          const float bb[4] = {__bfloat162float(bp[0]), __bfloat162float(bp[8]), __bfloat162float(bp[64]), __bfloat162float(bp[72])};
          #pragma unroll
          for (int i = 0; i < 96; i++) { acc[0][i] = bb[(i >> 1) & 1]; acc[1][i] = bb[2 + ((i >> 1) & 1)]; }
          pin(acc);
        }
        bar_sync<BAR_ORD2>(256);
        mainloop<192, 2, 1, false, BAR_ORD1>(acc, sbase, 0, 20, 32);
        bar_sync<BAR_Z1>(256);
        uint32_t z[6][4][4];
        #pragma unroll
        for (int i = 0; i < ZPRE; i++) ldsm4(st_base + (i >> 2) * 8192 + (st_x ^ ((i & 3) << 5)), z[i >> 2][i & 3][0], z[i >> 2][i & 3][1], z[i >> 2][i & 3][2], z[i >> 2][i & 3][3]);
        drain(acc, sbase, 0, 51);
        TS(2, 7);
        #pragma unroll
        for (int bx = 0; bx < 6; bx++) {
          if (bx >= 1) {
            #pragma unroll
            for (int i = ZPRE + (bx - 1) * 10; i < ZPRE + bx * 10; i++)
              if (i < 24) ldsm4(st_base + (i >> 2) * 8192 + (st_x ^ ((i & 3) << 5)), z[i >> 2][i & 3][0], z[i >> 2][i & 3][1], z[i >> 2][i & 3][2], z[i >> 2][i & 3][3]);
          }
          #pragma unroll
          for (int i = 0; i < 4; i++) {
            const float* a = &acc[bx / 3][8 * ((bx % 3) * 4 + i)];
            const uint32_t* zz = z[bx][i];
            stsm4(st_base + bx * 8192 + (st_x ^ (i << 5)),
                  hmul2_bf16(zz[0], pack_bf16(a[0], a[1])), hmul2_bf16(zz[1], pack_bf16(a[2], a[3])),
                  hmul2_bf16(zz[2], pack_bf16(a[4], a[5])), hmul2_bf16(zz[3], pack_bf16(a[6], a[7])));

          }
          if (bx % 3 == 2) {
            fence_async_smem();
            __syncwarp();
            if (l < 3) {
              tma_store_2d(&maps.m[M_HS], buf + (bx - 2 + l) * 8192 + w * 2048, ct * 192 + l * 64, rb * 128 + (bx / 3) * 64 + w * 16);
              bulk_commit();
            }
          }
        }
        bar_arrive<BAR_U>(256);
        TS(2, 8);
        if (l < 3) bulk_wait_all();
        __syncwarp();
        bar_arrive<BAR_PUB1>(160);
        TS(2, 9);
        return;
      }
      bar_arrive<BAR_U>(256);
      zero(acc);
      mainloop<192, 2, 1, false, BAR_ORD2>(acc, sbase, 0, 10, 10);
      drain(acc, sbase, 0, 19);
      TS(3, 2);
      bar_sync<BAR_BUF>(160);
      #pragma unroll
      for (int mi = 0; mi < 2; mi++)
        #pragma unroll
        for (int jj = 0; jj < 12; jj++) {
          const float* a = &acc[mi][8 * jj];
          stsm4(st_base + mi * 24576 + (jj >> 2) * 8192 + (st_x ^ ((jj & 3) << 5)),
                pack_bf16(a[0], a[1]), pack_bf16(a[2], a[3]), pack_bf16(a[4], a[5]), pack_bf16(a[6], a[7]));
        }
      __syncwarp();
      TS(3, 3);
      const uint32_t rbase = buf + (l >> 4) * 24576 + (w * 16 + (l & 15)) * 128;
      #pragma unroll 1
      for (int c2 = 0; c2 < 12; c2++) {
        const uint32_t ab = rbase + (c2 >> 2) * 8192;
        uint4 v[2];
        #pragma unroll
        for (int i = 0; i < 2; i++) v[i] = lds128(ab + (((((c2 & 3) * 2 + i) ^ l) & 7) << 4));
        #pragma unroll
        for (int i = 0; i < 2; i++)
          sts128(ab + (((((c2 & 3) * 2 + i) ^ l) & 7) << 4),
                 pack_bf16(gelu_tanh(bf_lo(v[i].x)), gelu_tanh(bf_hi(v[i].x))), pack_bf16(gelu_tanh(bf_lo(v[i].y)), gelu_tanh(bf_hi(v[i].y))),
                 pack_bf16(gelu_tanh(bf_lo(v[i].z)), gelu_tanh(bf_hi(v[i].z))), pack_bf16(gelu_tanh(bf_lo(v[i].w)), gelu_tanh(bf_hi(v[i].w))));
        __nanosleep(Z1_NS);
      }
      TS(3, 5);
      bar_arrive<BAR_Z1>(256);
    }
    float acc[2][80];
    if (grp == 1) {
      zero(acc);
      if (wg == 2) {
        mainloop<160, 2, 0, false, BAR_ORD2>(acc, sbase, 1, 0, 10);
      } else {
        weight_sums(win, wdre, rb * 4 + ct, epoch);
        TS(2, 1);
        bar_sync<BAR_ORD2>(256);
        mainloop<160, 2, 0, false, BAR_ORD1>(acc, sbase, 1, 10, 10);
      }
      drain(acc, sbase, 1, wg == 2 ? 9 : 19);
      TS(wg + 1, wg == 1 ? 7 : 2);
      if (wg == 1) bar_sync<BAR_Z1>(256); else bar_sync<BAR_STATS>(192);
      const uint32_t tb = buf + ((l >> 4) * 8 + (l & 7)) * 128 + (((w * 2 + ((l >> 3) & 1)) ^ (l & 7)) << 4);
      float2 st[4];
      #pragma unroll
      for (int r = 0; r < 4; r++) st[r] = wg == 2 ? rs[(r >> 1) * 64 + (r & 1) * 8] : make_float2(-1.f, 0.f);
      #pragma unroll
      for (int jj = 0; jj < 10; jj++) {
        const float2 c0 = cs[jj * 8], c1 = cs[jj * 8 + 4];
        #pragma unroll
        for (int mi = 0; mi < 2; mi++) {
          const float* a = &acc[mi][8 * jj];
          const float2 s0 = st[mi * 2], s1 = st[mi * 2 + 1];
          stsm4_t(tb + mi * 20480 + jj * 2048,
                  pack_bf16(fmaf(a[0], s0.x, s0.y * c0.x), fmaf(a[1], s0.x, s0.y * c0.y)), pack_bf16(fmaf(a[2], s1.x, s1.y * c0.x), fmaf(a[3], s1.x, s1.y * c0.y)),
                  pack_bf16(fmaf(a[4], s0.x, s0.y * c1.x), fmaf(a[5], s0.x, s0.y * c1.y)), pack_bf16(fmaf(a[6], s1.x, s1.y * c1.x), fmaf(a[7], s1.x, s1.y * c1.y)));
        }
      }
      fence_async_smem();
      if (wg == 1) bar_sync<BAR_WG1>(128); else bar_sync<BAR_WG2>(128);
      TS(wg + 1, wg == 1 ? 8 : 6);
      if (l == 0) {
        #pragma unroll 1
        for (int i = 0; i < 2; i++) {
          const unsigned d = wg == 2 ? ST_A : ST_B;
          if (d) __nanosleep(i == 0 ? w * d : 3 * d);
          tma_store_2d(&maps.m[M_ABS], buf + i * 20480 + w * 5120, rb * 128 + i * 64, (2 - wg) * DM + ct * 160 + w * 40);
          bulk_commit();
        }
        bulk_wait_all();
      }
      __syncwarp();
      TS(wg + 1, wg == 1 ? 9 : 10);
      if (wg == 1) {
        bar_arrive<BAR_PUB1>(160);
        return;
      }
      bar_arrive<BAR_PUB2>(160);
      bar_arrive<BAR_Z1>(256);
    }
    zero(acc);
    bar_sync<BAR_ORD1>(256);
    mainloop<160, 2, 0, false, 0>(acc, sbase, grp, grp == 0 ? 52 : 20, grp == 0 ? NX : 64 - NX);
    if (grp == 0) {
      bar_sync<BAR_U>(256);
      mainloop<160, 2, 2, true, 0, true>(acc, sbase, 0, 52 + NX, 3);
    }
    mainloop<160, 2, 2, true, 0>(acc, sbase, grp, gh + 3 - 3 * grp, total - gh - 3 + 3 * grp);
    const uint32_t slab = buf + w * (16 * 320);
    const uint32_t addr = slab + (((l >> 3) & 1) * 8 + (l & 7)) * 320 + (l >> 4) * 16;
    bar_sync<BAR_BUF>(160);
    mbar_wait(dep0 + 32, 0);
    drain(acc, sbase, grp, total - 1);
    TS(3, 12);
    #pragma unroll
    for (int mi = 0; mi < 2; mi++) {
      #pragma unroll
      for (int jj = 0; jj < 10; jj++) {
        const float* a = &acc[mi][8 * jj];
        stsm4(addr + mi * 20480 + jj * 32, pack_bf16(a[0], a[1]), pack_bf16(a[2], a[3]), pack_bf16(a[4], a[5]), pack_bf16(a[6], a[7]));
      }
      fence_async_smem();
      __syncwarp();
      if (l == 0) {
        tma_reduce_2d(&maps.m[M_OUT], slab + mi * 20480, ct * 160, rb * 128 + mi * 64 + w * 16);
        bulk_commit();
      }
    }
    TS(3, 13);
    if (l == 0) {
      bulk_wait_read();
      if (w == 0) atomicAdd(&g_done, 1u);
    }
    TS(3, 15);
  }
}

typedef CUresult (*EncodeFn)(CUtensorMap*, CUtensorMapDataType, cuuint32_t, void*, const cuuint64_t*, const cuuint64_t*,
                             const cuuint32_t*, const cuuint32_t*, CUtensorMapInterleave, CUtensorMapSwizzle,
                             CUtensorMapL2promotion, CUtensorMapFloatOOBfill);

void make2d(EncodeFn enc, CUtensorMap* m, const void* p, uint64_t cols, uint64_t rows, uint32_t bc, uint32_t br, bool swz = true) {
  cuuint64_t gd[2] = {cols, rows}, gs[1] = {cols * 2};
  cuuint32_t bd[2] = {bc, br}, es[2] = {1, 1};
  enc(m, CU_TENSOR_MAP_DATA_TYPE_BFLOAT16, 2, const_cast<void*>(p), gd, gs, bd, es, CU_TENSOR_MAP_INTERLEAVE_NONE,
      swz ? CU_TENSOR_MAP_SWIZZLE_128B : CU_TENSOR_MAP_SWIZZLE_NONE, CU_TENSOR_MAP_L2_PROMOTION_L2_128B, CU_TENSOR_MAP_FLOAT_OOB_FILL_NONE);
}
void make3d(EncodeFn enc, CUtensorMap* m, const void* p, uint64_t cols, uint64_t rows, uint32_t cw, uint32_t nc, uint32_t br = 64) {
  cuuint64_t gd[3] = {cw, rows, cols / cw}, gs[2] = {cols * 2, cw * 2};
  cuuint32_t bd[3] = {cw, br, nc}, es[3] = {1, 1, 1};
  enc(m, CU_TENSOR_MAP_DATA_TYPE_BFLOAT16, 3, const_cast<void*>(p), gd, gs, bd, es, CU_TENSOR_MAP_INTERLEAVE_NONE,
      cw == 64 ? CU_TENSOR_MAP_SWIZZLE_128B : CU_TENSOR_MAP_SWIZZLE_64B, CU_TENSOR_MAP_L2_PROMOTION_L2_128B, CU_TENSOR_MAP_FLOAT_OOB_FILL_NONE);
}

}

extern "C" void kernel_launch(void* const* d_in, const int* in_sizes, int n_in, void* d_out, int out_size) {
  const bf16* x = (const bf16*)d_in[0];
  const bf16* wsre = (const bf16*)d_in[1];
  const bf16* wsim = (const bf16*)d_in[2];
  const bf16* wdre = (const bf16*)d_in[3];
  const bf16* wdim = (const bf16*)d_in[4];
  const bf16* win = (const bf16*)d_in[6];
  const bf16* wsp = (const bf16*)d_in[7];
  const bf16* bsp = (const bf16*)d_in[8];
  const bf16* wout = (const bf16*)d_in[9];

  void* fn = nullptr;
  cudaDriverEntryPointQueryResult qr;
  cudaGetDriverEntryPoint("cuTensorMapEncodeTiled", &fn, cudaEnableDefault, &qr);
  EncodeFn enc = (EncodeFn)fn;
  void *abT, *z2, *h, *xn;
  cudaGetSymbolAddress(&xn, g_xn);
  cudaGetSymbolAddress(&abT, g_abT);
  cudaGetSymbolAddress(&z2, g_z2);
  cudaGetSymbolAddress(&h, g_h);

  Maps maps;
  make2d(enc, &maps.m[M_X], x, DM, SEQ, 64, 64);
  make2d(enc, &maps.m[M_XN], xn, DM, SEQ, 64, 64);
  make2d(enc, &maps.m[M_WSRE], wsre, SEQ, SEQ, 64, 64);
  make2d(enc, &maps.m[M_WSIM], wsim, SEQ, SEQ, 64, 64);
  make2d(enc, &maps.m[M_WSP], wsp, SEQ, SEQ, 64, 64);
  make2d(enc, &maps.m[M_H], h, FH, SEQ, 64, 64);
  make3d(enc, &maps.m[M_WIN3], win, FF, DM, 64, 3);
  make3d(enc, &maps.m[M_Z23], z2, FH, SEQ, 64, 3);
  make2d(enc, &maps.m[M_WDRE], wdre, DM, DM, 64, 160);
  make2d(enc, &maps.m[M_WDIM], wdim, DM, DM, 64, 160);
  make2d(enc, &maps.m[M_AB], abT, SEQ, 2 * DM, 64, 160);
  make3d(enc, &maps.m[M_WOUT], wout, DM, FH, 32, 5);
  make2d(enc, &maps.m[M_HS], h, FH, SEQ, 64, 16);
  make2d(enc, &maps.m[M_ZS], z2, FH, SEQ, 64, 32);
  make2d(enc, &maps.m[M_ABS], abT, SEQ, 2 * DM, 64, 40);
  make2d(enc, &maps.m[M_OUT], d_out, DM, SEQ, 160, 16, false);

  cudaFuncSetAttribute(fused_kernel, cudaFuncAttributeMaxDynamicSharedMemorySize, SMEM_BYTES);
  fused_kernel<<<132, 384, SMEM_BYTES>>>(maps, x, win, wdre, bsp, wout, (bf16*)d_out);
}
```

```cpp
#include <cuda_runtime.h>
#include <cuda_bf16.h>
#include <cuda.h>
#include <stdint.h>

namespace {

typedef __nv_bfloat16 bf16;

constexpr int SEQ = 2048, DM = 640, FF = 1536, FH = 768;
#define NOV 3
#define NXV 5
constexpr int NX = NXV;
constexpr int NO = NOV;
constexpr int NST_A = 4, NST_B = 5, MAXST = 5;
constexpr int A_BYTES = 16384;
constexpr int BAR_OFF = 0;
constexpr int READY_OFF = 128;
constexpr int COLSUM_OFF = 256;
constexpr int ROWSTAT_OFF = 1024;
constexpr int ZSTAT_OFF = 2048;
constexpr int RED_OFF = 3072;
constexpr int RING_OFF = 4096;
constexpr int STAGE_A = 40960, STAGE_B = 36864;
constexpr int SMEM_BYTES = RING_OFF + 5 * STAGE_B + 40960;
constexpr int KB_A = 52 + NX + 12 - NO;
constexpr int KB_B = 84 - NX + NO;
constexpr float LN_EPS = 1e-5f;
constexpr unsigned POLL_LIMIT = 100000;
constexpr unsigned POLL_NS = 100, WATCH_NS = 40;
constexpr unsigned Z1_NS = 600;
constexpr int PF_D = 8;
constexpr int ZPRE = 6;

#define ST_A 0
#define ST_B 400
#define HELP_NS 4000
constexpr int BAR_ORD1 = 1, BAR_ORD2 = 2, BAR_WG1 = 3, BAR_WG2 = 4, BAR_LN = 5, BAR_BUF = 6, BAR_Z1 = 7, BAR_PUB1 = 8, BAR_PUB2 = 9,
              BAR_STATS = 10, BAR_U = 11;

enum { M_X, M_XN, M_WSRE, M_WSIM, M_WSP, M_H, M_WIN3, M_Z23, M_WDRE, M_WDIM, M_AB, M_WOUT, M_OUT, M_HS, M_ZS, M_ABS, M_COUNT };
struct Maps { CUtensorMap m[M_COUNT]; };

__device__ __align__(1024) bf16 g_abT[2 * DM * SEQ];
__device__ __align__(1024) bf16 g_z2[SEQ * FH];
__device__ __align__(1024) bf16 g_h[SEQ * FH];
__device__ __align__(1024) bf16 g_xn[SEQ * DM];
__device__ __align__(16) uint2 g_xstat[SEQ];
__device__ __align__(16) uint2 g_csum[5 * FH + DM];
__device__ __align__(16) uint2 g_zstat[64 * 128];
__device__ __align__(256) unsigned char g_flags[108 * 256];
constexpr int F_A = 0, F_B = 4, F_Z = 8, F_H = 12, F_XN = 28, F_Y = 44;
__device__ unsigned g_done;
#define TS(role, ev)
#define TC(i)

extern __shared__ __align__(1024) uint8_t smem[];

__device__ __forceinline__ uint32_t smem_u32(const void* p) { return (uint32_t)__cvta_generic_to_shared(p); }
__device__ __forceinline__ void mbar_init(uint32_t bar, uint32_t cnt) { asm volatile("mbarrier.init.shared::cta.b64 [%0], %1;" :: "r"(bar), "r"(cnt)); }
__device__ __forceinline__ void mbar_expect_tx(uint32_t bar, uint32_t bytes) { asm volatile("mbarrier.arrive.expect_tx.shared::cta.b64 _, [%0], %1;" :: "r"(bar), "r"(bytes) : "memory"); }
__device__ __forceinline__ void mbar_arrive(uint32_t bar) { asm volatile("mbarrier.arrive.shared::cta.b64 _, [%0];" :: "r"(bar) : "memory"); }
__device__ __forceinline__ void mbar_arrive_cluster(uint32_t bar, uint32_t cta) {
  asm volatile("{\n.reg .b32 ra;\nmapa.shared::cluster.u32 ra, %0, %1;\nmbarrier.arrive.shared::cluster.b64 _, [ra];\n}" :: "r"(bar), "r"(cta) : "memory");
}
__device__ __forceinline__ void mbar_wait(uint32_t bar, uint32_t parity) {
  asm volatile("{\n.reg .pred p;\n.reg .u32 n;\nmov.u32 n, 0;\n"
               "LW: mbarrier.try_wait.parity.shared::cta.b64 p, [%0], %1, 2000;\n@p bra LD;\n"
               "add.u32 n, n, 1;\nsetp.lt.u32 p, n, 20000;\n@p bra LW;\nLD:\n}" :: "r"(bar), "r"(parity) : "memory");
}
__device__ __forceinline__ void tma_load_2d(uint32_t dst, const CUtensorMap* map, uint32_t bar, int c0, int c1) {
  asm volatile("cp.async.bulk.tensor.2d.shared::cluster.global.mbarrier::complete_tx::bytes [%0], [%1, {%3, %4}], [%2];"
    :: "r"(dst), "l"((uint64_t)map), "r"(bar), "r"(c0), "r"(c1) : "memory");
}
__device__ __forceinline__ void tma_load_3d(uint32_t dst, const CUtensorMap* map, uint32_t bar, int c0, int c1, int c2) {
  asm volatile("cp.async.bulk.tensor.3d.shared::cluster.global.mbarrier::complete_tx::bytes [%0], [%1, {%3, %4, %5}], [%2];"
    :: "r"(dst), "l"((uint64_t)map), "r"(bar), "r"(c0), "r"(c1), "r"(c2) : "memory");
}
__device__ __forceinline__ void tma_load_2d_mc(uint32_t dst, const CUtensorMap* map, uint32_t bar, int c0, int c1, uint16_t mask) {
  asm volatile("cp.async.bulk.tensor.2d.shared::cluster.global.mbarrier::complete_tx::bytes.multicast::cluster [%0], [%1, {%3, %4}], [%2], %5;"
    :: "r"(dst), "l"((uint64_t)map), "r"(bar), "r"(c0), "r"(c1), "h"(mask) : "memory");
}
__device__ __forceinline__ void tma_store_2d(const CUtensorMap* map, uint32_t src, int c0, int c1) {
  asm volatile("cp.async.bulk.tensor.2d.global.shared::cta.bulk_group [%0, {%2, %3}], [%1];"
    :: "l"((uint64_t)map), "r"(src), "r"(c0), "r"(c1) : "memory");
}
__device__ __forceinline__ void tma_reduce_2d(const CUtensorMap* map, uint32_t src, int c0, int c1) {
  asm volatile("cp.reduce.async.bulk.tensor.2d.global.shared::cta.add.tile.bulk_group [%0, {%2, %3}], [%1];"
    :: "l"((uint64_t)map), "r"(src), "r"(c0), "r"(c1) : "memory");
}
__device__ __forceinline__ void bulk_wait_all() { asm volatile("cp.async.bulk.wait_group 0;" ::: "memory"); }
__device__ __forceinline__ void bulk_commit() { asm volatile("cp.async.bulk.commit_group;" ::: "memory"); }
__device__ __forceinline__ void bulk_wait_read() { asm volatile("cp.async.bulk.wait_group.read 0;" ::: "memory"); }
__device__ __forceinline__ void fence_async_smem() { asm volatile("fence.proxy.async.shared::cta;" ::: "memory"); }
__device__ __forceinline__ void fence_async_global() { asm volatile("fence.proxy.async.global;" ::: "memory"); }
__device__ __forceinline__ void wgmma_fence() { asm volatile("wgmma.fence.sync.aligned;" ::: "memory"); }
__device__ __forceinline__ void wgmma_commit() { asm volatile("wgmma.commit_group.sync.aligned;" ::: "memory"); }
template<int N> __device__ __forceinline__ void wgmma_wait() { asm volatile("wgmma.wait_group.sync.aligned %0;" :: "n"(N) : "memory"); }
template<int ID> __device__ __forceinline__ void bar_sync(int n) { asm volatile("bar.sync %0, %1;" :: "n"(ID), "r"(n) : "memory"); }
template<int ID> __device__ __forceinline__ void bar_arrive(int n) { asm volatile("bar.arrive %0, %1;" :: "n"(ID), "r"(n) : "memory"); }
__device__ __forceinline__ void cluster_wait() { asm volatile("barrier.cluster.wait.aligned;" ::: "memory"); }
__device__ __forceinline__ uint64_t desc64(uint32_t lo, uint32_t hi) { return (uint64_t)lo | ((uint64_t)hi << 32); }
__device__ __forceinline__ uint2 ld_tag2(const uint2* p) {
  uint2 v; asm volatile("ld.relaxed.gpu.global.v2.u32 {%0,%1}, [%2];" : "=r"(v.x), "=r"(v.y) : "l"(p) : "memory"); return v;
}
__device__ __forceinline__ void st_tag2(uint2* p, uint32_t a, uint32_t b) {
  asm volatile("st.relaxed.gpu.global.v2.u32 [%0], {%1,%2};" :: "l"(p), "r"(a), "r"(b) : "memory");
}
__device__ __forceinline__ void stg128(void* p, uint4 v) {
  asm volatile("st.global.v4.u32 [%0], {%1,%2,%3,%4};" :: "l"(p), "r"(v.x), "r"(v.y), "r"(v.z), "r"(v.w));
}
__device__ __forceinline__ unsigned ld_relaxed(const unsigned* p) {
  unsigned v; asm volatile("ld.relaxed.gpu.global.u32 %0, [%1];" : "=r"(v) : "l"(p) : "memory"); return v;
}
__device__ __forceinline__ uint32_t pack_bf16(float lo, float hi) {
  uint32_t r; asm("cvt.rn.bf16x2.f32 %0, %1, %2;" : "=r"(r) : "f"(hi), "f"(lo)); return r;
}
__device__ __forceinline__ float bf_lo(uint32_t v) { return __uint_as_float(v << 16); }
__device__ __forceinline__ float bf_hi(uint32_t v) { return __uint_as_float(v & 0xFFFF0000u); }
__device__ __forceinline__ void stsm4(uint32_t addr, uint32_t a, uint32_t b, uint32_t c, uint32_t d) {
  asm volatile("stmatrix.sync.aligned.m8n8.x4.shared.b16 [%0], {%1,%2,%3,%4};" :: "r"(addr), "r"(a), "r"(b), "r"(c), "r"(d));
}
__device__ __forceinline__ void stsm4_t(uint32_t addr, uint32_t a, uint32_t b, uint32_t c, uint32_t d) {
  asm volatile("stmatrix.sync.aligned.m8n8.x4.trans.shared.b16 [%0], {%1,%2,%3,%4};" :: "r"(addr), "r"(a), "r"(b), "r"(c), "r"(d));
}
__device__ __forceinline__ void ldsm4(uint32_t addr, uint32_t& a, uint32_t& b, uint32_t& c, uint32_t& d) {
  asm volatile("ldmatrix.sync.aligned.m8n8.x4.shared.b16 {%0,%1,%2,%3}, [%4];" : "=r"(a), "=r"(b), "=r"(c), "=r"(d) : "r"(addr));
}
__device__ __forceinline__ uint4 lds128(uint32_t a) {
  uint4 v; asm volatile("ld.shared.v4.u32 {%0,%1,%2,%3}, [%4];" : "=r"(v.x), "=r"(v.y), "=r"(v.z), "=r"(v.w) : "r"(a)); return v;
}
__device__ __forceinline__ void sts128(uint32_t a, uint32_t x, uint32_t y, uint32_t z, uint32_t w) {
  asm volatile("st.shared.v4.u32 [%0], {%1,%2,%3,%4};" :: "r"(a), "r"(x), "r"(y), "r"(z), "r"(w));
}
__device__ __forceinline__ uint32_t hmul2_bf16(uint32_t a, uint32_t b) {
  uint32_t r; asm("mul.rn.bf16x2 %0, %1, %2;" : "=r"(r) : "r"(a), "r"(b)); return r;
}
__device__ __forceinline__ uint32_t hadd2_bf16(uint32_t a, uint32_t b) {
  uint32_t r; asm("add.rn.bf16x2 %0, %1, %2;" : "=r"(r) : "r"(a), "r"(b)); return r;
}
__device__ __forceinline__ uint32_t hfma2_bf16(uint32_t a, uint32_t b, uint32_t c) {
  uint32_t r; asm("fma.rn.bf16x2 %0, %1, %2, %3;" : "=r"(r) : "r"(a), "r"(b), "r"(c)); return r;
}
__device__ __forceinline__ float gelu_tanh(float v) {
  float u = v * fmaf(0.0356774081f, v * v, 0.7978845608f);
  float t; asm("tanh.approx.f32 %0, %1;" : "=f"(t) : "f"(u));
  float hv = 0.5f * v;
  return fmaf(hv, t, hv);
}

template<int TB>
__device__ __forceinline__ void wgmma_n192(float (&d)[96], uint64_t da, uint64_t db, int scale_d) {
  asm volatile("{\n.reg .pred p;\nsetp.ne.b32 p, %98, 0;\n"
   "wgmma.mma_async.sync.aligned.m64n192k16.f32.bf16.bf16 {%0,%1,%2,%3,%4,%5,%6,%7,%8,%9,%10,%11,%12,%13,%14,%15,%16,%17,%18,%19,%20,%21,%22,%23,%24,%25,%26,%27,%28,%29,%30,%31,%32,%33,%34,%35,%36,%37,%38,%39,%40,%41,%42,%43,%44,%45,%46,%47,%48,%49,%50,%51,%52,%53,%54,%55,%56,%57,%58,%59,%60,%61,%62,%63,%64,%65,%66,%67,%68,%69,%70,%71,%72,%73,%74,%75,%76,%77,%78,%79,%80,%81,%82,%83,%84,%85,%86,%87,%88,%89,%90,%91,%92,%93,%94,%95}, %96, %97, p, 1, 1, 0, %99;\n}"
   : "+f"(d[0]),"+f"(d[1]),"+f"(d[2]),"+f"(d[3]),"+f"(d[4]),"+f"(d[5]),"+f"(d[6]),"+f"(d[7]),"+f"(d[8]),"+f"(d[9]),"+f"(d[10]),"+f"(d[11]),"+f"(d[12]),"+f"(d[13]),"+f"(d[14]),"+f"(d[15]),"+f"(d[16]),"+f"(d[17]),"+f"(d[18]),"+f"(d[19]),"+f"(d[20]),"+f"(d[21]),"+f"(d[22]),"+f"(d[23]),"+f"(d[24]),"+f"(d[25]),"+f"(d[26]),"+f"(d[27]),"+f"(d[28]),"+f"(d[29]),"+f"(d[30]),"+f"(d[31]),"+f"(d[32]),"+f"(d[33]),"+f"(d[34]),"+f"(d[35]),"+f"(d[36]),"+f"(d[37]),"+f"(d[38]),"+f"(d[39]),"+f"(d[40]),"+f"(d[41]),"+f"(d[42]),"+f"(d[43]),"+f"(d[44]),"+f"(d[45]),"+f"(d[46]),"+f"(d[47]),"+f"(d[48]),"+f"(d[49]),"+f"(d[50]),"+f"(d[51]),"+f"(d[52]),"+f"(d[53]),"+f"(d[54]),"+f"(d[55]),"+f"(d[56]),"+f"(d[57]),"+f"(d[58]),"+f"(d[59]),"+f"(d[60]),"+f"(d[61]),"+f"(d[62]),"+f"(d[63]),"+f"(d[64]),"+f"(d[65]),"+f"(d[66]),"+f"(d[67]),"+f"(d[68]),"+f"(d[69]),"+f"(d[70]),"+f"(d[71]),"+f"(d[72]),"+f"(d[73]),"+f"(d[74]),"+f"(d[75]),"+f"(d[76]),"+f"(d[77]),"+f"(d[78]),"+f"(d[79]),"+f"(d[80]),"+f"(d[81]),"+f"(d[82]),"+f"(d[83]),"+f"(d[84]),"+f"(d[85]),"+f"(d[86]),"+f"(d[87]),"+f"(d[88]),"+f"(d[89]),"+f"(d[90]),"+f"(d[91]),"+f"(d[92]),"+f"(d[93]),"+f"(d[94]),"+f"(d[95])
   : "l"(da), "l"(db), "r"(scale_d), "n"(TB));
}
template<int TB>
__device__ __forceinline__ void wgmma_n160(float (&d)[80], uint64_t da, uint64_t db, int scale_d) {
  asm volatile("{\n.reg .pred p;\nsetp.ne.b32 p, %82, 0;\n"
   "wgmma.mma_async.sync.aligned.m64n160k16.f32.bf16.bf16 {%0,%1,%2,%3,%4,%5,%6,%7,%8,%9,%10,%11,%12,%13,%14,%15,%16,%17,%18,%19,%20,%21,%22,%23,%24,%25,%26,%27,%28,%29,%30,%31,%32,%33,%34,%35,%36,%37,%38,%39,%40,%41,%42,%43,%44,%45,%46,%47,%48,%49,%50,%51,%52,%53,%54,%55,%56,%57,%58,%59,%60,%61,%62,%63,%64,%65,%66,%67,%68,%69,%70,%71,%72,%73,%74,%75,%76,%77,%78,%79}, %80, %81, p, 1, 1, 0, %83;\n}"
   : "+f"(d[0]),"+f"(d[1]),"+f"(d[2]),"+f"(d[3]),"+f"(d[4]),"+f"(d[5]),"+f"(d[6]),"+f"(d[7]),"+f"(d[8]),"+f"(d[9]),"+f"(d[10]),"+f"(d[11]),"+f"(d[12]),"+f"(d[13]),"+f"(d[14]),"+f"(d[15]),"+f"(d[16]),"+f"(d[17]),"+f"(d[18]),"+f"(d[19]),"+f"(d[20]),"+f"(d[21]),"+f"(d[22]),"+f"(d[23]),"+f"(d[24]),"+f"(d[25]),"+f"(d[26]),"+f"(d[27]),"+f"(d[28]),"+f"(d[29]),"+f"(d[30]),"+f"(d[31]),"+f"(d[32]),"+f"(d[33]),"+f"(d[34]),"+f"(d[35]),"+f"(d[36]),"+f"(d[37]),"+f"(d[38]),"+f"(d[39]),"+f"(d[40]),"+f"(d[41]),"+f"(d[42]),"+f"(d[43]),"+f"(d[44]),"+f"(d[45]),"+f"(d[46]),"+f"(d[47]),"+f"(d[48]),"+f"(d[49]),"+f"(d[50]),"+f"(d[51]),"+f"(d[52]),"+f"(d[53]),"+f"(d[54]),"+f"(d[55]),"+f"(d[56]),"+f"(d[57]),"+f"(d[58]),"+f"(d[59]),"+f"(d[60]),"+f"(d[61]),"+f"(d[62]),"+f"(d[63]),"+f"(d[64]),"+f"(d[65]),"+f"(d[66]),"+f"(d[67]),"+f"(d[68]),"+f"(d[69]),"+f"(d[70]),"+f"(d[71]),"+f"(d[72]),"+f"(d[73]),"+f"(d[74]),"+f"(d[75]),"+f"(d[76]),"+f"(d[77]),"+f"(d[78]),"+f"(d[79])
   : "l"(da), "l"(db), "r"(scale_d), "n"(TB));
}

template<int N, int TB>
__device__ __forceinline__ void wgmma_n(float (&d)[N / 2], uint64_t da, uint64_t db) {
  if constexpr (N == 192) wgmma_n192<TB>(d, da, db, 1); else wgmma_n160<TB>(d, da, db, 1);
}

template<int M, int R>
__device__ __forceinline__ void pin(float (&acc)[M][R]) {
  #pragma unroll
  for (int mi = 0; mi < M; mi++)
    #pragma unroll
    for (int i = 0; i < R; i++) asm volatile("" : "+f"(acc[mi][i]) :: "memory");
}
template<int M, int R>
__device__ __forceinline__ void zero(float (&acc)[M][R]) {
  #pragma unroll
  for (int mi = 0; mi < M; mi++)
    #pragma unroll
    for (int i = 0; i < R; i++) acc[mi][i] = 0.f;
  pin(acc);
}

template<int N, int M, int TB, bool CONT, int ORD_BAR, bool AOWN = false>
__device__ __forceinline__ void mainloop(float (&acc)[M][N / 2], uint32_t sbase, int grp, int g0, int nk, int m0 = 0) {
  const uint32_t full0 = sbase + BAR_OFF, empty0 = full0 + 8 * MAXST, ring = sbase + RING_OFF;
  const int nst = grp == 0 ? NST_A : NST_B, total = grp == 0 ? KB_A : KB_B;
  const uint32_t sstep = (grp == 0 ? STAGE_A : STAGE_B) >> 4;
  const int t = threadIdx.x & 127;
  const uint32_t da0 = (((ring + m0 * 8192) & 0x3FFFF) >> 4) | 0x10000u;
  const uint32_t db0 = (((ring + A_BYTES) & 0x3FFFF) >> 4) | ((TB == 2 ? 256u : TB ? 512u : 1u) << 16);
  constexpr uint32_t HI_A = 0x40000040u, HI_B = TB == 2 ? 0x80000020u : 0x40000040u;
  int s = g0 % nst, ph = (g0 / nst) & 1, ps = s == 0 ? nst - 1 : s - 1;
  #pragma unroll 1
  for (int g = g0; g < g0 + nk; g++) {
    const uint32_t so = s * sstep;
    mbar_wait(full0 + 8 * s, ph);
    wgmma_fence();
    #pragma unroll
    for (int k = 0; k < 4; k++) {
      const uint64_t db = desc64(db0 + so + (TB == 2 ? k * 64 : TB ? k * 128 : k * 2), HI_B);
      #pragma unroll
      for (int mi = 0; mi < M; mi++)
        wgmma_n<N, TB != 0>(acc[mi], desc64(AOWN ? da0 + ((NST_A * STAGE_A) >> 4) + (g - g0) * 512 + mi * 1536 + k * 2 : da0 + so + mi * 512 + k * 2, HI_A), db);
    }
    wgmma_commit();
    if (ORD_BAR != 0 && g == g0 + nk - 1) bar_arrive<ORD_BAR>(256);
    wgmma_wait<1>();
    if (t < 2 * M && (CONT || g > g0) && g - 1 + nst < total) mbar_arrive_cluster(empty0 + 8 * ps, t & 1);
    ps = s;
    if (++s == nst) { s = 0; ph ^= 1; }
  }
}
template<int M, int R>
__device__ __forceinline__ void drain(float (&acc)[M][R], uint32_t sbase, int grp, int glast) {
  wgmma_wait<0>();
  pin(acc);
  const int t = threadIdx.x & 127;
  const int nst = grp == 0 ? NST_A : NST_B, total = grp == 0 ? KB_A : KB_B;
  if (t < 2 * M && glast + nst < total) mbar_arrive_cluster(sbase + BAR_OFF + 8 * MAXST + 8 * (glast % nst), t & 1);
}

__device__ __forceinline__ void set_flag(int slot, int byte, unsigned epoch) {
  asm volatile("st.relaxed.gpu.global.u8 [%0], %1;" :: "l"(g_flags + slot * 256 + byte), "r"(epoch & 255u) : "memory");
}
__device__ __forceinline__ unsigned get_flag(int slot, int byte) {
  unsigned v; asm volatile("ld.relaxed.gpu.global.u8 %0, [%1];" : "=r"(v) : "l"(g_flags + slot * 256 + byte) : "memory"); return v;
}
__device__ __forceinline__ void publish(int slot, int byte, unsigned epoch) {
  asm volatile("fence.acq_rel.gpu;" ::: "memory");
  set_flag(slot, byte, epoch);
}
__device__ __forceinline__ float sum8(uint4 v) {
  return ((bf_lo(v.x) + bf_hi(v.x)) + (bf_lo(v.y) + bf_hi(v.y))) + ((bf_lo(v.z) + bf_hi(v.z)) + (bf_lo(v.w) + bf_hi(v.w)));
}
__device__ __forceinline__ uint4 ldg128(const void* p) {
  uint4 v; asm volatile("ld.global.nc.v4.u32 {%0,%1,%2,%3}, [%4];" : "=r"(v.x), "=r"(v.y), "=r"(v.z), "=r"(v.w) : "l"(p)); return v;
}

__device__ __forceinline__ void ln_rows(const uint4 (&rv)[5], uint32_t buf, int cta, unsigned epoch) {
  const int t = threadIdx.x - 128, row = cta * 16 + (t >> 4), c = t & 15;
  const float sh = __shfl_sync(0xffffffffu, bf_lo(rv[0].x), t & 16);
  float d[40], s = 0.f, q = 0.f;
  #pragma unroll
  for (int j = 0; j < 5; j++) {
    const uint32_t u[4] = {rv[j].x, rv[j].y, rv[j].z, rv[j].w};
    #pragma unroll
    for (int e = 0; e < 4; e++) {
      const float d0 = bf_lo(u[e]) - sh, d1 = bf_hi(u[e]) - sh;
      d[j * 8 + e * 2] = d0; d[j * 8 + e * 2 + 1] = d1;
      s += d0 + d1; q = fmaf(d0, d0, q); q = fmaf(d1, d1, q);
    }
  }
  #pragma unroll
  for (int o = 1; o < 16; o <<= 1) { s += __shfl_xor_sync(0xffffffffu, s, o); q += __shfl_xor_sync(0xffffffffu, q, o); }
  const float md = s * (1.f / DM);
  const float r = rsqrtf(fmaxf(fmaf(q, 1.f / DM, -md * md), 0.f) + LN_EPS), o = -md * r;
  if (c == 0) st_tag2(&g_xstat[row], __float_as_uint(r), (__float_as_uint(-(md + sh) * r) & ~255u) | (epoch & 255u));
  #pragma unroll
  for (int j = 0; j < 5; j++) {
    const float* a = &d[j * 8];
    sts128(buf + (t >> 4) * 1280 + (c + 16 * j) * 16,
           pack_bf16(fmaf(a[0], r, o), fmaf(a[1], r, o)), pack_bf16(fmaf(a[2], r, o), fmaf(a[3], r, o)),
           pack_bf16(fmaf(a[4], r, o), fmaf(a[5], r, o)), pack_bf16(fmaf(a[6], r, o), fmaf(a[7], r, o)));
  }
  fence_async_smem();
  bar_arrive<BAR_LN>(288);
}

__device__ __forceinline__ void weight_sums(const bf16* __restrict__ win, const bf16* __restrict__ wdre, int j, unsigned epoch) {
  const int t = threadIdx.x & 127, w = t >> 5, l = t & 31;
  const int cj = min(j, 59), cg = cj % 12, rg = cj / 12, wr = j * 10 + min(t >> 3, 9);
  uint4 cv[8], rv[10];
  #pragma unroll
  for (int i = 0; i < 8; i++) cv[i] = ldg128(reinterpret_cast<const uint4*>(win + (size_t)(rg * 128 + w * 32 + i * 4 + (l >> 3)) * FF + FH + cg * 64) + (l & 7));
  #pragma unroll
  for (int i = 0; i < 10; i++) rv[i] = ldg128(reinterpret_cast<const uint4*>(wdre + (size_t)wr * DM) + (l & 7) + 8 * i);
  float v[8];
  #pragma unroll
  for (int e = 0; e < 8; e++) v[e] = 0.f;
  #pragma unroll
  for (int i = 0; i < 8; i++) {
    v[0] += bf_lo(cv[i].x); v[1] += bf_hi(cv[i].x); v[2] += bf_lo(cv[i].y); v[3] += bf_hi(cv[i].y);
    v[4] += bf_lo(cv[i].z); v[5] += bf_hi(cv[i].z); v[6] += bf_lo(cv[i].w); v[7] += bf_hi(cv[i].w);
  }
  #pragma unroll
  for (int st = 0; st < 2; st++) {
    const int n = 4 >> st;
    const bool up = (l & (4 * n)) != 0;
    #pragma unroll
    for (int e = 0; e < 4; e++)
      if (e < n) { const float keep = up ? v[e + n] : v[e], send = up ? v[e] : v[e + n]; v[e] = keep + __shfl_xor_sync(0xffffffffu, send, 4 * n); }
  }
  float* red = reinterpret_cast<float*>(smem + RED_OFF);
  *reinterpret_cast<float2*>(red + w * 64 + (l & 7) * 8 + (l >> 3) * 2) = make_float2(v[0], v[1]);
  float s = 0.f;
  #pragma unroll
  for (int i = 0; i < 10; i++) s += sum8(rv[i]);
  #pragma unroll
  for (int o = 1; o < 8; o <<= 1) s += __shfl_xor_sync(0xffffffffu, s, o);
  if ((l & 7) == 0) st_tag2(&g_csum[5 * FH + wr], __float_as_uint(s), epoch);
  bar_sync<BAR_WG1>(128);
  if (t < 64) st_tag2(&g_csum[rg * FH + cg * 64 + t], __float_as_uint((red[t] + red[64 + t]) + (red[128 + t] + red[192 + t])), epoch);
}

__device__ __forceinline__ void gather96(const uint2* src, float* dst, unsigned epoch) {
  unsigned it = 0;
  while (true) {
    bool ok = true;
    uint2 u[15];
    #pragma unroll
    for (int j = 0; j < 15; j++) u[j] = ld_tag2(src + (j % 5) * FH + (j / 5) * 32);
    #pragma unroll
    for (int j = 0; j < 15; j++) ok = ok && u[j].y == epoch;
    #pragma unroll
    for (int j = 0; j < 3; j++)
      dst[j * 32] = ((__uint_as_float(u[j * 5].x) + __uint_as_float(u[j * 5 + 1].x)) + (__uint_as_float(u[j * 5 + 2].x) + __uint_as_float(u[j * 5 + 3].x))) + __uint_as_float(u[j * 5 + 4].x);
    if (ok || ++it > POLL_LIMIT) break;
    __nanosleep(2 * POLL_NS);
  }
}

__device__ __forceinline__ void a_entry(int g, int grp, int ct, int& mi, int& kb) {
  if (g < 10) { mi = M_X; kb = g; }
  else if (g < 20) { mi = M_XN; kb = g - 10; }
  else if (g < 52) { mi = grp == 0 ? M_WSP : M_WSRE; kb = g - 20; }
  else if (grp == 0) {
    if (g < 52 + NX) { mi = M_WSIM; kb = g - 52 + 32 - NX; }
    else {
      const int i = g - 52 - NX;
      mi = M_H; kb = i < 3 ? ct * 3 + i : i < 6 ? (ct ^ 1) * 3 + i - 3 : ((ct >> 1) ^ 1) * 6 + i - 6;
    }
  } else {
    if (g < 84 - NX) { mi = M_WSIM; kb = g - 52; }
    else { mi = M_H; kb = ((ct >> 1) ^ 1) * 6 + g - (84 - NX) + 6 - NO; }
  }
}

__global__ void __cluster_dims__(2, 1, 1) __launch_bounds__(384, 1)
fused_kernel(const __grid_constant__ Maps maps, const bf16* __restrict__ x, const bf16* __restrict__ win, const bf16* __restrict__ wdre,
             const bf16* __restrict__ bsp, const bf16* __restrict__ wout, bf16* __restrict__ out) {
  const uint32_t sbase = smem_u32(smem);
  const uint32_t full0 = sbase + BAR_OFF, empty0 = full0 + 8 * MAXST, dep0 = empty0 + 8 * MAXST, ring = sbase + RING_OFF;
  const int tid = threadIdx.x, wg = __shfl_sync(0xffffffffu, tid >> 7, 0);
  if (blockIdx.x < 4) {
    if (tid == 0) {
      const unsigned epoch = (ld_relaxed(&g_done) >> 7) + 1u;
      for (int s = 0; s < 4; s++) mbar_init(sbase + 8 * s, 1);
      asm volatile("fence.mbarrier_init.release.cluster;" ::: "memory");
      __nanosleep(HELP_NS);
      const char* src = reinterpret_cast<const char*>(x) + (size_t)blockIdx.x * 655360;
      char* dst = reinterpret_cast<char*>(out) + (size_t)blockIdx.x * 655360;
      #pragma unroll 1
      for (int i = 0; i < 16 + 3; i++) {
        if (i < 16) {
          if (i >= 4) asm volatile("cp.async.bulk.wait_group.read 0;" ::: "memory");
          mbar_expect_tx(sbase + 8 * (i & 3), 40960);
          asm volatile("cp.async.bulk.shared::cluster.global.mbarrier::complete_tx::bytes [%0], [%1], 40960, [%2];"
                       :: "r"(sbase + 1024 + (i & 3) * 40960), "l"(src + (size_t)i * 40960), "r"(sbase + 8 * (i & 3)) : "memory");
        }
        if (i >= 3) {
          const int j = i - 3;
          mbar_wait(sbase + 8 * (j & 3), (j >> 2) & 1);
          asm volatile("cp.async.bulk.global.shared::cta.bulk_group [%0], [%1], 40960;" :: "l"(dst + (size_t)j * 40960), "r"(sbase + 1024 + (j & 3) * 40960) : "memory");
          bulk_commit();
        }
      }
      bulk_wait_all();
      for (int r = 0; r < 4; r++) set_flag(F_Y + blockIdx.x * 4 + r, 0, epoch);
    }
    return;
  }
  const int cta = blockIdx.x - 4, rank = cta & 1, grp = (cta >> 1) & 1, rb = cta >> 3, ct = ((cta >> 2) & 1) * 2 + rank;
  const int total = grp == 0 ? KB_A : KB_B, gh = grp == 0 ? 52 + NX : 84 - NX;
  const uint32_t stage_bytes = grp == 0 ? STAGE_A : STAGE_B;
  const int nst = grp == 0 ? NST_A : NST_B;
  const uint32_t buf = ring + nst * stage_bytes;

  uint4 rv[5];
  if (wg != 0) {
    #pragma unroll
    for (int j = 0; j < 5; j++) rv[j] = ldg128(reinterpret_cast<const uint4*>(x + (size_t)(cta * 16 + ((tid - 128) >> 4)) * DM) + (tid & 15) + 16 * j);
  }
  const unsigned epoch = (ld_relaxed(&g_done) >> 7) + 1u;
  if (tid == 0) {
    TS(0, 0);
    for (int s = 0; s < MAXST; s++) { mbar_init(full0 + 8 * s, 2); mbar_init(empty0 + 8 * s, 4); mbar_init(dep0 + 8 * s, 1); }
    *reinterpret_cast<volatile int*>(smem + READY_OFF) = 0;
    asm volatile("fence.mbarrier_init.release.cluster;" ::: "memory");
  }
  __syncthreads();
  asm volatile("barrier.cluster.arrive.relaxed.aligned;" ::: "memory");

  if (wg == 0) {
    asm volatile("setmaxnreg.dec.sync.aligned.u32 40;");
    const int warp = tid >> 5, lane = tid & 31;
    if (warp == 0) {
      const int row = rb * 128;
      if (lane == 0) {
        for (int g = 0; g < nst; g++) {
          mbar_expect_tx(full0 + 8 * g, A_BYTES);
          tma_load_2d(ring + g * stage_bytes, &maps.m[M_X], full0 + 8 * g, g * 64, row);
          tma_load_2d(ring + g * stage_bytes + 8192, &maps.m[M_X], full0 + 8 * g, g * 64, row + 64);
        }
      }
      __syncwarp();
      cluster_wait();
      if (lane == 0) {
        int s = 0, ph = 0;
        #pragma unroll 1
        for (int g = nst; g < total; g++) {
          int mi, kb;
          a_entry(g, grp, ct, mi, kb);
          if (g == 10 || g == gh + 6 - 6 * grp || (grp == 0 && g == gh + 3)) {
            TS(0, g > 10 ? 3 : 1);
            mbar_wait(dep0 + (g == 10 ? 0 : g == gh + 6 - 6 * grp ? 24 : 8), 0);
            fence_async_global();
            TS(0, g > 10 ? 4 : 2);
          }
          mbar_wait(empty0 + 8 * s, ph);
          if (grp == 0 && g >= gh && g < gh + 6) {
            if (g < gh + 3) {
              mbar_arrive(full0 + 8 * s);
            } else {
              mbar_expect_tx(full0 + 8 * s, A_BYTES);
              tma_load_2d(ring + s * stage_bytes, &maps.m[mi], full0 + 8 * s, kb * 64, row);
              tma_load_2d(ring + s * stage_bytes + 8192, &maps.m[mi], full0 + 8 * s, kb * 64, row + 64);
            }
          } else {
            mbar_expect_tx(full0 + 8 * s, A_BYTES);
            tma_load_2d_mc(ring + s * stage_bytes + rank * 8192, &maps.m[mi], full0 + 8 * s, kb * 64, row + rank * 64, 3);
          }
          if (++s == nst) { s = 0; ph ^= 1; }
          if (g + PF_D < gh) {
            a_entry(g + PF_D, grp, ct, mi, kb);
            if (mi >= M_WSRE && (kb & 1) == (ct >> 1))
              asm volatile("cp.async.bulk.prefetch.tensor.2d.L2.global.tile [%0, {%1, %2}];" :: "l"((uint64_t)&maps.m[mi]), "r"(kb * 64), "r"(row + rank * 64) : "memory");
          }
        }
        TS(0, 5);
      }
    } else if (warp == 1) {
      if (lane == 0) {
        int s = 0, ph = 1;
        int have = 0;
        #pragma unroll 1
        for (int g = 0; g < total; g++) {
          int mi, kb, c;
          a_entry(g, grp, ct, mi, kb);
          const bool nmaj = g >= gh || (grp == 0 && g < 52);
          uint32_t bytes = 20480;
          if (g >= gh) { mi = M_WOUT; c = ct * 5; }
          else if (g >= 52) { mi = M_AB; c = DM + ct * 160; }
          else if (grp == 0) { mi = g < 20 ? M_WIN3 : M_Z23; c = 3 * ct + (g < 10 ? 12 : 0); bytes = 24576; }
          else { mi = g < 10 ? M_WDRE : g < 20 ? M_WDIM : M_AB; c = ct * 160; }
          if (g >= 20 && g < 52 && ((g - 20) >> 1) >= have) {
            if (g == 20) TS(1, 0);
            unsigned it = 0;
            while ((have = *reinterpret_cast<volatile int*>(smem + READY_OFF)) <= ((g - 20) >> 1) && ++it < 50 * POLL_LIMIT) {}
            fence_async_global();
            if (g == 20) { TS(1, 1); TC(1); }
          }
          if (g == 52) { TS(1, 2); mbar_wait(dep0 + 16, 0); fence_async_global(); TS(1, 3); TC(2); }
          const uint32_t dst = ring + s * stage_bytes + A_BYTES, fb = full0 + 8 * s;
          mbar_wait(empty0 + 8 * s, ph);
          if (++s == nst) { s = 0; ph ^= 1; }
          mbar_expect_tx(fb, bytes);
          if (nmaj) tma_load_3d(dst, &maps.m[mi], fb, 0, kb * 64, c);
          else tma_load_2d(dst, &maps.m[mi], fb, kb * 64, c);
        }
      }
      __syncwarp();
      cluster_wait();
    } else if (warp == 2) {
      if (lane < M_COUNT) asm volatile("prefetch.tensormap [%0];" :: "l"((uint64_t)&maps.m[lane]) : "memory");
      cluster_wait();
      {
        unsigned it = 0;
        uint2 v[4];
        while (true) {
          bool ok = true;
          #pragma unroll
          for (int i = 0; i < 4; i++) { v[i] = ld_tag2(&g_xstat[rb * 128 + i * 32 + lane]); ok = ok && ((v[i].y ^ epoch) & 255u) == 0; }
          if (ok || ++it > POLL_LIMIT) break;
          __nanosleep(POLL_NS);
        }
        #pragma unroll
        for (int i = 0; i < 4; i++) reinterpret_cast<uint2*>(smem + ROWSTAT_OFF)[i * 32 + lane] = make_uint2(v[i].x, v[i].y & ~255u);
        __syncwarp();
        TS(0, 6);
      }
      const int hsrc = ((ct >> 1) ^ 1) * 2 + (grp == 0 ? (NO >= 3 ? 0 : lane & 1) : (NO <= 3 ? 1 : lane & 1));
      #pragma unroll 1
      for (int i = 0; i < 5; i++) {
        const int d = i == 3 ? 4 : i == 4 ? 3 : i;
        const int slot = d == 0 ? F_XN + rb : d == 4 ? F_Y + rb : d == 3 ? F_H + rb : d == 2 ? F_B + ct : grp == 0 ? F_Z + ct : F_A + ct;
        const int byte = d == 0 ? lane & 7 : d == 4 ? 0 : d == 3 ? hsrc : lane & 15;
        unsigned it = 0, m;
        while ((m = __ballot_sync(0xffffffffu, get_flag(slot, byte) != (epoch & 255u))) != 0 && ++it < POLL_LIMIT) {
          if (d == 1 && lane == 0) *reinterpret_cast<volatile int*>(smem + READY_OFF) = __ffs(m) - 1;
          __nanosleep(WATCH_NS);
        }
        if (d == 1 && lane == 0) *reinterpret_cast<volatile int*>(smem + READY_OFF) = 16;
        if (d < 4) TS(0, 8 + d * 2); else TS(0, 7);
        fence_async_global();
        __syncwarp();
        if (lane == 0 && d != 1) mbar_arrive(dep0 + 8 * d);
        if (d == 0) {
          if (grp == 0) {
            gather96(&g_csum[ct * 192 + 96 + lane], reinterpret_cast<float*>(smem + COLSUM_OFF) + 96 + lane, epoch);
            __syncwarp();
            bar_arrive<BAR_STATS>(320);
          } else {
            bar_arrive<BAR_STATS>(192);
          }
        }
        if (d == 2 && lane < 30) {
          asm volatile("prefetch.global.L2 [%0];" :: "l"(wout + (size_t)cta * 6 * DM + lane * 128));
          asm volatile("prefetch.global.L2 [%0];" :: "l"(wout + (size_t)cta * 6 * DM + lane * 128 + 64));
        }
      }
    } else {
      cluster_wait();
      bar_sync<BAR_LN>(288);
      if (lane == 0) {
        TS(1, 5);
        asm volatile("cp.async.bulk.global.shared::cta.bulk_group [%0], [%1], 20480;" :: "l"(g_xn + (size_t)cta * 16 * DM), "r"(buf) : "memory");
        bulk_commit();
        bulk_wait_all();
        set_flag(F_XN + rb, cta & 7, epoch);
        TS(1, 6);
      }
      __syncwarp();
      if (grp == 0) {
        gather96(&g_csum[ct * 192 + lane], reinterpret_cast<float*>(smem + COLSUM_OFF) + lane, epoch);
      } else {
        unsigned it = 0;
        while (true) {
          bool ok = true;
          #pragma unroll
          for (int j = 0; j < 5; j++) {
            const uint2 u = ld_tag2(&g_csum[5 * FH + ct * 160 + j * 32 + lane]);
            ok = ok && u.y == epoch;
            reinterpret_cast<uint32_t*>(smem + COLSUM_OFF)[j * 32 + lane] = u.x;
          }
          if (ok || ++it > POLL_LIMIT) break;
          __nanosleep(2 * POLL_NS);
        }
      }
      __syncwarp();
      TS(1, 4);
      if (grp == 0) {
        bar_arrive<BAR_STATS>(320);
        bar_sync<BAR_PUB1>(160);
        if (lane == 0) set_flag(F_Z + ct, rb, epoch);
        TS(1, 8);
        __syncwarp();
        bar_arrive<BAR_BUF>(160);
      } else {
        bar_arrive<BAR_STATS>(192);
        bar_sync<BAR_PUB2>(160);
        if (lane == 0) set_flag(F_A + ct, rb, epoch);
        TS(1, 9);
        __syncwarp();
      }
      bar_sync<BAR_PUB1>(160);
      if (lane == 0) {
        set_flag(grp == 0 ? F_H + rb : F_B + ct, grp == 0 ? ct : rb, epoch);
        if (grp == 0) mbar_arrive_cluster(dep0 + 8, rank ^ 1);
      }
      TS(1, 10);
      __syncwarp();
      bar_arrive<BAR_BUF>(160);
    }
  } else {
    asm volatile("setmaxnreg.inc.sync.aligned.u32 232;");
    const int t = tid & 127, w = t >> 5, l = t & 31;
    ln_rows(rv, buf, cta, epoch);
    TS(wg + 1, 0);
    cluster_wait();
    const uint32_t st_base = buf + (w * 16 + ((l >> 3) & 1) * 8 + (l & 7)) * 128;
    const uint32_t st_x = ((l >> 4) ^ (l & 7)) << 4;
    const float2* rs = reinterpret_cast<const float2*>(smem + ROWSTAT_OFF) + w * 16 + (l >> 2);
    const float2* cs = reinterpret_cast<const float2*>(smem + COLSUM_OFF) + (l & 3);
    if (grp == 0) {
      {
        const int mb = wg - 1;
        float acc[1][96];
        zero(acc);
        mainloop<192, 1, 1, false, 0>(acc, sbase, 0, 0, 10, mb);
        drain(acc, sbase, 0, 9);
        TS(wg + 1, 1);
        bar_sync<BAR_STATS>(320);
        const float2 s0 = rs[mb * 64], s1 = rs[mb * 64 + 8];
        const float nm[2] = {s0.y / s0.x, s1.y / s1.x}, hr[2] = {0.5f * s0.x, 0.5f * s1.x};
        const float k1[2] = {0.7978845608f * s0.x, 0.7978845608f * s1.x};
        const float k2[2] = {0.0356774081f * s0.x * s0.x * s0.x, 0.0356774081f * s1.x * s1.x * s1.x};
        float sm0 = 0.f, sm1 = 0.f, q0 = 0.f, q1 = 0.f;
        #pragma unroll
        for (int j = 0; j < 24; j++) {
          const float2 c = cs[j * 4];
          #pragma unroll
          for (int e = 0; e < 4; e++) acc[0][4 * j + e] = fmaf(nm[e >> 1], (e & 1) ? c.y : c.x, acc[0][4 * j + e]);
        }
        #pragma unroll
        for (int jj = 0; jj < 12; jj++) {
          float u[8];
          #pragma unroll
          for (int hf = 0; hf < 2; hf++) {
            #pragma unroll
            for (int e = 0; e < 4; e++) {
              const float wv = acc[0][8 * jj + 4 * hf + e];
              float th; asm("tanh.approx.f32 %0, %1;" : "=f"(th) : "f"(wv * fmaf(k2[e >> 1], wv * wv, k1[e >> 1])));
              const float hv = hr[e >> 1] * wv;
              u[4 * hf + e] = fmaf(hv, th, hv);
            }
            sm0 += u[4 * hf] + u[4 * hf + 1]; q0 = fmaf(u[4 * hf], u[4 * hf], q0); q0 = fmaf(u[4 * hf + 1], u[4 * hf + 1], q0);
            sm1 += u[4 * hf + 2] + u[4 * hf + 3]; q1 = fmaf(u[4 * hf + 2], u[4 * hf + 2], q1); q1 = fmaf(u[4 * hf + 3], u[4 * hf + 3], q1);
          }
          stsm4(st_base + mb * 24576 + (jj >> 2) * 8192 + (st_x ^ ((jj & 3) << 5)),
                pack_bf16(u[0], u[1]), pack_bf16(u[2], u[3]), pack_bf16(u[4], u[5]), pack_bf16(u[6], u[7]));
        }
        #pragma unroll
        for (int o = 1; o < 4; o <<= 1) {
          sm0 += __shfl_xor_sync(0xffffffffu, sm0, o); q0 += __shfl_xor_sync(0xffffffffu, q0, o);
          sm1 += __shfl_xor_sync(0xffffffffu, sm1, o); q1 += __shfl_xor_sync(0xffffffffu, q1, o);
        }
        if ((l & 3) < 2) {
          const float sm = (l & 1) ? sm1 : sm0, sv = (l & 1) ? q1 : q0;
          const int row = mb * 64 + w * 16 + (l & 1) * 8 + (l >> 2);
          const float mu = sm * (1.f / 192), m2 = fmaxf(sv - sm * mu, 0.f);
          st_tag2(&g_zstat[(rb * 4 + ct) * 128 + row], __float_as_uint(mu), (__float_as_uint(m2) & ~255u) | (epoch & 255u));
          reinterpret_cast<float2*>(smem + ZSTAT_OFF)[row] = make_float2(mu, m2);
        }
        TS(wg + 1, 4);
      }
      float acc[2][96];
      if (wg == 1) {
        bar_sync<BAR_U>(256);
        uint2 v[3];
        unsigned n = 0;
        while (true) {
          bool ok = true;
          #pragma unroll
          for (int j = 0; j < 3; j++) { v[j] = ld_tag2(&g_zstat[(rb * 4 + ((ct + 1 + j) & 3)) * 128 + t]); ok = ok && ((v[j].y ^ epoch) & 255u) == 0; }
          if (ok || ++n > POLL_LIMIT) break;
          __nanosleep(POLL_NS);
        }
        const float2 own = reinterpret_cast<const float2*>(smem + ZSTAT_OFF)[t];
        const float m0 = __uint_as_float(v[0].x), m1 = __uint_as_float(v[1].x), m3 = __uint_as_float(v[2].x);
        const float mean = 0.25f * ((own.x + m0) + (m1 + m3));
        const float d = (own.x - mean) * (own.x - mean) + (m0 - mean) * (m0 - mean) + (m1 - mean) * (m1 - mean) + (m3 - mean) * (m3 - mean);
        const float var = fmaf(192.f, d, (own.y + __uint_as_float(v[0].y & ~255u)) + (__uint_as_float(v[1].y & ~255u) + __uint_as_float(v[2].y & ~255u)));
        const float r = rsqrtf(var * (1.f / FH) + LN_EPS);
        TS(2, 5);
        const uint32_t rbase = buf + (t >> 6) * 24576 + (t & 63) * 128;
        const uint32_t m2 = pack_bf16(-mean, -mean), r2 = pack_bf16(r, r);
        const float res = (-mean - bf_lo(m2)) * r;
        const uint32_t e2 = pack_bf16(res, res);
        #pragma unroll 1
        for (int c = 0; c < 3; c++) {
          uint4 z[8];
          #pragma unroll
          for (int i = 0; i < 8; i++) z[i] = lds128(rbase + c * 8192 + (((i ^ l) & 7) << 4));
          #pragma unroll
          for (int i = 0; i < 8; i++)
            sts128(rbase + c * 8192 + (((i ^ l) & 7) << 4), hfma2_bf16(hadd2_bf16(z[i].x, m2), r2, e2), hfma2_bf16(hadd2_bf16(z[i].y, m2), r2, e2),
                   hfma2_bf16(hadd2_bf16(z[i].z, m2), r2, e2), hfma2_bf16(hadd2_bf16(z[i].w, m2), r2, e2));
          fence_async_smem();
          __syncwarp();
          if (l == 0) {
            tma_store_2d(&maps.m[M_ZS], buf + (w >> 1) * 24576 + c * 8192 + (w & 1) * 4096, ct * 192 + c * 64, rb * 128 + w * 32);
            bulk_commit();
          }
        }
        TS(2, 6);
        if (l == 0) bulk_wait_all();
        __syncwarp();
        bar_arrive<BAR_PUB1>(160);
        {
          const bf16* bp = bsp + rb * 128 + w * 16 + (l >> 2);
          const float bb[4] = {__bfloat162float(bp[0]), __bfloat162float(bp[8]), __bfloat162float(bp[64]), __bfloat162float(bp[72])};
          #pragma unroll
          for (int i = 0; i < 96; i++) { acc[0][i] = bb[(i >> 1) & 1]; acc[1][i] = bb[2 + ((i >> 1) & 1)]; }
          pin(acc);
        }
        bar_sync<BAR_ORD2>(256);
        mainloop<192, 2, 1, false, BAR_ORD1>(acc, sbase, 0, 20, 32);
        bar_sync<BAR_Z1>(256);
        uint32_t z[6][4][4];
        #pragma unroll
        for (int i = 0; i < ZPRE; i++) ldsm4(st_base + (i >> 2) * 8192 + (st_x ^ ((i & 3) << 5)), z[i >> 2][i & 3][0], z[i >> 2][i & 3][1], z[i >> 2][i & 3][2], z[i >> 2][i & 3][3]);
        drain(acc, sbase, 0, 51);
        TS(2, 7);
        #pragma unroll
        for (int bx = 0; bx < 6; bx++) {
          if (bx >= 1) {
            #pragma unroll
            for (int i = ZPRE + (bx - 1) * 10; i < ZPRE + bx * 10; i++)
              if (i < 24) ldsm4(st_base + (i >> 2) * 8192 + (st_x ^ ((i & 3) << 5)), z[i >> 2][i & 3][0], z[i >> 2][i & 3][1], z[i >> 2][i & 3][2], z[i >> 2][i & 3][3]);
          }
          #pragma unroll
          for (int i = 0; i < 4; i++) {
            const float* a = &acc[bx / 3][8 * ((bx % 3) * 4 + i)];
            const uint32_t* zz = z[bx][i];
            stsm4(st_base + bx * 8192 + (st_x ^ (i << 5)),
                  hmul2_bf16(zz[0], pack_bf16(a[0], a[1])), hmul2_bf16(zz[1], pack_bf16(a[2], a[3])),
                  hmul2_bf16(zz[2], pack_bf16(a[4], a[5])), hmul2_bf16(zz[3], pack_bf16(a[6], a[7])));

          }
          if (bx % 3 == 2) {
            fence_async_smem();
            __syncwarp();
            if (l < 3) {
              tma_store_2d(&maps.m[M_HS], buf + (bx - 2 + l) * 8192 + w * 2048, ct * 192 + l * 64, rb * 128 + (bx / 3) * 64 + w * 16);
              bulk_commit();
            }
          }
        }
        bar_arrive<BAR_U>(256);
        TS(2, 8);
        if (l < 3) bulk_wait_all();
        __syncwarp();
        bar_arrive<BAR_PUB1>(160);
        TS(2, 9);
        return;
      }
      bar_arrive<BAR_U>(256);
      zero(acc);
      mainloop<192, 2, 1, false, BAR_ORD2>(acc, sbase, 0, 10, 10);
      drain(acc, sbase, 0, 19);
      TS(3, 2);
      bar_sync<BAR_BUF>(160);
      #pragma unroll
      for (int mi = 0; mi < 2; mi++)
        #pragma unroll
        for (int jj = 0; jj < 12; jj++) {
          const float* a = &acc[mi][8 * jj];
          stsm4(st_base + mi * 24576 + (jj >> 2) * 8192 + (st_x ^ ((jj & 3) << 5)),
                pack_bf16(a[0], a[1]), pack_bf16(a[2], a[3]), pack_bf16(a[4], a[5]), pack_bf16(a[6], a[7]));
        }
      __syncwarp();
      TS(3, 3);
      const uint32_t rbase = buf + (l >> 4) * 24576 + (w * 16 + (l & 15)) * 128;
      #pragma unroll 1
      for (int c2 = 0; c2 < 12; c2++) {
        const uint32_t ab = rbase + (c2 >> 2) * 8192;
        uint4 v[2];
        #pragma unroll
        for (int i = 0; i < 2; i++) v[i] = lds128(ab + (((((c2 & 3) * 2 + i) ^ l) & 7) << 4));
        #pragma unroll
        for (int i = 0; i < 2; i++)
          sts128(ab + (((((c2 & 3) * 2 + i) ^ l) & 7) << 4),
                 pack_bf16(gelu_tanh(bf_lo(v[i].x)), gelu_tanh(bf_hi(v[i].x))), pack_bf16(gelu_tanh(bf_lo(v[i].y)), gelu_tanh(bf_hi(v[i].y))),
                 pack_bf16(gelu_tanh(bf_lo(v[i].z)), gelu_tanh(bf_hi(v[i].z))), pack_bf16(gelu_tanh(bf_lo(v[i].w)), gelu_tanh(bf_hi(v[i].w))));
        __nanosleep(Z1_NS);
      }
      TS(3, 5);
      bar_arrive<BAR_Z1>(256);
    }
    float acc[2][80];
    if (grp == 1) {
      zero(acc);
      if (wg == 2) {
        mainloop<160, 2, 0, false, BAR_ORD2>(acc, sbase, 1, 0, 10);
      } else {
        weight_sums(win, wdre, rb * 4 + ct, epoch);
        TS(2, 1);
        bar_sync<BAR_ORD2>(256);
        mainloop<160, 2, 0, false, BAR_ORD1>(acc, sbase, 1, 10, 10);
      }
      drain(acc, sbase, 1, wg == 2 ? 9 : 19);
      TS(wg + 1, wg == 1 ? 7 : 2);
      if (wg == 1) bar_sync<BAR_Z1>(256); else bar_sync<BAR_STATS>(192);
      const uint32_t tb = buf + ((l >> 4) * 8 + (l & 7)) * 128 + (((w * 2 + ((l >> 3) & 1)) ^ (l & 7)) << 4);
      float2 st[4];
      #pragma unroll
      for (int r = 0; r < 4; r++) st[r] = wg == 2 ? rs[(r >> 1) * 64 + (r & 1) * 8] : make_float2(-1.f, 0.f);
      float2 cv[20];
      #pragma unroll
      for (int j = 0; j < 20; j++) cv[j] = cs[j * 4];
      #pragma unroll
      for (int jj = 0; jj < 10; jj++) {
        const float2 c0 = cv[jj * 2], c1 = cv[jj * 2 + 1];
        #pragma unroll
        for (int mi = 0; mi < 2; mi++) {
          const float* a = &acc[mi][8 * jj];
          const float2 s0 = st[mi * 2], s1 = st[mi * 2 + 1];
          stsm4_t(tb + mi * 20480 + jj * 2048,
                  pack_bf16(fmaf(a[0], s0.x, s0.y * c0.x), fmaf(a[1], s0.x, s0.y * c0.y)), pack_bf16(fmaf(a[2], s1.x, s1.y * c0.x), fmaf(a[3], s1.x, s1.y * c0.y)),
                  pack_bf16(fmaf(a[4], s0.x, s0.y * c1.x), fmaf(a[5], s0.x, s0.y * c1.y)), pack_bf16(fmaf(a[6], s1.x, s1.y * c1.x), fmaf(a[7], s1.x, s1.y * c1.y)));
        }
      }
      fence_async_smem();
      if (wg == 1) bar_sync<BAR_WG1>(128); else bar_sync<BAR_WG2>(128);
      TS(wg + 1, wg == 1 ? 8 : 6);
      if (l == 0) {
        #pragma unroll 1
        for (int i = 0; i < 2; i++) {
          const unsigned d = wg == 2 ? ST_A : ST_B;
          if (d) __nanosleep(i == 0 ? w * d : 3 * d);
          tma_store_2d(&maps.m[M_ABS], buf + i * 20480 + w * 5120, rb * 128 + i * 64, (2 - wg) * DM + ct * 160 + w * 40);
          bulk_commit();
        }
        bulk_wait_all();
      }
      __syncwarp();
      TS(wg + 1, wg == 1 ? 9 : 10);
      if (wg == 1) {
        bar_arrive<BAR_PUB1>(160);
        return;
      }
      bar_arrive<BAR_PUB2>(160);
      bar_arrive<BAR_Z1>(256);
    }
    zero(acc);
    bar_sync<BAR_ORD1>(256);
    mainloop<160, 2, 0, false, 0>(acc, sbase, grp, grp == 0 ? 52 : 20, grp == 0 ? NX : 64 - NX);
    if (grp == 0) {
      bar_sync<BAR_U>(256);
      mainloop<160, 2, 2, true, 0, true>(acc, sbase, 0, 52 + NX, 3);
    }
    mainloop<160, 2, 2, true, 0>(acc, sbase, grp, gh + 3 - 3 * grp, total - gh - 3 + 3 * grp);
    const uint32_t slab = buf + w * (16 * 320);
    const uint32_t addr = slab + (((l >> 3) & 1) * 8 + (l & 7)) * 320 + (l >> 4) * 16;
    bar_sync<BAR_BUF>(160);
    mbar_wait(dep0 + 32, 0);
    drain(acc, sbase, grp, total - 1);
    TS(3, 12);
    #pragma unroll
    for (int mi = 0; mi < 2; mi++) {
      #pragma unroll
      for (int jj = 0; jj < 10; jj++) {
        const float* a = &acc[mi][8 * jj];
        stsm4(addr + mi * 20480 + jj * 32, pack_bf16(a[0], a[1]), pack_bf16(a[2], a[3]), pack_bf16(a[4], a[5]), pack_bf16(a[6], a[7]));
      }
      fence_async_smem();
      __syncwarp();
      if (l == 0) {
        tma_reduce_2d(&maps.m[M_OUT], slab + mi * 20480, ct * 160, rb * 128 + mi * 64 + w * 16);
        bulk_commit();
      }
    }
    TS(3, 13);
    if (l == 0) {
      bulk_wait_read();
      if (w == 0) atomicAdd(&g_done, 1u);
    }
    TS(3, 15);
  }
}

typedef CUresult (*EncodeFn)(CUtensorMap*, CUtensorMapDataType, cuuint32_t, void*, const cuuint64_t*, const cuuint64_t*,
                             const cuuint32_t*, const cuuint32_t*, CUtensorMapInterleave, CUtensorMapSwizzle,
                             CUtensorMapL2promotion, CUtensorMapFloatOOBfill);

void make2d(EncodeFn enc, CUtensorMap* m, const void* p, uint64_t cols, uint64_t rows, uint32_t bc, uint32_t br, bool swz = true) {
  cuuint64_t gd[2] = {cols, rows}, gs[1] = {cols * 2};
  cuuint32_t bd[2] = {bc, br}, es[2] = {1, 1};
  enc(m, CU_TENSOR_MAP_DATA_TYPE_BFLOAT16, 2, const_cast<void*>(p), gd, gs, bd, es, CU_TENSOR_MAP_INTERLEAVE_NONE,
      swz ? CU_TENSOR_MAP_SWIZZLE_128B : CU_TENSOR_MAP_SWIZZLE_NONE, CU_TENSOR_MAP_L2_PROMOTION_L2_128B, CU_TENSOR_MAP_FLOAT_OOB_FILL_NONE);
}
void make3d(EncodeFn enc, CUtensorMap* m, const void* p, uint64_t cols, uint64_t rows, uint32_t cw, uint32_t nc, uint32_t br = 64) {
  cuuint64_t gd[3] = {cw, rows, cols / cw}, gs[2] = {cols * 2, cw * 2};
  cuuint32_t bd[3] = {cw, br, nc}, es[3] = {1, 1, 1};
  enc(m, CU_TENSOR_MAP_DATA_TYPE_BFLOAT16, 3, const_cast<void*>(p), gd, gs, bd, es, CU_TENSOR_MAP_INTERLEAVE_NONE,
      cw == 64 ? CU_TENSOR_MAP_SWIZZLE_128B : CU_TENSOR_MAP_SWIZZLE_64B, CU_TENSOR_MAP_L2_PROMOTION_L2_128B, CU_TENSOR_MAP_FLOAT_OOB_FILL_NONE);
}

}

extern "C" void kernel_launch(void* const* d_in, const int* in_sizes, int n_in, void* d_out, int out_size) {
  const bf16* x = (const bf16*)d_in[0];
  const bf16* wsre = (const bf16*)d_in[1];
  const bf16* wsim = (const bf16*)d_in[2];
  const bf16* wdre = (const bf16*)d_in[3];
  const bf16* wdim = (const bf16*)d_in[4];
  const bf16* win = (const bf16*)d_in[6];
  const bf16* wsp = (const bf16*)d_in[7];
  const bf16* bsp = (const bf16*)d_in[8];
  const bf16* wout = (const bf16*)d_in[9];

  void* fn = nullptr;
  cudaDriverEntryPointQueryResult qr;
  cudaGetDriverEntryPoint("cuTensorMapEncodeTiled", &fn, cudaEnableDefault, &qr);
  EncodeFn enc = (EncodeFn)fn;
  void *abT, *z2, *h, *xn;
  cudaGetSymbolAddress(&xn, g_xn);
  cudaGetSymbolAddress(&abT, g_abT);
  cudaGetSymbolAddress(&z2, g_z2);
  cudaGetSymbolAddress(&h, g_h);

  Maps maps;
  make2d(enc, &maps.m[M_X], x, DM, SEQ, 64, 64);
  make2d(enc, &maps.m[M_XN], xn, DM, SEQ, 64, 64);
  make2d(enc, &maps.m[M_WSRE], wsre, SEQ, SEQ, 64, 64);
  make2d(enc, &maps.m[M_WSIM], wsim, SEQ, SEQ, 64, 64);
  make2d(enc, &maps.m[M_WSP], wsp, SEQ, SEQ, 64, 64);
  make2d(enc, &maps.m[M_H], h, FH, SEQ, 64, 64);
  make3d(enc, &maps.m[M_WIN3], win, FF, DM, 64, 3);
  make3d(enc, &maps.m[M_Z23], z2, FH, SEQ, 64, 3);
  make2d(enc, &maps.m[M_WDRE], wdre, DM, DM, 64, 160);
  make2d(enc, &maps.m[M_WDIM], wdim, DM, DM, 64, 160);
  make2d(enc, &maps.m[M_AB], abT, SEQ, 2 * DM, 64, 160);
  make3d(enc, &maps.m[M_WOUT], wout, DM, FH, 32, 5);
  make2d(enc, &maps.m[M_HS], h, FH, SEQ, 64, 16);
  make2d(enc, &maps.m[M_ZS], z2, FH, SEQ, 64, 32);
  make2d(enc, &maps.m[M_ABS], abT, SEQ, 2 * DM, 64, 40);
  make2d(enc, &maps.m[M_OUT], d_out, DM, SEQ, 160, 16, false);

  cudaFuncSetAttribute(fused_kernel, cudaFuncAttributeMaxDynamicSharedMemorySize, SMEM_BYTES);
  fused_kernel<<<132, 384, SMEM_BYTES>>>(maps, x, win, wdre, bsp, wout, (bf16*)d_out);
}
```

```cpp
#include <cuda_runtime.h>
#include <cuda_bf16.h>
#include <cuda.h>
#include <stdint.h>

namespace {

typedef __nv_bfloat16 bf16;

constexpr int SEQ = 2048, DM = 640, FF = 1536, FH = 768;
constexpr int NX = 5;
constexpr int NO = 3;
constexpr int NST_A = 4, NST_B = 5, MAXST = 5;
constexpr int A_BYTES = 16384;
constexpr int BAR_OFF = 0;
constexpr int READY_OFF = 128;
constexpr int COLSUM_OFF = 256;
constexpr int ROWSTAT_OFF = 1024;
constexpr int ZSTAT_OFF = 2048;
constexpr int RED_OFF = 3072;
constexpr int RING_OFF = 4096;
constexpr int STAGE_A = 40960, STAGE_B = 36864;
constexpr int SMEM_BYTES = RING_OFF + 5 * STAGE_B + 40960;
constexpr int KB_A = 52 + NX + 12 - NO;
constexpr int KB_B = 84 - NX + NO;
constexpr float LN_EPS = 1e-5f;
constexpr unsigned POLL_LIMIT = 100000;
constexpr unsigned POLL_NS = 100, WATCH_NS = 40;
constexpr unsigned Z1_NS = 600;
constexpr int PF_D = 8;
constexpr int ZPRE = 6;

constexpr unsigned ST_B = 400, HELP_NS = 4000;

constexpr int BAR_ORD1 = 1, BAR_ORD2 = 2, BAR_WG1 = 3, BAR_WG2 = 4, BAR_LN = 5, BAR_BUF = 6, BAR_Z1 = 7, BAR_PUB1 = 8, BAR_PUB2 = 9,
              BAR_STATS = 10, BAR_U = 11;

enum { M_X, M_XN, M_WSRE, M_WSIM, M_WSP, M_H, M_WIN3, M_Z23, M_WDRE, M_WDIM, M_AB, M_WOUT, M_OUT, M_HS, M_ZS, M_ABS, M_COUNT };
struct Maps { CUtensorMap m[M_COUNT]; };

__device__ __align__(1024) bf16 g_abT[2 * DM * SEQ];
__device__ __align__(1024) bf16 g_z2[SEQ * FH];
__device__ __align__(1024) bf16 g_h[SEQ * FH];
__device__ __align__(1024) bf16 g_xn[SEQ * DM];
__device__ __align__(16) uint2 g_xstat[SEQ];
__device__ __align__(16) uint2 g_csum[5 * FH + DM];
__device__ __align__(16) uint2 g_zstat[64 * 128];
__device__ __align__(256) unsigned char g_flags[108 * 256];
constexpr int F_A = 0, F_B = 4, F_Z = 8, F_H = 12, F_XN = 28, F_Y = 44;
__device__ unsigned g_done;
#define TS(role, ev)
#define TC(i)

extern __shared__ __align__(1024) uint8_t smem[];

__device__ __forceinline__ uint32_t smem_u32(const void* p) { return (uint32_t)__cvta_generic_to_shared(p); }
__device__ __forceinline__ void mbar_init(uint32_t bar, uint32_t cnt) { asm volatile("mbarrier.init.shared::cta.b64 [%0], %1;" :: "r"(bar), "r"(cnt)); }
__device__ __forceinline__ void mbar_expect_tx(uint32_t bar, uint32_t bytes) { asm volatile("mbarrier.arrive.expect_tx.shared::cta.b64 _, [%0], %1;" :: "r"(bar), "r"(bytes) : "memory"); }
__device__ __forceinline__ void mbar_arrive(uint32_t bar) { asm volatile("mbarrier.arrive.shared::cta.b64 _, [%0];" :: "r"(bar) : "memory"); }
__device__ __forceinline__ void mbar_arrive_cluster(uint32_t bar, uint32_t cta) {
  asm volatile("{\n.reg .b32 ra;\nmapa.shared::cluster.u32 ra, %0, %1;\nmbarrier.arrive.shared::cluster.b64 _, [ra];\n}" :: "r"(bar), "r"(cta) : "memory");
}
__device__ __forceinline__ void mbar_wait(uint32_t bar, uint32_t parity) {
  asm volatile("{\n.reg .pred p;\n.reg .u32 n;\nmov.u32 n, 0;\n"
               "LW: mbarrier.try_wait.parity.shared::cta.b64 p, [%0], %1, 2000;\n@p bra LD;\n"
               "add.u32 n, n, 1;\nsetp.lt.u32 p, n, 20000;\n@p bra LW;\nLD:\n}" :: "r"(bar), "r"(parity) : "memory");
}
__device__ __forceinline__ void tma_load_2d(uint32_t dst, const CUtensorMap* map, uint32_t bar, int c0, int c1) {
  asm volatile("cp.async.bulk.tensor.2d.shared::cluster.global.mbarrier::complete_tx::bytes [%0], [%1, {%3, %4}], [%2];"
    :: "r"(dst), "l"((uint64_t)map), "r"(bar), "r"(c0), "r"(c1) : "memory");
}
__device__ __forceinline__ void tma_load_3d(uint32_t dst, const CUtensorMap* map, uint32_t bar, int c0, int c1, int c2) {
  asm volatile("cp.async.bulk.tensor.3d.shared::cluster.global.mbarrier::complete_tx::bytes [%0], [%1, {%3, %4, %5}], [%2];"
    :: "r"(dst), "l"((uint64_t)map), "r"(bar), "r"(c0), "r"(c1), "r"(c2) : "memory");
}
__device__ __forceinline__ void tma_load_2d_mc(uint32_t dst, const CUtensorMap* map, uint32_t bar, int c0, int c1, uint16_t mask) {
  asm volatile("cp.async.bulk.tensor.2d.shared::cluster.global.mbarrier::complete_tx::bytes.multicast::cluster [%0], [%1, {%3, %4}], [%2], %5;"
    :: "r"(dst), "l"((uint64_t)map), "r"(bar), "r"(c0), "r"(c1), "h"(mask) : "memory");
}
__device__ __forceinline__ void tma_store_2d(const CUtensorMap* map, uint32_t src, int c0, int c1) {
  asm volatile("cp.async.bulk.tensor.2d.global.shared::cta.bulk_group [%0, {%2, %3}], [%1];"
    :: "l"((uint64_t)map), "r"(src), "r"(c0), "r"(c1) : "memory");
}
__device__ __forceinline__ void tma_reduce_2d(const CUtensorMap* map, uint32_t src, int c0, int c1) {
  asm volatile("cp.reduce.async.bulk.tensor.2d.global.shared::cta.add.tile.bulk_group [%0, {%2, %3}], [%1];"
    :: "l"((uint64_t)map), "r"(src), "r"(c0), "r"(c1) : "memory");
}
__device__ __forceinline__ void bulk_wait_all() { asm volatile("cp.async.bulk.wait_group 0;" ::: "memory"); }
__device__ __forceinline__ void bulk_commit() { asm volatile("cp.async.bulk.commit_group;" ::: "memory"); }
__device__ __forceinline__ void bulk_wait_read() { asm volatile("cp.async.bulk.wait_group.read 0;" ::: "memory"); }
__device__ __forceinline__ void fence_async_smem() { asm volatile("fence.proxy.async.shared::cta;" ::: "memory"); }
__device__ __forceinline__ void fence_async_global() { asm volatile("fence.proxy.async.global;" ::: "memory"); }
__device__ __forceinline__ void wgmma_fence() { asm volatile("wgmma.fence.sync.aligned;" ::: "memory"); }
__device__ __forceinline__ void wgmma_commit() { asm volatile("wgmma.commit_group.sync.aligned;" ::: "memory"); }
template<int N> __device__ __forceinline__ void wgmma_wait() { asm volatile("wgmma.wait_group.sync.aligned %0;" :: "n"(N) : "memory"); }
template<int ID> __device__ __forceinline__ void bar_sync(int n) { asm volatile("bar.sync %0, %1;" :: "n"(ID), "r"(n) : "memory"); }
template<int ID> __device__ __forceinline__ void bar_arrive(int n) { asm volatile("bar.arrive %0, %1;" :: "n"(ID), "r"(n) : "memory"); }
__device__ __forceinline__ void cluster_wait() { asm volatile("barrier.cluster.wait.aligned;" ::: "memory"); }
__device__ __forceinline__ uint64_t desc64(uint32_t lo, uint32_t hi) { return (uint64_t)lo | ((uint64_t)hi << 32); }
__device__ __forceinline__ uint2 ld_tag2(const uint2* p) {
  uint2 v; asm volatile("ld.relaxed.gpu.global.v2.u32 {%0,%1}, [%2];" : "=r"(v.x), "=r"(v.y) : "l"(p) : "memory"); return v;
}
__device__ __forceinline__ void st_tag2(uint2* p, uint32_t a, uint32_t b) {
  asm volatile("st.relaxed.gpu.global.v2.u32 [%0], {%1,%2};" :: "l"(p), "r"(a), "r"(b) : "memory");
}
__device__ __forceinline__ unsigned ld_relaxed(const unsigned* p) {
  unsigned v; asm volatile("ld.relaxed.gpu.global.u32 %0, [%1];" : "=r"(v) : "l"(p) : "memory"); return v;
}
__device__ __forceinline__ uint32_t pack_bf16(float lo, float hi) {
  uint32_t r; asm("cvt.rn.bf16x2.f32 %0, %1, %2;" : "=r"(r) : "f"(hi), "f"(lo)); return r;
}
__device__ __forceinline__ float bf_lo(uint32_t v) { return __uint_as_float(v << 16); }
__device__ __forceinline__ float bf_hi(uint32_t v) { return __uint_as_float(v & 0xFFFF0000u); }
__device__ __forceinline__ void stsm4(uint32_t addr, uint32_t a, uint32_t b, uint32_t c, uint32_t d) {
  asm volatile("stmatrix.sync.aligned.m8n8.x4.shared.b16 [%0], {%1,%2,%3,%4};" :: "r"(addr), "r"(a), "r"(b), "r"(c), "r"(d));
}
__device__ __forceinline__ void stsm4_t(uint32_t addr, uint32_t a, uint32_t b, uint32_t c, uint32_t d) {
  asm volatile("stmatrix.sync.aligned.m8n8.x4.trans.shared.b16 [%0], {%1,%2,%3,%4};" :: "r"(addr), "r"(a), "r"(b), "r"(c), "r"(d));
}
__device__ __forceinline__ void ldsm4(uint32_t addr, uint32_t& a, uint32_t& b, uint32_t& c, uint32_t& d) {
  asm volatile("ldmatrix.sync.aligned.m8n8.x4.shared.b16 {%0,%1,%2,%3}, [%4];" : "=r"(a), "=r"(b), "=r"(c), "=r"(d) : "r"(addr));
}
__device__ __forceinline__ uint4 lds128(uint32_t a) {
  uint4 v; asm volatile("ld.shared.v4.u32 {%0,%1,%2,%3}, [%4];" : "=r"(v.x), "=r"(v.y), "=r"(v.z), "=r"(v.w) : "r"(a)); return v;
}
__device__ __forceinline__ void sts128(uint32_t a, uint32_t x, uint32_t y, uint32_t z, uint32_t w) {
  asm volatile("st.shared.v4.u32 [%0], {%1,%2,%3,%4};" :: "r"(a), "r"(x), "r"(y), "r"(z), "r"(w));
}
__device__ __forceinline__ uint32_t hmul2_bf16(uint32_t a, uint32_t b) {
  uint32_t r; asm("mul.rn.bf16x2 %0, %1, %2;" : "=r"(r) : "r"(a), "r"(b)); return r;
}
__device__ __forceinline__ uint32_t hadd2_bf16(uint32_t a, uint32_t b) {
  uint32_t r; asm("add.rn.bf16x2 %0, %1, %2;" : "=r"(r) : "r"(a), "r"(b)); return r;
}
__device__ __forceinline__ uint32_t hfma2_bf16(uint32_t a, uint32_t b, uint32_t c) {
  uint32_t r; asm("fma.rn.bf16x2 %0, %1, %2, %3;" : "=r"(r) : "r"(a), "r"(b), "r"(c)); return r;
}
__device__ __forceinline__ float gelu_tanh(float v) {
  float u = v * fmaf(0.0356774081f, v * v, 0.7978845608f);
  float t; asm("tanh.approx.f32 %0, %1;" : "=f"(t) : "f"(u));
  float hv = 0.5f * v;
  return fmaf(hv, t, hv);
}

template<int TB>
__device__ __forceinline__ void wgmma_n192(float (&d)[96], uint64_t da, uint64_t db, int scale_d) {
  asm volatile("{\n.reg .pred p;\nsetp.ne.b32 p, %98, 0;\n"
   "wgmma.mma_async.sync.aligned.m64n192k16.f32.bf16.bf16 {%0,%1,%2,%3,%4,%5,%6,%7,%8,%9,%10,%11,%12,%13,%14,%15,%16,%17,%18,%19,%20,%21,%22,%23,%24,%25,%26,%27,%28,%29,%30,%31,%32,%33,%34,%35,%36,%37,%38,%39,%40,%41,%42,%43,%44,%45,%46,%47,%48,%49,%50,%51,%52,%53,%54,%55,%56,%57,%58,%59,%60,%61,%62,%63,%64,%65,%66,%67,%68,%69,%70,%71,%72,%73,%74,%75,%76,%77,%78,%79,%80,%81,%82,%83,%84,%85,%86,%87,%88,%89,%90,%91,%92,%93,%94,%95}, %96, %97, p, 1, 1, 0, %99;\n}"
   : "+f"(d[0]),"+f"(d[1]),"+f"(d[2]),"+f"(d[3]),"+f"(d[4]),"+f"(d[5]),"+f"(d[6]),"+f"(d[7]),"+f"(d[8]),"+f"(d[9]),"+f"(d[10]),"+f"(d[11]),"+f"(d[12]),"+f"(d[13]),"+f"(d[14]),"+f"(d[15]),"+f"(d[16]),"+f"(d[17]),"+f"(d[18]),"+f"(d[19]),"+f"(d[20]),"+f"(d[21]),"+f"(d[22]),"+f"(d[23]),"+f"(d[24]),"+f"(d[25]),"+f"(d[26]),"+f"(d[27]),"+f"(d[28]),"+f"(d[29]),"+f"(d[30]),"+f"(d[31]),"+f"(d[32]),"+f"(d[33]),"+f"(d[34]),"+f"(d[35]),"+f"(d[36]),"+f"(d[37]),"+f"(d[38]),"+f"(d[39]),"+f"(d[40]),"+f"(d[41]),"+f"(d[42]),"+f"(d[43]),"+f"(d[44]),"+f"(d[45]),"+f"(d[46]),"+f"(d[47]),"+f"(d[48]),"+f"(d[49]),"+f"(d[50]),"+f"(d[51]),"+f"(d[52]),"+f"(d[53]),"+f"(d[54]),"+f"(d[55]),"+f"(d[56]),"+f"(d[57]),"+f"(d[58]),"+f"(d[59]),"+f"(d[60]),"+f"(d[61]),"+f"(d[62]),"+f"(d[63]),"+f"(d[64]),"+f"(d[65]),"+f"(d[66]),"+f"(d[67]),"+f"(d[68]),"+f"(d[69]),"+f"(d[70]),"+f"(d[71]),"+f"(d[72]),"+f"(d[73]),"+f"(d[74]),"+f"(d[75]),"+f"(d[76]),"+f"(d[77]),"+f"(d[78]),"+f"(d[79]),"+f"(d[80]),"+f"(d[81]),"+f"(d[82]),"+f"(d[83]),"+f"(d[84]),"+f"(d[85]),"+f"(d[86]),"+f"(d[87]),"+f"(d[88]),"+f"(d[89]),"+f"(d[90]),"+f"(d[91]),"+f"(d[92]),"+f"(d[93]),"+f"(d[94]),"+f"(d[95])
   : "l"(da), "l"(db), "r"(scale_d), "n"(TB));
}
template<int TB>
__device__ __forceinline__ void wgmma_n160(float (&d)[80], uint64_t da, uint64_t db, int scale_d) {
  asm volatile("{\n.reg .pred p;\nsetp.ne.b32 p, %82, 0;\n"
   "wgmma.mma_async.sync.aligned.m64n160k16.f32.bf16.bf16 {%0,%1,%2,%3,%4,%5,%6,%7,%8,%9,%10,%11,%12,%13,%14,%15,%16,%17,%18,%19,%20,%21,%22,%23,%24,%25,%26,%27,%28,%29,%30,%31,%32,%33,%34,%35,%36,%37,%38,%39,%40,%41,%42,%43,%44,%45,%46,%47,%48,%49,%50,%51,%52,%53,%54,%55,%56,%57,%58,%59,%60,%61,%62,%63,%64,%65,%66,%67,%68,%69,%70,%71,%72,%73,%74,%75,%76,%77,%78,%79}, %80, %81, p, 1, 1, 0, %83;\n}"
   : "+f"(d[0]),"+f"(d[1]),"+f"(d[2]),"+f"(d[3]),"+f"(d[4]),"+f"(d[5]),"+f"(d[6]),"+f"(d[7]),"+f"(d[8]),"+f"(d[9]),"+f"(d[10]),"+f"(d[11]),"+f"(d[12]),"+f"(d[13]),"+f"(d[14]),"+f"(d[15]),"+f"(d[16]),"+f"(d[17]),"+f"(d[18]),"+f"(d[19]),"+f"(d[20]),"+f"(d[21]),"+f"(d[22]),"+f"(d[23]),"+f"(d[24]),"+f"(d[25]),"+f"(d[26]),"+f"(d[27]),"+f"(d[28]),"+f"(d[29]),"+f"(d[30]),"+f"(d[31]),"+f"(d[32]),"+f"(d[33]),"+f"(d[34]),"+f"(d[35]),"+f"(d[36]),"+f"(d[37]),"+f"(d[38]),"+f"(d[39]),"+f"(d[40]),"+f"(d[41]),"+f"(d[42]),"+f"(d[43]),"+f"(d[44]),"+f"(d[45]),"+f"(d[46]),"+f"(d[47]),"+f"(d[48]),"+f"(d[49]),"+f"(d[50]),"+f"(d[51]),"+f"(d[52]),"+f"(d[53]),"+f"(d[54]),"+f"(d[55]),"+f"(d[56]),"+f"(d[57]),"+f"(d[58]),"+f"(d[59]),"+f"(d[60]),"+f"(d[61]),"+f"(d[62]),"+f"(d[63]),"+f"(d[64]),"+f"(d[65]),"+f"(d[66]),"+f"(d[67]),"+f"(d[68]),"+f"(d[69]),"+f"(d[70]),"+f"(d[71]),"+f"(d[72]),"+f"(d[73]),"+f"(d[74]),"+f"(d[75]),"+f"(d[76]),"+f"(d[77]),"+f"(d[78]),"+f"(d[79])
   : "l"(da), "l"(db), "r"(scale_d), "n"(TB));
}

template<int N, int TB>
__device__ __forceinline__ void wgmma_n(float (&d)[N / 2], uint64_t da, uint64_t db) {
  if constexpr (N == 192) wgmma_n192<TB>(d, da, db, 1); else wgmma_n160<TB>(d, da, db, 1);
}

template<int M, int R>
__device__ __forceinline__ void pin(float (&acc)[M][R]) {
  #pragma unroll
  for (int mi = 0; mi < M; mi++)
    #pragma unroll
    for (int i = 0; i < R; i++) asm volatile("" : "+f"(acc[mi][i]) :: "memory");
}
template<int M, int R>
__device__ __forceinline__ void zero(float (&acc)[M][R]) {
  #pragma unroll
  for (int mi = 0; mi < M; mi++)
    #pragma unroll
    for (int i = 0; i < R; i++) acc[mi][i] = 0.f;
  pin(acc);
}

template<int N, int M, int TB, bool CONT, int ORD_BAR, bool AOWN = false>
__device__ __forceinline__ void mainloop(float (&acc)[M][N / 2], uint32_t sbase, int grp, int g0, int nk, int m0 = 0) {
  const uint32_t full0 = sbase + BAR_OFF, empty0 = full0 + 8 * MAXST, ring = sbase + RING_OFF;
  const int nst = grp == 0 ? NST_A : NST_B, total = grp == 0 ? KB_A : KB_B;
  const uint32_t sstep = (grp == 0 ? STAGE_A : STAGE_B) >> 4;
  const int t = threadIdx.x & 127;
  const uint32_t da0 = (((ring + m0 * 8192) & 0x3FFFF) >> 4) | 0x10000u;
  const uint32_t db0 = (((ring + A_BYTES) & 0x3FFFF) >> 4) | ((TB == 2 ? 256u : TB ? 512u : 1u) << 16);
  constexpr uint32_t HI_A = 0x40000040u, HI_B = TB == 2 ? 0x80000020u : 0x40000040u;
  int s = g0 % nst, ph = (g0 / nst) & 1, ps = s == 0 ? nst - 1 : s - 1;
  #pragma unroll 1
  for (int g = g0; g < g0 + nk; g++) {
    const uint32_t so = s * sstep;
    mbar_wait(full0 + 8 * s, ph);
    wgmma_fence();
    #pragma unroll
    for (int k = 0; k < 4; k++) {
      const uint64_t db = desc64(db0 + so + (TB == 2 ? k * 64 : TB ? k * 128 : k * 2), HI_B);
      #pragma unroll
      for (int mi = 0; mi < M; mi++)
        wgmma_n<N, TB != 0>(acc[mi], desc64(AOWN ? da0 + ((NST_A * STAGE_A) >> 4) + (g - g0) * 512 + mi * 1536 + k * 2 : da0 + so + mi * 512 + k * 2, HI_A), db);
    }
    wgmma_commit();
    if (ORD_BAR != 0 && g == g0 + nk - 1) bar_arrive<ORD_BAR>(256);
    wgmma_wait<1>();
    if (t < 2 * M && (CONT || g > g0) && g - 1 + nst < total) mbar_arrive_cluster(empty0 + 8 * ps, t & 1);
    ps = s;
    if (++s == nst) { s = 0; ph ^= 1; }
  }
}
template<int M, int R>
__device__ __forceinline__ void drain(float (&acc)[M][R], uint32_t sbase, int grp, int glast) {
  wgmma_wait<0>();
  pin(acc);
  const int t = threadIdx.x & 127;
  const int nst = grp == 0 ? NST_A : NST_B, total = grp == 0 ? KB_A : KB_B;
  if (t < 2 * M && glast + nst < total) mbar_arrive_cluster(sbase + BAR_OFF + 8 * MAXST + 8 * (glast % nst), t & 1);
}

__device__ __forceinline__ void set_flag(int slot, int byte, unsigned epoch) {
  asm volatile("st.relaxed.gpu.global.u8 [%0], %1;" :: "l"(g_flags + slot * 256 + byte), "r"(epoch & 255u) : "memory");
}
__device__ __forceinline__ unsigned get_flag(int slot, int byte) {
  unsigned v; asm volatile("ld.relaxed.gpu.global.u8 %0, [%1];" : "=r"(v) : "l"(g_flags + slot * 256 + byte) : "memory"); return v;
}
__device__ __forceinline__ float sum8(uint4 v) {
  return ((bf_lo(v.x) + bf_hi(v.x)) + (bf_lo(v.y) + bf_hi(v.y))) + ((bf_lo(v.z) + bf_hi(v.z)) + (bf_lo(v.w) + bf_hi(v.w)));
}
__device__ __forceinline__ uint4 ldg128(const void* p) {
  uint4 v; asm volatile("ld.global.nc.v4.u32 {%0,%1,%2,%3}, [%4];" : "=r"(v.x), "=r"(v.y), "=r"(v.z), "=r"(v.w) : "l"(p)); return v;
}

__device__ __forceinline__ void ln_rows(const uint4 (&rv)[5], uint32_t buf, int cta, unsigned epoch) {
  const int t = threadIdx.x - 128, row = cta * 16 + (t >> 4), c = t & 15;
  const float sh = __shfl_sync(0xffffffffu, bf_lo(rv[0].x), t & 16);
  float d[40], s = 0.f, q = 0.f;
  #pragma unroll
  for (int j = 0; j < 5; j++) {
    const uint32_t u[4] = {rv[j].x, rv[j].y, rv[j].z, rv[j].w};
    #pragma unroll
    for (int e = 0; e < 4; e++) {
      const float d0 = bf_lo(u[e]) - sh, d1 = bf_hi(u[e]) - sh;
      d[j * 8 + e * 2] = d0; d[j * 8 + e * 2 + 1] = d1;
      s += d0 + d1; q = fmaf(d0, d0, q); q = fmaf(d1, d1, q);
    }
  }
  #pragma unroll
  for (int o = 1; o < 16; o <<= 1) { s += __shfl_xor_sync(0xffffffffu, s, o); q += __shfl_xor_sync(0xffffffffu, q, o); }
  const float md = s * (1.f / DM);
  const float r = rsqrtf(fmaxf(fmaf(q, 1.f / DM, -md * md), 0.f) + LN_EPS), o = -md * r;
  if (c == 0) st_tag2(&g_xstat[row], __float_as_uint(r), (__float_as_uint(-(md + sh) * r) & ~255u) | (epoch & 255u));
  #pragma unroll
  for (int j = 0; j < 5; j++) {
    const float* a = &d[j * 8];
    sts128(buf + (t >> 4) * 1280 + (c + 16 * j) * 16,
           pack_bf16(fmaf(a[0], r, o), fmaf(a[1], r, o)), pack_bf16(fmaf(a[2], r, o), fmaf(a[3], r, o)),
           pack_bf16(fmaf(a[4], r, o), fmaf(a[5], r, o)), pack_bf16(fmaf(a[6], r, o), fmaf(a[7], r, o)));
  }
  fence_async_smem();
  bar_arrive<BAR_LN>(288);
}

__device__ __forceinline__ void weight_sums(const bf16* __restrict__ win, const bf16* __restrict__ wdre, int j, unsigned epoch) {
  const int t = threadIdx.x & 127, w = t >> 5, l = t & 31;
  const int cj = min(j, 59), cg = cj % 12, rg = cj / 12, wr = j * 10 + min(t >> 3, 9);
  uint4 cv[8], rv[10];
  #pragma unroll
  for (int i = 0; i < 8; i++) cv[i] = ldg128(reinterpret_cast<const uint4*>(win + (size_t)(rg * 128 + w * 32 + i * 4 + (l >> 3)) * FF + FH + cg * 64) + (l & 7));
  #pragma unroll
  for (int i = 0; i < 10; i++) rv[i] = ldg128(reinterpret_cast<const uint4*>(wdre + (size_t)wr * DM) + (l & 7) + 8 * i);
  float v[8];
  #pragma unroll
  for (int e = 0; e < 8; e++) v[e] = 0.f;
  #pragma unroll
  for (int i = 0; i < 8; i++) {
    v[0] += bf_lo(cv[i].x); v[1] += bf_hi(cv[i].x); v[2] += bf_lo(cv[i].y); v[3] += bf_hi(cv[i].y);
    v[4] += bf_lo(cv[i].z); v[5] += bf_hi(cv[i].z); v[6] += bf_lo(cv[i].w); v[7] += bf_hi(cv[i].w);
  }
  #pragma unroll
  for (int st = 0; st < 2; st++) {
    const int n = 4 >> st;
    const bool up = (l & (4 * n)) != 0;
    #pragma unroll
    for (int e = 0; e < 4; e++)
      if (e < n) { const float keep = up ? v[e + n] : v[e], send = up ? v[e] : v[e + n]; v[e] = keep + __shfl_xor_sync(0xffffffffu, send, 4 * n); }
  }
  float* red = reinterpret_cast<float*>(smem + RED_OFF);
  *reinterpret_cast<float2*>(red + w * 64 + (l & 7) * 8 + (l >> 3) * 2) = make_float2(v[0], v[1]);
  float s = 0.f;
  #pragma unroll
  for (int i = 0; i < 10; i++) s += sum8(rv[i]);
  #pragma unroll
  for (int o = 1; o < 8; o <<= 1) s += __shfl_xor_sync(0xffffffffu, s, o);
  if ((l & 7) == 0) st_tag2(&g_csum[5 * FH + wr], __float_as_uint(s), epoch);
  bar_sync<BAR_WG1>(128);
  if (t < 64) st_tag2(&g_csum[rg * FH + cg * 64 + t], __float_as_uint((red[t] + red[64 + t]) + (red[128 + t] + red[192 + t])), epoch);
}

__device__ __forceinline__ void gather96(const uint2* src, float* dst, unsigned epoch) {
  unsigned it = 0;
  while (true) {
    bool ok = true;
    uint2 u[15];
    #pragma unroll
    for (int j = 0; j < 15; j++) u[j] = ld_tag2(src + (j % 5) * FH + (j / 5) * 32);
    #pragma unroll
    for (int j = 0; j < 15; j++) ok = ok && u[j].y == epoch;
    #pragma unroll
    for (int j = 0; j < 3; j++)
      dst[j * 32] = ((__uint_as_float(u[j * 5].x) + __uint_as_float(u[j * 5 + 1].x)) + (__uint_as_float(u[j * 5 + 2].x) + __uint_as_float(u[j * 5 + 3].x))) + __uint_as_float(u[j * 5 + 4].x);
    if (ok || ++it > POLL_LIMIT) break;
    __nanosleep(2 * POLL_NS);
  }
}

__device__ __forceinline__ void a_entry(int g, int grp, int ct, int& mi, int& kb) {
  if (g < 10) { mi = M_X; kb = g; }
  else if (g < 20) { mi = M_XN; kb = g - 10; }
  else if (g < 52) { mi = grp == 0 ? M_WSP : M_WSRE; kb = g - 20; }
  else if (grp == 0) {
    if (g < 52 + NX) { mi = M_WSIM; kb = g - 52 + 32 - NX; }
    else {
      const int i = g - 52 - NX;
      mi = M_H; kb = i < 3 ? ct * 3 + i : i < 6 ? (ct ^ 1) * 3 + i - 3 : ((ct >> 1) ^ 1) * 6 + i - 6;
    }
  } else {
    if (g < 84 - NX) { mi = M_WSIM; kb = g - 52; }
    else { mi = M_H; kb = ((ct >> 1) ^ 1) * 6 + g - (84 - NX) + 6 - NO; }
  }
}

__global__ void __cluster_dims__(2, 1, 1) __launch_bounds__(384, 1)
fused_kernel(const __grid_constant__ Maps maps, const bf16* __restrict__ x, const bf16* __restrict__ win, const bf16* __restrict__ wdre,
             const bf16* __restrict__ bsp, const bf16* __restrict__ wout, bf16* __restrict__ out) {
  const uint32_t sbase = smem_u32(smem);
  const uint32_t full0 = sbase + BAR_OFF, empty0 = full0 + 8 * MAXST, dep0 = empty0 + 8 * MAXST, ring = sbase + RING_OFF;
  const int tid = threadIdx.x, wg = __shfl_sync(0xffffffffu, tid >> 7, 0);
  if (blockIdx.x < 4) {
    if (tid == 0) {
      const unsigned epoch = (ld_relaxed(&g_done) >> 7) + 1u;
      for (int s = 0; s < 4; s++) mbar_init(sbase + 8 * s, 1);
      asm volatile("fence.mbarrier_init.release.cluster;" ::: "memory");
      __nanosleep(HELP_NS);
      const char* src = reinterpret_cast<const char*>(x) + (size_t)blockIdx.x * 655360;
      char* dst = reinterpret_cast<char*>(out) + (size_t)blockIdx.x * 655360;
      #pragma unroll 1
      for (int i = 0; i < 16 + 3; i++) {
        if (i < 16) {
          if (i >= 4) asm volatile("cp.async.bulk.wait_group.read 0;" ::: "memory");
          mbar_expect_tx(sbase + 8 * (i & 3), 40960);
          asm volatile("cp.async.bulk.shared::cluster.global.mbarrier::complete_tx::bytes [%0], [%1], 40960, [%2];"
                       :: "r"(sbase + 1024 + (i & 3) * 40960), "l"(src + (size_t)i * 40960), "r"(sbase + 8 * (i & 3)) : "memory");
        }
        if (i >= 3) {
          const int j = i - 3;
          mbar_wait(sbase + 8 * (j & 3), (j >> 2) & 1);
          asm volatile("cp.async.bulk.global.shared::cta.bulk_group [%0], [%1], 40960;" :: "l"(dst + (size_t)j * 40960), "r"(sbase + 1024 + (j & 3) * 40960) : "memory");
          bulk_commit();
        }
      }
      bulk_wait_all();
      for (int r = 0; r < 4; r++) set_flag(F_Y + blockIdx.x * 4 + r, 0, epoch);
    }
    return;
  }
  const int cta = blockIdx.x - 4, rank = cta & 1, grp = (cta >> 1) & 1, rb = cta >> 3, ct = ((cta >> 2) & 1) * 2 + rank;
  const int total = grp == 0 ? KB_A : KB_B, gh = grp == 0 ? 52 + NX : 84 - NX;
  const uint32_t stage_bytes = grp == 0 ? STAGE_A : STAGE_B;
  const int nst = grp == 0 ? NST_A : NST_B;
  const uint32_t buf = ring + nst * stage_bytes;

  uint4 rv[5];
  if (wg != 0) {
    #pragma unroll
    for (int j = 0; j < 5; j++) rv[j] = ldg128(reinterpret_cast<const uint4*>(x + (size_t)(cta * 16 + ((tid - 128) >> 4)) * DM) + (tid & 15) + 16 * j);
  }
  const unsigned epoch = (ld_relaxed(&g_done) >> 7) + 1u;
  if (tid == 0) {
    TS(0, 0);
    for (int s = 0; s < MAXST; s++) { mbar_init(full0 + 8 * s, 2); mbar_init(empty0 + 8 * s, 4); mbar_init(dep0 + 8 * s, 1); }
    *reinterpret_cast<volatile int*>(smem + READY_OFF) = 0;
    asm volatile("fence.mbarrier_init.release.cluster;" ::: "memory");
  }
  __syncthreads();
  asm volatile("barrier.cluster.arrive.relaxed.aligned;" ::: "memory");

  if (wg == 0) {
    asm volatile("setmaxnreg.dec.sync.aligned.u32 40;");
    const int warp = tid >> 5, lane = tid & 31;
    if (warp == 0) {
      const int row = rb * 128;
      if (lane == 0) {
        for (int g = 0; g < nst; g++) {
          mbar_expect_tx(full0 + 8 * g, A_BYTES);
          tma_load_2d(ring + g * stage_bytes, &maps.m[M_X], full0 + 8 * g, g * 64, row);
          tma_load_2d(ring + g * stage_bytes + 8192, &maps.m[M_X], full0 + 8 * g, g * 64, row + 64);
        }
      }
      __syncwarp();
      cluster_wait();
      if (lane == 0) {
        int s = 0, ph = 0;
        #pragma unroll 1
        for (int g = nst; g < total; g++) {
          int mi, kb;
          a_entry(g, grp, ct, mi, kb);
          if (g == 10 || g == gh + 6 - 6 * grp || (grp == 0 && g == gh + 3)) {
            TS(0, g > 10 ? 3 : 1);
            mbar_wait(dep0 + (g == 10 ? 0 : g == gh + 6 - 6 * grp ? 24 : 8), 0);
            fence_async_global();
            TS(0, g > 10 ? 4 : 2);
          }
          mbar_wait(empty0 + 8 * s, ph);
          if (grp == 0 && g >= gh && g < gh + 6) {
            if (g < gh + 3) {
              mbar_arrive(full0 + 8 * s);
            } else {
              mbar_expect_tx(full0 + 8 * s, A_BYTES);
              tma_load_2d(ring + s * stage_bytes, &maps.m[mi], full0 + 8 * s, kb * 64, row);
              tma_load_2d(ring + s * stage_bytes + 8192, &maps.m[mi], full0 + 8 * s, kb * 64, row + 64);
            }
          } else {
            mbar_expect_tx(full0 + 8 * s, A_BYTES);
            tma_load_2d_mc(ring + s * stage_bytes + rank * 8192, &maps.m[mi], full0 + 8 * s, kb * 64, row + rank * 64, 3);
          }
          if (++s == nst) { s = 0; ph ^= 1; }
          if (g + PF_D < gh) {
            a_entry(g + PF_D, grp, ct, mi, kb);
            if (mi >= M_WSRE && (kb & 1) == (ct >> 1))
              asm volatile("cp.async.bulk.prefetch.tensor.2d.L2.global.tile [%0, {%1, %2}];" :: "l"((uint64_t)&maps.m[mi]), "r"(kb * 64), "r"(row + rank * 64) : "memory");
          }
        }
        TS(0, 5);
      }
    } else if (warp == 1) {
      if (lane == 0) {
        int s = 0, ph = 1;
        int have = 0;
        #pragma unroll 1
        for (int g = 0; g < total; g++) {
          int mi, kb, c;
          a_entry(g, grp, ct, mi, kb);
          const bool nmaj = g >= gh || (grp == 0 && g < 52);
          uint32_t bytes = 20480;
          if (g >= gh) { mi = M_WOUT; c = ct * 5; }
          else if (g >= 52) { mi = M_AB; c = DM + ct * 160; }
          else if (grp == 0) { mi = g < 20 ? M_WIN3 : M_Z23; c = 3 * ct + (g < 10 ? 12 : 0); bytes = 24576; }
          else { mi = g < 10 ? M_WDRE : g < 20 ? M_WDIM : M_AB; c = ct * 160; }
          if (g >= 20 && g < 52 && ((g - 20) >> 1) >= have) {
            if (g == 20) TS(1, 0);
            unsigned it = 0;
            while ((have = *reinterpret_cast<volatile int*>(smem + READY_OFF)) <= ((g - 20) >> 1) && ++it < 50 * POLL_LIMIT) {}
            fence_async_global();
            if (g == 20) { TS(1, 1); TC(1); }
          }
          if (g == 52) { TS(1, 2); mbar_wait(dep0 + 16, 0); fence_async_global(); TS(1, 3); TC(2); }
          const uint32_t dst = ring + s * stage_bytes + A_BYTES, fb = full0 + 8 * s;
          mbar_wait(empty0 + 8 * s, ph);
          if (++s == nst) { s = 0; ph ^= 1; }
          mbar_expect_tx(fb, bytes);
          if (nmaj) tma_load_3d(dst, &maps.m[mi], fb, 0, kb * 64, c);
          else tma_load_2d(dst, &maps.m[mi], fb, kb * 64, c);
        }
      }
      __syncwarp();
      cluster_wait();
    } else if (warp == 2) {
      if (lane < M_COUNT) asm volatile("prefetch.tensormap [%0];" :: "l"((uint64_t)&maps.m[lane]) : "memory");
      cluster_wait();
      {
        unsigned it = 0;
        uint2 v[4];
        while (true) {
          bool ok = true;
          #pragma unroll
          for (int i = 0; i < 4; i++) { v[i] = ld_tag2(&g_xstat[rb * 128 + i * 32 + lane]); ok = ok && ((v[i].y ^ epoch) & 255u) == 0; }
          if (ok || ++it > POLL_LIMIT) break;
          __nanosleep(POLL_NS);
        }
        #pragma unroll
        for (int i = 0; i < 4; i++) reinterpret_cast<uint2*>(smem + ROWSTAT_OFF)[i * 32 + lane] = make_uint2(v[i].x, v[i].y & ~255u);
        __syncwarp();
        TS(0, 6);
      }
      const int hsrc = ((ct >> 1) ^ 1) * 2 + (grp == 0 ? (NO >= 3 ? 0 : lane & 1) : (NO <= 3 ? 1 : lane & 1));
      #pragma unroll 1
      for (int i = 0; i < 5; i++) {
        const int d = i == 3 ? 4 : i == 4 ? 3 : i;
        const int slot = d == 0 ? F_XN + rb : d == 4 ? F_Y + rb : d == 3 ? F_H + rb : d == 2 ? F_B + ct : grp == 0 ? F_Z + ct : F_A + ct;
        const int byte = d == 0 ? lane & 7 : d == 4 ? 0 : d == 3 ? hsrc : lane & 15;
        unsigned it = 0, m;
        while ((m = __ballot_sync(0xffffffffu, get_flag(slot, byte) != (epoch & 255u))) != 0 && ++it < POLL_LIMIT) {
          if (d == 1 && lane == 0) *reinterpret_cast<volatile int*>(smem + READY_OFF) = __ffs(m) - 1;
          __nanosleep(WATCH_NS);
        }
        if (d == 1 && lane == 0) *reinterpret_cast<volatile int*>(smem + READY_OFF) = 16;
        if (d < 4) TS(0, 8 + d * 2); else TS(0, 7);
        fence_async_global();
        __syncwarp();
        if (lane == 0 && d != 1) mbar_arrive(dep0 + 8 * d);
        if (d == 0) {
          if (grp == 0) {
            gather96(&g_csum[ct * 192 + 96 + lane], reinterpret_cast<float*>(smem + COLSUM_OFF) + 96 + lane, epoch);
            __syncwarp();
            bar_arrive<BAR_STATS>(320);
          } else {
            bar_arrive<BAR_STATS>(192);
          }
        }
        if (d == 2 && lane < 30) {
          asm volatile("prefetch.global.L2 [%0];" :: "l"(wout + (size_t)cta * 6 * DM + lane * 128));
          asm volatile("prefetch.global.L2 [%0];" :: "l"(wout + (size_t)cta * 6 * DM + lane * 128 + 64));
        }
      }
    } else {
      cluster_wait();
      bar_sync<BAR_LN>(288);
      if (lane == 0) {
        TS(1, 5);
        asm volatile("cp.async.bulk.global.shared::cta.bulk_group [%0], [%1], 20480;" :: "l"(g_xn + (size_t)cta * 16 * DM), "r"(buf) : "memory");
        bulk_commit();
        bulk_wait_all();
        set_flag(F_XN + rb, cta & 7, epoch);
        TS(1, 6);
      }
      __syncwarp();
      if (grp == 0) {
        gather96(&g_csum[ct * 192 + lane], reinterpret_cast<float*>(smem + COLSUM_OFF) + lane, epoch);
      } else {
        unsigned it = 0;
        while (true) {
          bool ok = true;
          #pragma unroll
          for (int j = 0; j < 5; j++) {
            const uint2 u = ld_tag2(&g_csum[5 * FH + ct * 160 + j * 32 + lane]);
            ok = ok && u.y == epoch;
            reinterpret_cast<uint32_t*>(smem + COLSUM_OFF)[j * 32 + lane] = u.x;
          }
          if (ok || ++it > POLL_LIMIT) break;
          __nanosleep(2 * POLL_NS);
        }
      }
      __syncwarp();
      TS(1, 4);
      if (grp == 0) {
        bar_arrive<BAR_STATS>(320);
        bar_sync<BAR_PUB1>(160);
        if (lane == 0) set_flag(F_Z + ct, rb, epoch);
        TS(1, 8);
        __syncwarp();
        bar_arrive<BAR_BUF>(160);
      } else {
        bar_arrive<BAR_STATS>(192);
        bar_sync<BAR_PUB2>(160);
        if (lane == 0) set_flag(F_A + ct, rb, epoch);
        TS(1, 9);
        __syncwarp();
      }
      bar_sync<BAR_PUB1>(160);
      if (lane == 0) {
        set_flag(grp == 0 ? F_H + rb : F_B + ct, grp == 0 ? ct : rb, epoch);
        if (grp == 0) mbar_arrive_cluster(dep0 + 8, rank ^ 1);
      }
      TS(1, 10);
      __syncwarp();
      bar_arrive<BAR_BUF>(160);
    }
  } else {
    asm volatile("setmaxnreg.inc.sync.aligned.u32 232;");
    const int t = tid & 127, w = t >> 5, l = t & 31;
    ln_rows(rv, buf, cta, epoch);
    TS(wg + 1, 0);
    cluster_wait();
    const uint32_t st_base = buf + (w * 16 + ((l >> 3) & 1) * 8 + (l & 7)) * 128;
    const uint32_t st_x = ((l >> 4) ^ (l & 7)) << 4;
    const float2* rs = reinterpret_cast<const float2*>(smem + ROWSTAT_OFF) + w * 16 + (l >> 2);
    const float2* cs = reinterpret_cast<const float2*>(smem + COLSUM_OFF) + (l & 3);
    if (grp == 0) {
      {
        const int mb = wg - 1;
        float acc[1][96];
        zero(acc);
        mainloop<192, 1, 1, false, 0>(acc, sbase, 0, 0, 10, mb);
        drain(acc, sbase, 0, 9);
        TS(wg + 1, 1);
        bar_sync<BAR_STATS>(320);
        const float2 s0 = rs[mb * 64], s1 = rs[mb * 64 + 8];
        const float nm[2] = {s0.y / s0.x, s1.y / s1.x}, hr[2] = {0.5f * s0.x, 0.5f * s1.x};
        const float k1[2] = {0.7978845608f * s0.x, 0.7978845608f * s1.x};
        const float k2[2] = {0.0356774081f * s0.x * s0.x * s0.x, 0.0356774081f * s1.x * s1.x * s1.x};
        float sm0 = 0.f, sm1 = 0.f, q0 = 0.f, q1 = 0.f;
        #pragma unroll
        for (int j = 0; j < 24; j++) {
          const float2 c = cs[j * 4];
          #pragma unroll
          for (int e = 0; e < 4; e++) acc[0][4 * j + e] = fmaf(nm[e >> 1], (e & 1) ? c.y : c.x, acc[0][4 * j + e]);
        }
        #pragma unroll
        for (int jj = 0; jj < 12; jj++) {
          float u[8];
          #pragma unroll
          for (int hf = 0; hf < 2; hf++) {
            #pragma unroll
            for (int e = 0; e < 4; e++) {
              const float wv = acc[0][8 * jj + 4 * hf + e];
              float th; asm("tanh.approx.f32 %0, %1;" : "=f"(th) : "f"(wv * fmaf(k2[e >> 1], wv * wv, k1[e >> 1])));
              const float hv = hr[e >> 1] * wv;
              u[4 * hf + e] = fmaf(hv, th, hv);
            }
            sm0 += u[4 * hf] + u[4 * hf + 1]; q0 = fmaf(u[4 * hf], u[4 * hf], q0); q0 = fmaf(u[4 * hf + 1], u[4 * hf + 1], q0);
            sm1 += u[4 * hf + 2] + u[4 * hf + 3]; q1 = fmaf(u[4 * hf + 2], u[4 * hf + 2], q1); q1 = fmaf(u[4 * hf + 3], u[4 * hf + 3], q1);
          }
          stsm4(st_base + mb * 24576 + (jj >> 2) * 8192 + (st_x ^ ((jj & 3) << 5)),
                pack_bf16(u[0], u[1]), pack_bf16(u[2], u[3]), pack_bf16(u[4], u[5]), pack_bf16(u[6], u[7]));
        }
        #pragma unroll
        for (int o = 1; o < 4; o <<= 1) {
          sm0 += __shfl_xor_sync(0xffffffffu, sm0, o); q0 += __shfl_xor_sync(0xffffffffu, q0, o);
          sm1 += __shfl_xor_sync(0xffffffffu, sm1, o); q1 += __shfl_xor_sync(0xffffffffu, q1, o);
        }
        if ((l & 3) < 2) {
          const float sm = (l & 1) ? sm1 : sm0, sv = (l & 1) ? q1 : q0;
          const int row = mb * 64 + w * 16 + (l & 1) * 8 + (l >> 2);
          const float mu = sm * (1.f / 192), m2 = fmaxf(sv - sm * mu, 0.f);
          st_tag2(&g_zstat[(rb * 4 + ct) * 128 + row], __float_as_uint(mu), (__float_as_uint(m2) & ~255u) | (epoch & 255u));
          reinterpret_cast<float2*>(smem + ZSTAT_OFF)[row] = make_float2(mu, m2);
        }
        TS(wg + 1, 4);
      }
      float acc[2][96];
      if (wg == 1) {
        bar_sync<BAR_U>(256);
        uint2 v[3];
        unsigned n = 0;
        while (true) {
          bool ok = true;
          #pragma unroll
          for (int j = 0; j < 3; j++) { v[j] = ld_tag2(&g_zstat[(rb * 4 + ((ct + 1 + j) & 3)) * 128 + t]); ok = ok && ((v[j].y ^ epoch) & 255u) == 0; }
          if (ok || ++n > POLL_LIMIT) break;
          __nanosleep(POLL_NS);
        }
        const float2 own = reinterpret_cast<const float2*>(smem + ZSTAT_OFF)[t];
        const float m0 = __uint_as_float(v[0].x), m1 = __uint_as_float(v[1].x), m3 = __uint_as_float(v[2].x);
        const float mean = 0.25f * ((own.x + m0) + (m1 + m3));
        const float d = (own.x - mean) * (own.x - mean) + (m0 - mean) * (m0 - mean) + (m1 - mean) * (m1 - mean) + (m3 - mean) * (m3 - mean);
        const float var = fmaf(192.f, d, (own.y + __uint_as_float(v[0].y & ~255u)) + (__uint_as_float(v[1].y & ~255u) + __uint_as_float(v[2].y & ~255u)));
        const float r = rsqrtf(var * (1.f / FH) + LN_EPS);
        TS(2, 5);
        const uint32_t rbase = buf + (t >> 6) * 24576 + (t & 63) * 128;
        const uint32_t m2 = pack_bf16(-mean, -mean), r2 = pack_bf16(r, r);
        const float res = (-mean - bf_lo(m2)) * r;
        const uint32_t e2 = pack_bf16(res, res);
        #pragma unroll 1
        for (int c = 0; c < 3; c++) {
          uint4 z[8];
          #pragma unroll
          for (int i = 0; i < 8; i++) z[i] = lds128(rbase + c * 8192 + (((i ^ l) & 7) << 4));
          #pragma unroll
          for (int i = 0; i < 8; i++)
            sts128(rbase + c * 8192 + (((i ^ l) & 7) << 4), hfma2_bf16(hadd2_bf16(z[i].x, m2), r2, e2), hfma2_bf16(hadd2_bf16(z[i].y, m2), r2, e2),
                   hfma2_bf16(hadd2_bf16(z[i].z, m2), r2, e2), hfma2_bf16(hadd2_bf16(z[i].w, m2), r2, e2));
          fence_async_smem();
          __syncwarp();
          if (l == 0) {
            tma_store_2d(&maps.m[M_ZS], buf + (w >> 1) * 24576 + c * 8192 + (w & 1) * 4096, ct * 192 + c * 64, rb * 128 + w * 32);
            bulk_commit();
          }
        }
        TS(2, 6);
        if (l == 0) bulk_wait_all();
        __syncwarp();
        bar_arrive<BAR_PUB1>(160);
        {
          const bf16* bp = bsp + rb * 128 + w * 16 + (l >> 2);
          const float bb[4] = {__bfloat162float(bp[0]), __bfloat162float(bp[8]), __bfloat162float(bp[64]), __bfloat162float(bp[72])};
          #pragma unroll
          for (int i = 0; i < 96; i++) { acc[0][i] = bb[(i >> 1) & 1]; acc[1][i] = bb[2 + ((i >> 1) & 1)]; }
          pin(acc);
        }
        bar_sync<BAR_ORD2>(256);
        mainloop<192, 2, 1, false, BAR_ORD1>(acc, sbase, 0, 20, 32);
        bar_sync<BAR_Z1>(256);
        uint32_t z[6][4][4];
        #pragma unroll
        for (int i = 0; i < ZPRE; i++) ldsm4(st_base + (i >> 2) * 8192 + (st_x ^ ((i & 3) << 5)), z[i >> 2][i & 3][0], z[i >> 2][i & 3][1], z[i >> 2][i & 3][2], z[i >> 2][i & 3][3]);
        drain(acc, sbase, 0, 51);
        TS(2, 7);
        #pragma unroll
        for (int bx = 0; bx < 6; bx++) {
          if (bx >= 1) {
            #pragma unroll
            for (int i = ZPRE + (bx - 1) * 10; i < ZPRE + bx * 10; i++)
              if (i < 24) ldsm4(st_base + (i >> 2) * 8192 + (st_x ^ ((i & 3) << 5)), z[i >> 2][i & 3][0], z[i >> 2][i & 3][1], z[i >> 2][i & 3][2], z[i >> 2][i & 3][3]);
          }
          #pragma unroll
          for (int i = 0; i < 4; i++) {
            const float* a = &acc[bx / 3][8 * ((bx % 3) * 4 + i)];
            const uint32_t* zz = z[bx][i];
            stsm4(st_base + bx * 8192 + (st_x ^ (i << 5)),
                  hmul2_bf16(zz[0], pack_bf16(a[0], a[1])), hmul2_bf16(zz[1], pack_bf16(a[2], a[3])),
                  hmul2_bf16(zz[2], pack_bf16(a[4], a[5])), hmul2_bf16(zz[3], pack_bf16(a[6], a[7])));

          }
          if (bx % 3 == 2) {
            fence_async_smem();
            __syncwarp();
            if (l < 3) {
              tma_store_2d(&maps.m[M_HS], buf + (bx - 2 + l) * 8192 + w * 2048, ct * 192 + l * 64, rb * 128 + (bx / 3) * 64 + w * 16);
              bulk_commit();
            }
          }
        }
        bar_arrive<BAR_U>(256);
        TS(2, 8);
        if (l < 3) bulk_wait_all();
        __syncwarp();
        bar_arrive<BAR_PUB1>(160);
        TS(2, 9);
        return;
      }
      bar_arrive<BAR_U>(256);
      zero(acc);
      mainloop<192, 2, 1, false, BAR_ORD2>(acc, sbase, 0, 10, 10);
      drain(acc, sbase, 0, 19);
      TS(3, 2);
      bar_sync<BAR_BUF>(160);
      #pragma unroll
      for (int mi = 0; mi < 2; mi++)
        #pragma unroll
        for (int jj = 0; jj < 12; jj++) {
          const float* a = &acc[mi][8 * jj];
          stsm4(st_base + mi * 24576 + (jj >> 2) * 8192 + (st_x ^ ((jj & 3) << 5)),
                pack_bf16(a[0], a[1]), pack_bf16(a[2], a[3]), pack_bf16(a[4], a[5]), pack_bf16(a[6], a[7]));
        }
      __syncwarp();
      TS(3, 3);
      const uint32_t rbase = buf + (l >> 4) * 24576 + (w * 16 + (l & 15)) * 128;
      #pragma unroll 1
      for (int c2 = 0; c2 < 12; c2++) {
        const uint32_t ab = rbase + (c2 >> 2) * 8192;
        uint4 v[2];
        #pragma unroll
        for (int i = 0; i < 2; i++) v[i] = lds128(ab + (((((c2 & 3) * 2 + i) ^ l) & 7) << 4));
        #pragma unroll
        for (int i = 0; i < 2; i++)
          sts128(ab + (((((c2 & 3) * 2 + i) ^ l) & 7) << 4),
                 pack_bf16(gelu_tanh(bf_lo(v[i].x)), gelu_tanh(bf_hi(v[i].x))), pack_bf16(gelu_tanh(bf_lo(v[i].y)), gelu_tanh(bf_hi(v[i].y))),
                 pack_bf16(gelu_tanh(bf_lo(v[i].z)), gelu_tanh(bf_hi(v[i].z))), pack_bf16(gelu_tanh(bf_lo(v[i].w)), gelu_tanh(bf_hi(v[i].w))));
        __nanosleep(Z1_NS);
      }
      TS(3, 5);
      bar_arrive<BAR_Z1>(256);
    }
    float acc[2][80];
    if (grp == 1) {
      zero(acc);
      if (wg == 2) {
        mainloop<160, 2, 0, false, BAR_ORD2>(acc, sbase, 1, 0, 10);
      } else {
        weight_sums(win, wdre, rb * 4 + ct, epoch);
        TS(2, 1);
        bar_sync<BAR_ORD2>(256);
        mainloop<160, 2, 0, false, BAR_ORD1>(acc, sbase, 1, 10, 10);
      }
      drain(acc, sbase, 1, wg == 2 ? 9 : 19);
      TS(wg + 1, wg == 1 ? 7 : 2);
      if (wg == 1) bar_sync<BAR_Z1>(256); else bar_sync<BAR_STATS>(192);
      const uint32_t tb = buf + ((l >> 4) * 8 + (l & 7)) * 128 + (((w * 2 + ((l >> 3) & 1)) ^ (l & 7)) << 4);
      float2 st[4];
      #pragma unroll
      for (int r = 0; r < 4; r++) st[r] = wg == 2 ? rs[(r >> 1) * 64 + (r & 1) * 8] : make_float2(-1.f, 0.f);
      float2 cv[20];
      #pragma unroll
      for (int j = 0; j < 20; j++) cv[j] = cs[j * 4];
      #pragma unroll
      for (int jj = 0; jj < 10; jj++) {
        const float2 c0 = cv[jj * 2], c1 = cv[jj * 2 + 1];
        #pragma unroll
        for (int mi = 0; mi < 2; mi++) {
          const float* a = &acc[mi][8 * jj];
          const float2 s0 = st[mi * 2], s1 = st[mi * 2 + 1];
          stsm4_t(tb + mi * 20480 + jj * 2048,
                  pack_bf16(fmaf(a[0], s0.x, s0.y * c0.x), fmaf(a[1], s0.x, s0.y * c0.y)), pack_bf16(fmaf(a[2], s1.x, s1.y * c0.x), fmaf(a[3], s1.x, s1.y * c0.y)),
                  pack_bf16(fmaf(a[4], s0.x, s0.y * c1.x), fmaf(a[5], s0.x, s0.y * c1.y)), pack_bf16(fmaf(a[6], s1.x, s1.y * c1.x), fmaf(a[7], s1.x, s1.y * c1.y)));
        }
      }
      fence_async_smem();
      if (wg == 1) bar_sync<BAR_WG1>(128); else bar_sync<BAR_WG2>(128);
      TS(wg + 1, wg == 1 ? 8 : 6);
      if (l == 0) {
        #pragma unroll 1
        for (int i = 0; i < 2; i++) {
          if (wg == 1) __nanosleep(i == 0 ? w * ST_B : 3 * ST_B);
          tma_store_2d(&maps.m[M_ABS], buf + i * 20480 + w * 5120, rb * 128 + i * 64, (2 - wg) * DM + ct * 160 + w * 40);
          bulk_commit();
        }
        bulk_wait_all();
      }
      __syncwarp();
      TS(wg + 1, wg == 1 ? 9 : 10);
      if (wg == 1) {
        bar_arrive<BAR_PUB1>(160);
        return;
      }
      bar_arrive<BAR_PUB2>(160);
      bar_arrive<BAR_Z1>(256);
    }
    zero(acc);
    bar_sync<BAR_ORD1>(256);
    mainloop<160, 2, 0, false, 0>(acc, sbase, grp, grp == 0 ? 52 : 20, grp == 0 ? NX : 64 - NX);
    if (grp == 0) {
      bar_sync<BAR_U>(256);
      mainloop<160, 2, 2, true, 0, true>(acc, sbase, 0, 52 + NX, 3);
    }
    mainloop<160, 2, 2, true, 0>(acc, sbase, grp, gh + 3 - 3 * grp, total - gh - 3 + 3 * grp);
    const uint32_t slab = buf + w * (16 * 320);
    const uint32_t addr = slab + (((l >> 3) & 1) * 8 + (l & 7)) * 320 + (l >> 4) * 16;
    bar_sync<BAR_BUF>(160);
    mbar_wait(dep0 + 32, 0);
    drain(acc, sbase, grp, total - 1);
    TS(3, 12);
    #pragma unroll
    for (int mi = 0; mi < 2; mi++) {
      #pragma unroll
      for (int jj = 0; jj < 10; jj++) {
        const float* a = &acc[mi][8 * jj];
        stsm4(addr + mi * 20480 + jj * 32, pack_bf16(a[0], a[1]), pack_bf16(a[2], a[3]), pack_bf16(a[4], a[5]), pack_bf16(a[6], a[7]));
      }
      fence_async_smem();
      __syncwarp();
      if (l == 0) {
        tma_reduce_2d(&maps.m[M_OUT], slab + mi * 20480, ct * 160, rb * 128 + mi * 64 + w * 16);
        bulk_commit();
      }
    }
    TS(3, 13);
    if (l == 0) {
      bulk_wait_read();
      if (w == 0) atomicAdd(&g_done, 1u);
    }
    TS(3, 15);
  }
}

typedef CUresult (*EncodeFn)(CUtensorMap*, CUtensorMapDataType, cuuint32_t, void*, const cuuint64_t*, const cuuint64_t*,
                             const cuuint32_t*, const cuuint32_t*, CUtensorMapInterleave, CUtensorMapSwizzle,
                             CUtensorMapL2promotion, CUtensorMapFloatOOBfill);

void make2d(EncodeFn enc, CUtensorMap* m, const void* p, uint64_t cols, uint64_t rows, uint32_t bc, uint32_t br, bool swz = true) {
  cuuint64_t gd[2] = {cols, rows}, gs[1] = {cols * 2};
  cuuint32_t bd[2] = {bc, br}, es[2] = {1, 1};
  enc(m, CU_TENSOR_MAP_DATA_TYPE_BFLOAT16, 2, const_cast<void*>(p), gd, gs, bd, es, CU_TENSOR_MAP_INTERLEAVE_NONE,
      swz ? CU_TENSOR_MAP_SWIZZLE_128B : CU_TENSOR_MAP_SWIZZLE_NONE, CU_TENSOR_MAP_L2_PROMOTION_L2_128B, CU_TENSOR_MAP_FLOAT_OOB_FILL_NONE);
}
void make3d(EncodeFn enc, CUtensorMap* m, const void* p, uint64_t cols, uint64_t rows, uint32_t cw, uint32_t nc, uint32_t br = 64) {
  cuuint64_t gd[3] = {cw, rows, cols / cw}, gs[2] = {cols * 2, cw * 2};
  cuuint32_t bd[3] = {cw, br, nc}, es[3] = {1, 1, 1};
  enc(m, CU_TENSOR_MAP_DATA_TYPE_BFLOAT16, 3, const_cast<void*>(p), gd, gs, bd, es, CU_TENSOR_MAP_INTERLEAVE_NONE,
      cw == 64 ? CU_TENSOR_MAP_SWIZZLE_128B : CU_TENSOR_MAP_SWIZZLE_64B, CU_TENSOR_MAP_L2_PROMOTION_L2_128B, CU_TENSOR_MAP_FLOAT_OOB_FILL_NONE);
}

}

extern "C" void kernel_launch(void* const* d_in, const int* in_sizes, int n_in, void* d_out, int out_size) {
  const bf16* x = (const bf16*)d_in[0];
  const bf16* wsre = (const bf16*)d_in[1];
  const bf16* wsim = (const bf16*)d_in[2];
  const bf16* wdre = (const bf16*)d_in[3];
  const bf16* wdim = (const bf16*)d_in[4];
  const bf16* win = (const bf16*)d_in[6];
  const bf16* wsp = (const bf16*)d_in[7];
  const bf16* bsp = (const bf16*)d_in[8];
  const bf16* wout = (const bf16*)d_in[9];

  void* fn = nullptr;
  cudaDriverEntryPointQueryResult qr;
  cudaGetDriverEntryPoint("cuTensorMapEncodeTiled", &fn, cudaEnableDefault, &qr);
  EncodeFn enc = (EncodeFn)fn;
  void *abT, *z2, *h, *xn;
  cudaGetSymbolAddress(&xn, g_xn);
  cudaGetSymbolAddress(&abT, g_abT);
  cudaGetSymbolAddress(&z2, g_z2);
  cudaGetSymbolAddress(&h, g_h);

  Maps maps;
  make2d(enc, &maps.m[M_X], x, DM, SEQ, 64, 64);
  make2d(enc, &maps.m[M_XN], xn, DM, SEQ, 64, 64);
  make2d(enc, &maps.m[M_WSRE], wsre, SEQ, SEQ, 64, 64);
  make2d(enc, &maps.m[M_WSIM], wsim, SEQ, SEQ, 64, 64);
  make2d(enc, &maps.m[M_WSP], wsp, SEQ, SEQ, 64, 64);
  make2d(enc, &maps.m[M_H], h, FH, SEQ, 64, 64);
  make3d(enc, &maps.m[M_WIN3], win, FF, DM, 64, 3);
  make3d(enc, &maps.m[M_Z23], z2, FH, SEQ, 64, 3);
  make2d(enc, &maps.m[M_WDRE], wdre, DM, DM, 64, 160);
  make2d(enc, &maps.m[M_WDIM], wdim, DM, DM, 64, 160);
  make2d(enc, &maps.m[M_AB], abT, SEQ, 2 * DM, 64, 160);
  make3d(enc, &maps.m[M_WOUT], wout, DM, FH, 32, 5);
  make2d(enc, &maps.m[M_HS], h, FH, SEQ, 64, 16);
  make2d(enc, &maps.m[M_ZS], z2, FH, SEQ, 64, 32);
  make2d(enc, &maps.m[M_ABS], abT, SEQ, 2 * DM, 64, 40);
  make2d(enc, &maps.m[M_OUT], d_out, DM, SEQ, 160, 16, false);

  cudaFuncSetAttribute(fused_kernel, cudaFuncAttributeMaxDynamicSharedMemorySize, SMEM_BYTES);
  fused_kernel<<<132, 384, SMEM_BYTES>>>(maps, x, win, wdre, bsp, wout, (bf16*)d_out);
}
```

```cpp
#include <cuda_runtime.h>
#include <cuda_bf16.h>
#include <cuda.h>
#include <stdint.h>

namespace {

typedef __nv_bfloat16 bf16;

constexpr int SEQ = 2048, DM = 640, FF = 1536, FH = 768;
constexpr int NX = 6;
constexpr int NO = 3;
constexpr int NST_A = 4, NST_B = 5, MAXST = 5;
constexpr int A_BYTES = 16384;
constexpr int BAR_OFF = 0;
constexpr int READY_OFF = 128;
constexpr int COLSUM_OFF = 256;
constexpr int ROWSTAT_OFF = 1024;
constexpr int ZSTAT_OFF = 2048;
constexpr int RED_OFF = 3072;
constexpr int RING_OFF = 4096;
constexpr int STAGE_A = 40960, STAGE_B = 36864;
constexpr int SMEM_BYTES = RING_OFF + 5 * STAGE_B + 40960;
constexpr int KB_A = 52 + NX + 12 - NO;
constexpr int KB_B = 84 - NX + NO;
constexpr float LN_EPS = 1e-5f;
constexpr unsigned POLL_LIMIT = 100000;
constexpr unsigned POLL_NS = 100, WATCH_NS = 40;
constexpr unsigned Z1_NS = 600;
constexpr int PF_D = 8;
constexpr int ZPRE = 6;

constexpr unsigned ST_A = 200, ST_B = 700;
constexpr unsigned HELP_NS = 4000;

constexpr int BAR_ORD1 = 1, BAR_ORD2 = 2, BAR_WG1 = 3, BAR_WG2 = 4, BAR_LN = 5, BAR_BUF = 6, BAR_Z1 = 7, BAR_PUB1 = 8, BAR_PUB2 = 9,
              BAR_STATS = 10, BAR_U = 11;

enum { M_X, M_XN, M_WSRE, M_WSIM, M_WSP, M_H, M_WIN3, M_Z23, M_WDRE, M_WDIM, M_AB, M_WOUT, M_OUT, M_HS, M_ZS, M_ABS, M_COUNT };
struct Maps { CUtensorMap m[M_COUNT]; };

__device__ __align__(1024) bf16 g_abT[2 * DM * SEQ];
__device__ __align__(1024) bf16 g_z2[SEQ * FH];
__device__ __align__(1024) bf16 g_h[SEQ * FH];
__device__ __align__(1024) bf16 g_xn[SEQ * DM];
__device__ __align__(16) uint2 g_xstat[SEQ];
__device__ __align__(16) uint2 g_csum[5 * FH + DM];
__device__ __align__(16) uint2 g_zstat[64 * 128];
__device__ __align__(256) unsigned char g_flags[108 * 256];
constexpr int F_A = 0, F_B = 4, F_Z = 8, F_H = 12, F_XN = 28, F_Y = 44;
__device__ unsigned g_done;
#define TS(role, ev)
#define TC(i)

extern __shared__ __align__(1024) uint8_t smem[];

__device__ __forceinline__ uint32_t smem_u32(const void* p) { return (uint32_t)__cvta_generic_to_shared(p); }
__device__ __forceinline__ void mbar_init(uint32_t bar, uint32_t cnt) { asm volatile("mbarrier.init.shared::cta.b64 [%0], %1;" :: "r"(bar), "r"(cnt)); }
__device__ __forceinline__ void mbar_expect_tx(uint32_t bar, uint32_t bytes) { asm volatile("mbarrier.arrive.expect_tx.shared::cta.b64 _, [%0], %1;" :: "r"(bar), "r"(bytes) : "memory"); }
__device__ __forceinline__ void mbar_arrive(uint32_t bar) { asm volatile("mbarrier.arrive.shared::cta.b64 _, [%0];" :: "r"(bar) : "memory"); }
__device__ __forceinline__ void mbar_arrive_cluster(uint32_t bar, uint32_t cta) {
  asm volatile("{\n.reg .b32 ra;\nmapa.shared::cluster.u32 ra, %0, %1;\nmbarrier.arrive.shared::cluster.b64 _, [ra];\n}" :: "r"(bar), "r"(cta) : "memory");
}
__device__ __forceinline__ void mbar_wait(uint32_t bar, uint32_t parity) {
  asm volatile("{\n.reg .pred p;\n.reg .u32 n;\nmov.u32 n, 0;\n"
               "LW: mbarrier.try_wait.parity.shared::cta.b64 p, [%0], %1, 2000;\n@p bra LD;\n"
               "add.u32 n, n, 1;\nsetp.lt.u32 p, n, 20000;\n@p bra LW;\nLD:\n}" :: "r"(bar), "r"(parity) : "memory");
}
__device__ __forceinline__ void tma_load_2d(uint32_t dst, const CUtensorMap* map, uint32_t bar, int c0, int c1) {
  asm volatile("cp.async.bulk.tensor.2d.shared::cluster.global.mbarrier::complete_tx::bytes [%0], [%1, {%3, %4}], [%2];"
    :: "r"(dst), "l"((uint64_t)map), "r"(bar), "r"(c0), "r"(c1) : "memory");
}
__device__ __forceinline__ void tma_load_3d(uint32_t dst, const CUtensorMap* map, uint32_t bar, int c0, int c1, int c2) {
  asm volatile("cp.async.bulk.tensor.3d.shared::cluster.global.mbarrier::complete_tx::bytes [%0], [%1, {%3, %4, %5}], [%2];"
    :: "r"(dst), "l"((uint64_t)map), "r"(bar), "r"(c0), "r"(c1), "r"(c2) : "memory");
}
__device__ __forceinline__ void tma_load_2d_mc(uint32_t dst, const CUtensorMap* map, uint32_t bar, int c0, int c1, uint16_t mask) {
  asm volatile("cp.async.bulk.tensor.2d.shared::cluster.global.mbarrier::complete_tx::bytes.multicast::cluster [%0], [%1, {%3, %4}], [%2], %5;"
    :: "r"(dst), "l"((uint64_t)map), "r"(bar), "r"(c0), "r"(c1), "h"(mask) : "memory");
}
__device__ __forceinline__ void tma_store_2d(const CUtensorMap* map, uint32_t src, int c0, int c1) {
  asm volatile("cp.async.bulk.tensor.2d.global.shared::cta.bulk_group [%0, {%2, %3}], [%1];"
    :: "l"((uint64_t)map), "r"(src), "r"(c0), "r"(c1) : "memory");
}
__device__ __forceinline__ void tma_reduce_2d(const CUtensorMap* map, uint32_t src, int c0, int c1) {
  asm volatile("cp.reduce.async.bulk.tensor.2d.global.shared::cta.add.tile.bulk_group [%0, {%2, %3}], [%1];"
    :: "l"((uint64_t)map), "r"(src), "r"(c0), "r"(c1) : "memory");
}
__device__ __forceinline__ void bulk_wait_all() { asm volatile("cp.async.bulk.wait_group 0;" ::: "memory"); }
__device__ __forceinline__ void bulk_commit() { asm volatile("cp.async.bulk.commit_group;" ::: "memory"); }
__device__ __forceinline__ void bulk_wait_read() { asm volatile("cp.async.bulk.wait_group.read 0;" ::: "memory"); }
__device__ __forceinline__ void fence_async_smem() { asm volatile("fence.proxy.async.shared::cta;" ::: "memory"); }
__device__ __forceinline__ void fence_async_global() { asm volatile("fence.proxy.async.global;" ::: "memory"); }
__device__ __forceinline__ void wgmma_fence() { asm volatile("wgmma.fence.sync.aligned;" ::: "memory"); }
__device__ __forceinline__ void wgmma_commit() { asm volatile("wgmma.commit_group.sync.aligned;" ::: "memory"); }
template<int N> __device__ __forceinline__ void wgmma_wait() { asm volatile("wgmma.wait_group.sync.aligned %0;" :: "n"(N) : "memory"); }
template<int ID> __device__ __forceinline__ void bar_sync(int n) { asm volatile("bar.sync %0, %1;" :: "n"(ID), "r"(n) : "memory"); }
template<int ID> __device__ __forceinline__ void bar_arrive(int n) { asm volatile("bar.arrive %0, %1;" :: "n"(ID), "r"(n) : "memory"); }
__device__ __forceinline__ void cluster_wait() { asm volatile("barrier.cluster.wait.aligned;" ::: "memory"); }
__device__ __forceinline__ uint64_t desc64(uint32_t lo, uint32_t hi) { return (uint64_t)lo | ((uint64_t)hi << 32); }
__device__ __forceinline__ uint2 ld_tag2(const uint2* p) {
  uint2 v; asm volatile("ld.relaxed.gpu.global.v2.u32 {%0,%1}, [%2];" : "=r"(v.x), "=r"(v.y) : "l"(p) : "memory"); return v;
}
__device__ __forceinline__ void st_tag2(uint2* p, uint32_t a, uint32_t b) {
  asm volatile("st.relaxed.gpu.global.v2.u32 [%0], {%1,%2};" :: "l"(p), "r"(a), "r"(b) : "memory");
}
__device__ __forceinline__ unsigned ld_relaxed(const unsigned* p) {
  unsigned v; asm volatile("ld.relaxed.gpu.global.u32 %0, [%1];" : "=r"(v) : "l"(p) : "memory"); return v;
}
__device__ __forceinline__ uint32_t pack_bf16(float lo, float hi) {
  uint32_t r; asm("cvt.rn.bf16x2.f32 %0, %1, %2;" : "=r"(r) : "f"(hi), "f"(lo)); return r;
}
__device__ __forceinline__ float bf_lo(uint32_t v) { return __uint_as_float(v << 16); }
__device__ __forceinline__ float bf_hi(uint32_t v) { return __uint_as_float(v & 0xFFFF0000u); }
__device__ __forceinline__ void stsm4(uint32_t addr, uint32_t a, uint32_t b, uint32_t c, uint32_t d) {
  asm volatile("stmatrix.sync.aligned.m8n8.x4.shared.b16 [%0], {%1,%2,%3,%4};" :: "r"(addr), "r"(a), "r"(b), "r"(c), "r"(d));
}
__device__ __forceinline__ void stsm4_t(uint32_t addr, uint32_t a, uint32_t b, uint32_t c, uint32_t d) {
  asm volatile("stmatrix.sync.aligned.m8n8.x4.trans.shared.b16 [%0], {%1,%2,%3,%4};" :: "r"(addr), "r"(a), "r"(b), "r"(c), "r"(d));
}
__device__ __forceinline__ void ldsm4(uint32_t addr, uint32_t& a, uint32_t& b, uint32_t& c, uint32_t& d) {
  asm volatile("ldmatrix.sync.aligned.m8n8.x4.shared.b16 {%0,%1,%2,%3}, [%4];" : "=r"(a), "=r"(b), "=r"(c), "=r"(d) : "r"(addr));
}
__device__ __forceinline__ uint4 lds128(uint32_t a) {
  uint4 v; asm volatile("ld.shared.v4.u32 {%0,%1,%2,%3}, [%4];" : "=r"(v.x), "=r"(v.y), "=r"(v.z), "=r"(v.w) : "r"(a)); return v;
}
__device__ __forceinline__ void sts128(uint32_t a, uint32_t x, uint32_t y, uint32_t z, uint32_t w) {
  asm volatile("st.shared.v4.u32 [%0], {%1,%2,%3,%4};" :: "r"(a), "r"(x), "r"(y), "r"(z), "r"(w));
}
__device__ __forceinline__ uint32_t hmul2_bf16(uint32_t a, uint32_t b) {
  uint32_t r; asm("mul.rn.bf16x2 %0, %1, %2;" : "=r"(r) : "r"(a), "r"(b)); return r;
}
__device__ __forceinline__ uint32_t hadd2_bf16(uint32_t a, uint32_t b) {
  uint32_t r; asm("add.rn.bf16x2 %0, %1, %2;" : "=r"(r) : "r"(a), "r"(b)); return r;
}
__device__ __forceinline__ uint32_t hfma2_bf16(uint32_t a, uint32_t b, uint32_t c) {
  uint32_t r; asm("fma.rn.bf16x2 %0, %1, %2, %3;" : "=r"(r) : "r"(a), "r"(b), "r"(c)); return r;
}
__device__ __forceinline__ float gelu_tanh(float v) {
  float u = v * fmaf(0.0356774081f, v * v, 0.7978845608f);
  float t; asm("tanh.approx.f32 %0, %1;" : "=f"(t) : "f"(u));
  float hv = 0.5f * v;
  return fmaf(hv, t, hv);
}

template<int TB>
__device__ __forceinline__ void wgmma_n192(float (&d)[96], uint64_t da, uint64_t db, int scale_d) {
  asm volatile("{\n.reg .pred p;\nsetp.ne.b32 p, %98, 0;\n"
   "wgmma.mma_async.sync.aligned.m64n192k16.f32.bf16.bf16 {%0,%1,%2,%3,%4,%5,%6,%7,%8,%9,%10,%11,%12,%13,%14,%15,%16,%17,%18,%19,%20,%21,%22,%23,%24,%25,%26,%27,%28,%29,%30,%31,%32,%33,%34,%35,%36,%37,%38,%39,%40,%41,%42,%43,%44,%45,%46,%47,%48,%49,%50,%51,%52,%53,%54,%55,%56,%57,%58,%59,%60,%61,%62,%63,%64,%65,%66,%67,%68,%69,%70,%71,%72,%73,%74,%75,%76,%77,%78,%79,%80,%81,%82,%83,%84,%85,%86,%87,%88,%89,%90,%91,%92,%93,%94,%95}, %96, %97, p, 1, 1, 0, %99;\n}"
   : "+f"(d[0]),"+f"(d[1]),"+f"(d[2]),"+f"(d[3]),"+f"(d[4]),"+f"(d[5]),"+f"(d[6]),"+f"(d[7]),"+f"(d[8]),"+f"(d[9]),"+f"(d[10]),"+f"(d[11]),"+f"(d[12]),"+f"(d[13]),"+f"(d[14]),"+f"(d[15]),"+f"(d[16]),"+f"(d[17]),"+f"(d[18]),"+f"(d[19]),"+f"(d[20]),"+f"(d[21]),"+f"(d[22]),"+f"(d[23]),"+f"(d[24]),"+f"(d[25]),"+f"(d[26]),"+f"(d[27]),"+f"(d[28]),"+f"(d[29]),"+f"(d[30]),"+f"(d[31]),"+f"(d[32]),"+f"(d[33]),"+f"(d[34]),"+f"(d[35]),"+f"(d[36]),"+f"(d[37]),"+f"(d[38]),"+f"(d[39]),"+f"(d[40]),"+f"(d[41]),"+f"(d[42]),"+f"(d[43]),"+f"(d[44]),"+f"(d[45]),"+f"(d[46]),"+f"(d[47]),"+f"(d[48]),"+f"(d[49]),"+f"(d[50]),"+f"(d[51]),"+f"(d[52]),"+f"(d[53]),"+f"(d[54]),"+f"(d[55]),"+f"(d[56]),"+f"(d[57]),"+f"(d[58]),"+f"(d[59]),"+f"(d[60]),"+f"(d[61]),"+f"(d[62]),"+f"(d[63]),"+f"(d[64]),"+f"(d[65]),"+f"(d[66]),"+f"(d[67]),"+f"(d[68]),"+f"(d[69]),"+f"(d[70]),"+f"(d[71]),"+f"(d[72]),"+f"(d[73]),"+f"(d[74]),"+f"(d[75]),"+f"(d[76]),"+f"(d[77]),"+f"(d[78]),"+f"(d[79]),"+f"(d[80]),"+f"(d[81]),"+f"(d[82]),"+f"(d[83]),"+f"(d[84]),"+f"(d[85]),"+f"(d[86]),"+f"(d[87]),"+f"(d[88]),"+f"(d[89]),"+f"(d[90]),"+f"(d[91]),"+f"(d[92]),"+f"(d[93]),"+f"(d[94]),"+f"(d[95])
   : "l"(da), "l"(db), "r"(scale_d), "n"(TB));
}
template<int TB>
__device__ __forceinline__ void wgmma_n160(float (&d)[80], uint64_t da, uint64_t db, int scale_d) {
  asm volatile("{\n.reg .pred p;\nsetp.ne.b32 p, %82, 0;\n"
   "wgmma.mma_async.sync.aligned.m64n160k16.f32.bf16.bf16 {%0,%1,%2,%3,%4,%5,%6,%7,%8,%9,%10,%11,%12,%13,%14,%15,%16,%17,%18,%19,%20,%21,%22,%23,%24,%25,%26,%27,%28,%29,%30,%31,%32,%33,%34,%35,%36,%37,%38,%39,%40,%41,%42,%43,%44,%45,%46,%47,%48,%49,%50,%51,%52,%53,%54,%55,%56,%57,%58,%59,%60,%61,%62,%63,%64,%65,%66,%67,%68,%69,%70,%71,%72,%73,%74,%75,%76,%77,%78,%79}, %80, %81, p, 1, 1, 0, %83;\n}"
   : "+f"(d[0]),"+f"(d[1]),"+f"(d[2]),"+f"(d[3]),"+f"(d[4]),"+f"(d[5]),"+f"(d[6]),"+f"(d[7]),"+f"(d[8]),"+f"(d[9]),"+f"(d[10]),"+f"(d[11]),"+f"(d[12]),"+f"(d[13]),"+f"(d[14]),"+f"(d[15]),"+f"(d[16]),"+f"(d[17]),"+f"(d[18]),"+f"(d[19]),"+f"(d[20]),"+f"(d[21]),"+f"(d[22]),"+f"(d[23]),"+f"(d[24]),"+f"(d[25]),"+f"(d[26]),"+f"(d[27]),"+f"(d[28]),"+f"(d[29]),"+f"(d[30]),"+f"(d[31]),"+f"(d[32]),"+f"(d[33]),"+f"(d[34]),"+f"(d[35]),"+f"(d[36]),"+f"(d[37]),"+f"(d[38]),"+f"(d[39]),"+f"(d[40]),"+f"(d[41]),"+f"(d[42]),"+f"(d[43]),"+f"(d[44]),"+f"(d[45]),"+f"(d[46]),"+f"(d[47]),"+f"(d[48]),"+f"(d[49]),"+f"(d[50]),"+f"(d[51]),"+f"(d[52]),"+f"(d[53]),"+f"(d[54]),"+f"(d[55]),"+f"(d[56]),"+f"(d[57]),"+f"(d[58]),"+f"(d[59]),"+f"(d[60]),"+f"(d[61]),"+f"(d[62]),"+f"(d[63]),"+f"(d[64]),"+f"(d[65]),"+f"(d[66]),"+f"(d[67]),"+f"(d[68]),"+f"(d[69]),"+f"(d[70]),"+f"(d[71]),"+f"(d[72]),"+f"(d[73]),"+f"(d[74]),"+f"(d[75]),"+f"(d[76]),"+f"(d[77]),"+f"(d[78]),"+f"(d[79])
   : "l"(da), "l"(db), "r"(scale_d), "n"(TB));
}

template<int N, int TB>
__device__ __forceinline__ void wgmma_n(float (&d)[N / 2], uint64_t da, uint64_t db) {
  if constexpr (N == 192) wgmma_n192<TB>(d, da, db, 1); else wgmma_n160<TB>(d, da, db, 1);
}

template<int M, int R>
__device__ __forceinline__ void pin(float (&acc)[M][R]) {
  #pragma unroll
  for (int mi = 0; mi < M; mi++)
    #pragma unroll
    for (int i = 0; i < R; i++) asm volatile("" : "+f"(acc[mi][i]) :: "memory");
}
template<int M, int R>
__device__ __forceinline__ void zero(float (&acc)[M][R]) {
  #pragma unroll
  for (int mi = 0; mi < M; mi++)
    #pragma unroll
    for (int i = 0; i < R; i++) acc[mi][i] = 0.f;
  pin(acc);
}

template<int N, int M, int TB, bool CONT, int ORD_BAR, bool AOWN = false>
__device__ __forceinline__ void mainloop(float (&acc)[M][N / 2], uint32_t sbase, int grp, int g0, int nk, int m0 = 0) {
  const uint32_t full0 = sbase + BAR_OFF, empty0 = full0 + 8 * MAXST, ring = sbase + RING_OFF;
  const int nst = grp == 0 ? NST_A : NST_B, total = grp == 0 ? KB_A : KB_B;
  const uint32_t sstep = (grp == 0 ? STAGE_A : STAGE_B) >> 4;
  const int t = threadIdx.x & 127;
  const uint32_t da0 = (((ring + m0 * 8192) & 0x3FFFF) >> 4) | 0x10000u;
  const uint32_t db0 = (((ring + A_BYTES) & 0x3FFFF) >> 4) | ((TB == 2 ? 256u : TB ? 512u : 1u) << 16);
  constexpr uint32_t HI_A = 0x40000040u, HI_B = TB == 2 ? 0x80000020u : 0x40000040u;
  int s = g0 % nst, ph = (g0 / nst) & 1, ps = s == 0 ? nst - 1 : s - 1;
  #pragma unroll 1
  for (int g = g0; g < g0 + nk; g++) {
    const uint32_t so = s * sstep;
    mbar_wait(full0 + 8 * s, ph);
    wgmma_fence();
    #pragma unroll
    for (int k = 0; k < 4; k++) {
      const uint64_t db = desc64(db0 + so + (TB == 2 ? k * 64 : TB ? k * 128 : k * 2), HI_B);
      #pragma unroll
      for (int mi = 0; mi < M; mi++)
        wgmma_n<N, TB != 0>(acc[mi], desc64(AOWN ? da0 + ((NST_A * STAGE_A) >> 4) + (g - g0) * 512 + mi * 1536 + k * 2 : da0 + so + mi * 512 + k * 2, HI_A), db);
    }
    wgmma_commit();
    if (ORD_BAR != 0 && g == g0 + nk - 1) bar_arrive<ORD_BAR>(256);
    wgmma_wait<1>();
    if (t < 2 * M && (CONT || g > g0) && g - 1 + nst < total) mbar_arrive_cluster(empty0 + 8 * ps, t & 1);
    ps = s;
    if (++s == nst) { s = 0; ph ^= 1; }
  }
}
template<int M, int R>
__device__ __forceinline__ void drain(float (&acc)[M][R], uint32_t sbase, int grp, int glast) {
  wgmma_wait<0>();
  pin(acc);
  const int t = threadIdx.x & 127;
  const int nst = grp == 0 ? NST_A : NST_B, total = grp == 0 ? KB_A : KB_B;
  if (t < 2 * M && glast + nst < total) mbar_arrive_cluster(sbase + BAR_OFF + 8 * MAXST + 8 * (glast % nst), t & 1);
}

__device__ __forceinline__ void set_flag(int slot, int byte, unsigned epoch) {
  asm volatile("st.relaxed.gpu.global.u8 [%0], %1;" :: "l"(g_flags + slot * 256 + byte), "r"(epoch & 255u) : "memory");
}
__device__ __forceinline__ unsigned get_flag(int slot, int byte) {
  unsigned v; asm volatile("ld.relaxed.gpu.global.u8 %0, [%1];" : "=r"(v) : "l"(g_flags + slot * 256 + byte) : "memory"); return v;
}
__device__ __forceinline__ float sum8(uint4 v) {
  return ((bf_lo(v.x) + bf_hi(v.x)) + (bf_lo(v.y) + bf_hi(v.y))) + ((bf_lo(v.z) + bf_hi(v.z)) + (bf_lo(v.w) + bf_hi(v.w)));
}
__device__ __forceinline__ uint4 ldg128(const void* p) {
  uint4 v; asm volatile("ld.global.nc.v4.u32 {%0,%1,%2,%3}, [%4];" : "=r"(v.x), "=r"(v.y), "=r"(v.z), "=r"(v.w) : "l"(p)); return v;
}

__device__ __forceinline__ void ln_rows(const uint4 (&rv)[5], uint32_t buf, int cta, unsigned epoch) {
  const int t = threadIdx.x - 128, row = cta * 16 + (t >> 4), c = t & 15;
  const float sh = __shfl_sync(0xffffffffu, bf_lo(rv[0].x), t & 16);
  float d[40], s = 0.f, q = 0.f;
  #pragma unroll
  for (int j = 0; j < 5; j++) {
    const uint32_t u[4] = {rv[j].x, rv[j].y, rv[j].z, rv[j].w};
    #pragma unroll
    for (int e = 0; e < 4; e++) {
      const float d0 = bf_lo(u[e]) - sh, d1 = bf_hi(u[e]) - sh;
      d[j * 8 + e * 2] = d0; d[j * 8 + e * 2 + 1] = d1;
      s += d0 + d1; q = fmaf(d0, d0, q); q = fmaf(d1, d1, q);
    }
  }
  #pragma unroll
  for (int o = 1; o < 16; o <<= 1) { s += __shfl_xor_sync(0xffffffffu, s, o); q += __shfl_xor_sync(0xffffffffu, q, o); }
  const float md = s * (1.f / DM);
  const float r = rsqrtf(fmaxf(fmaf(q, 1.f / DM, -md * md), 0.f) + LN_EPS), o = -md * r;
  if (c == 0) st_tag2(&g_xstat[row], __float_as_uint(r), (__float_as_uint(-(md + sh) * r) & ~255u) | (epoch & 255u));
  #pragma unroll
  for (int j = 0; j < 5; j++) {
    const float* a = &d[j * 8];
    sts128(buf + (t >> 4) * 1280 + (c + 16 * j) * 16,
           pack_bf16(fmaf(a[0], r, o), fmaf(a[1], r, o)), pack_bf16(fmaf(a[2], r, o), fmaf(a[3], r, o)),
           pack_bf16(fmaf(a[4], r, o), fmaf(a[5], r, o)), pack_bf16(fmaf(a[6], r, o), fmaf(a[7], r, o)));
  }
  fence_async_smem();
  bar_arrive<BAR_LN>(288);
}

__device__ __forceinline__ void weight_sums(const bf16* __restrict__ win, const bf16* __restrict__ wdre, int j, unsigned epoch) {
  const int t = threadIdx.x & 127, w = t >> 5, l = t & 31;
  const int cj = min(j, 59), cg = cj % 12, rg = cj / 12, wr = j * 10 + min(t >> 3, 9);
  uint4 cv[8], rv[10];
  #pragma unroll
  for (int i = 0; i < 8; i++) cv[i] = ldg128(reinterpret_cast<const uint4*>(win + (size_t)(rg * 128 + w * 32 + i * 4 + (l >> 3)) * FF + FH + cg * 64) + (l & 7));
  #pragma unroll
  for (int i = 0; i < 10; i++) rv[i] = ldg128(reinterpret_cast<const uint4*>(wdre + (size_t)wr * DM) + (l & 7) + 8 * i);
  float v[8];
  #pragma unroll
  for (int e = 0; e < 8; e++) v[e] = 0.f;
  #pragma unroll
  for (int i = 0; i < 8; i++) {
    v[0] += bf_lo(cv[i].x); v[1] += bf_hi(cv[i].x); v[2] += bf_lo(cv[i].y); v[3] += bf_hi(cv[i].y);
    v[4] += bf_lo(cv[i].z); v[5] += bf_hi(cv[i].z); v[6] += bf_lo(cv[i].w); v[7] += bf_hi(cv[i].w);
  }
  #pragma unroll
  for (int st = 0; st < 2; st++) {
    const int n = 4 >> st;
    const bool up = (l & (4 * n)) != 0;
    #pragma unroll
    for (int e = 0; e < 4; e++)
      if (e < n) { const float keep = up ? v[e + n] : v[e], send = up ? v[e] : v[e + n]; v[e] = keep + __shfl_xor_sync(0xffffffffu, send, 4 * n); }
  }
  float* red = reinterpret_cast<float*>(smem + RED_OFF);
  *reinterpret_cast<float2*>(red + w * 64 + (l & 7) * 8 + (l >> 3) * 2) = make_float2(v[0], v[1]);
  float s = 0.f;
  #pragma unroll
  for (int i = 0; i < 10; i++) s += sum8(rv[i]);
  #pragma unroll
  for (int o = 1; o < 8; o <<= 1) s += __shfl_xor_sync(0xffffffffu, s, o);
  if ((l & 7) == 0) st_tag2(&g_csum[5 * FH + wr], __float_as_uint(s), epoch);
  bar_sync<BAR_WG1>(128);
  if (t < 64) st_tag2(&g_csum[rg * FH + cg * 64 + t], __float_as_uint((red[t] + red[64 + t]) + (red[128 + t] + red[192 + t])), epoch);
}

__device__ __forceinline__ void gather96(const uint2* src, float* dst, unsigned epoch) {
  unsigned it = 0;
  while (true) {
    bool ok = true;
    uint2 u[15];
    #pragma unroll
    for (int j = 0; j < 15; j++) u[j] = ld_tag2(src + (j % 5) * FH + (j / 5) * 32);
    #pragma unroll
    for (int j = 0; j < 15; j++) ok = ok && u[j].y == epoch;
    #pragma unroll
    for (int j = 0; j < 3; j++)
      dst[j * 32] = ((__uint_as_float(u[j * 5].x) + __uint_as_float(u[j * 5 + 1].x)) + (__uint_as_float(u[j * 5 + 2].x) + __uint_as_float(u[j * 5 + 3].x))) + __uint_as_float(u[j * 5 + 4].x);
    if (ok || ++it > POLL_LIMIT) break;
    __nanosleep(2 * POLL_NS);
  }
}

__device__ __forceinline__ void a_entry(int g, int grp, int ct, int& mi, int& kb) {
  if (g < 10) { mi = M_X; kb = g; }
  else if (g < 20) { mi = M_XN; kb = g - 10; }
  else if (g < 52) { mi = grp == 0 ? M_WSP : M_WSRE; kb = g - 20; }
  else if (grp == 0) {
    if (g < 52 + NX) { mi = M_WSIM; kb = g - 52 + 32 - NX; }
    else {
      const int i = g - 52 - NX;
      mi = M_H; kb = i < 3 ? ct * 3 + i : i < 6 ? (ct ^ 1) * 3 + i - 3 : ((ct >> 1) ^ 1) * 6 + i - 6;
    }
  } else {
    if (g < 84 - NX) { mi = M_WSIM; kb = g - 52; }
    else { mi = M_H; kb = ((ct >> 1) ^ 1) * 6 + g - (84 - NX) + 6 - NO; }
  }
}

__global__ void __cluster_dims__(2, 1, 1) __launch_bounds__(384, 1)
fused_kernel(const __grid_constant__ Maps maps, const bf16* __restrict__ x, const bf16* __restrict__ win, const bf16* __restrict__ wdre,
             const bf16* __restrict__ bsp, const bf16* __restrict__ wout, bf16* __restrict__ out) {
  const uint32_t sbase = smem_u32(smem);
  const uint32_t full0 = sbase + BAR_OFF, empty0 = full0 + 8 * MAXST, dep0 = empty0 + 8 * MAXST, ring = sbase + RING_OFF;
  const int tid = threadIdx.x, wg = __shfl_sync(0xffffffffu, tid >> 7, 0);
  if (blockIdx.x < 4) {
    if (tid == 0) {
      const unsigned epoch = (ld_relaxed(&g_done) >> 7) + 1u;
      for (int s = 0; s < 4; s++) mbar_init(sbase + 8 * s, 1);
      asm volatile("fence.mbarrier_init.release.cluster;" ::: "memory");
      __nanosleep(HELP_NS);
      const char* src = reinterpret_cast<const char*>(x) + (size_t)blockIdx.x * 655360;
      char* dst = reinterpret_cast<char*>(out) + (size_t)blockIdx.x * 655360;
      #pragma unroll 1
      for (int i = 0; i < 16 + 3; i++) {
        if (i < 16) {
          if (i >= 4) asm volatile("cp.async.bulk.wait_group.read 0;" ::: "memory");
          mbar_expect_tx(sbase + 8 * (i & 3), 40960);
          asm volatile("cp.async.bulk.shared::cluster.global.mbarrier::complete_tx::bytes [%0], [%1], 40960, [%2];"
                       :: "r"(sbase + 1024 + (i & 3) * 40960), "l"(src + (size_t)i * 40960), "r"(sbase + 8 * (i & 3)) : "memory");
        }
        if (i >= 3) {
          const int j = i - 3;
          mbar_wait(sbase + 8 * (j & 3), (j >> 2) & 1);
          asm volatile("cp.async.bulk.global.shared::cta.bulk_group [%0], [%1], 40960;" :: "l"(dst + (size_t)j * 40960), "r"(sbase + 1024 + (j & 3) * 40960) : "memory");
          bulk_commit();
        }
      }
      bulk_wait_all();
      for (int r = 0; r < 4; r++) set_flag(F_Y + blockIdx.x * 4 + r, 0, epoch);
    }
    return;
  }
  const int cta = blockIdx.x - 4, rank = cta & 1, grp = (cta >> 1) & 1, rb = cta >> 3, ct = ((cta >> 2) & 1) * 2 + rank;
  const int total = grp == 0 ? KB_A : KB_B, gh = grp == 0 ? 52 + NX : 84 - NX;
  const uint32_t stage_bytes = grp == 0 ? STAGE_A : STAGE_B;
  const int nst = grp == 0 ? NST_A : NST_B;
  const uint32_t buf = ring + nst * stage_bytes;

  uint4 rv[5];
  if (wg != 0) {
    #pragma unroll
    for (int j = 0; j < 5; j++) rv[j] = ldg128(reinterpret_cast<const uint4*>(x + (size_t)(cta * 16 + ((tid - 128) >> 4)) * DM) + (tid & 15) + 16 * j);
  }
  const unsigned epoch = (ld_relaxed(&g_done) >> 7) + 1u;
  if (tid == 0) {
    TS(0, 0);
    for (int s = 0; s < MAXST; s++) { mbar_init(full0 + 8 * s, 2); mbar_init(empty0 + 8 * s, 4); mbar_init(dep0 + 8 * s, 1); }
    *reinterpret_cast<volatile int*>(smem + READY_OFF) = 0;
    asm volatile("fence.mbarrier_init.release.cluster;" ::: "memory");
  }
  __syncthreads();
  asm volatile("barrier.cluster.arrive.relaxed.aligned;" ::: "memory");

  if (wg == 0) {
    asm volatile("setmaxnreg.dec.sync.aligned.u32 40;");
    const int warp = tid >> 5, lane = tid & 31;
    if (warp == 0) {
      const int row = rb * 128;
      if (lane == 0) {
        for (int g = 0; g < nst; g++) {
          mbar_expect_tx(full0 + 8 * g, A_BYTES);
          tma_load_2d(ring + g * stage_bytes, &maps.m[M_X], full0 + 8 * g, g * 64, row);
          tma_load_2d(ring + g * stage_bytes + 8192, &maps.m[M_X], full0 + 8 * g, g * 64, row + 64);
        }
      }
      __syncwarp();
      cluster_wait();
      if (lane == 0) {
        int s = 0, ph = 0;
        #pragma unroll 1
        for (int g = nst; g < total; g++) {
          int mi, kb;
          a_entry(g, grp, ct, mi, kb);
          if (g == 10 || g == gh + 6 - 6 * grp || (grp == 0 && g == gh + 3)) {
            TS(0, g > 10 ? 3 : 1);
            mbar_wait(dep0 + (g == 10 ? 0 : g == gh + 6 - 6 * grp ? 24 : 8), 0);
            fence_async_global();
            TS(0, g > 10 ? 4 : 2);
          }
          mbar_wait(empty0 + 8 * s, ph);
          if (grp == 0 && g >= gh && g < gh + 6) {
            if (g < gh + 3) {
              mbar_arrive(full0 + 8 * s);
            } else {
              mbar_expect_tx(full0 + 8 * s, A_BYTES);
              tma_load_2d(ring + s * stage_bytes, &maps.m[mi], full0 + 8 * s, kb * 64, row);
              tma_load_2d(ring + s * stage_bytes + 8192, &maps.m[mi], full0 + 8 * s, kb * 64, row + 64);
            }
          } else {
            mbar_expect_tx(full0 + 8 * s, A_BYTES);
            tma_load_2d_mc(ring + s * stage_bytes + rank * 8192, &maps.m[mi], full0 + 8 * s, kb * 64, row + rank * 64, 3);
          }
          if (++s == nst) { s = 0; ph ^= 1; }
          if (g + PF_D < gh) {
            a_entry(g + PF_D, grp, ct, mi, kb);
            if (mi >= M_WSRE && (kb & 1) == (ct >> 1))
              asm volatile("cp.async.bulk.prefetch.tensor.2d.L2.global.tile [%0, {%1, %2}];" :: "l"((uint64_t)&maps.m[mi]), "r"(kb * 64), "r"(row + rank * 64) : "memory");
          }
        }
        TS(0, 5);
      }
    } else if (warp == 1) {
      if (lane == 0) {
        int s = 0, ph = 1;
        int have = 0;
        #pragma unroll 1
        for (int g = 0; g < total; g++) {
          int mi, kb, c;
          a_entry(g, grp, ct, mi, kb);
          const bool nmaj = g >= gh || (grp == 0 && g < 52);
          uint32_t bytes = 20480;
          if (g >= gh) { mi = M_WOUT; c = ct * 5; }
          else if (g >= 52) { mi = M_AB; c = DM + ct * 160; }
          else if (grp == 0) { mi = g < 20 ? M_WIN3 : M_Z23; c = 3 * ct + (g < 10 ? 12 : 0); bytes = 24576; }
          else { mi = g < 10 ? M_WDRE : g < 20 ? M_WDIM : M_AB; c = ct * 160; }
          if (g >= 20 && g < 52 && ((g - 20) >> 1) >= have) {
            if (g == 20) TS(1, 0);
            unsigned it = 0;
            while ((have = *reinterpret_cast<volatile int*>(smem + READY_OFF)) <= ((g - 20) >> 1) && ++it < 50 * POLL_LIMIT) {}
            fence_async_global();
            if (g == 20) { TS(1, 1); TC(1); }
          }
          if (g == 52) { TS(1, 2); mbar_wait(dep0 + 16, 0); fence_async_global(); TS(1, 3); TC(2); }
          const uint32_t dst = ring + s * stage_bytes + A_BYTES, fb = full0 + 8 * s;
          mbar_wait(empty0 + 8 * s, ph);
          if (++s == nst) { s = 0; ph ^= 1; }
          mbar_expect_tx(fb, bytes);
          if (nmaj) tma_load_3d(dst, &maps.m[mi], fb, 0, kb * 64, c);
          else tma_load_2d(dst, &maps.m[mi], fb, kb * 64, c);
        }
      }
      __syncwarp();
      cluster_wait();
    } else if (warp == 2) {
      if (lane < M_COUNT) asm volatile("prefetch.tensormap [%0];" :: "l"((uint64_t)&maps.m[lane]) : "memory");
      cluster_wait();
      {
        unsigned it = 0;
        uint2 v[4];
        while (true) {
          bool ok = true;
          #pragma unroll
          for (int i = 0; i < 4; i++) { v[i] = ld_tag2(&g_xstat[rb * 128 + i * 32 + lane]); ok = ok && ((v[i].y ^ epoch) & 255u) == 0; }
          if (ok || ++it > POLL_LIMIT) break;
          __nanosleep(POLL_NS);
        }
        #pragma unroll
        for (int i = 0; i < 4; i++) reinterpret_cast<uint2*>(smem + ROWSTAT_OFF)[i * 32 + lane] = make_uint2(v[i].x, v[i].y & ~255u);
        __syncwarp();
        TS(0, 6);
      }
      const int hsrc = ((ct >> 1) ^ 1) * 2 + (grp == 0 ? (NO >= 3 ? 0 : lane & 1) : (NO <= 3 ? 1 : lane & 1));
      #pragma unroll 1
      for (int i = 0; i < 5; i++) {
        const int d = i == 3 ? 4 : i == 4 ? 3 : i;
        const int slot = d == 0 ? F_XN + rb : d == 4 ? F_Y + rb : d == 3 ? F_H + rb : d == 2 ? F_B + ct : grp == 0 ? F_Z + ct : F_A + ct;
        const int byte = d == 0 ? lane & 7 : d == 4 ? 0 : d == 3 ? hsrc : lane & 15;
        unsigned it = 0, m;
        while ((m = __ballot_sync(0xffffffffu, get_flag(slot, byte) != (epoch & 255u))) != 0 && ++it < POLL_LIMIT) {
          if (d == 1 && lane == 0) *reinterpret_cast<volatile int*>(smem + READY_OFF) = __ffs(m) - 1;
          __nanosleep(WATCH_NS);
        }
        if (d == 1 && lane == 0) *reinterpret_cast<volatile int*>(smem + READY_OFF) = 16;
        if (d < 4) TS(0, 8 + d * 2); else TS(0, 7);
        fence_async_global();
        __syncwarp();
        if (lane == 0 && d != 1) mbar_arrive(dep0 + 8 * d);
        if (d == 0) {
          if (grp == 0) {
            gather96(&g_csum[ct * 192 + 96 + lane], reinterpret_cast<float*>(smem + COLSUM_OFF) + 96 + lane, epoch);
            __syncwarp();
            bar_arrive<BAR_STATS>(320);
          } else {
            bar_arrive<BAR_STATS>(192);
          }
        }
        if (d == 2 && lane < 30) {
          asm volatile("prefetch.global.L2 [%0];" :: "l"(wout + (size_t)cta * 6 * DM + lane * 128));
          asm volatile("prefetch.global.L2 [%0];" :: "l"(wout + (size_t)cta * 6 * DM + lane * 128 + 64));
        }
      }
    } else {
      cluster_wait();
      bar_sync<BAR_LN>(288);
      if (lane == 0) {
        TS(1, 5);
        asm volatile("cp.async.bulk.global.shared::cta.bulk_group [%0], [%1], 20480;" :: "l"(g_xn + (size_t)cta * 16 * DM), "r"(buf) : "memory");
        bulk_commit();
        bulk_wait_all();
        set_flag(F_XN + rb, cta & 7, epoch);
        TS(1, 6);
      }
      __syncwarp();
      if (grp == 0) {
        gather96(&g_csum[ct * 192 + lane], reinterpret_cast<float*>(smem + COLSUM_OFF) + lane, epoch);
      } else {
        unsigned it = 0;
        while (true) {
          bool ok = true;
          #pragma unroll
          for (int j = 0; j < 5; j++) {
            const uint2 u = ld_tag2(&g_csum[5 * FH + ct * 160 + j * 32 + lane]);
            ok = ok && u.y == epoch;
            reinterpret_cast<uint32_t*>(smem + COLSUM_OFF)[j * 32 + lane] = u.x;
          }
          if (ok || ++it > POLL_LIMIT) break;
          __nanosleep(2 * POLL_NS);
        }
      }
      __syncwarp();
      TS(1, 4);
      if (grp == 0) {
        bar_arrive<BAR_STATS>(320);
        bar_sync<BAR_PUB1>(160);
        if (lane == 0) set_flag(F_Z + ct, rb, epoch);
        TS(1, 8);
        __syncwarp();
        bar_arrive<BAR_BUF>(160);
      } else {
        bar_arrive<BAR_STATS>(192);
        bar_sync<BAR_PUB2>(160);
        if (lane == 0) set_flag(F_A + ct, rb, epoch);
        TS(1, 9);
        __syncwarp();
      }
      bar_sync<BAR_PUB1>(160);
      if (lane == 0) {
        set_flag(grp == 0 ? F_H + rb : F_B + ct, grp == 0 ? ct : rb, epoch);
        if (grp == 0) mbar_arrive_cluster(dep0 + 8, rank ^ 1);
      }
      TS(1, 10);
      __syncwarp();
      bar_arrive<BAR_BUF>(160);
    }
  } else {
    asm volatile("setmaxnreg.inc.sync.aligned.u32 232;");
    const int t = tid & 127, w = t >> 5, l = t & 31;
    ln_rows(rv, buf, cta, epoch);
    TS(wg + 1, 0);
    cluster_wait();
    const uint32_t st_base = buf + (w * 16 + ((l >> 3) & 1) * 8 + (l & 7)) * 128;
    const uint32_t st_x = ((l >> 4) ^ (l & 7)) << 4;
    const float2* rs = reinterpret_cast<const float2*>(smem + ROWSTAT_OFF) + w * 16 + (l >> 2);
    const float2* cs = reinterpret_cast<const float2*>(smem + COLSUM_OFF) + (l & 3);
    if (grp == 0) {
      {
        const int mb = wg - 1;
        float acc[1][96];
        zero(acc);
        mainloop<192, 1, 1, false, 0>(acc, sbase, 0, 0, 10, mb);
        drain(acc, sbase, 0, 9);
        TS(wg + 1, 1);
        bar_sync<BAR_STATS>(320);
        const float2 s0 = rs[mb * 64], s1 = rs[mb * 64 + 8];
        const float nm[2] = {s0.y / s0.x, s1.y / s1.x}, hr[2] = {0.5f * s0.x, 0.5f * s1.x};
        const float k1[2] = {0.7978845608f * s0.x, 0.7978845608f * s1.x};
        const float k2[2] = {0.0356774081f * s0.x * s0.x * s0.x, 0.0356774081f * s1.x * s1.x * s1.x};
        float sm0 = 0.f, sm1 = 0.f, q0 = 0.f, q1 = 0.f;
        #pragma unroll
        for (int j = 0; j < 24; j++) {
          const float2 c = cs[j * 4];
          #pragma unroll
          for (int e = 0; e < 4; e++) acc[0][4 * j + e] = fmaf(nm[e >> 1], (e & 1) ? c.y : c.x, acc[0][4 * j + e]);
        }
        #pragma unroll
        for (int jj = 0; jj < 12; jj++) {
          float u[8];
          #pragma unroll
          for (int hf = 0; hf < 2; hf++) {
            #pragma unroll
            for (int e = 0; e < 4; e++) {
              const float wv = acc[0][8 * jj + 4 * hf + e];
              float th; asm("tanh.approx.f32 %0, %1;" : "=f"(th) : "f"(wv * fmaf(k2[e >> 1], wv * wv, k1[e >> 1])));
              const float hv = hr[e >> 1] * wv;
              u[4 * hf + e] = fmaf(hv, th, hv);
            }
            sm0 += u[4 * hf] + u[4 * hf + 1]; q0 = fmaf(u[4 * hf], u[4 * hf], q0); q0 = fmaf(u[4 * hf + 1], u[4 * hf + 1], q0);
            sm1 += u[4 * hf + 2] + u[4 * hf + 3]; q1 = fmaf(u[4 * hf + 2], u[4 * hf + 2], q1); q1 = fmaf(u[4 * hf + 3], u[4 * hf + 3], q1);
          }
          stsm4(st_base + mb * 24576 + (jj >> 2) * 8192 + (st_x ^ ((jj & 3) << 5)),
                pack_bf16(u[0], u[1]), pack_bf16(u[2], u[3]), pack_bf16(u[4], u[5]), pack_bf16(u[6], u[7]));
        }
        #pragma unroll
        for (int o = 1; o < 4; o <<= 1) {
          sm0 += __shfl_xor_sync(0xffffffffu, sm0, o); q0 += __shfl_xor_sync(0xffffffffu, q0, o);
          sm1 += __shfl_xor_sync(0xffffffffu, sm1, o); q1 += __shfl_xor_sync(0xffffffffu, q1, o);
        }
        if ((l & 3) < 2) {
          const float sm = (l & 1) ? sm1 : sm0, sv = (l & 1) ? q1 : q0;
          const int row = mb * 64 + w * 16 + (l & 1) * 8 + (l >> 2);
          const float mu = sm * (1.f / 192), m2 = fmaxf(sv - sm * mu, 0.f);
          st_tag2(&g_zstat[(rb * 4 + ct) * 128 + row], __float_as_uint(mu), (__float_as_uint(m2) & ~255u) | (epoch & 255u));
          reinterpret_cast<float2*>(smem + ZSTAT_OFF)[row] = make_float2(mu, m2);
        }
        TS(wg + 1, 4);
      }
      float acc[2][96];
      if (wg == 1) {
        const bf16* bp = bsp + rb * 128 + w * 16 + (l >> 2);
        const float bb[4] = {__bfloat162float(bp[0]), __bfloat162float(bp[8]), __bfloat162float(bp[64]), __bfloat162float(bp[72])};
        bar_sync<BAR_U>(256);
        uint2 v[3];
        unsigned n = 0;
        while (true) {
          bool ok = true;
          #pragma unroll
          for (int j = 0; j < 3; j++) { v[j] = ld_tag2(&g_zstat[(rb * 4 + ((ct + 1 + j) & 3)) * 128 + t]); ok = ok && ((v[j].y ^ epoch) & 255u) == 0; }
          if (ok || ++n > POLL_LIMIT) break;
          __nanosleep(POLL_NS);
        }
        const float2 own = reinterpret_cast<const float2*>(smem + ZSTAT_OFF)[t];
        const float m0 = __uint_as_float(v[0].x), m1 = __uint_as_float(v[1].x), m3 = __uint_as_float(v[2].x);
        const float mean = 0.25f * ((own.x + m0) + (m1 + m3));
        const float d = (own.x - mean) * (own.x - mean) + (m0 - mean) * (m0 - mean) + (m1 - mean) * (m1 - mean) + (m3 - mean) * (m3 - mean);
        const float var = fmaf(192.f, d, (own.y + __uint_as_float(v[0].y & ~255u)) + (__uint_as_float(v[1].y & ~255u) + __uint_as_float(v[2].y & ~255u)));
        const float r = rsqrtf(var * (1.f / FH) + LN_EPS);
        TS(2, 5);
        const uint32_t rbase = buf + (t >> 6) * 24576 + (t & 63) * 128;
        const uint32_t m2 = pack_bf16(-mean, -mean), r2 = pack_bf16(r, r);
        const float res = (-mean - bf_lo(m2)) * r;
        const uint32_t e2 = pack_bf16(res, res);
        #pragma unroll 1
        for (int c = 0; c < 3; c++) {
          uint4 z[8];
          #pragma unroll
          for (int i = 0; i < 8; i++) z[i] = lds128(rbase + c * 8192 + (((i ^ l) & 7) << 4));
          #pragma unroll
          for (int i = 0; i < 8; i++)
            sts128(rbase + c * 8192 + (((i ^ l) & 7) << 4), hfma2_bf16(hadd2_bf16(z[i].x, m2), r2, e2), hfma2_bf16(hadd2_bf16(z[i].y, m2), r2, e2),
                   hfma2_bf16(hadd2_bf16(z[i].z, m2), r2, e2), hfma2_bf16(hadd2_bf16(z[i].w, m2), r2, e2));
          fence_async_smem();
          __syncwarp();
          if (l == 0) {
            tma_store_2d(&maps.m[M_ZS], buf + (w >> 1) * 24576 + c * 8192 + (w & 1) * 4096, ct * 192 + c * 64, rb * 128 + w * 32);
            bulk_commit();
          }
        }
        TS(2, 6);
        if (l == 0) bulk_wait_all();
        __syncwarp();
        bar_arrive<BAR_PUB1>(160);
        {
          #pragma unroll
          for (int i = 0; i < 96; i++) { acc[0][i] = bb[(i >> 1) & 1]; acc[1][i] = bb[2 + ((i >> 1) & 1)]; }
          pin(acc);
        }
        bar_sync<BAR_ORD2>(256);
        mainloop<192, 2, 1, false, BAR_ORD1>(acc, sbase, 0, 20, 32);
        bar_sync<BAR_Z1>(256);
        uint32_t z[6][4][4];
        #pragma unroll
        for (int i = 0; i < ZPRE; i++) ldsm4(st_base + (i >> 2) * 8192 + (st_x ^ ((i & 3) << 5)), z[i >> 2][i & 3][0], z[i >> 2][i & 3][1], z[i >> 2][i & 3][2], z[i >> 2][i & 3][3]);
        drain(acc, sbase, 0, 51);
        TS(2, 7);
        #pragma unroll
        for (int bx = 0; bx < 6; bx++) {
          if (bx >= 1) {
            #pragma unroll
            for (int i = ZPRE + (bx - 1) * 10; i < ZPRE + bx * 10; i++)
              if (i < 24) ldsm4(st_base + (i >> 2) * 8192 + (st_x ^ ((i & 3) << 5)), z[i >> 2][i & 3][0], z[i >> 2][i & 3][1], z[i >> 2][i & 3][2], z[i >> 2][i & 3][3]);
          }
          #pragma unroll
          for (int i = 0; i < 4; i++) {
            const float* a = &acc[bx / 3][8 * ((bx % 3) * 4 + i)];
            const uint32_t* zz = z[bx][i];
            stsm4(st_base + bx * 8192 + (st_x ^ (i << 5)),
                  hmul2_bf16(zz[0], pack_bf16(a[0], a[1])), hmul2_bf16(zz[1], pack_bf16(a[2], a[3])),
                  hmul2_bf16(zz[2], pack_bf16(a[4], a[5])), hmul2_bf16(zz[3], pack_bf16(a[6], a[7])));

          }
          if (bx % 3 == 2) {
            fence_async_smem();
            if (bx == 5) bar_arrive<BAR_U>(256);
            __syncwarp();
            if (l < 3) {
              tma_store_2d(&maps.m[M_HS], buf + (bx - 2 + l) * 8192 + w * 2048, ct * 192 + l * 64, rb * 128 + (bx / 3) * 64 + w * 16);
              bulk_commit();
            }
          }
        }
        TS(2, 8);
        if (l < 3) bulk_wait_all();
        __syncwarp();
        bar_arrive<BAR_PUB1>(160);
        TS(2, 9);
        return;
      }
      bar_arrive<BAR_U>(256);
      zero(acc);
      mainloop<192, 2, 1, false, BAR_ORD2>(acc, sbase, 0, 10, 10);
      drain(acc, sbase, 0, 19);
      TS(3, 2);
      bar_sync<BAR_BUF>(160);
      #pragma unroll
      for (int mi = 0; mi < 2; mi++)
        #pragma unroll
        for (int jj = 0; jj < 12; jj++) {
          const float* a = &acc[mi][8 * jj];
          stsm4(st_base + mi * 24576 + (jj >> 2) * 8192 + (st_x ^ ((jj & 3) << 5)),
                pack_bf16(a[0], a[1]), pack_bf16(a[2], a[3]), pack_bf16(a[4], a[5]), pack_bf16(a[6], a[7]));
        }
      __syncwarp();
      TS(3, 3);
      const uint32_t rbase = buf + (l >> 4) * 24576 + (w * 16 + (l & 15)) * 128;
      #pragma unroll 1
      for (int c2 = 0; c2 < 12; c2++) {
        const uint32_t ab = rbase + (c2 >> 2) * 8192;
        uint4 v[2];
        #pragma unroll
        for (int i = 0; i < 2; i++) v[i] = lds128(ab + (((((c2 & 3) * 2 + i) ^ l) & 7) << 4));
        #pragma unroll
        for (int i = 0; i < 2; i++)
          sts128(ab + (((((c2 & 3) * 2 + i) ^ l) & 7) << 4),
                 pack_bf16(gelu_tanh(bf_lo(v[i].x)), gelu_tanh(bf_hi(v[i].x))), pack_bf16(gelu_tanh(bf_lo(v[i].y)), gelu_tanh(bf_hi(v[i].y))),
                 pack_bf16(gelu_tanh(bf_lo(v[i].z)), gelu_tanh(bf_hi(v[i].z))), pack_bf16(gelu_tanh(bf_lo(v[i].w)), gelu_tanh(bf_hi(v[i].w))));
        __nanosleep(Z1_NS);
      }
      TS(3, 5);
      bar_arrive<BAR_Z1>(256);
    }
    float acc[2][80];
    if (grp == 1) {
      zero(acc);
      if (wg == 2) {
        mainloop<160, 2, 0, false, BAR_ORD2>(acc, sbase, 1, 0, 10);
      } else {
        weight_sums(win, wdre, rb * 4 + ct, epoch);
        TS(2, 1);
        bar_sync<BAR_ORD2>(256);
        mainloop<160, 2, 0, false, BAR_ORD1>(acc, sbase, 1, 10, 10);
      }
      drain(acc, sbase, 1, wg == 2 ? 9 : 19);
      TS(wg + 1, wg == 1 ? 7 : 2);
      if (wg == 1) bar_sync<BAR_Z1>(256); else bar_sync<BAR_STATS>(192);
      const uint32_t tb = buf + ((l >> 4) * 8 + (l & 7)) * 128 + (((w * 2 + ((l >> 3) & 1)) ^ (l & 7)) << 4);
      float2 st[4];
      #pragma unroll
      for (int r = 0; r < 4; r++) st[r] = wg == 2 ? rs[(r >> 1) * 64 + (r & 1) * 8] : make_float2(-1.f, 0.f);
      float2 cv[20];
      #pragma unroll
      for (int j = 0; j < 20; j++) cv[j] = cs[j * 4];
      #pragma unroll
      for (int jj = 0; jj < 10; jj++) {
        const float2 c0 = cv[jj * 2], c1 = cv[jj * 2 + 1];
        #pragma unroll
        for (int mi = 0; mi < 2; mi++) {
          const float* a = &acc[mi][8 * jj];
          const float2 s0 = st[mi * 2], s1 = st[mi * 2 + 1];
          stsm4_t(tb + mi * 20480 + jj * 2048,
                  pack_bf16(fmaf(a[0], s0.x, s0.y * c0.x), fmaf(a[1], s0.x, s0.y * c0.y)), pack_bf16(fmaf(a[2], s1.x, s1.y * c0.x), fmaf(a[3], s1.x, s1.y * c0.y)),
                  pack_bf16(fmaf(a[4], s0.x, s0.y * c1.x), fmaf(a[5], s0.x, s0.y * c1.y)), pack_bf16(fmaf(a[6], s1.x, s1.y * c1.x), fmaf(a[7], s1.x, s1.y * c1.y)));
        }
      }
      fence_async_smem();
      if (wg == 1) bar_sync<BAR_WG1>(128); else bar_sync<BAR_WG2>(128);
      TS(wg + 1, wg == 1 ? 8 : 6);
      if (l == 0) {
        #pragma unroll 1
        for (int i = 0; i < 2; i++) {
          __nanosleep((i == 0 ? w : 3) * (wg == 2 ? ST_A : ST_B));
          tma_store_2d(&maps.m[M_ABS], buf + i * 20480 + w * 5120, rb * 128 + i * 64, (2 - wg) * DM + ct * 160 + w * 40);
          bulk_commit();
        }
        bulk_wait_all();
      }
      __syncwarp();
      TS(wg + 1, wg == 1 ? 9 : 10);
      if (wg == 1) {
        bar_arrive<BAR_PUB1>(160);
        return;
      }
      bar_arrive<BAR_PUB2>(160);
      bar_arrive<BAR_Z1>(256);
    }
    zero(acc);
    bar_sync<BAR_ORD1>(256);
    mainloop<160, 2, 0, false, 0>(acc, sbase, grp, grp == 0 ? 52 : 20, grp == 0 ? NX : 64 - NX);
    if (grp == 0) {
      bar_sync<BAR_U>(256);
      mainloop<160, 2, 2, true, 0, true>(acc, sbase, 0, 52 + NX, 3);
    }
    mainloop<160, 2, 2, true, 0>(acc, sbase, grp, gh + 3 - 3 * grp, total - gh - 3 + 3 * grp);
    const uint32_t slab = buf + w * (16 * 320);
    const uint32_t addr = slab + (((l >> 3) & 1) * 8 + (l & 7)) * 320 + (l >> 4) * 16;
    bar_sync<BAR_BUF>(160);
    mbar_wait(dep0 + 32, 0);
    drain(acc, sbase, grp, total - 1);
    TS(3, 12);
    #pragma unroll
    for (int mi = 0; mi < 2; mi++) {
      #pragma unroll
      for (int jj = 0; jj < 10; jj++) {
        const float* a = &acc[mi][8 * jj];
        stsm4(addr + mi * 20480 + jj * 32, pack_bf16(a[0], a[1]), pack_bf16(a[2], a[3]), pack_bf16(a[4], a[5]), pack_bf16(a[6], a[7]));
      }
      fence_async_smem();
      __syncwarp();
      if (l == 0) {
        tma_reduce_2d(&maps.m[M_OUT], slab + mi * 20480, ct * 160, rb * 128 + mi * 64 + w * 16);
        bulk_commit();
      }
    }
    TS(3, 13);
    if (l == 0) {
      bulk_wait_read();
      if (w == 0) atomicAdd(&g_done, 1u);
    }
    TS(3, 15);
  }
}

typedef CUresult (*EncodeFn)(CUtensorMap*, CUtensorMapDataType, cuuint32_t, void*, const cuuint64_t*, const cuuint64_t*,
                             const cuuint32_t*, const cuuint32_t*, CUtensorMapInterleave, CUtensorMapSwizzle,
                             CUtensorMapL2promotion, CUtensorMapFloatOOBfill);

void make2d(EncodeFn enc, CUtensorMap* m, const void* p, uint64_t cols, uint64_t rows, uint32_t bc, uint32_t br, bool swz = true) {
  cuuint64_t gd[2] = {cols, rows}, gs[1] = {cols * 2};
  cuuint32_t bd[2] = {bc, br}, es[2] = {1, 1};
  enc(m, CU_TENSOR_MAP_DATA_TYPE_BFLOAT16, 2, const_cast<void*>(p), gd, gs, bd, es, CU_TENSOR_MAP_INTERLEAVE_NONE,
      swz ? CU_TENSOR_MAP_SWIZZLE_128B : CU_TENSOR_MAP_SWIZZLE_NONE, CU_TENSOR_MAP_L2_PROMOTION_L2_128B, CU_TENSOR_MAP_FLOAT_OOB_FILL_NONE);
}
void make3d(EncodeFn enc, CUtensorMap* m, const void* p, uint64_t cols, uint64_t rows, uint32_t cw, uint32_t nc, uint32_t br = 64) {
  cuuint64_t gd[3] = {cw, rows, cols / cw}, gs[2] = {cols * 2, cw * 2};
  cuuint32_t bd[3] = {cw, br, nc}, es[3] = {1, 1, 1};
  enc(m, CU_TENSOR_MAP_DATA_TYPE_BFLOAT16, 3, const_cast<void*>(p), gd, gs, bd, es, CU_TENSOR_MAP_INTERLEAVE_NONE,
      cw == 64 ? CU_TENSOR_MAP_SWIZZLE_128B : CU_TENSOR_MAP_SWIZZLE_64B, CU_TENSOR_MAP_L2_PROMOTION_L2_128B, CU_TENSOR_MAP_FLOAT_OOB_FILL_NONE);
}

}

extern "C" void kernel_launch(void* const* d_in, const int* in_sizes, int n_in, void* d_out, int out_size) {
  const bf16* x = (const bf16*)d_in[0];
  const bf16* wsre = (const bf16*)d_in[1];
  const bf16* wsim = (const bf16*)d_in[2];
  const bf16* wdre = (const bf16*)d_in[3];
  const bf16* wdim = (const bf16*)d_in[4];
  const bf16* win = (const bf16*)d_in[6];
  const bf16* wsp = (const bf16*)d_in[7];
  const bf16* bsp = (const bf16*)d_in[8];
  const bf16* wout = (const bf16*)d_in[9];

  void* fn = nullptr;
  cudaDriverEntryPointQueryResult qr;
  cudaGetDriverEntryPoint("cuTensorMapEncodeTiled", &fn, cudaEnableDefault, &qr);
  EncodeFn enc = (EncodeFn)fn;
  void *abT, *z2, *h, *xn;
  cudaGetSymbolAddress(&xn, g_xn);
  cudaGetSymbolAddress(&abT, g_abT);
  cudaGetSymbolAddress(&z2, g_z2);
  cudaGetSymbolAddress(&h, g_h);

  Maps maps;
  make2d(enc, &maps.m[M_X], x, DM, SEQ, 64, 64);
  make2d(enc, &maps.m[M_XN], xn, DM, SEQ, 64, 64);
  make2d(enc, &maps.m[M_WSRE], wsre, SEQ, SEQ, 64, 64);
  make2d(enc, &maps.m[M_WSIM], wsim, SEQ, SEQ, 64, 64);
  make2d(enc, &maps.m[M_WSP], wsp, SEQ, SEQ, 64, 64);
  make2d(enc, &maps.m[M_H], h, FH, SEQ, 64, 64);
  make3d(enc, &maps.m[M_WIN3], win, FF, DM, 64, 3);
  make3d(enc, &maps.m[M_Z23], z2, FH, SEQ, 64, 3);
  make2d(enc, &maps.m[M_WDRE], wdre, DM, DM, 64, 160);
  make2d(enc, &maps.m[M_WDIM], wdim, DM, DM, 64, 160);
  make2d(enc, &maps.m[M_AB], abT, SEQ, 2 * DM, 64, 160);
  make3d(enc, &maps.m[M_WOUT], wout, DM, FH, 32, 5);
  make2d(enc, &maps.m[M_HS], h, FH, SEQ, 64, 16);
  make2d(enc, &maps.m[M_ZS], z2, FH, SEQ, 64, 32);
  make2d(enc, &maps.m[M_ABS], abT, SEQ, 2 * DM, 64, 40);
  make2d(enc, &maps.m[M_OUT], d_out, DM, SEQ, 160, 16, false);

  cudaFuncSetAttribute(fused_kernel, cudaFuncAttributeMaxDynamicSharedMemorySize, SMEM_BYTES);
  fused_kernel<<<132, 384, SMEM_BYTES>>>(maps, x, win, wdre, bsp, wout, (bf16*)d_out);
}
```
